```python
import torch

def _softmax(x, axis=-1):
    return torch.softmax(x, dim=axis)
def _gelu(x):
    return torch.nn.functional.gelu(x, approximate="tanh")
def _silu(x):
    return torch.nn.functional.silu(x)
def _sigmoid(x):
    return torch.sigmoid(x)
def _layernorm(x, axis=-1, eps=1e-5):
    m = x.mean(dim=axis, keepdim=True)
    v = x.var(dim=axis, keepdim=True, unbiased=False)
    return (x - m) / torch.sqrt(v + eps)
def _scatter_add(tgt, idx, src, axis=0):
    return tgt.clone().index_add_(axis, idx, src)
def _segment_sum(src, seg, n):
    out = torch.zeros((n,) + src.shape[1:], dtype=src.dtype)
    return out.index_add_(0, seg, src)
def _pad(x, pw):
    flat = tuple(v for pair in reversed(pw) for v in pair)
    return torch.nn.functional.pad(x, flat)

kernel_name = 'sequential_preLN__compressed_kv_cla__moe_arch_mod__prompt'

def setup_inputs():

    _w = (lambda a: (lambda t: t.to(torch.bfloat16) if t.is_floating_point() else t)(torch.as_tensor(a)))
    def _A_setup():
        B, H, Sq, Sk, D, M = 1, 32, 2048, 2048, 128, 1024
        Dc = 4 * D
        return {
            "x": _w((lambda *s: torch.randn(*s, dtype=torch.bfloat16) * 0.1)(B, Sq, M)),
            "c_kv": _w((lambda *s: torch.randn(*s, dtype=torch.bfloat16) * 1.6)(B, Sk, Dc)),
            "w_q": _w((lambda *s: torch.randn(*s, dtype=torch.bfloat16) * 0.8)(M, H, D) * (M ** -0.5)),
            "w_uk": _w((lambda *s: torch.randn(*s, dtype=torch.bfloat16) * 0.8)(Dc, H, D) * (Dc ** -0.5)),
            "w_uv": _w((lambda *s: torch.randn(*s, dtype=torch.bfloat16) * 1.6)(Dc, H, D) * (Dc ** -0.5)),
            "w_o": _w((lambda *s: torch.randn(*s, dtype=torch.bfloat16) * 1.6)(H, D, M) * ((H * D) ** -0.5)),
        }
    _A_in = _A_setup()

    def _B_setup():
        B, S, D, F, C = 1, 2048, 1024, 3584, 2
        return {
            "x": _w((lambda *s: torch.randn(*s, dtype=torch.bfloat16) * 0.1)(B, S, D)),
            "w_r": _w((lambda *s: torch.randn(*s, dtype=torch.bfloat16) * 0.2)(D)),
            "w_gate": _w((lambda *s: torch.randn(*s, dtype=torch.bfloat16) * 0.2)(D, F)),
            "w_up": _w((lambda *s: torch.randn(*s, dtype=torch.bfloat16) * 0.2)(D, F)),
            "w_down": _w((lambda *s: torch.randn(*s, dtype=torch.bfloat16) * 0.2)(F, D)),
        }
    _B_in = _B_setup()

    return {
        "A_x": _A_in["x"],
        "A_c_kv": _A_in["c_kv"],
        "A_w_q": _A_in["w_q"],
        "A_w_uk": _A_in["w_uk"],
        "A_w_uv": _A_in["w_uv"],
        "A_w_o": _A_in["w_o"],
        "B_x": _B_in["x"],
        "B_w_r": _B_in["w_r"],
        "B_w_gate": _B_in["w_gate"],
        "B_w_up": _B_in["w_up"],
        "B_w_down": _B_in["w_down"],
    }

def reference(A_x, A_c_kv, A_w_q, A_w_uk, A_w_uv, A_w_o, B_x, B_w_r, B_w_gate, B_w_up, B_w_down):
    def _A_ref(x, c_kv, w_q, w_uk, w_uv, w_o):
        B, Sq, M = x.shape[0], x.shape[1], x.shape[2]
        Sk = c_kv.shape[1]
        H, D = w_q.shape[1], w_q.shape[2]
        q = torch.einsum("bqm,mhd->bhqd", x, w_q)
        k = torch.einsum("bkc,chd->bhkd", c_kv, w_uk)
        v = torch.einsum("bkc,chd->bhkd", c_kv, w_uv)
        scores = torch.einsum("bhqd,bhkd->bhqk", q, k) * (D ** -0.5)
        off = Sk - Sq
        qi = torch.arange(Sq)[:, None]
        kj = torch.arange(Sk)[None, :]
        cmask = kj <= (qi + off)
        scores = torch.where(cmask[None, None], scores, -1e9)
        p = _softmax(scores, axis=-1)
        ctx = torch.einsum("bhqk,bhkd->bhqd", p, v)
        return torch.einsum("bhqd,hdm->bqm", ctx, w_o)

    def _B_ref(x, w_r, w_gate, w_up, w_down):
        B, S, D = x.shape
        C = 2
        r = x @ w_r
        idx = torch.argsort(-r, axis=-1)[:, :C]
        idx_e = (lambda x, n, axis: torch.repeat_interleave(x, n, dim=axis))(idx.reshape(B, C, 1), D, axis=2)
        x_sel = (lambda x, i, axis: torch.take_along_dim(x, i, dim=axis))(x, idx_e, axis=1)
        g = _silu(x_sel @ w_gate)
        u = x_sel @ w_up
        y = (g * u) @ w_down
        r_sel = _sigmoid((lambda x, i, axis: torch.take_along_dim(x, i, dim=axis))(r, idx, axis=1))
        y = y * r_sel.reshape(B, C, 1)
        b_off = (torch.arange(B) * S).reshape(B, 1)
        flat_idx = (idx + b_off).reshape(B * C)
        zero = (x * 0.0).reshape(B * S, D)
        upd = _scatter_add(zero, flat_idx, y.reshape(B * C, D), axis=0)
        return x + upd.reshape(B, S, D)

    x = A_x
    h = x + _A_ref(_layernorm(x, axis=-1), A_c_kv, A_w_q, A_w_uk, A_w_uv, A_w_o)
    h2 = h + _B_ref(_layernorm(h, axis=-1), B_w_r, B_w_gate, B_w_up, B_w_down)
    return h2
```

```cpp
#include <cuda_runtime.h>
#include <cuda_bf16.h>
#include <cuda.h>
#include <stdint.h>
#include <utility>

#pragma nv_diag_suppress 549
namespace {

constexpr int SEQ = 2048, DM = 1024, NH = 32, HD = 128, DC = 512, NQ = NH * HD, FF = 3584;

__device__ __align__(1024) __nv_bfloat16 g_xn[SEQ * DM];
__device__ __align__(1024) __nv_bfloat16 g_kv[2 * SEQ * NQ];
__device__ __align__(1024) __nv_bfloat16 g_ctx[SEQ * NQ];
constexpr int XR_PS = 0;
constexpr int XR_KEY = 128;
constexpr int XR_CAND = 136;
constexpr int XR_Y = 648;
constexpr int XR_SIZE = 1104;
__device__ __align__(1024) uint4 g_xr[128 * XR_SIZE];
constexpr int C_LN = 0, C_KV = 16, C_CTX = 32, C_NUM = 64;
__device__ unsigned g_cnt[C_NUM];

#define TL(k, i, cond) do {} while (0)
#define TC(w, g, i) do {} while (0)
#define TL_EXTRA 0

__device__ __forceinline__ uint32_t s2u(const void* p) { return (uint32_t)__cvta_generic_to_shared(p); }
__device__ __forceinline__ void mbar_arrive(uint32_t b) { asm volatile("mbarrier.arrive.shared::cta.b64 _, [%0];" ::"r"(b) : "memory"); }
__device__ __forceinline__ void mbar_arrive_both(uint32_t b, uint32_t lane, bool cond) {
  asm volatile("{\n.reg .pred p;\n.reg .b32 r;\nsetp.lt.u32 p, %1, %2;\nmapa.shared::cluster.u32 r, %0, %1;\n@p mbarrier.arrive.shared::cluster.b64 _, [r];\n}"
               ::"r"(b), "r"(lane), "r"(cond ? 2 : 0) : "memory");
}
__device__ __forceinline__ void mbar_wait(uint32_t b, uint32_t ph) {
  asm volatile(
      "{\n.reg .pred p;\n.reg .u32 n;\nmov.u32 n, 0;\n"
      "LW:\nmbarrier.try_wait.parity.shared::cta.b64 p, [%0], %1, 20000;\n@p bra LD;\n"
      "add.u32 n, n, 1;\nsetp.lt.u32 p, n, 0x40000;\n@p bra LW;\ntrap;\nLD:\n}" ::"r"(b), "r"(ph) : "memory");
}
__device__ __forceinline__ void mbar_wait_c(uint32_t b, uint32_t ph) {
  asm volatile(
      "{\n.reg .pred p;\n.reg .u32 n;\nmov.u32 n, 0;\n"
      "LW:\nmbarrier.try_wait.parity.shared::cta.b64 p, [%0], %1;\n@p bra.uni LD;\n"
      "add.u32 n, n, 1;\nsetp.lt.u32 p, n, 0x100000;\n@p bra.uni LW;\ntrap;\nLD:\n}" ::"r"(b), "r"(ph) : "memory");
}
template <bool SLEEP = false>
__device__ __forceinline__ void spin_until_ge(const unsigned* p, unsigned target) {
  asm volatile(
      "{\n.reg .pred p, q;\n.reg .u32 n, v;\nmov.u32 n, 0;\nsetp.ne.u32 q, %2, 0;\n"
      "LW:\nld.acquire.gpu.global.u32 v, [%0];\nsetp.ge.u32 p, v, %1;\n@p bra LD;\n@q nanosleep.u32 200;\n"
      "add.u32 n, n, 1;\nsetp.lt.u32 p, n, 0x400000;\n@p bra LW;\ntrap;\nLD:\n}" ::"l"(p), "r"(target), "n"((int)SLEEP) : "memory");
}
__device__ __forceinline__ uint4 poll_chunk(const uint4* p) {
  uint4 v;
  asm volatile(
      "{\n.reg .pred p;\n.reg .u32 n, m;\nmov.u32 n, 0;\n"
      "LW:\nld.relaxed.gpu.global.v4.u32 {%0,%1,%2,%3}, [%4];\nmax.u32 m, %0, %1;\nmax.u32 m, m, %2;\nmax.u32 m, m, %3;\n"
      "setp.ne.u32 p, m, 0xFFFFFFFF;\n@p bra LD;\n"
      "add.u32 n, n, 1;\nsetp.lt.u32 p, n, 0x400000;\n@p bra LW;\ntrap;\nLD:\n}"
      : "=r"(v.x), "=r"(v.y), "=r"(v.z), "=r"(v.w) : "l"(p) : "memory");
  return v;
}
template <int N>
__device__ __forceinline__ void poll_chunks(uint4 (&v)[N], const uint4* p, int stride) {
#pragma unroll 1
  for (int n = 0; n < 0x400000; n++) {
    uint32_t m = 0;
#pragma unroll
    for (int i = 0; i < N; i++) {
      asm volatile("ld.relaxed.gpu.global.v4.u32 {%0,%1,%2,%3}, [%4];" : "=r"(v[i].x), "=r"(v[i].y), "=r"(v[i].z), "=r"(v[i].w) : "l"(p + i * stride) : "memory");
    }
#pragma unroll
    for (int i = 0; i < N; i++) m = max(max(m, max(v[i].x, v[i].y)), max(v[i].z, v[i].w));
    if (m != 0xFFFFFFFFu) break;
  }
}
__device__ __forceinline__ void fence_async_all() { asm volatile("fence.proxy.async;" ::: "memory"); }
__device__ __forceinline__ void bar_sync(int id, int n) { asm volatile("bar.sync %0, %1;" ::"r"(id), "r"(n) : "memory"); }
__device__ __forceinline__ void bar_arrive(int id, int n) { asm volatile("bar.arrive %0, %1;" ::"r"(id), "r"(n) : "memory"); }
__device__ __forceinline__ void cluster_arrive() { asm volatile("barrier.cluster.arrive.relaxed.aligned;" ::: "memory"); }
__device__ __forceinline__ void cluster_wait() { asm volatile("barrier.cluster.wait.acquire.aligned;" ::: "memory"); }
__device__ __forceinline__ void fence_gpu() { asm volatile("fence.acq_rel.gpu;" ::: "memory"); }
__device__ __forceinline__ void red_add(unsigned* p, unsigned v) { asm volatile("red.relaxed.gpu.global.add.u32 [%0], %1;" ::"l"(p), "r"(v) : "memory"); }
#define ELECT "{\n.reg .pred E;\nelect.sync _|E, 0xFFFFFFFF;\n@E "
__device__ __forceinline__ void e_init(uint32_t b, uint32_t c) { asm volatile(ELECT "mbarrier.init.shared::cta.b64 [%0], %1;\n}" ::"r"(b), "r"(c) : "memory"); }
__device__ __forceinline__ void e_expect(uint32_t b, uint32_t bytes) { asm volatile(ELECT "mbarrier.arrive.expect_tx.shared::cta.b64 _, [%0], %1;\n}" ::"r"(b), "r"(bytes) : "memory"); }
__device__ __forceinline__ void e_arrive(uint32_t b) { asm volatile(ELECT "mbarrier.arrive.shared::cta.b64 _, [%0];\n}" ::"r"(b) : "memory"); }
__device__ __forceinline__ void prefetch_tm(const CUtensorMap* m) { asm volatile(ELECT "prefetch.tensormap [%0];\n}" ::"l"(m) : "memory"); }
__device__ __forceinline__ void tma_ld2(uint32_t dst, const CUtensorMap* m, uint32_t bar, int c0, int c1) {
  asm volatile(ELECT "cp.async.bulk.tensor.2d.shared::cta.global.mbarrier::complete_tx::bytes [%0], [%1, {%3,%4}], [%2];\n}" ::"r"(dst), "l"(m), "r"(bar), "r"(c0), "r"(c1) : "memory");
}
__device__ __forceinline__ void tma_ld3(uint32_t dst, const CUtensorMap* m, uint32_t bar, int c0, int c1, int c2) {
  asm volatile(ELECT "cp.async.bulk.tensor.3d.shared::cta.global.mbarrier::complete_tx::bytes [%0], [%1, {%3,%4,%5}], [%2];\n}" ::"r"(dst), "l"(m), "r"(bar), "r"(c0), "r"(c1), "r"(c2) : "memory");
}
__device__ __forceinline__ void tma_ld2_mc(uint32_t dst, const CUtensorMap* m, uint32_t bar, int c0, int c1, uint16_t mask) {
  asm volatile(ELECT "cp.async.bulk.tensor.2d.shared::cluster.global.mbarrier::complete_tx::bytes.multicast::cluster [%0], [%1, {%3,%4}], [%2], %5;\n}" ::"r"(dst), "l"(m), "r"(bar), "r"(c0), "r"(c1), "h"(mask) : "memory");
}
__device__ __forceinline__ void tma_ld3_mc(uint32_t dst, const CUtensorMap* m, uint32_t bar, int c0, int c1, int c2, uint16_t mask) {
  asm volatile(ELECT "cp.async.bulk.tensor.3d.shared::cluster.global.mbarrier::complete_tx::bytes.multicast::cluster [%0], [%1, {%3,%4,%5}], [%2], %6;\n}" ::"r"(dst), "l"(m), "r"(bar), "r"(c0), "r"(c1), "r"(c2), "h"(mask) : "memory");
}
__device__ __forceinline__ void tma_pf2(const CUtensorMap* m, int c0, int c1) { asm volatile(ELECT "cp.async.bulk.prefetch.tensor.2d.L2.global [%0, {%1,%2}];\n}" ::"l"(m), "r"(c0), "r"(c1) : "memory"); }
__device__ __forceinline__ void tma_pf3(const CUtensorMap* m, int c0, int c1, int c2) { asm volatile(ELECT "cp.async.bulk.prefetch.tensor.3d.L2.global [%0, {%1,%2,%3}];\n}" ::"l"(m), "r"(c0), "r"(c1), "r"(c2) : "memory"); }
__device__ __forceinline__ void sched_fence() { asm volatile("pmevent 0;" ::: "memory"); }
__device__ __forceinline__ void l2_prefetch(const void* p, uint32_t bytes) { asm volatile(ELECT "cp.async.bulk.prefetch.L2.global [%0], %1;\n}" ::"l"(p), "r"(bytes) : "memory"); }

__device__ __forceinline__ void wg_fence() { asm volatile("wgmma.fence.sync.aligned;" ::: "memory"); }
__device__ __forceinline__ void wg_commit() { asm volatile("wgmma.commit_group.sync.aligned;" ::: "memory"); }
template <int N> __device__ __forceinline__ void wg_wait() { asm volatile("wgmma.wait_group.sync.aligned %0;" ::"n"(N) : "memory"); }
template <int N> __device__ __forceinline__ void reg_alloc() { asm volatile("setmaxnreg.inc.sync.aligned.u32 %0;" ::"n"(N)); }
template <int N> __device__ __forceinline__ void reg_dealloc() { asm volatile("setmaxnreg.dec.sync.aligned.u32 %0;" ::"n"(N)); }
template <int N> __device__ __forceinline__ void fence_regs(float (&d)[N]) {
#pragma unroll
  for (int i = 0; i < N; i++) asm volatile("" : "+f"(d[i])::"memory");
}
template <int N> __device__ __forceinline__ void fence_regs(uint32_t (&d)[N]) {
#pragma unroll
  for (int i = 0; i < N; i++) asm volatile("" : "+r"(d[i])::"memory");
}

__device__ __forceinline__ uint32_t mk_desc(uint32_t addr, uint32_t lbo) { return ((addr & 0x3FFFF) >> 4) | ((lbo >> 4) << 16); }

#define R8(b) "+f"(d[b + 0]), "+f"(d[b + 1]), "+f"(d[b + 2]), "+f"(d[b + 3]), "+f"(d[b + 4]), "+f"(d[b + 5]), "+f"(d[b + 6]), "+f"(d[b + 7])
#define REGS64 "%0,%1,%2,%3,%4,%5,%6,%7,%8,%9,%10,%11,%12,%13,%14,%15,%16,%17,%18,%19,%20,%21,%22,%23,%24,%25,%26,%27,%28,%29,%30,%31," \
               "%32,%33,%34,%35,%36,%37,%38,%39,%40,%41,%42,%43,%44,%45,%46,%47,%48,%49,%50,%51,%52,%53,%54,%55,%56,%57,%58,%59,%60,%61,%62,%63"
#define REGS128 REGS64 ",%64,%65,%66,%67,%68,%69,%70,%71,%72,%73,%74,%75,%76,%77,%78,%79,%80,%81,%82,%83,%84,%85,%86,%87,%88,%89,%90,%91,%92,%93,%94,%95," \
               "%96,%97,%98,%99,%100,%101,%102,%103,%104,%105,%106,%107,%108,%109,%110,%111,%112,%113,%114,%115,%116,%117,%118,%119,%120,%121,%122,%123,%124,%125,%126,%127"

#define DESC(d, r, o) "add.u32 t, " r ", " o ";\nmov.b64 " d ", {t, h};\n"
#define MMA_PRE(acc) "{\n.reg .pred p;\n.reg .b32 t, h;\n.reg .b64 da, db;\nmov.b32 h, 0x40000040;\nsetp.ne.b32 p, " acc ", 0;\n"
template <int TB, int OA, int OB>
__device__ __forceinline__ void mma_n256_ss(float (&d)[128], uint32_t a, uint32_t b, int acc) {
  asm volatile(MMA_PRE("%130") DESC("da", "%128", "%132") DESC("db", "%129", "%133")
               "wgmma.mma_async.sync.aligned.m64n256k16.f32.bf16.bf16 {" REGS128 "}, da, db, p, 1, 1, 0, %131;\n}\n"
               : R8(0), R8(8), R8(16), R8(24), R8(32), R8(40), R8(48), R8(56), R8(64), R8(72), R8(80), R8(88), R8(96), R8(104), R8(112), R8(120)
               : "r"(a), "r"(b), "r"(acc), "n"(TB), "n"(OA >> 4), "n"(OB >> 4));
}
template <int TB, int OA, int OB>
__device__ __forceinline__ void mma_n128_ss(float (&d)[64], uint32_t a, uint32_t b, int acc) {
  asm volatile(MMA_PRE("%66") DESC("da", "%64", "%68") DESC("db", "%65", "%69")
               "wgmma.mma_async.sync.aligned.m64n128k16.f32.bf16.bf16 {" REGS64 "}, da, db, p, 1, 1, 0, %67;\n}\n"
               : R8(0), R8(8), R8(16), R8(24), R8(32), R8(40), R8(48), R8(56)
               : "r"(a), "r"(b), "r"(acc), "n"(TB), "n"(OA >> 4), "n"(OB >> 4));
}
template <int TB, int OB>
__device__ __forceinline__ void mma_n128_rs(float (&d)[64], const uint32_t* a, uint32_t b, int acc) {
  asm volatile(MMA_PRE("%69") DESC("db", "%68", "%71")
               "wgmma.mma_async.sync.aligned.m64n128k16.f32.bf16.bf16 {" REGS64 "}, {%64,%65,%66,%67}, db, p, 1, 1, %70;\n}\n"
               : R8(0), R8(8), R8(16), R8(24), R8(32), R8(40), R8(48), R8(56)
               : "r"(a[0]), "r"(a[1]), "r"(a[2]), "r"(a[3]), "r"(b), "r"(acc), "n"(TB), "n"(OB >> 4));
}
template <int V> struct IC { static constexpr int value = V; __host__ __device__ constexpr operator int() const { return V; } };
template <int N, class F, int... I>
__device__ __forceinline__ void static_for_(F f, std::integer_sequence<int, I...>) { (f(IC<I>{}), ...); }
template <int N, class F>
__device__ __forceinline__ void static_for(F f) { static_for_<N>(f, std::make_integer_sequence<int, N>{}); }
__device__ __forceinline__ uint32_t pack_bf16(float lo, float hi) {
  uint32_t r;
  asm("cvt.rn.bf16x2.f32 %0, %1, %2;" : "=r"(r) : "f"(hi), "f"(lo));
  return r;
}
__device__ __forceinline__ float bf_lo(uint32_t v) { return __uint_as_float(v << 16); }
__device__ __forceinline__ float bf_hi(uint32_t v) { return __uint_as_float(v & 0xFFFF0000u); }
__device__ __forceinline__ float bf_round(float v) { return bf_lo(pack_bf16(v, v)); }
__device__ __forceinline__ void stsm4(uint32_t addr, uint32_t r0, uint32_t r1, uint32_t r2, uint32_t r3) {
  asm volatile("stmatrix.sync.aligned.m8n8.x4.shared.b16 [%0], {%1,%2,%3,%4};" ::"r"(addr), "r"(r0), "r"(r1), "r"(r2), "r"(r3) : "memory");
}
__device__ __forceinline__ uint4 lds128(uint32_t addr) {
  uint4 v;
  asm volatile("ld.shared.v4.u32 {%0,%1,%2,%3}, [%4];" : "=r"(v.x), "=r"(v.y), "=r"(v.z), "=r"(v.w) : "r"(addr));
  return v;
}
__device__ __forceinline__ float ex2(float x) {
  float y;
  asm("ex2.approx.ftz.f32 %0, %1;" : "=f"(y) : "f"(x));
  return y;
}
__device__ __forceinline__ void stage_store_128(uint32_t base, int lane, const uint32_t* pk) {
  const int row = (lane & 7) + ((lane >> 3) & 1) * 8;
  const uint32_t rb = base + row * 128;
  const int hi = lane >> 4;
#pragma unroll
  for (int j = 0; j < 8; j++) {
    const int chunk = 2 * j + hi;
    const uint32_t a = rb + (j >> 2) * 8192 + (((chunk & 7) ^ (lane & 7)) << 4);
    stsm4(a, pk[4 * j + 0], pk[4 * j + 1], pk[4 * j + 2], pk[4 * j + 3]);
  }
}
__device__ __forceinline__ void ln_round(float mean, float var, float& m_bf, float& inv_s) {
  const uint32_t mv = pack_bf16(mean, var);
  m_bf = bf_lo(mv);
  float sq, rc;
  asm("sqrt.approx.f32 %0, %1;" : "=f"(sq) : "f"(bf_round(bf_hi(mv) + 1e-5f)));
  asm("rcp.approx.ftz.f32 %0, %1;" : "=f"(rc) : "f"(bf_round(sq)));
  inv_s = rc;
}
__device__ __forceinline__ uint32_t hadd2_bf(uint32_t a, uint32_t b) {
  uint32_t r;
  asm("add.rn.bf16x2 %0, %1, %2;" : "=r"(r) : "r"(a), "r"(b));
  return r;
}
__device__ __forceinline__ uint32_t ln_apply(uint32_t h, uint32_t nm2, float inv_s) {
  const uint32_t d = hadd2_bf(h, nm2);
  return pack_bf16(bf_lo(d) * inv_s, bf_hi(d) * inv_s);
}
__device__ __forceinline__ void mma16816(float* d, uint32_t a0, uint32_t a1, uint32_t a2, uint32_t a3, uint32_t b0, uint32_t b1) {
  asm volatile("mma.sync.aligned.m16n8k16.row.col.f32.bf16.bf16.f32 {%0,%1,%2,%3}, {%4,%5,%6,%7}, {%8,%9}, {%0,%1,%2,%3};"
               : "+f"(d[0]), "+f"(d[1]), "+f"(d[2]), "+f"(d[3]) : "r"(a0), "r"(a1), "r"(a2), "r"(a3), "r"(b0), "r"(b1));
}

constexpr float AT_C = 0.08838834764831845f * 1.4426950408889634f;
#define L_MIN 2.3283064e-10f
#define L_MAX 1.0995116e12f
#define SP1 6
#define SP2 12
struct AtState {
  float S[64], O[64];
  uint32_t P[32], Q[32];
  float l[4];
};
template <int I0, int I1>
__device__ __forceinline__ void at_exp(AtState& s) {
#pragma unroll
  for (int i = I0; i < I1; i++) {
    asm volatile("ex2.approx.ftz.f32 %0, %0;" : "+f"(s.S[i]));
    asm volatile("add.f32 %0, %0, %1;" : "+f"(s.l[i & 3]) : "f"(s.S[i]));
  }
}
template <int I0, int I1>
__device__ __forceinline__ void at_pack(AtState& s) {
#pragma unroll
  for (int i = I0; i < I1; i++) asm volatile("cvt.rn.bf16x2.f32 %0, %1, %2;" : "=r"(s.P[i]) : "f"(s.S[2 * i + 1]), "f"(s.S[2 * i]));
}
template <int J0>
__device__ __forceinline__ void at_mask(AtState& s, int r, int lane) {
  const int d = r + (lane >> 2) - (lane & 3) * 2;
#pragma unroll
  for (int j = 0; j < 8; j++) {
    float dummy0 = 0.f, dummy1 = 0.f;
    float& lo0 = j < 7 ? s.S[4 * (J0 + (j < 7 ? j + 1 : j)) + 2] : dummy0;
    float& lo1 = j < 7 ? s.S[4 * (J0 + (j < 7 ? j + 1 : j)) + 3] : dummy1;
    asm("{\n.reg .pred p, q;\nsetp.lt.s32 p, %4, %5;\nsetp.le.s32 q, %4, %5;\n"
        "@p add.f32 %0, %0, 0fFF800000;\n@q add.f32 %1, %1, 0fFF800000;\n@p add.f32 %2, %2, 0fFF800000;\n@q add.f32 %3, %3, 0fFF800000;\n}"
        : "+f"(s.S[4 * (J0 + j)]), "+f"(s.S[4 * (J0 + j) + 1]), "+f"(lo0), "+f"(lo1) : "r"(d), "r"(8 * j));
  }
}
__device__ __forceinline__ uint32_t ld_pair(const __nv_bfloat16* p) {
  uint32_t r;
  asm volatile("{\n.reg .b16 a, b;\nld.global.cg.b16 a, [%1];\nld.global.cg.b16 b, [%1 + 8192];\nmov.b32 %0, {a, b};\n}" : "=r"(r) : "l"(p) : "memory");
  return r;
}
__device__ __forceinline__ uint32_t ld_word(const uint32_t* p) {
  uint32_t r;
  asm volatile("ld.global.cg.b32 %0, [%1];" : "=r"(r) : "l"(p) : "memory");
  return r;
}
__device__ __forceinline__ void slow_rows(const __nv_bfloat16* wq, int head, int row0, int lane) {
  const int r = lane >> 2, c = lane & 3;
  uint32_t q[32];
  float o[32];
#pragma unroll
  for (int i = 0; i < 32; i++) q[i] = 0;
  const uint32_t* xa = reinterpret_cast<const uint32_t*>(g_xn + (size_t)(row0 + r) * DM) + c;
#pragma unroll 1
  for (int h = 0; h < 2; h++) {
    const __nv_bfloat16* wb = wq + (size_t)2 * c * NQ + head * HD + 64 * h + 8 * (r >> 1) + (r & 1);
#pragma unroll
    for (int i = 0; i < 32; i++) o[i] = 0.f;
#pragma unroll 1
    for (int kk = 0; kk < DM / 16; kk++) {
      const uint32_t a0 = ld_word(xa + 8 * kk), a1 = ld_word(xa + 8 * kk + 4 * DM), a2 = ld_word(xa + 8 * kk + 4), a3 = ld_word(xa + 8 * kk + 4 * DM + 4);
#pragma unroll
      for (int n = 0; n < 8; n++) {
        const __nv_bfloat16* b = wb + (size_t)16 * kk * NQ + 32 * (n >> 2) + 2 * (n & 3);
        mma16816(o + 4 * n, a0, a1, a2, a3, ld_pair(b), ld_pair(b + 8 * NQ));
      }
    }
#pragma unroll
    for (int i = 0; i < 16; i++) { q[i] = q[16 + i]; q[16 + i] = pack_bf16(o[2 * i] * AT_C, o[2 * i + 1] * AT_C); }
  }
#pragma unroll 1
  for (int h = 0; h < 2; h++) {
    float m0 = -INFINITY, m1 = -INFINITY, l0 = 0.f, l1 = 0.f;
#pragma unroll
    for (int i = 0; i < 32; i++) o[i] = 0.f;
#pragma unroll 1
    for (int k0 = 0; k0 <= row0; k0 += 16) {
      float e[8] = {0.f, 0.f, 0.f, 0.f, 0.f, 0.f, 0.f, 0.f};
      const uint32_t* kp = reinterpret_cast<const uint32_t*>(g_kv + (size_t)(k0 + r) * NQ + head * HD) + c;
#pragma unroll
      for (int kk = 0; kk < 8; kk++) {
        mma16816(e, q[4 * kk], q[4 * kk + 1], q[4 * kk + 2], q[4 * kk + 3], ld_word(kp + 8 * kk), ld_word(kp + 8 * kk + 4));
        mma16816(e + 4, q[4 * kk], q[4 * kk + 1], q[4 * kk + 2], q[4 * kk + 3], ld_word(kp + 8 * kk + 4 * NQ), ld_word(kp + 8 * kk + 4 * NQ + 4));
      }
      if (k0 == row0) {
#pragma unroll
        for (int i = 0; i < 8; i++) if ((i >> 2) * 8 + 2 * c + (i & 1) > r + (i & 2) * 4) e[i] = -INFINITY;
      }
      float a0 = fmaxf(fmaxf(e[0], e[1]), fmaxf(e[4], e[5])), a1 = fmaxf(fmaxf(e[2], e[3]), fmaxf(e[6], e[7]));
      a0 = fmaxf(a0, __shfl_xor_sync(~0u, a0, 1)); a1 = fmaxf(a1, __shfl_xor_sync(~0u, a1, 1));
      a0 = fmaxf(a0, __shfl_xor_sync(~0u, a0, 2)); a1 = fmaxf(a1, __shfl_xor_sync(~0u, a1, 2));
      a0 = fmaxf(a0, m0); a1 = fmaxf(a1, m1);
      const float sc0 = ex2(m0 - a0), sc1 = ex2(m1 - a1);
      m0 = a0; m1 = a1;
#pragma unroll
      for (int i = 0; i < 8; i++) e[i] = ex2(e[i] - ((i & 2) ? m1 : m0));
      l0 = l0 * sc0 + (e[0] + e[1]) + (e[4] + e[5]);
      l1 = l1 * sc1 + (e[2] + e[3]) + (e[6] + e[7]);
      const uint32_t p0 = pack_bf16(e[0], e[1]), p1 = pack_bf16(e[2], e[3]), p2 = pack_bf16(e[4], e[5]), p3 = pack_bf16(e[6], e[7]);
      const __nv_bfloat16* vp = g_kv + (size_t)(SEQ + k0 + 2 * c) * NQ + head * HD + 64 * h + r;
#pragma unroll
      for (int n = 0; n < 8; n++) {
        o[4 * n] *= sc0; o[4 * n + 1] *= sc0; o[4 * n + 2] *= sc1; o[4 * n + 3] *= sc1;
        mma16816(o + 4 * n, p0, p1, p2, p3, ld_pair(vp + 8 * n), ld_pair(vp + 8 * n + 8 * NQ));
      }
    }
    l0 += __shfl_xor_sync(~0u, l0, 1); l1 += __shfl_xor_sync(~0u, l1, 1);
    l0 += __shfl_xor_sync(~0u, l0, 2); l1 += __shfl_xor_sync(~0u, l1, 2);
#pragma unroll
    for (int i = 0; i < 4; i++) {
      const float* v = o + 16 * (i >> 1) + 2 * (i & 1);
      const float f = __fdividef(1.f, (i & 1) ? l1 : l0);
      *reinterpret_cast<uint4*>(g_ctx + (size_t)(row0 + r + (i & 1) * 8) * NQ + head * HD + 64 * h + (i >> 1) * 32 + c * 8) =
          make_uint4(pack_bf16(v[0] * f, v[1] * f), pack_bf16(v[4] * f, v[5] * f), pack_bf16(v[8] * f, v[9] * f), pack_bf16(v[12] * f, v[13] * f));
    }
  }
}

constexpr int UNIT = 16384, SLOT = 32768;
constexpr int OFF_STG = 2 * SLOT;
__host__ __device__ constexpr int kv_a(int kb) { return (kb < 6 ? kb : 3 * kb - 10) * UNIT; }
__host__ __device__ constexpr int kv_b(int s) { return (s == 2 ? 6 : 9 + 3 * s) * UNIT; }
__host__ __device__ constexpr int q_aw(int s) { return (3 * s + (s & 1)) * UNIT; }
__host__ __device__ constexpr int q_b(int s) { return (3 * s + 2 - 2 * (s & 1)) * UNIT; }
__host__ __device__ constexpr int k_slot(int j, int r) { return (j < 2 ? 2 * j : (r == 2 ? 0 : 3 + r)) * SLOT; }
__host__ __device__ constexpr int v_slot(int j) { return (6 - (j & 1)) * SLOT; }
__host__ __device__ constexpr int r3(int st) { return (st + (st >= 2)) * SLOT; }
constexpr int OFF_BAR = 229376;
constexpr int OFF_MISC = OFF_BAR + 512;
constexpr int SMEM_BYTES = OFF_MISC + 2080 + TL_EXTRA;
constexpr int OFF_RSTAT = OFF_MISC + 1056;
enum : int {
  B_FULL1 = 0, B_FULLQ = 3, B_FULLB = 7, B_KF = 8, B_VF = 11, B_FULL3 = 13, B_WF = 19, B_DEP = 21, B_OUT2 = 26, B_PF = 27, B_SET = 28,
  B_SET2 = 29, B_LNGO = 30, B_WR = 31,
  B_KE = 32, B_VE = 35, B_WE = 37, B_PUB = 39, B_OUT = 45,
  B_EMPTY1 = 46, B_EMPTYQ = 49, B_X = 53, B_EMPTY3 = 57,
  B_NUM = 63
};
constexpr int PRE = 3;
#define LN_PF 5
#define LN_GO 9
#define PFW 1
#define PFX 9
#define PFKV 0
#define SYNC3 0
#define SYNC3A 5
#define SYNC3W 6
#define CTX_ST "st.global.v4.u32"
#define PF3 0
#define PD3 7
#define PFF 0
#define PWAIT mbar_wait_c
#define GRAB0 4
#define SIDE_NS 400
#define REL_AT 5
#define KV_FIRST 0
constexpr int WIN = 6;
constexpr int NIT = 64;
constexpr int NLATE = (8 - WIN) / 2;
constexpr int IT_WD = NIT + NLATE, OFF_SCR = r3((NIT + NLATE + 2) % 6);
#define PF_KB 52
#define PF_CLK 500
#define SET_KB 46
struct Params {
  CUtensorMap xn, ckv, wq, wk, wv, kv_ld, ctx_ld, wo, x, wd, wg, wu, out;
};

__global__ void __cluster_dims__(2, 1, 1) __launch_bounds__(384, 1)
fused_kernel(const __grid_constant__ Params p, const __nv_bfloat16* __restrict__ x, const __nv_bfloat16* __restrict__ wq,
             const __nv_bfloat16* __restrict__ w_r, const __nv_bfloat16* __restrict__ wgate, const __nv_bfloat16* __restrict__ wup,
             __nv_bfloat16* __restrict__ out) {
  extern __shared__ __align__(1024) uint8_t sp[];
  const uint32_t sb = s2u(sp);
  const uint32_t bar = sb + OFF_BAR;
  auto B = [&](int i) { return bar + 8 * i; };
  const int tid = threadIdx.x, warp = __shfl_sync(~0u, tid >> 5, 0), wg = warp >> 2, lane = tid & 31;
  const int cta = blockIdx.x, rank = cta & 1, cl = cta >> 1;
  const int mp = cl < 4 ? 1 : (cl < 36 ? (cl & 7) : (0x3207654 >> (4 * ((cl - 36) % 7))) & 7);
  const int gq = cl < 4 ? 4 + cl : (cl < 36 ? (cl - 4) >> 3 : 4 + (cl - 36) / 7);
  const int mt = 2 * mp + rank;
  const int qa = 15 - gq;
  const int rid = mt * 8 + gq;
  const int fid = mt * 7 + gq;
  const bool ffn = gq < 7;
  uint4* const xr = g_xr + rid * XR_SIZE;
  TL(0, 0, warp == 4);
  if (warp == 0) {
#pragma unroll 1
    for (int kb = 0; kb < PRE; kb++) {
      e_init(B(B_FULL1 + kb), 1);
      asm volatile("fence.mbarrier_init.release.cluster;" ::: "memory");
      e_expect(B(B_FULL1 + kb), 3 * UNIT);
      tma_ld2(sb + kv_a(kb), &p.ckv, B(B_FULL1 + kb), kb * 64, mt * 128);
      tma_ld3(sb + kv_b(kb) + rank * UNIT, &p.wk, B(B_FULL1 + kb), 0, kb * 64, (gq + KV_FIRST * 8) * 4 + rank * 2);
      tma_ld3(sb + kv_b(kb) + UNIT - rank * UNIT, &p.wk, B(B_FULL1 + kb), 0, kb * 64, (gq + KV_FIRST * 8) * 4 + 2 - rank * 2);
    }
  }
  if (warp > 0) {
#pragma unroll 1
    for (int i = PRE - 1 + warp; i < B_NUM; i += 11) e_init(B(i), i >= B_EMPTY1 ? 16 : (i >= B_KE ? 8 : (i == B_WR ? 2 : 1)));
    asm volatile("fence.mbarrier_init.release.cluster;" ::: "memory");
  }
  __syncwarp();
  cluster_arrive();
  if (warp == 1) {
    if (mt >= 2 * PRE) tma_pf3(&p.wk, 0, (mt >> 1) * 64, (gq + KV_FIRST * 8) * 4 + (mt & 1) * 2);
    if (gq >= PRE) tma_pf2(&p.ckv, gq * 64, mt * 128);
  } else if (warp == 2) {
    prefetch_tm(&p.wv); prefetch_tm(&p.wq); prefetch_tm(&p.xn); prefetch_tm(&p.kv_ld);
  }
  __syncwarp();
  cluster_wait();
  if (wg == 0) {
    reg_dealloc<40>();
    auto side_piece = [&](int c, int piece) {
      const uint32_t fb = B(B_WF + (c & 1));
      if (piece == 0) e_expect(fb, UNIT);
      tma_ld2(sb + OFF_STG + (c & 1) * UNIT + piece * 4096, (piece & 2) ? &p.wg : &p.wu, fb, fid * 32, c * 128 + (piece & 1) * 64);
    };
    if (warp == 0) {
      {
        int st = 0; uint32_t ph = 1;
#pragma unroll 1
        for (int i = 0; i < 32; i++) {
          const int t = i >> 3, kb = i & 7;
          if (i >= PRE) {
            const uint32_t fb = B(B_FULL1 + st);
            PWAIT(B(B_EMPTY1 + st), ph);
            e_expect(fb, t == 0 ? 3 * UNIT : 2 * UNIT);
            if (t == 0) tma_ld2(sb + kv_a(kb), &p.ckv, fb, kb * 64, mt * 128);
            tma_ld3_mc(sb + kv_b(st) + rank * UNIT, (t & 1) ? &p.wv : &p.wk, fb, 0, kb * 64, (gq + ((t >> 1) ^ KV_FIRST) * 8) * 4 + rank * 2, 3);
          }
          if (i == LN_PF || i == LN_PF + 1) l2_prefetch(x + (size_t)cta * 16 * DM + (i - LN_PF) * 8 * DM, 16384);
          if (i == LN_GO) e_arrive(B(B_LNGO));
          if (kb == 0 && t < 3) tma_pf3((t & 1) ? &p.wk : &p.wv, 0, (mt >> 1) * 64, (gq + (((t + 1) >> 1) ^ KV_FIRST) * 8) * 4 + (mt & 1) * 2);
          if (kb < 2 && t == 3) tma_pf3(&p.wq, 0, (gq + 8 * kb) * 64, mt * 2);
          if (++st == 3) { st = 0; ph ^= 1; }
        }
        prefetch_tm(&p.ctx_ld); prefetch_tm(&p.wo); prefetch_tm(&p.wd); prefetch_tm(&p.x); prefetch_tm(&p.wg); prefetch_tm(&p.wu);
        PWAIT(B(B_DEP + 0), 0);
        uint32_t kpar = 7, vpar = 3;
        auto load_aw = [&](int kb, int head) {
          const uint32_t d = sb + q_aw(kb & 3), fb = B(B_FULLQ + (kb & 3));
          tma_ld2_mc(d + rank * 8192, &p.xn, fb, kb * 64, qa * 128 + rank * 64, 3);
          tma_ld3(d + UNIT, &p.wq, fb, 0, kb * 64, head * 2);
        };
        auto load_b = [&](int kb, uint32_t fb) { tma_ld2_mc(sb + q_b(kb & 3) + rank * 8192, &p.xn, fb, kb * 64, gq * 128 + rank * 64, 3); };
        auto load3 = [&](int kb, int s) {
          const uint32_t d = sb + r3(s), fb = B(B_FULL3 + s);
          e_expect(fb, SLOT);
          tma_ld2(d, &p.ctx_ld, fb, kb * 64, mt * 128);
          tma_ld3_mc(d + UNIT + rank * 8192, &p.wo, fb, 0, kb * 64, gq * 2 + rank, 3);
        };
#pragma unroll 1
        for (int half = 0; half < 2; half++) {
          const int head = mt + 16 * half;
#pragma unroll 1
          for (int kb = 2 * half; kb < 16; kb++) {
            if (kb >= 4) PWAIT(B(B_EMPTYQ + (kb & 3)), ((kb >> 2) & 1) ^ 1);
            else if (half) PWAIT(B(B_X + 2), 0);
            else if (kb > 0) PWAIT(B(B_EMPTY1 + (kb + 1) % 3), kb == 1);
            e_expect(B(B_FULLQ + (kb & 3)), 3 * UNIT);
            load_aw(kb, head);
            load_b(kb, B(B_FULLQ + (kb & 3)));
          }
          PWAIT(B(B_DEP + 1 + half), 0);
          tma_pf3(&p.kv_ld, 0, 0, head * 2);
          auto load_v = [&](int j) {
            const int r = j & 1;
            PWAIT(B(B_VE + r), (vpar >> r) & 1);
            vpar ^= 1 << r;
            e_expect(B(B_VF + r), SLOT);
            tma_ld3(sb + v_slot(j), &p.kv_ld, B(B_VF + r), 0, SEQ + (j > qa ? j - qa - 1 : j) * 128, head * 2);
          };
          int r = 0;
#pragma unroll 1
          for (int j = 0; j < 17; j++) {
            if (j < 2) PWAIT(B(B_EMPTYQ + j), 1);
            if (j == 2) PWAIT(B(B_KE), kpar & 1);
            PWAIT(B(B_KE + r), (kpar >> r) & 1);
            kpar ^= 1 << r;
            e_expect(B(B_KF + r), SLOT);
            tma_ld3(sb + k_slot(j, r), &p.kv_ld, B(B_KF + r), 0, (j > qa ? j - qa - 1 : j) * 128, head * 2);
            if (++r == 3) r = 0;
            if (j == 2) PWAIT(B(B_EMPTYQ + 3), 1);
            if (j != 1) load_v(j ? j - 1 : 0);
            if (half == 0) {
              if (j == 1 + gq || j == 9 + gq) tma_pf3(&p.wq, 0, (j - 1) * 64, (mt + 16) * 2);
            } else if (ffn && j >= 5 && j < 13) {
              side_piece((j - 5) >> 2, (j - 5) & 3);
            }
          }
          PWAIT(B(B_X + 0), half);
          if (half == 0) {
            for (int kb = 0; kb < 2; kb++) { e_expect(B(B_FULLQ + kb), 2 * UNIT); load_aw(kb, mt + 16); }
          } else {
            PWAIT(B(B_DEP + 3), 0);
            load3(0, 0);
          }
          load_v(16);
          PWAIT(B(B_X + 1), half);
          if (half == 0) { e_expect(B(B_FULLB), 2 * UNIT); load_b(0, B(B_FULLB)); load_b(1, B(B_FULLB)); }
        }
        prefetch_tm(&p.out);
        st = 1; ph = 1;
#pragma unroll 1
        for (int kb = 1; kb < 64; kb++) {
          if (kb == 32) PWAIT(B(B_DEP + 4), 0);
          if (kb >= 6) PWAIT(B(B_EMPTY3 + st), ph);
          else if (kb == 3 || kb == 5) PWAIT(B(B_X + (kb + 1) / 2), 1);
          load3(kb, st);
          if (++st == 6) { st = 0; ph ^= 1; }
          if (kb == PF_KB) e_arrive(B(B_PF));
          if (kb == SET_KB) e_arrive(B(B_SET));
          if (kb == 58) l2_prefetch(xr, XR_CAND * 16);
        }
        if (ffn) {
#pragma unroll 1
          for (int j = 0; j < NLATE + 2; j++) {
            PWAIT(B(B_EMPTY3 + st), ph);
            const uint32_t d = sb + r3(st), fb = B(B_FULL3 + st);
            e_expect(fb, SLOT);
            if (j < NLATE) {
#pragma unroll 1
              for (int h = 0; h < 8; h++) tma_ld2(d + h * 4096, (h & 2) ? &p.wg : &p.wu, fb, fid * 32, (WIN + 2 * j + (h >> 2)) * 128 + (h & 1) * 64);
            } else {
              tma_ld3(d, &p.wd, fb, 0, fid * 32, 8 * (j - NLATE));
            }
            if (++st == 6) { st = 0; ph ^= 1; }
          }
        }
      }
    } else {
      if (warp >= 2) {
#pragma unroll 1
        for (int i = tid - 64; i < XR_CAND; i += 64) xr[i] = make_uint4(~0u, ~0u, ~0u, ~0u);
        if (warp == 2) { __syncwarp(); if (lane == 0) mbar_arrive(B(B_WR)); }
      }
      if (warp == 3) {
        float ws = 0.f;
#pragma unroll
        for (int j = 0; j < 4; j++) {
          const uint4 q = __ldg(reinterpret_cast<const uint4*>(w_r) + j * 32 + lane);
          ws += bf_lo(q.x) + bf_hi(q.x) + bf_lo(q.y) + bf_hi(q.y) + bf_lo(q.z) + bf_hi(q.z) + bf_lo(q.w) + bf_hi(q.w);
        }
#pragma unroll
        for (int o = 16; o; o >>= 1) ws += __shfl_xor_sync(~0u, ws, o);
        uint2* tab = reinterpret_cast<uint2*>(sp + OFF_MISC + 512);
        tab[lane] = make_uint2(0x3F803F80u, 0x3F803F80u);
        tab[32 + lane] = __ldg(reinterpret_cast<const uint2*>(w_r + gq * 128) + lane);
        if (lane == 0) *reinterpret_cast<float*>(sp + OFF_MISC + 1024) = ws;
        __syncwarp();
        if (lane == 0) mbar_arrive(B(B_WR));
      }
      __syncwarp();
      mbar_wait(B(B_LNGO), 0);
#pragma unroll 1
      for (int r = warp == 2 ? 0 : (warp + 1) >> 1; r < 16; r += 3) {
        const uint4* src = reinterpret_cast<const uint4*>(x + (size_t)(cta * 16 + r) * DM) + lane;
        uint4 v[4];
#pragma unroll
        for (int j = 0; j < 4; j++) v[j] = __ldg(src + j * 32);
        float a0 = 0.f, a1 = 0.f, b0 = 0.f, b1 = 0.f;
#pragma unroll
        for (int j = 0; j < 4; j++) {
          const uint32_t u[4] = {v[j].x, v[j].y, v[j].z, v[j].w};
#pragma unroll
          for (int i = 0; i < 4; i++) { const float a = bf_lo(u[i]), b = bf_hi(u[i]); a0 += a; a1 += b; b0 = fmaf(a, a, b0); b1 = fmaf(b, b, b1); }
        }
        a0 += a1; b0 += b1;
#pragma unroll
        for (int o = 16; o; o >>= 1) { a0 += __shfl_xor_sync(~0u, a0, o); b0 += __shfl_xor_sync(~0u, b0, o); }
        const float mean = a0 * (1.f / DM);
        float mb, inv;
        ln_round(mean, fmaxf(fmaf(b0, 1.f / DM, -mean * mean), 0.f), mb, inv);
        const uint32_t nm2 = pack_bf16(-mb, -mb);
        uint4* dst = reinterpret_cast<uint4*>(g_xn + (size_t)(cta * 16 + r) * DM) + lane;
#pragma unroll
        for (int j = 0; j < 4; j++)
          dst[j * 32] = make_uint4(ln_apply(v[j].x, nm2, inv), ln_apply(v[j].y, nm2, inv), ln_apply(v[j].z, nm2, inv), ln_apply(v[j].w, nm2, inv));
      }
      __syncwarp();
      if (lane == 0) {
        fence_gpu();
        red_add(&g_cnt[C_LN + (cta >> 3)], 1);
        TL(0, 20 + warp, true);
        if (warp == 3) {
          spin_until_ge<true>(&g_cnt[C_LN + gq], 24);
#pragma unroll 1
          for (int i = 0; i < 5; i++) {
            const int c = i == 0 ? C_LN + qa : (i < 3 ? C_KV + (i - 1) * 8 + mp : C_CTX + (i - 3) * 16 + mt);
            spin_until_ge<true>(&g_cnt[c], i == 0 ? 24 : 16);
            fence_async_all();
            mbar_arrive(B(B_DEP + i));
          }
        } else if (warp == 1) {
          mbar_wait(B(B_WR), 0);
#pragma unroll 1
          for (int i = 0; i < 6; i++) {
            const int c = i < 2 ? C_KV + gq + (i ^ KV_FIRST) * 8 : C_CTX + ((i - 2) >> 1) * 16 + ((i & 1) ? gq : qa);
            mbar_wait(B(B_PUB + i), 0);
            fence_gpu();
            red_add(&g_cnt[c], 1);
          }
        }
      }
      __syncwarp();
      if (warp == 1) {
#pragma unroll 1
        for (int c = 2; c < WIN + 2; c++) {
          mbar_wait(B(B_WE + (c & 1)), ((c >> 1) & 1) ^ 1);
          __syncwarp();
          if (c >= WIN) {
            e_expect(B(B_WF + (c & 1)), UNIT);
            tma_ld3(sb + OFF_STG + (c & 1) * UNIT, &p.x, B(B_WF + (c & 1)), 0, mt * 128 + (c & 1) * 64, gq * 2);
          } else if (ffn) {
#pragma unroll 1
            for (int i = 0; i < 4; i++) { side_piece(c, i); __nanosleep(SIDE_NS); }
          }
        }
      }
      if (warp == 2) {
        mbar_wait(B(B_SET), 0);
#pragma unroll 1
        for (int i = XR_CAND + lane; i < XR_SIZE; i += 32) xr[i] = make_uint4(~0u, ~0u, ~0u, ~0u);
        __syncwarp();
        if (lane == 0) { fence_gpu(); mbar_arrive(B(B_SET2)); }
        __syncwarp();
        mbar_wait(B(B_PF), 0);
        uint32_t t0;
        asm volatile("mov.u32 %0, %%clock;" : "=r"(t0));
        constexpr int NF = (8 - WIN) * 4;
#pragma unroll 1
        for (int i = 0; i < NF; i++) {
          const char* a = (const char*)(((i & 2) ? wgate : wup) + (size_t)((WIN + (i >> 2)) * 128 + cta) * FF) + min((i & 1) * 32 + lane, 55) * 128;
          asm volatile("prefetch.global.L2 [%0];" ::"l"(a));
#pragma unroll 1
          for (int n = 0; n < 64; n++) {
            __nanosleep(100);
            uint32_t t;
            asm volatile("mov.u32 %0, %%clock;" : "=r"(t));
            if (t - t0 >= (uint32_t)(i + 1) * PF_CLK) break;
          }
        }
      }
      __syncwarp();
      mbar_wait(B(B_OUT), 0);
#pragma unroll 1
      for (int i = warp - 1; i < 64; i += 3) {
        const int row = 2 * i + (lane >> 4);
        const uint2 rs = *reinterpret_cast<const uint2*>(sp + OFF_RSTAT + row * 8);
        uint4* q = reinterpret_cast<uint4*>(sp + OFF_STG + (row >> 6) * 16384 + ((lane & 15) >> 3) * 8192 + (row & 63) * 128 + ((lane & 7) << 4));
        const uint4 v = *q;
        const float inv = __uint_as_float(rs.y);
        *q = make_uint4(hadd2_bf(v.x, ln_apply(v.x, rs.x, inv)), hadd2_bf(v.y, ln_apply(v.y, rs.x, inv)),
                        hadd2_bf(v.z, ln_apply(v.z, rs.x, inv)), hadd2_bf(v.w, ln_apply(v.w, rs.x, inv)));
      }
      asm volatile("fence.proxy.async.shared::cta;" ::: "memory");
      bar_sync(4, 96);
      if (warp == 1) {
        mbar_wait(B(B_OUT2), 0);
        const uint32_t* keys = reinterpret_cast<const uint32_t*>(sp + OFF_MISC);
        const int t0 = 0x7FFF - (keys[16] & 0x7FFF) - mt * 128, t1 = 0x7FFF - (keys[17] & 0x7FFF) - mt * 128;
        const int grp = lane >> 1;
        if (grp != (t0 >> 3) && grp != (t1 >> 3))
          asm volatile("cp.async.bulk.tensor.2d.global.shared::cta.bulk_group [%0, {%2,%3}], [%1];" ::"l"(&p.out),
                       "r"(sb + OFF_STG + (grp >> 3) * 16384 + (lane & 1) * 8192 + (grp & 7) * 1024), "r"(gq * 128 + (lane & 1) * 64), "r"(mt * 128 + grp * 8) : "memory");
        asm volatile("cp.async.bulk.commit_group;" ::: "memory");
#pragma unroll 1
        for (int k = 0; k < 8; k++) {
          const int tt = k < 4 ? t0 : t1, row = (tt & ~7) + (k & 3) * 2 + (lane >> 4);
          if (tt >= 0 && tt < 128 && row != t0 && row != t1)
            *reinterpret_cast<uint4*>(out + (size_t)(mt * 128 + row) * DM + gq * 128 + (lane & 15) * 8) =
                lds128(sb + OFF_STG + (row >> 6) * 16384 + ((lane & 15) >> 3) * 8192 + (row & 63) * 128 + (((lane & 7) ^ (row & 7)) << 4));
        }
        asm volatile("cp.async.bulk.wait_group.read 0;" ::: "memory");
      }
      TL(2, 25, warp == 1);
    }
    __syncwarp();
    cluster_arrive();
    cluster_wait();
  } else {
    reg_alloc<232>();
    const int w = wg - 1, cw = warp - 4, ct = tid - 128;
    const uint32_t stg = sb + OFF_STG + w * 16384 + (cw & 3) * 2048;
    auto publish = [&](int i) { __syncwarp(); e_arrive(B(B_PUB + i)); };
    auto release2 = [&](uint32_t b, bool cond = true) { mbar_arrive_both(b, lane, cond); };
    AtState s;
    const uint32_t dA = mk_desc(sb + w * 8192, 16);
    const uint32_t dW = mk_desc(sb, 8192);
    auto mma_kb = [&](float (&d)[64], uint32_t a, uint32_t b, int accum) {
      static_for<4>([&](auto k) { mma_n128_ss<1, k * 32, k * 2048>(d, dA + (a >> 4), dW + (b >> 4), k == 0 ? accum : 1); });
    };
    auto mma_kc = [&](float (&d)[64], auto a, auto b, int accum) {
      static_for<4>([&](auto k) { mma_n128_ss<1, decltype(a)::value + k * 32, decltype(b)::value + k * 2048>(d, dA, dW, k == 0 ? accum : 1); });
    };
    auto issue_q = [&](int kb, int accum) {
      const int st = kb & 3;
      mbar_wait_c(B(B_FULLQ + st), (kb >> 2) & 1);
      wg_fence();
      mma_kb(s.S, q_aw(st), q_aw(st) + UNIT, accum);
      mma_kb(s.O, q_b(st), q_aw(st) + UNIT, accum);
      wg_commit();
    };
    {
      uint4 pk[16];
      __nv_bfloat16* pdst = g_kv;
      auto put = [&](int i) { __stcs(reinterpret_cast<uint4*>(pdst + (i & 1) * 8 * NQ + (i >> 1) * 32), pk[i]); };
      float acc1[128];
      TL(0, 1, warp == 4);
      int st = 0; uint32_t ph = 0;
      auto issue = [&](int kb, int accum) {
        mbar_wait_c(B(B_FULL1 + st), ph);
        wg_fence();
        static_for<4>([&](auto k) { mma_n256_ss<1, k * 32, k * 2048>(acc1, dA + (kv_a(kb) >> 4), dW + (kv_b(st) >> 4), k == 0 ? accum : 1); });
        wg_commit();
      };
#pragma unroll 1
      for (int t = 0; t < 4; t++) {
        issue(0, 0);
        TL(0, 2 + 2 * t, warp == 4);
        if (t > 0) { put(0); put(1); }
        int prev = st;
        if (++st == 3) { st = 0; ph ^= 1; }
#pragma unroll 1
        for (int kb = 1; kb < 8; kb++) {
          if (kb == 7 && w == 1) bar_sync(5, 256);
          issue(kb, 1);
          if (kb == 7 && w == 0) bar_arrive(5, 256);
          if (t > 0) {
#pragma unroll
            for (int i = 1; i < 8; i++) if (kb == i) { put(2 * i); put(2 * i + 1); }
            if (kb == 7 && t == 2) publish(0);
          }
          wg_wait<1>();
          release2(B(B_EMPTY1 + prev));
          prev = st;
          if (++st == 3) { st = 0; ph ^= 1; }
        }
        pdst = g_kv + (size_t)((t & 1) * SEQ + mt * 128 + cw * 16 + (lane >> 2)) * NQ + (gq + ((t >> 1) ^ KV_FIRST) * 8) * 256 + (lane & 3) * 8;
        wg_wait<0>();
        fence_regs(acc1);
        release2(B(B_EMPTY1 + prev));
        TL(0, 3 + 2 * t, warp == 4);
#pragma unroll
        for (int a = 0; a < 8; a++)
#pragma unroll
          for (int h = 0; h < 2; h++)
            pk[2 * a + h] = make_uint4(pack_bf16(acc1[16 * a + 2 * h], acc1[16 * a + 2 * h + 1]), pack_bf16(acc1[16 * a + 4 + 2 * h], acc1[16 * a + 5 + 2 * h]),
                                       pack_bf16(acc1[16 * a + 8 + 2 * h], acc1[16 * a + 9 + 2 * h]), pack_bf16(acc1[16 * a + 12 + 2 * h], acc1[16 * a + 13 + 2 * h]));
      }
      issue_q(0, 0);
      TL(0, 10, warp == 4);
      put(0); put(1);
#pragma unroll 1
      for (int kb = 1; kb < 8; kb++) {
        issue_q(kb, 1);
#pragma unroll
        for (int i = 1; i < 8; i++) if (kb == i) { put(2 * i); put(2 * i + 1); }
        wg_wait<1>();
        release2(B(B_EMPTYQ + ((kb - 1) & 3)));
      }
      publish(1);
      TL(0, 11, warp == 4);
    }
    {
      const int wrow = cw * 16;
      const uint32_t dK = mk_desc(sb, 16), dV = mk_desc(sb, 16384);
      uint32_t kph = 0, vph = 0;
      auto q_store = [&](const float (&d)[64]) {
        const int r0 = lane >> 2;
        const uint32_t a = sb + SLOT + (wrow + r0) * 128 + (((lane & 3) ^ (((r0 & 1) << 2) | (r0 >> 1))) << 4);
#pragma unroll
        for (int i = 0; i < 8; i++) {
          const float* o = d + 16 * (i >> 1) + 2 * (i & 1);
          asm volatile("st.shared.v4.u32 [%0], {%1,%2,%3,%4};" ::"r"((a ^ ((i & 2) << 5)) + (i >> 2) * UNIT + (i & 1) * 1024),
                       "r"(pack_bf16(o[0] * AT_C, o[1] * AT_C)), "r"(pack_bf16(o[4] * AT_C, o[5] * AT_C)),
                       "r"(pack_bf16(o[8] * AT_C, o[9] * AT_C)), "r"(pack_bf16(o[12] * AT_C, o[13] * AT_C)) : "memory");
        }
        __syncwarp();
      };
      auto q_load = [&]() {
        const uint32_t a = sb + SLOT + (wrow + (lane & 15)) * 128 + (((lane >> 4) ^ (((lane & 1) << 2) | ((lane >> 1) & 3))) << 4);
#pragma unroll
        for (int k = 0; k < 8; k++)
          asm volatile("ldmatrix.sync.aligned.m8n8.x4.shared.b16 {%0,%1,%2,%3}, [%4];"
                       : "=r"(s.Q[4 * k]), "=r"(s.Q[4 * k + 1]), "=r"(s.Q[4 * k + 2]), "=r"(s.Q[4 * k + 3]) : "r"((a ^ ((k & 3) << 5)) + (k >> 2) * UNIT) : "memory");
      };
      auto issue_s = [&](uint32_t off) {
        static_for<8>([&](auto k) { mma_n128_rs<0, (k >> 2) * 16384 + (k & 3) * 32>(s.S, s.Q + 4 * k, dK + (off >> 4), k != 0); });
        wg_commit();
      };
      auto issue_pv = [&](int jv, int accum) {
        mbar_wait_c(B(B_VF + (jv & 1)), (vph >> (jv & 1)) & 1);
        vph ^= 1 << (jv & 1);
        wg_fence();
        static_for<8>([&](auto k) {
          mma_n128_rs<1, k * 2048>(s.O, s.P + 4 * k, dV + (v_slot(jv) >> 4), k == 0 ? accum : 1);
          if ((k & 3) == 3) wg_commit();
        });
      };
      if (w == 1) bar_arrive(1, 256);
#pragma unroll 1
      for (int half = 0; half < 2; half++) {
        const int head = mt + 16 * half;
        uint32_t redo = 0;
        auto epilogue = [&](int qt, float l0, float l1, auto between) {
          l0 += __shfl_xor_sync(~0u, l0, 1); l1 += __shfl_xor_sync(~0u, l1, 1);
          l0 += __shfl_xor_sync(~0u, l0, 2); l1 += __shfl_xor_sync(~0u, l1, 2);
          const float inv[2] = {__fdividef(1.f, l0), __fdividef(1.f, l1)};
          const bool bad = __any_sync(~0u, !(l0 >= L_MIN && l0 <= L_MAX && l1 >= L_MIN && l1 <= L_MAX));
          __nv_bfloat16* dst = g_ctx + (size_t)(qt * 128 + wrow + (lane >> 2)) * NQ + head * 128 + (lane & 3) * 8;
          auto one = [&](auto ic) {
            constexpr int i = decltype(ic)::value;
            between(ic);
            const float* o = s.O + 16 * (i >> 1) + 2 * (i & 1);
            const float c = inv[i & 1];
            asm volatile(CTX_ST " [%0], {%1,%2,%3,%4};" ::"l"(dst + (i & 1) * 8 * NQ + (i >> 1) * 32), "r"(pack_bf16(o[0] * c, o[1] * c)),
                         "r"(pack_bf16(o[4] * c, o[5] * c)), "r"(pack_bf16(o[8] * c, o[9] * c)), "r"(pack_bf16(o[12] * c, o[13] * c)) : "memory");
          };
          static_for<8>(one);
          return bad;
        };
        auto nothing = [](auto) {};
#pragma unroll 1
        for (int kb = half ? 2 : 8; kb < 14; kb++) {
          issue_q(kb, 1);
          wg_wait<1>();
          release2(B(B_EMPTYQ), kb == 2);
          release2(B(B_EMPTYQ + ((kb - 1) & 3)));
        }
        TL(1, 20 * half + 0, warp == 4);
        mbar_wait_c(B(B_FULLQ + 2), 1);
        mbar_wait_c(B(B_FULLQ + 3), 1);
        bar_sync(1 + w, 256);
        wg_fence();
        mma_kc(s.S, IC<q_aw(2)>{}, IC<q_aw(2) + UNIT>{}, 1);
        mma_kc(s.S, IC<q_aw(3)>{}, IC<q_aw(3) + UNIT>{}, 1);
        wg_commit();
        bar_arrive(2 - w, 256);
        wg_wait<1>();
        release2(B(B_EMPTYQ + 1));
        bar_sync(6 + w, 128);
        wg_wait<0>();
        fence_regs(s.S);
        q_store(s.S);
        q_load();
        TL(1, 20 * half + 1, warp == 4);
        mbar_wait_c(B(B_KF), kph & 1);
        kph ^= 1;
        bar_sync(1 + w, 256);
        fence_regs(s.S); fence_regs(s.O); fence_regs(s.Q);
        wg_fence();
        issue_s(k_slot(0, 0));
        mma_kc(s.O, IC<q_b(2)>{}, IC<q_aw(2) + UNIT>{}, 1);
        mma_kc(s.O, IC<q_b(3)>{}, IC<q_aw(3) + UNIT>{}, 1);
        wg_commit();
        bar_arrive(2 - w, 256);
        wg_wait<1>();
        fence_regs(s.S);
        e_arrive(B(B_KE));
        s.l[0] = s.l[1] = s.l[2] = s.l[3] = 0.f;
        at_exp<0, 48>(s);
        at_pack<0, 22>(s);
        sched_fence();
        wg_wait<0>();
        fence_regs(s.O);
        release2(B(B_EMPTYQ + 2)); release2(B(B_EMPTYQ + 3));
        at_exp<48, 64>(s);
        at_pack<22, 32>(s);
        q_store(s.O);
        TL(1, 20 * half + 2, warp == 4);
        int j = 1, kr = 1;
        auto step = [&](auto kind_c, bool first_, int pv_acc) {
          constexpr int KIND = decltype(kind_c)::value;
          TC(w, j + 17 * half, 0);
          mbar_wait_c(B(B_KF + kr), (kph >> kr) & 1);
          kph ^= 1 << kr;
          bar_sync(1 + w, 256);
          TC(w, j + 17 * half, 2);
          fence_regs(s.S); fence_regs(s.O); fence_regs(s.P); fence_regs(s.Q);
          wg_fence();
          issue_s(k_slot(j, kr));
          issue_pv(j - 1, pv_acc);
          bar_arrive(2 - w, 256);
          const float l0 = s.l[0] + s.l[1], l1 = s.l[2] + s.l[3];
          if (KIND == 1 || (KIND == 2 && first_)) s.l[0] = s.l[1] = s.l[2] = s.l[3] = 0.f;
          wg_wait<2>();
          TC(w, j + 17 * half, 4);
          fence_regs(s.S); fence_regs(s.Q);
          e_arrive(B(B_KE + kr));
          auto pv_half = [&]() { sched_fence(); wg_wait<1>(); fence_regs(s.P); };
          auto pv_done = [&]() {
            sched_fence();
            wg_wait<0>();
            fence_regs(s.O); fence_regs(s.P);
            e_arrive(B(B_VE + ((j - 1) & 1)));
          };
          if (KIND == 2) {
            q_load();
            if (w == 0) {
              at_mask<0>(s, wrow, lane);
              at_exp<0, 16>(s);
              pv_half();
              at_exp<16, 32>(s);
              at_pack<0, 16>(s);
              pv_done();
#pragma unroll
              for (int i = 16; i < 32; i++) s.P[i] = 0;
            } else {
              at_mask<8>(s, wrow - 64, lane);
              at_exp<0, 4 * SP1 - 4>(s);
              pv_half();
              at_exp<4 * SP1 - 4, 4 * SP2 - 4>(s);
              at_pack<0, 16>(s);
              pv_done();
              at_exp<4 * SP2 - 4, 64>(s);
              at_pack<16, 32>(s);
            }
            if (first_) { if (epilogue(qa, l0, l1, nothing)) redo = 1; else publish(2 + 2 * half); }
          } else {
            at_exp<0, 4 * SP1>(s);
            pv_half();
            at_exp<4 * SP1, 4 * SP2>(s);
            at_pack<0, 16>(s);
            pv_done();
            if (KIND == 1) {
              const bool bad = epilogue(qa, l0, l1, [&](auto ic) {
                constexpr int n = (64 - 4 * SP2) / 8, i0 = 4 * SP2 + decltype(ic)::value * n;
                at_exp<i0, i0 + n>(s);
              });
              at_pack<16, 32>(s);
              if (bad) redo = 1; else publish(2 + 2 * half);
            } else {
              at_exp<4 * SP2, 64>(s);
              at_pack<16, 32>(s);
            }
          }
          release2(B(B_X + j - 14), j >= 14);
          if (++kr == 3) kr = 0;
          TL(1, 20 * half + 2 + j, warp == 4);
          j++;
        };
#pragma unroll 1
        for (int t = 0; t < 2; t++) {
          const int qt = t ? gq : qa;
          if (t && qt > 0) step(IC<1>{}, true, 1);
#pragma unroll 1
          for (int i = 1; i < qt; i++) step(IC<0>{}, false, i != 1);
          step(IC<2>{}, qt == 0, qt != 1);
        }
        bar_sync(1 + w, 256);
        fence_regs(s.S); fence_regs(s.O); fence_regs(s.P);
        issue_pv(16, gq != 0);
        mbar_wait_c(B(half ? B_FULL3 : B_FULLQ), 0);
        wg_fence();
        mma_kc(s.S, IC<0>{}, IC<UNIT>{}, 0);
        mbar_wait_c(B(half ? B_FULL3 + 1 : B_FULLQ + 1), 0);
        wg_fence();
        mma_kb(s.S, (2 - half) * SLOT, (2 - half) * SLOT + UNIT, 1);
        wg_commit();
        if (w == 0 || half == 0) bar_arrive(2 - w, 256);
        wg_wait<1>();
        fence_regs(s.O);
        e_arrive(B(B_VE));
        release2(B(B_X + 3));
        if (epilogue(gq, s.l[0] + s.l[1], s.l[2] + s.l[3], [&](auto ic) {
              if (ic == REL_AT) {
                wg_wait<0>();
                release2(B(B_EMPTY3), half); release2(B(B_EMPTY3 + 1), half);
              }
            })) redo |= 2;
        fence_regs(s.S);
        if (__builtin_expect(__any_sync(~0u, redo != 0), 0)) {
#pragma unroll 1
          for (int t = 0; t < 2; t++) {
            if (__any_sync(~0u, (redo >> t) & 1)) slow_rows(wq, head, (t ? gq : qa) * 128 + wrow, lane);
          }
          if (__any_sync(~0u, redo & 1)) publish(2 + 2 * half);
#pragma unroll
          for (int i = 0; i < 64; i++) s.O[i] = 0.f;
        }
        publish(3 + 2 * half);
        TL(1, 20 * half + 19, warp == 4);
        if (half) break;
        mbar_wait_c(B(B_FULLB), 0);
        fence_regs(s.O);
        wg_fence();
        mma_kc(s.O, IC<q_b(0)>{}, IC<q_aw(0) + UNIT>{}, 0);
        mma_kc(s.O, IC<q_b(1)>{}, IC<q_aw(1) + UNIT>{}, 1);
        wg_commit();
      }
    }
    const int wr_ = cw * 16 + (lane & 7) + (lane >> 4) * 8;
    const uint32_t wl = sb + wr_ * 64 + ((((lane >> 3) & 1) ^ ((wr_ >> 1) & 3)) << 4);
    __syncwarp();
    float (&acc)[64] = s.S;
    uint32_t wf[128];
    {
      int st = 2, prev = 2; uint32_t ph = 0;
      auto run = [&](int k0, int k1) {
#pragma unroll 1
        for (int kb = k0; kb < k1; kb++) {
          mbar_wait_c(B(B_FULL3 + st), ph);
          wg_fence();
          mma_kb(acc, r3(st), r3(st) + UNIT, 1);
          wg_commit();
          wg_wait<1>();
          release2(B(B_EMPTY3 + prev), prev != st);
          prev = st;
          if (++st == 6) { st = 0; ph ^= 1; }
          if ((kb & 7) == 7) TL(2, 2 + (kb >> 3), warp == 4);
        }
      };
      static_for<WIN>([&](auto c) {
        run(c == 0 ? 2 : GRAB0 + 8 * c - 8, GRAB0 + 8 * c);
        if (ffn) mbar_wait_c(B(B_WF + (c & 1)), (c >> 1) & 1);
#pragma unroll
        for (int m = 0; m < 4; m++)
          asm volatile("ldmatrix.sync.aligned.m8n8.x4.trans.shared.b16 {%0,%1,%2,%3}, [%4];"
                       : "=r"(wf[16 * c + 4 * m]), "=r"(wf[16 * c + 4 * m + 1]), "=r"(wf[16 * c + 4 * m + 2]), "=r"(wf[16 * c + 4 * m + 3])
                       : "r"((wl + OFF_STG + (c & 1) * UNIT + (m >> 1) * 8192) ^ ((m & 1) << 5)) : "memory");
        e_arrive(B(B_WE + (c & 1)));
      });
      run(GRAB0 + 8 * WIN - 8, 64);
    }
    const int r0 = lane >> 2;
    uint32_t hp[32], tb[16];
    mbar_wait_c(B(B_WF + w), ffn ? (WIN >> 1) & 1 : 0);
    mbar_wait_c(B(B_WR), 0);
    mbar_wait_c(B(B_SET2), 0);
#pragma unroll
    for (int j = 0; j < 16; j++) {
      const uint32_t q = stg + r0 * 128 + (lane & 3) * 4 + (j >> 3) * 8192 + (((j & 7) ^ r0) << 4);
      asm volatile("ld.shared.u32 %0, [%1];" : "=r"(hp[2 * j]) : "r"(q) : "memory");
      asm volatile("ld.shared.u32 %0, [%1];" : "=r"(hp[2 * j + 1]) : "r"(q + 1024) : "memory");
      asm volatile("ld.shared.u32 %0, [%1];" : "=r"(tb[j]) : "r"(sb + OFF_MISC + 512 + (r0 & 1) * 256 + (lane & 3) * 4 + j * 16) : "memory");
    }
    wg_wait<0>();
    fence_regs(acc);
    TL(2, 10, warp == 4);
    {
      float d[4] = {0.f, 0.f, 0.f, 0.f}, qa[4] = {0.f, 0.f, 0.f, 0.f}, qb[4] = {0.f, 0.f, 0.f, 0.f};
#pragma unroll
      for (int j = 0; j < 16; j++) {
        hp[2 * j] = hadd2_bf(hp[2 * j], pack_bf16(acc[4 * j], acc[4 * j + 1]));
        hp[2 * j + 1] = hadd2_bf(hp[2 * j + 1], pack_bf16(acc[4 * j + 2], acc[4 * j + 3]));
        if (j & 1) {
          mma16816(d, hp[2 * j - 2], hp[2 * j - 1], hp[2 * j], hp[2 * j + 1], tb[j - 1], tb[j]);
          mma16816(qa, hp[2 * j - 2], hp[2 * j - 1], hp[2 * j], hp[2 * j + 1], hp[2 * j - 2], hp[2 * j]);
          mma16816(qb, hp[2 * j - 2], hp[2 * j - 1], hp[2 * j], hp[2 * j + 1], hp[2 * j - 1], hp[2 * j + 1]);
        }
      }
      const float s2a = __shfl_sync(~0u, (r0 & 1) ? qa[1] : qa[0], r0 * 4 + (r0 >> 1));
      const float s2b = __shfl_sync(~0u, (r0 & 1) ? qb[3] : qb[2], r0 * 4 + (r0 >> 1));
      if ((lane & 3) == 0) {
        __stcg(reinterpret_cast<float4*>(xr + XR_PS + cw * 16 + r0), make_float4(d[0], s2a, d[1], 0.f));
        __stcg(reinterpret_cast<float4*>(xr + XR_PS + cw * 16 + r0 + 8), make_float4(d[2], s2b, d[3], 0.f));
      }
    }
    __syncwarp();
    stage_store_128(stg, lane, hp);
    TL(2, 11, warp == 4);
    __syncwarp();
    uint32_t* keys = reinterpret_cast<uint32_t*>(sp + OFF_MISC);
    {
      uint4 ps[4];
      poll_chunks(ps, g_xr + (mt * 8 + (ct & 1) * 4) * XR_SIZE + XR_PS + (ct >> 1), XR_SIZE);
      TL(2, 12, warp == 4);
      auto F = [](uint32_t u) { return __uint_as_float(u); };
      float s1 = (F(ps[0].x) + F(ps[1].x)) + (F(ps[2].x) + F(ps[3].x)), s2 = (F(ps[0].y) + F(ps[1].y)) + (F(ps[2].y) + F(ps[3].y));
      float s3 = (F(ps[0].z) + F(ps[1].z)) + (F(ps[2].z) + F(ps[3].z));
      s1 += __shfl_xor_sync(~0u, s1, 1); s2 += __shfl_xor_sync(~0u, s2, 1); s3 += __shfl_xor_sync(~0u, s3, 1);
      const float mean = s1 * (1.f / DM);
      float mb, inv;
      ln_round(mean, fmaxf(fmaf(s2, 1.f / DM, -mean * mean), 0.f), mb, inv);
      uint32_t u = pack_bf16((s3 - mb * *reinterpret_cast<const float*>(sp + OFF_MISC + 1024)) * inv, 0.f);
      if (u == 0x8000u) u = 0;
      u = (u & 0x8000u) ? (~u & 0xFFFFu) : (u | 0x8000u);
      const uint32_t key = (u << 16) | (0x7FFFu - (mt * 128 + (ct >> 1)));
      const uint32_t nm2 = pack_bf16(-mb, -mb);
      if (!(ct & 1)) *reinterpret_cast<uint2*>(sp + OFF_RSTAT + (ct >> 1) * 8) = make_uint2(nm2, __float_as_uint(inv));
      const uint32_t c1 = __reduce_max_sync(~0u, key);
      const uint32_t c2 = __reduce_max_sync(~0u, key == c1 ? 0u : key);
      if (lane == 0) __stcg(reinterpret_cast<uint2*>(xr + XR_KEY) + cw, make_uint2(c1, c2));
      const int row = (0x7FFF - (((lane >> 4) ? c2 : c1) & 0x7FFF)) & 15;
      const uint32_t rn = __shfl_sync(~0u, nm2, row * 2);
      const float ri = __shfl_sync(~0u, inv, row * 2);
      const uint4 v = lds128(stg + ((lane & 15) >> 3) * 8192 + row * 128 + (((lane & 7) ^ (row & 7)) << 4));
      __stcg(xr + XR_CAND + cw * 64 + 32 + lane, make_uint4(ln_apply(v.x, rn, ri), ln_apply(v.y, rn, ri), ln_apply(v.z, rn, ri), ln_apply(v.w, rn, ri)));
      __stcg(xr + XR_CAND + cw * 64 + lane, v);
    }
    publish(B_OUT - B_PUB);
    TL(2, 13, warp == 4);
    uint32_t wd[16][4];
    if (cw == 0) {
        uint4 kv[2];
        poll_chunks(kv, g_xr + ((lane >> 1) * 8 + gq) * XR_SIZE + XR_KEY + (lane & 1) * 2, 1);
        const uint32_t a1 = max(kv[0].x, kv[0].z), a2 = max(min(kv[0].x, kv[0].z), max(kv[0].y, kv[0].w));
        const uint32_t b1 = max(kv[1].x, kv[1].z), b2 = max(min(kv[1].x, kv[1].z), max(kv[1].y, kv[1].w));
        const uint32_t k1 = max(a1, b1), k2 = max(min(a1, b1), max(a2, b2));
        const uint32_t m1 = __reduce_max_sync(~0u, k1);
        const uint32_t m2 = __reduce_max_sync(~0u, k1 == m1 ? k2 : k1);
        if (lane == 0) {
          keys[16] = m1; keys[17] = m2;
          mbar_arrive(B(B_OUT2));
        }
    }
    bar_sync(3, 256);
    cluster_arrive();
    const uint32_t top1 = keys[16], top2 = keys[17];
    TL(2, 14, warp == 4);
    const int t0 = 0x7FFF - (top1 & 0x7FFF), t1 = 0x7FFF - (top2 & 0x7FFF);
    auto cand = [&](int second, int chunk) {
      const int tk = second ? t1 : t0;
      return g_xr + ((tk >> 7) * 8 + (chunk >> 4)) * XR_SIZE + XR_CAND + ((tk >> 4) & 7) * 64 + ((second && (t0 >> 4) == (t1 >> 4)) ? 16 : 0) + (chunk & 15);
    };
    if (rid == 127 && ct < C_NUM) g_cnt[ct] = 0;
    if (ffn) {
      const int c8 = ct & 127;
      *reinterpret_cast<uint4*>(sp + OFF_SCR + w * 2064 + c8 * 16) = poll_chunk(cand(w, c8) + 32);
#pragma unroll
      for (int c = WIN; c < 8; c++) {
        const int it = NIT + (c - WIN) / 2;
        if (((c - WIN) & 1) == 0) mbar_wait_c(B(B_FULL3 + it % 6), (it / 6) & 1);
#pragma unroll
        for (int m = 0; m < 4; m++)
          asm volatile("ldmatrix.sync.aligned.m8n8.x4.trans.shared.b16 {%0,%1,%2,%3}, [%4];"
                       : "=r"(wf[16 * c + 4 * m]), "=r"(wf[16 * c + 4 * m + 1]), "=r"(wf[16 * c + 4 * m + 2]), "=r"(wf[16 * c + 4 * m + 3])
                       : "r"((wl + r3(it % 6) + ((c - WIN) & 1) * 16384 + (m >> 1) * 8192) ^ ((m & 1) << 5)) : "memory");
      }
      bar_sync(3, 256);
      TL(2, 15, warp == 4);
      float d[4][4];
#pragma unroll
      for (int m = 0; m < 4; m++) d[m][0] = d[m][1] = d[m][2] = d[m][3] = 0.f;
#pragma unroll
      for (int k = 0; k < 8; k++) {
        const uint8_t* bp = sp + OFF_SCR + (r0 & 1) * 2064 + (k * 128 + cw * 16 + (lane & 3) * 2) * 2;
        const uint32_t b0 = *reinterpret_cast<const uint32_t*>(bp), b1 = *reinterpret_cast<const uint32_t*>(bp + 16);
#pragma unroll
        for (int m = 0; m < 4; m++) mma16816(d[m], wf[16 * k + 4 * m], wf[16 * k + 4 * m + 1], wf[16 * k + 4 * m + 2], wf[16 * k + 4 * m + 3], b0, b1);
      }
      float* red = reinterpret_cast<float*>(sp + OFF_SCR + 8192);
      if ((lane & 3) == 0) {
#pragma unroll
        for (int m = 0; m < 4; m++) {
          *reinterpret_cast<float2*>(red + cw * 128 + (m * 16 + r0) * 2) = make_float2(d[m][0], d[m][1]);
          *reinterpret_cast<float2*>(red + cw * 128 + (m * 16 + 8 + r0) * 2) = make_float2(d[m][2], d[m][3]);
        }
      }
      const int wds = w ? (IT_WD + 1) % 6 : IT_WD % 6;
      mbar_wait_c(B(B_FULL3 + wds), w ? ((IT_WD + 1) / 6) & 1 : (IT_WD / 6) & 1);
#pragma unroll
      for (int i = 0; i < 16; i++) {
        const int k = (i & 1) * 16 + (lane & 7) + (lane >> 4) * 8;
        asm volatile("ldmatrix.sync.aligned.m8n8.x4.trans.shared.b16 {%0,%1,%2,%3}, [%4];"
                     : "=r"(wd[i][0]), "=r"(wd[i][1]), "=r"(wd[i][2]), "=r"(wd[i][3])
                     : "r"(sb + (w ? r3((IT_WD + 1) % 6) : r3(IT_WD % 6)) + (2 * (cw & 3) + (i >> 3)) * 4096 + k * 128 + (((2 * ((i >> 1) & 3) + ((lane >> 3) & 1)) ^ (lane & 7)) << 4)) : "memory");
      }
      bar_sync(3, 256);
      TL(2, 16, warp == 4);
      if (ct < 64) {
        float u = 0.f, gg = 0.f;
#pragma unroll
        for (int i = 0; i < 8; i++) { u += red[i * 128 + ct]; gg += red[i * 128 + 64 + ct]; }
        u = bf_round(u); gg = bf_round(gg);
        const float sg = bf_round(__fdividef(gg, 1.f + __expf(-gg)));
        reinterpret_cast<__nv_bfloat16*>(sp + OFF_MISC + 128)[(ct & 1) * 40 + (ct >> 1)] = __float2bfloat16_rn(sg * u);
      }
      bar_sync(3, 256);
      TL(2, 17, warp == 4);
      const uint32_t* ap = reinterpret_cast<const uint32_t*>(sp + OFF_MISC + 128 + (r0 & 1) * 80 + (lane & 3) * 4);
      const uint32_t a0 = ap[0], a1 = ap[4], a2 = ap[8], a3 = ap[12];
      float2* yp = reinterpret_cast<float2*>(sp + OFF_SCR + 16384) + cw * 128 + r0;
#pragma unroll
      for (int i = 0; i < 8; i++) {
        float y[4] = {0.f, 0.f, 0.f, 0.f};
        mma16816(y, wd[2 * i][0], wd[2 * i][1], wd[2 * i][2], wd[2 * i][3], a0, a1);
        mma16816(y, wd[2 * i + 1][0], wd[2 * i + 1][1], wd[2 * i + 1][2], wd[2 * i + 1][3], a2, a3);
        if ((lane & 3) == 0) { yp[i * 16] = make_float2(y[0], y[1]); yp[i * 16 + 8] = make_float2(y[2], y[3]); }
      }
      __syncwarp();
      uint4* yd = g_xr + (cw * 16 + (lane >> 2)) * XR_SIZE + XR_Y + fid * 4 + (lane & 3);
      __stcg(yd, lds128(sb + OFF_SCR + 16384 + cw * 1024 + lane * 16));
      __stcg(yd + 8 * XR_SIZE, lds128(sb + OFF_SCR + 16384 + cw * 1024 + 512 + lane * 16));
    }
    TL(2, 18, warp == 4);
    TL(2, 38, warp == 11);
    {
      float* red2 = reinterpret_cast<float*>(sp + OFF_SCR + 12288);
      uint4 hv, hx;
      float rs;
      if (cw == 7) {
        hv = poll_chunk(cand(lane & 1, rid));
        hx = poll_chunk(cand(lane & 1, rid) + 32);
        uint32_t u = ((lane & 1) ? top2 : top1) >> 16;
        u = (u & 0x8000u) ? (u & 0x7FFFu) : (~u & 0xFFFFu);
        rs = bf_round(__fdividef(1.f, 1.f + __expf(-__uint_as_float(u << 16))));
        TL(2, 37, rs > -1.f);
      } else {
        uint4 z[2];
        poll_chunks(z, xr + XR_Y + ct * 2, 1);
        __syncwarp();
        TL(2, 30 + cw, true);
        float v[8] = {__uint_as_float(z[0].x), __uint_as_float(z[0].y), __uint_as_float(z[0].z), __uint_as_float(z[0].w),
                      __uint_as_float(z[1].x), __uint_as_float(z[1].y), __uint_as_float(z[1].z), __uint_as_float(z[1].w)};
#pragma unroll
        for (int i = 0; i < 4; i++) { const bool up = lane & 8; v[i] = (up ? v[i + 4] : v[i]) + __shfl_xor_sync(~0u, up ? v[i] : v[i + 4], 8); }
#pragma unroll
        for (int i = 0; i < 2; i++) { const bool up = lane & 4; v[i] = (up ? v[i + 2] : v[i]) + __shfl_xor_sync(~0u, up ? v[i] : v[i + 2], 4); }
        { const bool up = lane & 2; v[0] = (up ? v[1] : v[0]) + __shfl_xor_sync(~0u, up ? v[0] : v[1], 2); }
        v[0] += __shfl_xor_sync(~0u, v[0], 16);
        if (lane < 16) red2[cw * 16 + (lane & 1) * 8 + (lane >> 1)] = v[0];
      }
      bar_sync(3, 256);
      TL(2, 19, warp == 4);
      if (cw == 7) {
        float y = 0.f;
#pragma unroll
        for (int i = 0; i < 7; i++) y += red2[i * 16 + (lane & 15)];
        const uint32_t hw[4] = {hv.x, hv.y, hv.z, hv.w}, hm[4] = {hx.x, hx.y, hx.z, hx.w};
        uint32_t o[4];
#pragma unroll
        for (int e = 0; e < 4; e++) {
          const uint32_t yb = pack_bf16(__shfl_sync(~0u, y, 4 * e + (lane & 1)), __shfl_sync(~0u, y, 4 * e + 2 + (lane & 1)));
          o[e] = hadd2_bf(hw[e], hadd2_bf(hm[e], pack_bf16(bf_lo(yb) * rs, bf_hi(yb) * rs)));
        }
        if (lane < 2) reinterpret_cast<uint4*>(out + (size_t)(lane ? t1 : t0) * DM)[rid] = make_uint4(o[0], o[1], o[2], o[3]);
        TL(2, 21, true);
      }
    }
    TL(2, 20, warp == 4);
    __syncwarp();
    cluster_wait();
  }
}

typedef CUresult (*EncodeFn)(CUtensorMap*, CUtensorMapDataType, cuuint32_t, void*, const cuuint64_t*, const cuuint64_t*, const cuuint32_t*,
                             const cuuint32_t*, CUtensorMapInterleave, CUtensorMapSwizzle, CUtensorMapL2promotion, CUtensorMapFloatOOBfill);
EncodeFn g_enc = nullptr;

void map2(CUtensorMap* m, const void* ptr, uint64_t rows, uint64_t cols, uint32_t bc, uint32_t br) {
  const CUtensorMapSwizzle sw = bc == 64 ? CU_TENSOR_MAP_SWIZZLE_128B : CU_TENSOR_MAP_SWIZZLE_64B;
  cuuint64_t gd[2] = {cols, rows}, gs[1] = {cols * 2};
  cuuint32_t bd[2] = {bc, br}, es[2] = {1, 1};
  g_enc(m, CU_TENSOR_MAP_DATA_TYPE_BFLOAT16, 2, (void*)ptr, gd, gs, bd, es, CU_TENSOR_MAP_INTERLEAVE_NONE, sw,
        CU_TENSOR_MAP_L2_PROMOTION_L2_128B, CU_TENSOR_MAP_FLOAT_OOB_FILL_NONE);
}
void map3(CUtensorMap* m, const void* ptr, uint64_t rows, uint64_t cols, uint32_t br, uint32_t bch) {
  cuuint64_t gd[3] = {64, rows, cols / 64}, gs[2] = {cols * 2, 128};
  cuuint32_t bd[3] = {64, br, bch}, es[3] = {1, 1, 1};
  g_enc(m, CU_TENSOR_MAP_DATA_TYPE_BFLOAT16, 3, (void*)ptr, gd, gs, bd, es, CU_TENSOR_MAP_INTERLEAVE_NONE, CU_TENSOR_MAP_SWIZZLE_128B,
        CU_TENSOR_MAP_L2_PROMOTION_L2_128B, CU_TENSOR_MAP_FLOAT_OOB_FILL_NONE);
}

}

extern "C" void kernel_launch(void* const* d_in, const int* in_sizes, int n_in, void* d_out, int out_size) {
  const __nv_bfloat16* x = (const __nv_bfloat16*)d_in[0];
  const __nv_bfloat16* ckv = (const __nv_bfloat16*)d_in[1];
  const __nv_bfloat16* wq = (const __nv_bfloat16*)d_in[2];
  const __nv_bfloat16* wk = (const __nv_bfloat16*)d_in[3];
  const __nv_bfloat16* wv = (const __nv_bfloat16*)d_in[4];
  const __nv_bfloat16* wo = (const __nv_bfloat16*)d_in[5];
  const __nv_bfloat16* w_r = (const __nv_bfloat16*)d_in[7];
  const __nv_bfloat16* wgate = (const __nv_bfloat16*)d_in[8];
  const __nv_bfloat16* wup = (const __nv_bfloat16*)d_in[9];
  const __nv_bfloat16* wdown = (const __nv_bfloat16*)d_in[10];
  __nv_bfloat16* out = (__nv_bfloat16*)d_out;

  if (!g_enc) {
    void* fn = nullptr;
    cudaDriverEntryPointQueryResult qr;
    cudaGetDriverEntryPoint("cuTensorMapEncodeTiled", &fn, cudaEnableDefault, &qr);
    g_enc = (EncodeFn)fn;
    cudaFuncSetAttribute(fused_kernel, cudaFuncAttributeMaxDynamicSharedMemorySize, SMEM_BYTES);
  }
  void *xn, *kv, *ctx;
  cudaGetSymbolAddress(&xn, g_xn);
  cudaGetSymbolAddress(&kv, g_kv);
  cudaGetSymbolAddress(&ctx, g_ctx);

  Params p;
  map2(&p.xn, xn, SEQ, DM, 64, 64);
  map2(&p.ckv, ckv, SEQ, DC, 64, 128);
  map3(&p.wq, wq, DM, NQ, 64, 2);
  map3(&p.wk, wk, DC, NQ, 64, 2);
  map3(&p.wv, wv, DC, NQ, 64, 2);
  map3(&p.kv_ld, kv, 2 * SEQ, NQ, 128, 2);
  map2(&p.ctx_ld, ctx, SEQ, NQ, 64, 128);
  map3(&p.wo, wo, NQ, DM, 64, 1);
  map3(&p.x, x, SEQ, DM, 64, 2);
  map3(&p.wd, wdown, FF, DM, 32, 8);
  map2(&p.out, out, SEQ, DM, 64, 8);
  map2(&p.wg, wgate, DM, FF, 32, 64);
  map2(&p.wu, wup, DM, FF, 32, 64);
  fused_kernel<<<128, 384, SMEM_BYTES, cudaStreamPerThread>>>(p, x, wq, w_r, wgate, wup, out);
}
```

```cpp
#include <cuda_runtime.h>
#include <cuda_bf16.h>
#include <cuda.h>
#include <stdint.h>
#include <utility>

#pragma nv_diag_suppress 549
namespace {

constexpr int SEQ = 2048, DM = 1024, NH = 32, HD = 128, DC = 512, NQ = NH * HD, FF = 3584;

__device__ __align__(1024) __nv_bfloat16 g_xn[SEQ * DM];
__device__ __align__(1024) __nv_bfloat16 g_kv[2 * SEQ * NQ];
__device__ __align__(1024) __nv_bfloat16 g_ctx[SEQ * NQ];
constexpr int XR_PS = 0;
constexpr int XR_KEY = 128;
constexpr int XR_CAND = 136;
constexpr int XR_Y = 648;
constexpr int XR_SIZE = 1104;
__device__ __align__(1024) uint4 g_xr[128 * XR_SIZE];
constexpr int C_LN = 0, C_KV = 16, C_CTX = 32, C_NUM = 64;
__device__ unsigned g_cnt[C_NUM];

#define TL(k, i, cond) do {} while (0)
#define TC(w, g, i) do {} while (0)
#define TL_EXTRA 0
#define TK(i) do {} while (0)

__device__ __forceinline__ uint32_t s2u(const void* p) { return (uint32_t)__cvta_generic_to_shared(p); }
__device__ __forceinline__ void mbar_arrive(uint32_t b) { asm volatile("mbarrier.arrive.shared::cta.b64 _, [%0];" ::"r"(b) : "memory"); }
__device__ __forceinline__ void mbar_arrive_both(uint32_t b, uint32_t lane, bool cond) {
  asm volatile("{\n.reg .pred p;\n.reg .b32 r;\nsetp.lt.u32 p, %1, %2;\nmapa.shared::cluster.u32 r, %0, %1;\n@p mbarrier.arrive.shared::cluster.b64 _, [r];\n}"
               ::"r"(b), "r"(lane), "r"(cond ? 2 : 0) : "memory");
}
__device__ __forceinline__ bool mbar_test(uint32_t b, uint32_t ph) {
  uint32_t ok;
  asm volatile("{\n.reg .pred p;\nmbarrier.test_wait.parity.shared::cta.b64 p, [%1], %2;\nselp.u32 %0, 1, 0, p;\n}" : "=r"(ok) : "r"(b), "r"(ph) : "memory");
  return __all_sync(~0u, ok);
}
__device__ __forceinline__ void mbar_wait(uint32_t b, uint32_t ph) {
  asm volatile(
      "{\n.reg .pred p;\n.reg .u32 n;\nmov.u32 n, 0;\n"
      "LW:\nmbarrier.try_wait.parity.shared::cta.b64 p, [%0], %1, 20000;\n@p bra LD;\n"
      "add.u32 n, n, 1;\nsetp.lt.u32 p, n, 0x40000;\n@p bra LW;\ntrap;\nLD:\n}" ::"r"(b), "r"(ph) : "memory");
}
__device__ __forceinline__ void mbar_wait_u(uint32_t b, uint32_t ph) {
  asm volatile(
      "{\n.reg .pred p;\n.reg .u32 n;\nmov.u32 n, 0;\n"
      "LW:\nmbarrier.try_wait.parity.shared::cta.b64 p, [%0], %1, 20000;\n@p bra.uni LD;\n"
      "add.u32 n, n, 1;\nsetp.lt.u32 p, n, 0x40000;\n@p bra.uni LW;\ntrap;\nLD:\n}" ::"r"(b), "r"(ph) : "memory");
}
__device__ __forceinline__ void mbar_wait_c(uint32_t b, uint32_t ph) {
  asm volatile(
      "{\n.reg .pred p;\n.reg .u32 n;\nmov.u32 n, 0;\n"
      "LW:\nmbarrier.try_wait.parity.shared::cta.b64 p, [%0], %1;\n@p bra.uni LD;\n"
      "add.u32 n, n, 1;\nsetp.lt.u32 p, n, 0x100000;\n@p bra.uni LW;\ntrap;\nLD:\n}" ::"r"(b), "r"(ph) : "memory");
}
template <bool SLEEP = false>
__device__ __forceinline__ void spin_until_ge(const unsigned* p, unsigned target) {
  asm volatile(
      "{\n.reg .pred p, q;\n.reg .u32 n, v;\nmov.u32 n, 0;\nsetp.ne.u32 q, %2, 0;\n"
      "LW:\nld.acquire.gpu.global.u32 v, [%0];\nsetp.ge.u32 p, v, %1;\n@p bra LD;\n@q nanosleep.u32 200;\n"
      "add.u32 n, n, 1;\nsetp.lt.u32 p, n, 0x400000;\n@p bra LW;\ntrap;\nLD:\n}" ::"l"(p), "r"(target), "n"((int)SLEEP) : "memory");
}
__device__ __forceinline__ uint4 poll_chunk(const uint4* p) {
  uint4 v;
  asm volatile(
      "{\n.reg .pred p;\n.reg .u32 n, m;\nmov.u32 n, 0;\n"
      "LW:\nld.relaxed.gpu.global.v4.u32 {%0,%1,%2,%3}, [%4];\nmax.u32 m, %0, %1;\nmax.u32 m, m, %2;\nmax.u32 m, m, %3;\n"
      "setp.ne.u32 p, m, 0xFFFFFFFF;\n@p bra LD;\n"
      "add.u32 n, n, 1;\nsetp.lt.u32 p, n, 0x400000;\n@p bra LW;\ntrap;\nLD:\n}"
      : "=r"(v.x), "=r"(v.y), "=r"(v.z), "=r"(v.w) : "l"(p) : "memory");
  return v;
}
template <int N>
__device__ __forceinline__ void poll_chunks(uint4 (&v)[N], const uint4* p, int stride) {
#pragma unroll 1
  for (int n = 0; n < 0x400000; n++) {
    uint32_t m = 0;
#pragma unroll
    for (int i = 0; i < N; i++) {
      asm volatile("ld.relaxed.gpu.global.v4.u32 {%0,%1,%2,%3}, [%4];" : "=r"(v[i].x), "=r"(v[i].y), "=r"(v[i].z), "=r"(v[i].w) : "l"(p + i * stride) : "memory");
    }
#pragma unroll
    for (int i = 0; i < N; i++) m = max(max(m, max(v[i].x, v[i].y)), max(v[i].z, v[i].w));
    if (m != 0xFFFFFFFFu) break;
  }
}
__device__ __forceinline__ void fence_async_all() { asm volatile("fence.proxy.async;" ::: "memory"); }
__device__ __forceinline__ void bar_sync(int id, int n) { asm volatile("bar.sync %0, %1;" ::"r"(id), "r"(n) : "memory"); }
__device__ __forceinline__ void bar_arrive(int id, int n) { asm volatile("bar.arrive %0, %1;" ::"r"(id), "r"(n) : "memory"); }
__device__ __forceinline__ void cluster_arrive() { asm volatile("barrier.cluster.arrive.relaxed.aligned;" ::: "memory"); }
__device__ __forceinline__ void cluster_wait() { asm volatile("barrier.cluster.wait.acquire.aligned;" ::: "memory"); }
__device__ __forceinline__ void fence_gpu() { asm volatile("fence.acq_rel.gpu;" ::: "memory"); }
__device__ __forceinline__ void red_add(unsigned* p, unsigned v) { asm volatile("red.relaxed.gpu.global.add.u32 [%0], %1;" ::"l"(p), "r"(v) : "memory"); }
#define ELECT "{\n.reg .pred E;\nelect.sync _|E, 0xFFFFFFFF;\n@E "
__device__ __forceinline__ void e_init(uint32_t b, uint32_t c) { asm volatile(ELECT "mbarrier.init.shared::cta.b64 [%0], %1;\n}" ::"r"(b), "r"(c) : "memory"); }
__device__ __forceinline__ void e_expect(uint32_t b, uint32_t bytes) { asm volatile(ELECT "mbarrier.arrive.expect_tx.shared::cta.b64 _, [%0], %1;\n}" ::"r"(b), "r"(bytes) : "memory"); }
__device__ __forceinline__ void e_arrive(uint32_t b) { asm volatile(ELECT "mbarrier.arrive.shared::cta.b64 _, [%0];\n}" ::"r"(b) : "memory"); }
__device__ __forceinline__ void prefetch_tm(const CUtensorMap* m) { asm volatile(ELECT "prefetch.tensormap [%0];\n}" ::"l"(m) : "memory"); }
__device__ __forceinline__ void tma_ld2(uint32_t dst, const CUtensorMap* m, uint32_t bar, int c0, int c1) {
  asm volatile(ELECT "cp.async.bulk.tensor.2d.shared::cta.global.mbarrier::complete_tx::bytes [%0], [%1, {%3,%4}], [%2];\n}" ::"r"(dst), "l"(m), "r"(bar), "r"(c0), "r"(c1) : "memory");
}
__device__ __forceinline__ void tma_ld3(uint32_t dst, const CUtensorMap* m, uint32_t bar, int c0, int c1, int c2) {
  asm volatile(ELECT "cp.async.bulk.tensor.3d.shared::cta.global.mbarrier::complete_tx::bytes [%0], [%1, {%3,%4,%5}], [%2];\n}" ::"r"(dst), "l"(m), "r"(bar), "r"(c0), "r"(c1), "r"(c2) : "memory");
}
__device__ __forceinline__ void tma_ld2_mc(uint32_t dst, const CUtensorMap* m, uint32_t bar, int c0, int c1, uint16_t mask) {
  asm volatile(ELECT "cp.async.bulk.tensor.2d.shared::cluster.global.mbarrier::complete_tx::bytes.multicast::cluster [%0], [%1, {%3,%4}], [%2], %5;\n}" ::"r"(dst), "l"(m), "r"(bar), "r"(c0), "r"(c1), "h"(mask) : "memory");
}
__device__ __forceinline__ void tma_ld3_mc(uint32_t dst, const CUtensorMap* m, uint32_t bar, int c0, int c1, int c2, uint16_t mask) {
  asm volatile(ELECT "cp.async.bulk.tensor.3d.shared::cluster.global.mbarrier::complete_tx::bytes.multicast::cluster [%0], [%1, {%3,%4,%5}], [%2], %6;\n}" ::"r"(dst), "l"(m), "r"(bar), "r"(c0), "r"(c1), "r"(c2), "h"(mask) : "memory");
}
__device__ __forceinline__ void tma_pf2(const CUtensorMap* m, int c0, int c1) { asm volatile(ELECT "cp.async.bulk.prefetch.tensor.2d.L2.global [%0, {%1,%2}];\n}" ::"l"(m), "r"(c0), "r"(c1) : "memory"); }
__device__ __forceinline__ void tma_pf3(const CUtensorMap* m, int c0, int c1, int c2) { asm volatile(ELECT "cp.async.bulk.prefetch.tensor.3d.L2.global [%0, {%1,%2,%3}];\n}" ::"l"(m), "r"(c0), "r"(c1), "r"(c2) : "memory"); }
__device__ __forceinline__ void sched_fence() { asm volatile("pmevent 0;" ::: "memory"); }
__device__ __forceinline__ void l2_prefetch(const void* p, uint32_t bytes) { asm volatile(ELECT "cp.async.bulk.prefetch.L2.global [%0], %1;\n}" ::"l"(p), "r"(bytes) : "memory"); }

__device__ __forceinline__ void wg_fence() { asm volatile("wgmma.fence.sync.aligned;" ::: "memory"); }
__device__ __forceinline__ void wg_commit() { asm volatile("wgmma.commit_group.sync.aligned;" ::: "memory"); }
template <int N> __device__ __forceinline__ void wg_wait() { asm volatile("wgmma.wait_group.sync.aligned %0;" ::"n"(N) : "memory"); }
template <int N> __device__ __forceinline__ void reg_alloc() { asm volatile("setmaxnreg.inc.sync.aligned.u32 %0;" ::"n"(N)); }
template <int N> __device__ __forceinline__ void reg_dealloc() { asm volatile("setmaxnreg.dec.sync.aligned.u32 %0;" ::"n"(N)); }
template <int N> __device__ __forceinline__ void fence_regs(float (&d)[N]) {
#pragma unroll
  for (int i = 0; i < N; i++) asm volatile("" : "+f"(d[i])::"memory");
}
template <int N> __device__ __forceinline__ void fence_regs(uint32_t (&d)[N]) {
#pragma unroll
  for (int i = 0; i < N; i++) asm volatile("" : "+r"(d[i])::"memory");
}

__device__ __forceinline__ uint32_t mk_desc(uint32_t addr, uint32_t lbo) { return ((addr & 0x3FFFF) >> 4) | ((lbo >> 4) << 16); }

#define R8(b) "+f"(d[b + 0]), "+f"(d[b + 1]), "+f"(d[b + 2]), "+f"(d[b + 3]), "+f"(d[b + 4]), "+f"(d[b + 5]), "+f"(d[b + 6]), "+f"(d[b + 7])
#define REGS64 "%0,%1,%2,%3,%4,%5,%6,%7,%8,%9,%10,%11,%12,%13,%14,%15,%16,%17,%18,%19,%20,%21,%22,%23,%24,%25,%26,%27,%28,%29,%30,%31," \
               "%32,%33,%34,%35,%36,%37,%38,%39,%40,%41,%42,%43,%44,%45,%46,%47,%48,%49,%50,%51,%52,%53,%54,%55,%56,%57,%58,%59,%60,%61,%62,%63"
#define REGS128 REGS64 ",%64,%65,%66,%67,%68,%69,%70,%71,%72,%73,%74,%75,%76,%77,%78,%79,%80,%81,%82,%83,%84,%85,%86,%87,%88,%89,%90,%91,%92,%93,%94,%95," \
               "%96,%97,%98,%99,%100,%101,%102,%103,%104,%105,%106,%107,%108,%109,%110,%111,%112,%113,%114,%115,%116,%117,%118,%119,%120,%121,%122,%123,%124,%125,%126,%127"

#define DESC(d, r, o) "add.u32 t, " r ", " o ";\nmov.b64 " d ", {t, h};\n"
#define MMA_PRE(acc) "{\n.reg .pred p;\n.reg .b32 t, h;\n.reg .b64 da, db;\nmov.b32 h, 0x40000040;\nsetp.ne.b32 p, " acc ", 0;\n"
template <int TB, int OA, int OB>
__device__ __forceinline__ void mma_n256_ss(float (&d)[128], uint32_t a, uint32_t b, int acc) {
  asm volatile(MMA_PRE("%130") DESC("da", "%128", "%132") DESC("db", "%129", "%133")
               "wgmma.mma_async.sync.aligned.m64n256k16.f32.bf16.bf16 {" REGS128 "}, da, db, p, 1, 1, 0, %131;\n}\n"
               : R8(0), R8(8), R8(16), R8(24), R8(32), R8(40), R8(48), R8(56), R8(64), R8(72), R8(80), R8(88), R8(96), R8(104), R8(112), R8(120)
               : "r"(a), "r"(b), "r"(acc), "n"(TB), "n"(OA >> 4), "n"(OB >> 4));
}
template <int TB, int OA, int OB>
__device__ __forceinline__ void mma_n128_ss(float (&d)[64], uint32_t a, uint32_t b, int acc) {
  asm volatile(MMA_PRE("%66") DESC("da", "%64", "%68") DESC("db", "%65", "%69")
               "wgmma.mma_async.sync.aligned.m64n128k16.f32.bf16.bf16 {" REGS64 "}, da, db, p, 1, 1, 0, %67;\n}\n"
               : R8(0), R8(8), R8(16), R8(24), R8(32), R8(40), R8(48), R8(56)
               : "r"(a), "r"(b), "r"(acc), "n"(TB), "n"(OA >> 4), "n"(OB >> 4));
}
template <int TB, int OB>
__device__ __forceinline__ void mma_n128_rs(float (&d)[64], const uint32_t* a, uint32_t b, int acc) {
  asm volatile(MMA_PRE("%69") DESC("db", "%68", "%71")
               "wgmma.mma_async.sync.aligned.m64n128k16.f32.bf16.bf16 {" REGS64 "}, {%64,%65,%66,%67}, db, p, 1, 1, %70;\n}\n"
               : R8(0), R8(8), R8(16), R8(24), R8(32), R8(40), R8(48), R8(56)
               : "r"(a[0]), "r"(a[1]), "r"(a[2]), "r"(a[3]), "r"(b), "r"(acc), "n"(TB), "n"(OB >> 4));
}
template <int OB>
__device__ __forceinline__ void mma_n64_rs(float (&d)[64], const uint32_t* a, uint32_t b, int acc) {
  asm volatile(MMA_PRE("%37") DESC("db", "%36", "%38")
               "wgmma.mma_async.sync.aligned.m64n64k16.f32.bf16.bf16 {%0,%1,%2,%3,%4,%5,%6,%7,%8,%9,%10,%11,%12,%13,%14,%15,%16,%17,%18,%19,%20,%21,"
               "%22,%23,%24,%25,%26,%27,%28,%29,%30,%31}, {%32,%33,%34,%35}, db, p, 1, 1, 0;\n}\n"
               : R8(0), R8(8), R8(16), R8(24)
               : "r"(a[0]), "r"(a[1]), "r"(a[2]), "r"(a[3]), "r"(b), "r"(acc), "n"(OB >> 4));
}
template <int V> struct IC { static constexpr int value = V; __host__ __device__ constexpr operator int() const { return V; } };
template <int N, class F, int... I>
__device__ __forceinline__ void static_for_(F f, std::integer_sequence<int, I...>) { (f(IC<I>{}), ...); }
template <int N, class F>
__device__ __forceinline__ void static_for(F f) { static_for_<N>(f, std::make_integer_sequence<int, N>{}); }
__device__ __forceinline__ uint32_t pack_bf16(float lo, float hi) {
  uint32_t r;
  asm("cvt.rn.bf16x2.f32 %0, %1, %2;" : "=r"(r) : "f"(hi), "f"(lo));
  return r;
}
__device__ __forceinline__ float bf_lo(uint32_t v) { return __uint_as_float(v << 16); }
__device__ __forceinline__ float bf_hi(uint32_t v) { return __uint_as_float(v & 0xFFFF0000u); }
__device__ __forceinline__ float bf_round(float v) { return bf_lo(pack_bf16(v, v)); }
__device__ __forceinline__ void stsm4(uint32_t addr, uint32_t r0, uint32_t r1, uint32_t r2, uint32_t r3) {
  asm volatile("stmatrix.sync.aligned.m8n8.x4.shared.b16 [%0], {%1,%2,%3,%4};" ::"r"(addr), "r"(r0), "r"(r1), "r"(r2), "r"(r3) : "memory");
}
__device__ __forceinline__ uint4 lds128(uint32_t addr) {
  uint4 v;
  asm volatile("ld.shared.v4.u32 {%0,%1,%2,%3}, [%4];" : "=r"(v.x), "=r"(v.y), "=r"(v.z), "=r"(v.w) : "r"(addr));
  return v;
}
__device__ __forceinline__ float ex2(float x) {
  float y;
  asm("ex2.approx.ftz.f32 %0, %1;" : "=f"(y) : "f"(x));
  return y;
}
__device__ __forceinline__ void stage_store_128(uint32_t base, int lane, const uint32_t* pk) {
  const int row = (lane & 7) + ((lane >> 3) & 1) * 8;
  const uint32_t rb = base + row * 128;
  const int hi = lane >> 4;
#pragma unroll
  for (int j = 0; j < 8; j++) {
    const int chunk = 2 * j + hi;
    const uint32_t a = rb + (j >> 2) * 8192 + (((chunk & 7) ^ (lane & 7)) << 4);
    stsm4(a, pk[4 * j + 0], pk[4 * j + 1], pk[4 * j + 2], pk[4 * j + 3]);
  }
}
__device__ __forceinline__ void ln_round(float mean, float var, float& m_bf, float& inv_s) {
  const uint32_t mv = pack_bf16(mean, var);
  m_bf = bf_lo(mv);
  float sq, rc;
  asm("sqrt.approx.f32 %0, %1;" : "=f"(sq) : "f"(bf_round(bf_hi(mv) + 1e-5f)));
  asm("rcp.approx.ftz.f32 %0, %1;" : "=f"(rc) : "f"(bf_round(sq)));
  inv_s = rc;
}
__device__ __forceinline__ uint32_t hadd2_bf(uint32_t a, uint32_t b) {
  uint32_t r;
  asm("add.rn.bf16x2 %0, %1, %2;" : "=r"(r) : "r"(a), "r"(b));
  return r;
}
__device__ __forceinline__ uint32_t ln_apply(uint32_t h, uint32_t nm2, float inv_s) {
  const uint32_t d = hadd2_bf(h, nm2);
  return pack_bf16(bf_lo(d) * inv_s, bf_hi(d) * inv_s);
}
__device__ __forceinline__ void mma16816(float* d, uint32_t a0, uint32_t a1, uint32_t a2, uint32_t a3, uint32_t b0, uint32_t b1) {
  asm volatile("mma.sync.aligned.m16n8k16.row.col.f32.bf16.bf16.f32 {%0,%1,%2,%3}, {%4,%5,%6,%7}, {%8,%9}, {%0,%1,%2,%3};"
               : "+f"(d[0]), "+f"(d[1]), "+f"(d[2]), "+f"(d[3]) : "r"(a0), "r"(a1), "r"(a2), "r"(a3), "r"(b0), "r"(b1));
}

constexpr float AT_C = 0.08838834764831845f * 1.4426950408889634f;
#define L_MIN 2.3283064e-10f
#define L_MAX 1.0995116e12f
#define SP1 6
#define SP2 12
struct AtState {
  float S[64], O[64];
  uint32_t P[32], Q[32];
  float l[4];
};
#define SUMV 0
#define LAG 0
template <int I0, int I1, int N = 64>
__device__ __forceinline__ void at_exp(AtState& s) {
#pragma unroll
  for (int i = I0; i < I1; i++) asm volatile("ex2.approx.ftz.f32 %0, %0;" : "+f"(s.S[i]));
#pragma unroll
  for (int i = I0 > 0 ? I0 - LAG : 0; i < (I1 < N ? I1 - LAG : N); i++) asm volatile("add.f32 %0, %0, %1;" : "+f"(s.l[i & 3]) : "f"(s.S[i]));
}
__device__ __forceinline__ void at_sum(AtState& s) {
}
template <int I0, int I1>
__device__ __forceinline__ void at_pack(AtState& s) {
#pragma unroll
  for (int i = I0; i < I1; i++) asm volatile("cvt.rn.bf16x2.f32 %0, %1, %2;" : "=r"(s.P[i]) : "f"(s.S[2 * i + 1]), "f"(s.S[2 * i]));
}
template <int J0>
__device__ __forceinline__ void at_mask(AtState& s, int r, int lane) {
  const int d = r + (lane >> 2) - (lane & 3) * 2;
#pragma unroll
  for (int j = 0; j < 8; j++) {
    float dummy0 = 0.f, dummy1 = 0.f;
    float& lo0 = j < 7 ? s.S[4 * (J0 + (j < 7 ? j + 1 : j)) + 2] : dummy0;
    float& lo1 = j < 7 ? s.S[4 * (J0 + (j < 7 ? j + 1 : j)) + 3] : dummy1;
    asm("{\n.reg .pred p, q;\nsetp.lt.s32 p, %4, %5;\nsetp.le.s32 q, %4, %5;\n"
        "@p add.f32 %0, %0, 0fFF800000;\n@q add.f32 %1, %1, 0fFF800000;\n@p add.f32 %2, %2, 0fFF800000;\n@q add.f32 %3, %3, 0fFF800000;\n}"
        : "+f"(s.S[4 * (J0 + j)]), "+f"(s.S[4 * (J0 + j) + 1]), "+f"(lo0), "+f"(lo1) : "r"(d), "r"(8 * j));
  }
}
__device__ __forceinline__ uint32_t ld_pair(const __nv_bfloat16* p) {
  uint32_t r;
  asm volatile("{\n.reg .b16 a, b;\nld.global.cg.b16 a, [%1];\nld.global.cg.b16 b, [%1 + 8192];\nmov.b32 %0, {a, b};\n}" : "=r"(r) : "l"(p) : "memory");
  return r;
}
__device__ __forceinline__ uint32_t ld_word(const uint32_t* p) {
  uint32_t r;
  asm volatile("ld.global.cg.b32 %0, [%1];" : "=r"(r) : "l"(p) : "memory");
  return r;
}
__device__ __forceinline__ void slow_rows(const __nv_bfloat16* wq, int head, int row0, int lane) {
  const int r = lane >> 2, c = lane & 3;
  uint32_t q[32];
  float o[32];
#pragma unroll
  for (int i = 0; i < 32; i++) q[i] = 0;
  const uint32_t* xa = reinterpret_cast<const uint32_t*>(g_xn + (size_t)(row0 + r) * DM) + c;
#pragma unroll 1
  for (int h = 0; h < 2; h++) {
    const __nv_bfloat16* wb = wq + (size_t)2 * c * NQ + head * HD + 64 * h + 8 * (r >> 1) + (r & 1);
#pragma unroll
    for (int i = 0; i < 32; i++) o[i] = 0.f;
#pragma unroll 1
    for (int kk = 0; kk < DM / 16; kk++) {
      const uint32_t a0 = ld_word(xa + 8 * kk), a1 = ld_word(xa + 8 * kk + 4 * DM), a2 = ld_word(xa + 8 * kk + 4), a3 = ld_word(xa + 8 * kk + 4 * DM + 4);
#pragma unroll
      for (int n = 0; n < 8; n++) {
        const __nv_bfloat16* b = wb + (size_t)16 * kk * NQ + 32 * (n >> 2) + 2 * (n & 3);
        mma16816(o + 4 * n, a0, a1, a2, a3, ld_pair(b), ld_pair(b + 8 * NQ));
      }
    }
#pragma unroll
    for (int i = 0; i < 16; i++) { q[i] = q[16 + i]; q[16 + i] = pack_bf16(o[2 * i] * AT_C, o[2 * i + 1] * AT_C); }
  }
#pragma unroll 1
  for (int h = 0; h < 2; h++) {
    float m0 = -INFINITY, m1 = -INFINITY, l0 = 0.f, l1 = 0.f;
#pragma unroll
    for (int i = 0; i < 32; i++) o[i] = 0.f;
#pragma unroll 1
    for (int k0 = 0; k0 <= row0; k0 += 16) {
      float e[8] = {0.f, 0.f, 0.f, 0.f, 0.f, 0.f, 0.f, 0.f};
      const uint32_t* kp = reinterpret_cast<const uint32_t*>(g_kv + (size_t)(k0 + r) * NQ + head * HD) + c;
#pragma unroll
      for (int kk = 0; kk < 8; kk++) {
        mma16816(e, q[4 * kk], q[4 * kk + 1], q[4 * kk + 2], q[4 * kk + 3], ld_word(kp + 8 * kk), ld_word(kp + 8 * kk + 4));
        mma16816(e + 4, q[4 * kk], q[4 * kk + 1], q[4 * kk + 2], q[4 * kk + 3], ld_word(kp + 8 * kk + 4 * NQ), ld_word(kp + 8 * kk + 4 * NQ + 4));
      }
      if (k0 == row0) {
#pragma unroll
        for (int i = 0; i < 8; i++) if ((i >> 2) * 8 + 2 * c + (i & 1) > r + (i & 2) * 4) e[i] = -INFINITY;
      }
      float a0 = fmaxf(fmaxf(e[0], e[1]), fmaxf(e[4], e[5])), a1 = fmaxf(fmaxf(e[2], e[3]), fmaxf(e[6], e[7]));
      a0 = fmaxf(a0, __shfl_xor_sync(~0u, a0, 1)); a1 = fmaxf(a1, __shfl_xor_sync(~0u, a1, 1));
      a0 = fmaxf(a0, __shfl_xor_sync(~0u, a0, 2)); a1 = fmaxf(a1, __shfl_xor_sync(~0u, a1, 2));
      a0 = fmaxf(a0, m0); a1 = fmaxf(a1, m1);
      const float sc0 = ex2(m0 - a0), sc1 = ex2(m1 - a1);
      m0 = a0; m1 = a1;
#pragma unroll
      for (int i = 0; i < 8; i++) e[i] = ex2(e[i] - ((i & 2) ? m1 : m0));
      l0 = l0 * sc0 + (e[0] + e[1]) + (e[4] + e[5]);
      l1 = l1 * sc1 + (e[2] + e[3]) + (e[6] + e[7]);
      const uint32_t p0 = pack_bf16(e[0], e[1]), p1 = pack_bf16(e[2], e[3]), p2 = pack_bf16(e[4], e[5]), p3 = pack_bf16(e[6], e[7]);
      const __nv_bfloat16* vp = g_kv + (size_t)(SEQ + k0 + 2 * c) * NQ + head * HD + 64 * h + r;
#pragma unroll
      for (int n = 0; n < 8; n++) {
        o[4 * n] *= sc0; o[4 * n + 1] *= sc0; o[4 * n + 2] *= sc1; o[4 * n + 3] *= sc1;
        mma16816(o + 4 * n, p0, p1, p2, p3, ld_pair(vp + 8 * n), ld_pair(vp + 8 * n + 8 * NQ));
      }
    }
    l0 += __shfl_xor_sync(~0u, l0, 1); l1 += __shfl_xor_sync(~0u, l1, 1);
    l0 += __shfl_xor_sync(~0u, l0, 2); l1 += __shfl_xor_sync(~0u, l1, 2);
#pragma unroll
    for (int i = 0; i < 4; i++) {
      const float* v = o + 16 * (i >> 1) + 2 * (i & 1);
      const float f = __fdividef(1.f, (i & 1) ? l1 : l0);
      *reinterpret_cast<uint4*>(g_ctx + (size_t)(row0 + r + (i & 1) * 8) * NQ + head * HD + 64 * h + (i >> 1) * 32 + c * 8) =
          make_uint4(pack_bf16(v[0] * f, v[1] * f), pack_bf16(v[4] * f, v[5] * f), pack_bf16(v[8] * f, v[9] * f), pack_bf16(v[12] * f, v[13] * f));
    }
  }
}

constexpr int UNIT = 16384, SLOT = 32768;
constexpr int OFF_STG = 2 * SLOT;
__host__ __device__ constexpr int kv_a(int kb) { return (kb < 6 ? kb : 3 * kb - 10) * UNIT; }
__host__ __device__ constexpr int kv_b(int s) { return (s == 2 ? 6 : 9 + 3 * s) * UNIT; }
__host__ __device__ constexpr int q_aw(int s) { return (3 * s + (s & 1)) * UNIT; }
__host__ __device__ constexpr int q_b(int s) { return (3 * s + 2 - 2 * (s & 1)) * UNIT; }
__host__ __device__ constexpr int k_slot(int j, int r) { return (j < 2 ? 2 * j : (r == 2 ? 0 : 3 + r)) * SLOT; }
__host__ __device__ constexpr int v_slot(int j) { return (6 - (j & 1)) * SLOT; }
__host__ __device__ constexpr int r3(int st) { return (st + (st >= 2)) * SLOT; }
constexpr int OFF_BAR = 229376;
constexpr int OFF_MISC = OFF_BAR + 512;
constexpr int SMEM_BYTES = OFF_MISC + 2080 + TL_EXTRA;
constexpr int OFF_RSTAT = OFF_MISC + 1056;
enum : int {
  B_FULL1 = 0, B_FULLQ = 3, B_FULLB = 7, B_KF = 8, B_VF = 11, B_FULL3 = 13, B_WF = 19, B_DEP = 21, B_OUT2 = 26, B_PF = 27, B_SET = 28,
  B_SET2 = 29, B_LNGO = 30, B_WR = 31,
  B_KE = 32, B_VE = 35, B_WE = 37, B_PUB = 39, B_OUT = 45,
  B_EMPTY1 = 46, B_EMPTYQ = 49, B_X = 53, B_EMPTY3 = 57,
  B_NUM = 63
};
constexpr int PRE = 3;
#define LN_PF 99
#define LN_GO 5
#define PFW 9
#define PFX 9
#define PFKV 0
#define SYNC3 0
#define SYNC3A 5
#define SYNC3W 6
#define CTX_ST "st.global.cs.v4.u32"
#define PF3 0
#define PD3 7
#define PFF 0
#define PWAIT mbar_wait_c
#define GRAB0 4
#define SIDE_NS 400
#define REL_AT 3
#define STARTV 2
#define SET_NS 40
#define WRAP 16 - j
#define EP1 3
#define MASKV 0
#define PACE 0
#define TRIMS 1
#define TRIMPV 1
#define KTEST 1
#define DELAY0 1
#define AWAIT mbar_wait_c
#define KWAIT mbar_wait_c
#define PFJ 16
#define PFQ 3
#define PFP 1
#define PFQ0 4
#define PFP0 5
#define PUT0 2
#define PUTD 2
#define NOFFN0 0
#define WEF 1
#define KV_FIRST 1
constexpr int WIN = 6;
constexpr int NIT = 64;
constexpr int NLATE = (8 - WIN) / 2;
constexpr int IT_WD = NIT + NLATE, OFF_SCR = r3((NIT + NLATE + 2) % 6);
#define PF_KB 52
#define PF_CLK 500
#define SET_KB 44
struct Params {
  CUtensorMap xn, ckv, wq, wk, wv, kv_ld, ctx_ld, wo, x, wd, wg, wu, out;
};

__global__ void __cluster_dims__(2, 1, 1) __launch_bounds__(384, 1)
fused_kernel(const __grid_constant__ Params p, const __nv_bfloat16* __restrict__ x, const __nv_bfloat16* __restrict__ wq,
             const __nv_bfloat16* __restrict__ w_r, const __nv_bfloat16* __restrict__ wgate, const __nv_bfloat16* __restrict__ wup,
             __nv_bfloat16* __restrict__ out, uint32_t zero) {
  extern __shared__ __align__(1024) uint8_t sp[];
  const uint32_t sb = s2u(sp);
  const uint32_t bar = sb + OFF_BAR;
  auto B = [&](int i) { return bar + 8 * i; };
  const int tid = threadIdx.x, warp = __shfl_sync(~0u, tid >> 5, 0), wg = warp >> 2, lane = tid & 31;
  const int cta = blockIdx.x, rank = cta & 1, cl = cta >> 1;
  const int mp = cl < 4 ? 1 : (cl < 36 ? (cl & 7) : (0x3207654 >> (4 * ((cl - 36) % 7))) & 7);
  const int gq = cl < 4 ? 4 + cl : (cl < 36 ? (cl - 4) >> 3 : 4 + (cl - 36) / 7);
  const int mt = 2 * mp + rank;
  const int qa = 15 - gq;
  const int rid = mt * 8 + gq;
  const int fid = mt * 7 + gq - NOFFN0;
  const bool ffn = NOFFN0 ? gq > 0 : gq < 7;
  uint4* const xr = g_xr + rid * XR_SIZE;
  TL(0, 0, warp == 4);
  auto load_pre = [&](int kb) {
    e_expect(B(B_FULL1 + kb), 3 * UNIT);
    tma_ld2(sb + kv_a(kb), &p.ckv, B(B_FULL1 + kb), kb * 64, mt * 128);
    tma_ld3(sb + kv_b(kb) + rank * UNIT, &p.wk, B(B_FULL1 + kb), 0, kb * 64, (gq + KV_FIRST * 8) * 4 + rank * 2);
    tma_ld3(sb + kv_b(kb) + UNIT - rank * UNIT, &p.wk, B(B_FULL1 + kb), 0, kb * 64, (gq + KV_FIRST * 8) * 4 + 2 - rank * 2);
  };
  if (warp == 0) {
    e_init(B(B_FULL1), 1);
    asm volatile("fence.mbarrier_init.release.cluster;" ::: "memory");
    load_pre(0);
#pragma unroll
    for (int kb = 1; kb < PRE; kb++) e_init(B(B_FULL1 + kb), 1);
  } else {
#pragma unroll 1
    for (int i = PRE - 1 + warp; i < B_NUM; i += 11) e_init(B(i), i >= B_EMPTY1 ? 16 : (i >= B_KE ? 8 : (i == B_WR ? 2 : 1)));
  }
  asm volatile("fence.mbarrier_init.release.cluster;" ::: "memory");
  cluster_arrive();
  if (wg == 0) {
    reg_dealloc<40>();
    if (warp == 0) {
#pragma unroll 1
      for (int kb = STARTV ? 1 : 0; kb < PRE; kb++) load_pre(kb);
      if (mt >= 2 * PRE) tma_pf3(&p.wk, 0, (mt >> 1) * 64, (gq + KV_FIRST * 8) * 4 + (mt & 1) * 2);
      if (gq >= PRE) tma_pf2(&p.ckv, gq * 64, mt * 128);
      prefetch_tm(&p.wv); prefetch_tm(&p.wq); prefetch_tm(&p.xn); prefetch_tm(&p.kv_ld);
    }
    __syncwarp();
    cluster_wait();
    auto side_piece = [&](int c, int piece) {
      const uint32_t fb = B(B_WF + (c & 1));
      if (piece == 0) e_expect(fb, UNIT);
      tma_ld2(sb + OFF_STG + (c & 1) * UNIT + piece * 4096, (piece & 2) ? &p.wg : &p.wu, fb, fid * 32, c * 128 + (piece & 1) * 64);
    };
    if (warp == 0) {
      {
        int st = 0; uint32_t ph = 1;
#pragma unroll 1
        for (int i = 0; i < 32; i++) {
          const int t = i >> 3, kb = i & 7;
          if (i >= PRE) {
            const uint32_t fb = B(B_FULL1 + st);
            KWAIT(B(B_EMPTY1 + st), ph);
            e_expect(fb, t == 0 ? 3 * UNIT : 2 * UNIT);
            if (t == 0) tma_ld2(sb + kv_a(kb), &p.ckv, fb, kb * 64, mt * 128);
            tma_ld3_mc(sb + kv_b(st) + rank * UNIT, (t & 1) ? &p.wv : &p.wk, fb, 0, kb * 64, (gq + ((t >> 1) ^ KV_FIRST) * 8) * 4 + rank * 2, 3);
          }
          if (i == LN_PF || i == LN_PF + 1) l2_prefetch(x + (size_t)cta * 16 * DM + (i - LN_PF) * 8 * DM, 16384);
          if (i == LN_GO) e_arrive(B(B_LNGO));
          if (kb == 0 && t < 3) tma_pf3((t & 1) ? &p.wk : &p.wv, 0, (mt >> 1) * 64, (gq + (((t + 1) >> 1) ^ KV_FIRST) * 8) * 4 + (mt & 1) * 2);
          if (kb < 2 && t == 3) tma_pf3(&p.wq, 0, (gq + 8 * kb) * 64, mt * 2);
          if (++st == 3) { st = 0; ph ^= 1; }
        }
        prefetch_tm(&p.ctx_ld); prefetch_tm(&p.wo); prefetch_tm(&p.wd); prefetch_tm(&p.x); prefetch_tm(&p.wg); prefetch_tm(&p.wu);
        PWAIT(B(B_DEP + 0), 0);
        uint32_t kpar = 7, vpar = 3;
        auto load_aw = [&](int kb, int head) {
          const uint32_t d = sb + q_aw(kb & 3), fb = B(B_FULLQ + (kb & 3));
          tma_ld2_mc(d + rank * 8192, &p.xn, fb, kb * 64, gq * 128 + rank * 64, 3);
          tma_ld3(d + UNIT, &p.wq, fb, 0, kb * 64, head * 2);
        };
        auto load_b = [&](int kb, uint32_t fb) { tma_ld2_mc(sb + q_b(kb & 3) + rank * 8192, &p.xn, fb, kb * 64, qa * 128 + rank * 64, 3); };
        auto load3 = [&](int kb, int s) {
          const uint32_t d = sb + r3(s), fb = B(B_FULL3 + s);
          e_expect(fb, SLOT);
          tma_ld2(d, &p.ctx_ld, fb, kb * 64, mt * 128);
          tma_ld3_mc(d + UNIT + rank * 8192, &p.wo, fb, 0, kb * 64, gq * 2 + rank, 3);
        };
#pragma unroll 1
        for (int half = 0; half < 2; half++) {
          const int head = mt + 16 * half;
#pragma unroll 1
          for (int kb = 2 * half; kb < 16; kb++) {
            if (kb >= 4) KWAIT(B(B_EMPTYQ + (kb & 3)), ((kb >> 2) & 1) ^ 1);
            else if (half) PWAIT(B(B_X + 2), 0);
            else if (kb > 0) PWAIT(B(B_EMPTY1 + (kb + 1) % 3), kb == 1);
            e_expect(B(B_FULLQ + (kb & 3)), 3 * UNIT);
            load_aw(kb, head);
            load_b(kb, B(B_FULLQ + (kb & 3)));
          }
          PWAIT(B(B_DEP + 1 + half), 0);
          tma_pf3(&p.kv_ld, 0, 0, head * 2);
          auto load_v = [&](int j) {
            const int r = j & 1;
            AWAIT(B(B_VE + r), (vpar >> r) & 1);
            vpar ^= 1 << r;
            e_expect(B(B_VF + r), SLOT);
            tma_ld3(sb + v_slot(j), &p.kv_ld, B(B_VF + r), 0, SEQ + (j > qa ? WRAP : j) * 128, head * 2);
          };
          int r = 0;
#pragma unroll 1
          for (int j = 0; j < 17; j++) {
            if (j < 2) PWAIT(B(B_EMPTYQ + j), 1);
            if (j == 2) PWAIT(B(B_KE), kpar & 1);
            AWAIT(B(B_KE + r), (kpar >> r) & 1);
            kpar ^= 1 << r;
            e_expect(B(B_KF + r), SLOT);
            tma_ld3(sb + k_slot(j, r), &p.kv_ld, B(B_KF + r), 0, (j > qa ? WRAP : j) * 128, head * 2);
            if (++r == 3) r = 0;
            if (j == 2) PWAIT(B(B_EMPTYQ + 3), 1);
            if (j != 1) load_v(j ? j - 1 : 0);
            if (j == PFJ) {
              if (half == 0) {
                if (PFQ & 1) tma_pf3(&p.wq, 0, (PFQ0 + gq) * 64, (mt + 16) * 2);
                if (PFQ & 2) tma_pf2(&p.xn, (PFQ0 + (mp & 3)) * 64, ((mp & 4) ? qa : gq) * 128 + rank * 64);
              } else {
                PWAIT(B(B_DEP + 3), 0);
                if (PFP & 1) tma_pf3(&p.wo, 0, (PFP0 + mp) * 64, gq * 2 + rank);
                if (PFP & 2) tma_pf2(&p.ctx_ld, (PFP0 + gq) * 64, mt * 128);
              }
            }
            if (half == 0) {
            } else if (ffn && j >= 5 && j < 13) {
              side_piece((j - 5) >> 2, (j - 5) & 3);
            }
          }
          PWAIT(B(B_X + 0), half);
          if (half == 0) {
            for (int kb = 0; kb < 2; kb++) { e_expect(B(B_FULLQ + kb), 2 * UNIT); load_aw(kb, mt + 16); }
          } else {
            load3(0, 0);
          }
          load_v(16);
          PWAIT(B(B_X + 1), half);
          if (half == 0) { e_expect(B(B_FULLB), 2 * UNIT); load_b(0, B(B_FULLB)); load_b(1, B(B_FULLB)); }
        }
        prefetch_tm(&p.out);
        st = 1; ph = 1;
#pragma unroll 1
        for (int kb = 1; kb < 64; kb++) {
          if (kb == 32) PWAIT(B(B_DEP + 4), 0);
          if (kb >= 6) PWAIT(B(B_EMPTY3 + st), ph);
          else if (kb == 3 || kb == 5) PWAIT(B(B_X + (kb + 1) / 2), 1);
          load3(kb, st);
          if (++st == 6) { st = 0; ph ^= 1; }
          if (kb == PF_KB) e_arrive(B(B_PF));
          if (kb == SET_KB) e_arrive(B(B_SET));
          if (kb == 58) l2_prefetch(xr, XR_CAND * 16);
        }
        if (ffn) {
#pragma unroll 1
          for (int j = 0; j < NLATE + 2; j++) {
            PWAIT(B(B_EMPTY3 + st), ph);
            const uint32_t d = sb + r3(st), fb = B(B_FULL3 + st);
            e_expect(fb, SLOT);
            if (j < NLATE) {
#pragma unroll 1
              for (int h = 0; h < 8; h++) tma_ld2(d + h * 4096, (h & 2) ? &p.wg : &p.wu, fb, fid * 32, (WIN + 2 * j + (h >> 2)) * 128 + (h & 1) * 64);
            } else {
              tma_ld3(d, &p.wd, fb, 0, fid * 32, 8 * (j - NLATE));
            }
            if (++st == 6) { st = 0; ph ^= 1; }
          }
        }
      }
    } else {
      if (warp >= 2) {
#pragma unroll 1
        for (int i = tid - 64; i < XR_CAND; i += 64) xr[i] = make_uint4(~0u, ~0u, ~0u, ~0u);
        if (warp == 2) { __syncwarp(); if (lane == 0) mbar_arrive(B(B_WR)); }
      }
      if (warp == 3) {
        float ws = 0.f;
#pragma unroll
        for (int j = 0; j < 4; j++) {
          const uint4 q = __ldg(reinterpret_cast<const uint4*>(w_r) + j * 32 + lane);
          ws += bf_lo(q.x) + bf_hi(q.x) + bf_lo(q.y) + bf_hi(q.y) + bf_lo(q.z) + bf_hi(q.z) + bf_lo(q.w) + bf_hi(q.w);
        }
#pragma unroll
        for (int o = 16; o; o >>= 1) ws += __shfl_xor_sync(~0u, ws, o);
        uint2* tab = reinterpret_cast<uint2*>(sp + OFF_MISC + 512);
        tab[lane] = make_uint2(0x3F803F80u, 0x3F803F80u);
        tab[32 + lane] = __ldg(reinterpret_cast<const uint2*>(w_r + gq * 128) + lane);
        if (lane == 0) *reinterpret_cast<float*>(sp + OFF_MISC + 1024) = ws;
        __syncwarp();
        if (lane == 0) mbar_arrive(B(B_WR));
      }
      __syncwarp();
      mbar_wait(B(B_LNGO), 0);
#pragma unroll 1
      for (int r = warp == 2 ? 0 : (warp + 1) >> 1; r < 16; r += 3) {
        const uint4* src = reinterpret_cast<const uint4*>(x + (size_t)(cta * 16 + r) * DM) + lane;
        uint4 v[4];
#pragma unroll
        for (int j = 0; j < 4; j++) v[j] = __ldg(src + j * 32);
        float a0 = 0.f, a1 = 0.f, b0 = 0.f, b1 = 0.f;
#pragma unroll
        for (int j = 0; j < 4; j++) {
          const uint32_t u[4] = {v[j].x, v[j].y, v[j].z, v[j].w};
#pragma unroll
          for (int i = 0; i < 4; i++) { const float a = bf_lo(u[i]), b = bf_hi(u[i]); a0 += a; a1 += b; b0 = fmaf(a, a, b0); b1 = fmaf(b, b, b1); }
        }
        a0 += a1; b0 += b1;
#pragma unroll
        for (int o = 16; o; o >>= 1) { a0 += __shfl_xor_sync(~0u, a0, o); b0 += __shfl_xor_sync(~0u, b0, o); }
        const float mean = a0 * (1.f / DM);
        float mb, inv;
        ln_round(mean, fmaxf(fmaf(b0, 1.f / DM, -mean * mean), 0.f), mb, inv);
        const uint32_t nm2 = pack_bf16(-mb, -mb);
        uint4* dst = reinterpret_cast<uint4*>(g_xn + (size_t)(cta * 16 + r) * DM) + lane;
#pragma unroll
        for (int j = 0; j < 4; j++)
          dst[j * 32] = make_uint4(ln_apply(v[j].x, nm2, inv), ln_apply(v[j].y, nm2, inv), ln_apply(v[j].z, nm2, inv), ln_apply(v[j].w, nm2, inv));
      }
      __syncwarp();
      if (lane == 0) {
        fence_gpu();
        red_add(&g_cnt[C_LN + (cta >> 3)], 1);
        TL(0, 20 + warp, true);
        if (warp == 3) {
          spin_until_ge<true>(&g_cnt[C_LN + gq], 24);
#pragma unroll 1
          for (int i = 0; i < 5; i++) {
            const int c = i == 0 ? C_LN + qa : (i < 3 ? C_KV + (i - 1) * 8 + mp : C_CTX + (i - 3) * 16 + mt);
            spin_until_ge<true>(&g_cnt[c], i == 0 ? 24 : 16);
            fence_async_all();
            mbar_arrive(B(B_DEP + i));
          }
        } else if (warp == 1) {
          mbar_wait(B(B_WR), 0);
#pragma unroll 1
          for (int i = 0; i < 6; i++) {
            const int c = i < 2 ? C_KV + gq + (i ^ KV_FIRST) * 8 : C_CTX + ((i - 2) >> 1) * 16 + ((i & 1) ? qa : gq);
            mbar_wait(B(B_PUB + i), 0);
            fence_gpu();
            red_add(&g_cnt[c], 1);
          }
        }
      }
      __syncwarp();
      if (warp == 2) {
#pragma unroll 1
        for (int c = 2; c < WIN + 2; c++) {
          if (c == WIN + 1) {
            mbar_wait(B(B_SET), 0);
#pragma unroll 1
            for (int i = XR_CAND + lane; i < XR_SIZE; i += 32) { xr[i] = make_uint4(~0u, ~0u, ~0u, ~0u); __nanosleep(SET_NS); }
          }
          mbar_wait(B(B_WE + (c & 1)), ((c >> 1) & 1) ^ 1);
          __syncwarp();
          if (c >= WIN) {
            e_expect(B(B_WF + (c & 1)), UNIT);
            tma_ld3(sb + OFF_STG + (c & 1) * UNIT, &p.x, B(B_WF + (c & 1)), 0, mt * 128 + (c & 1) * 64, gq * 2);
          } else if (ffn) {
#pragma unroll 1
            for (int i = 0; i < 4; i++) { side_piece(c, i); __nanosleep(SIDE_NS); }
          }
        }
        if (lane == 0) { fence_gpu(); mbar_arrive(B(B_SET2)); }
        __syncwarp();
        mbar_wait(B(B_PF), 0);
        uint32_t t0;
        asm volatile("mov.u32 %0, %%clock;" : "=r"(t0));
        constexpr int NF = (8 - WIN) * 4;
#pragma unroll 1
        for (int i = 0; i < NF; i++) {
          const char* a = (const char*)(((i & 2) ? wgate : wup) + (size_t)((WIN + (i >> 2)) * 128 + cta) * FF) + min((i & 1) * 32 + lane, 55) * 128;
          asm volatile("prefetch.global.L2 [%0];" ::"l"(a));
#pragma unroll 1
          for (int n = 0; n < 64; n++) {
            __nanosleep(100);
            uint32_t t;
            asm volatile("mov.u32 %0, %%clock;" : "=r"(t));
            if (t - t0 >= (uint32_t)(i + 1) * PF_CLK) break;
          }
        }
      }
      __syncwarp();
      mbar_wait(B(B_OUT), 0);
#pragma unroll 1
      for (int i = warp - 1; i < 64; i += 3) {
        const int row = 2 * i + (lane >> 4);
        const uint2 rs = *reinterpret_cast<const uint2*>(sp + OFF_RSTAT + row * 8);
        uint4* q = reinterpret_cast<uint4*>(sp + OFF_STG + (row >> 6) * 16384 + ((lane & 15) >> 3) * 8192 + (row & 63) * 128 + ((lane & 7) << 4));
        const uint4 v = *q;
        const float inv = __uint_as_float(rs.y);
        *q = make_uint4(hadd2_bf(v.x, ln_apply(v.x, rs.x, inv)), hadd2_bf(v.y, ln_apply(v.y, rs.x, inv)),
                        hadd2_bf(v.z, ln_apply(v.z, rs.x, inv)), hadd2_bf(v.w, ln_apply(v.w, rs.x, inv)));
      }
      asm volatile("fence.proxy.async.shared::cta;" ::: "memory");
      bar_sync(4, 96);
      if (warp == 1) {
        mbar_wait(B(B_OUT2), 0);
        const uint32_t* keys = reinterpret_cast<const uint32_t*>(sp + OFF_MISC);
        const int t0 = 0x7FFF - (keys[16] & 0x7FFF) - mt * 128, t1 = 0x7FFF - (keys[17] & 0x7FFF) - mt * 128;
        const int grp = lane >> 1;
        if (grp != (t0 >> 3) && grp != (t1 >> 3))
          asm volatile("cp.async.bulk.tensor.2d.global.shared::cta.bulk_group [%0, {%2,%3}], [%1];" ::"l"(&p.out),
                       "r"(sb + OFF_STG + (grp >> 3) * 16384 + (lane & 1) * 8192 + (grp & 7) * 1024), "r"(gq * 128 + (lane & 1) * 64), "r"(mt * 128 + grp * 8) : "memory");
        asm volatile("cp.async.bulk.commit_group;" ::: "memory");
#pragma unroll 1
        for (int k = 0; k < 8; k++) {
          const int tt = k < 4 ? t0 : t1, row = (tt & ~7) + (k & 3) * 2 + (lane >> 4);
          if (tt >= 0 && tt < 128 && row != t0 && row != t1)
            *reinterpret_cast<uint4*>(out + (size_t)(mt * 128 + row) * DM + gq * 128 + (lane & 15) * 8) =
                lds128(sb + OFF_STG + (row >> 6) * 16384 + ((lane & 15) >> 3) * 8192 + (row & 63) * 128 + (((lane & 7) ^ (row & 7)) << 4));
        }
        asm volatile("cp.async.bulk.wait_group.read 0;" ::: "memory");
      }
      TL(2, 25, warp == 1);
    }
    __syncwarp();
    cluster_arrive();
    cluster_wait();
  } else {
    reg_alloc<232>();
    cluster_wait();
    const int w = wg - 1, cw = warp - 4, ct = tid - 128;
    const uint32_t stg = sb + OFF_STG + w * 16384 + (cw & 3) * 2048;
    auto publish = [&](int i) { __syncwarp(); e_arrive(B(B_PUB + i)); };
    auto release2 = [&](uint32_t b, bool cond = true) { mbar_arrive_both(b, lane, cond); };
    AtState s;
    const uint32_t dA = mk_desc(sb + w * 8192, 16);
    const uint32_t dW = mk_desc(sb, 8192);
    auto mma_kb = [&](float (&d)[64], uint32_t a, uint32_t b, int accum) {
      static_for<4>([&](auto k) { mma_n128_ss<1, k * 32, k * 2048>(d, dA + (a >> 4), dW + (b >> 4), k == 0 ? accum : 1); });
    };
    auto mma_kc = [&](float (&d)[64], auto a, auto b, int accum) {
      static_for<4>([&](auto k) { mma_n128_ss<1, decltype(a)::value + k * 32, decltype(b)::value + k * 2048>(d, dA, dW, k == 0 ? accum : 1); });
    };
    auto issue_q = [&](int kb, auto accum) {
      const int st = kb & 3;
      mbar_wait_c(B(B_FULLQ + st), (kb >> 2) & 1);
      wg_fence();
      mma_kb(s.S, q_aw(st), q_aw(st) + UNIT, accum);
      wg_commit();
      if (accum) {
        wg_wait<1>();
        release2(B(B_EMPTYQ + ((kb - 1) & 3)));
        wg_fence();
      }
      mma_kb(s.O, q_b(st), q_aw(st) + UNIT, accum);
      wg_commit();
    };
    {
      uint4 pk[16];
      __nv_bfloat16* pdst = g_kv;
      auto put = [&](int i) { __stcs(reinterpret_cast<uint4*>(pdst + (i & 1) * 8 * NQ + (i >> 1) * 32), pk[i]); };
      float acc1[128];
      TL(0, 1, warp == 4);
      int st = 0; uint32_t ph = 0;
      auto issue = [&](int kb, int accum) {
        mbar_wait_c(B(B_FULL1 + st), ph);
        wg_fence();
        static_for<4>([&](auto k) { mma_n256_ss<1, k * 32, k * 2048>(acc1, dA + (kv_a(kb) >> 4), dW + (kv_b(st) >> 4), k == 0 ? accum : 1); });
        wg_commit();
      };
#pragma unroll 1
      for (int t = 0; t < 4; t++) {
        issue(0, 0);
        TL(0, 2 + 2 * t, warp == 4);
        if (t > 0) { put(0); put(1); }
        int prev = st;
        if (++st == 3) { st = 0; ph ^= 1; }
#pragma unroll 1
        for (int kb = 1; kb < 8; kb++) {
          if (kb == 7 && w == 1) bar_sync(5, 256);
          issue(kb, 1);
          if (kb == 7 && w == 0) bar_arrive(5, 256);
          if (t > 0) {
#pragma unroll
            for (int i = 1; i < 8; i++) if (kb == i) { put(2 * i); put(2 * i + 1); }
            if (kb == 7 && t == 2) publish(0);
          }
          wg_wait<1>();
          TK(24 + t * 8 + kb - 1);
          release2(B(B_EMPTY1 + prev));
          prev = st;
          if (++st == 3) { st = 0; ph ^= 1; }
        }
        pdst = g_kv + (size_t)((t & 1) * SEQ + mt * 128 + cw * 16 + (lane >> 2)) * NQ + (gq + ((t >> 1) ^ KV_FIRST) * 8) * 256 + (lane & 3) * 8;
        wg_wait<0>();
        TK(24 + t * 8 + 7);
        fence_regs(acc1);
        release2(B(B_EMPTY1 + prev));
        TL(0, 3 + 2 * t, warp == 4);
#pragma unroll
        for (int a = 0; a < 8; a++)
#pragma unroll
          for (int h = 0; h < 2; h++)
            pk[2 * a + h] = make_uint4(pack_bf16(acc1[16 * a + 2 * h], acc1[16 * a + 2 * h + 1]), pack_bf16(acc1[16 * a + 4 + 2 * h], acc1[16 * a + 5 + 2 * h]),
                                       pack_bf16(acc1[16 * a + 8 + 2 * h], acc1[16 * a + 9 + 2 * h]), pack_bf16(acc1[16 * a + 12 + 2 * h], acc1[16 * a + 13 + 2 * h]));
      }
      issue_q(0, IC<0>{});
      TL(0, 10, warp == 4);
      put(0); put(1);
#pragma unroll 1
      for (int kb = 1; kb < 8; kb++) {
        issue_q(kb, IC<1>{});
        TK(66 + kb - 1);
#pragma unroll
        for (int i = 1; i < 8; i++) if (kb == i) { put(2 * i); put(2 * i + 1); }
      }
      publish(1);
      TL(0, 11, warp == 4);
    }
    __nv_bfloat16* cdst;
    uint32_t redo = 0;
    auto put_ctx = [&](int i, bool cond) {
      asm volatile("{\n.reg .pred p;\nsetp.ne.u32 p, %5, 0;\n@p " CTX_ST " [%0], {%1,%2,%3,%4};\n}" ::"l"(cdst + (i & 1) * 8 * NQ + (i >> 1) * 32),
                   "r"(s.P[4 * i]), "r"(s.P[4 * i + 1]), "r"(s.P[4 * i + 2]), "r"(s.P[4 * i + 3]), "r"((uint32_t)(cond && !(redo & 2))) : "memory");
    };
    {
      const int wrow = cw * 16;
      const uint32_t dK = mk_desc(sb, 16), dV = mk_desc(sb, 16384);
      uint32_t kph = 0, vph = 0;
      auto q_store = [&](const float (&d)[64]) {
        const int r0 = lane >> 2;
        const uint32_t a = sb + SLOT + (wrow + r0) * 128 + (((lane & 3) ^ (((r0 & 1) << 2) | (r0 >> 1))) << 4);
#pragma unroll
        for (int i = 0; i < 8; i++) {
          const float* o = d + 16 * (i >> 1) + 2 * (i & 1);
          asm volatile("st.shared.v4.u32 [%0], {%1,%2,%3,%4};" ::"r"((a ^ ((i & 2) << 5)) + (i >> 2) * UNIT + (i & 1) * 1024),
                       "r"(pack_bf16(o[0] * AT_C, o[1] * AT_C)), "r"(pack_bf16(o[4] * AT_C, o[5] * AT_C)),
                       "r"(pack_bf16(o[8] * AT_C, o[9] * AT_C)), "r"(pack_bf16(o[12] * AT_C, o[13] * AT_C)) : "memory");
        }
        __syncwarp();
      };
      auto q_load = [&](auto k0, auto k1) {
        const uint32_t a = sb + SLOT + (wrow + (lane & 15)) * 128 + (((lane >> 4) ^ (((lane & 1) << 2) | ((lane >> 1) & 3))) << 4);
#pragma unroll
        for (int k = k0; k < k1; k++)
          asm volatile("ldmatrix.sync.aligned.m8n8.x4.shared.b16 {%0,%1,%2,%3}, [%4];"
                       : "=r"(s.Q[4 * k]), "=r"(s.Q[4 * k + 1]), "=r"(s.Q[4 * k + 2]), "=r"(s.Q[4 * k + 3]) : "r"((a ^ ((k & 3) << 5)) + (k >> 2) * UNIT) : "memory");
      };
      auto q_load_if = [&](auto k, bool cond, float after) {
        const uint32_t a = sb + SLOT + (wrow + (lane & 15)) * 128 + (((lane >> 4) ^ (((lane & 1) << 2) | ((lane >> 1) & 3))) << 4);
        asm volatile("{\n.reg .pred p;\nsetp.ne.u32 p, %5, 0;\n@p ldmatrix.sync.aligned.m8n8.x4.shared.b16 {%0,%1,%2,%3}, [%4];\n}"
                     : "+r"(s.Q[4 * k]), "+r"(s.Q[4 * k + 1]), "+r"(s.Q[4 * k + 2]), "+r"(s.Q[4 * k + 3])
                     : "r"((a ^ ((k & 3) << 5)) + (k >> 2) * UNIT + (__float_as_uint(after) >> 31)), "r"((uint32_t)cond) : "memory");
      };
      auto issue_s = [&](uint32_t off) {
        static_for<8>([&](auto k) { mma_n128_rs<0, (k >> 2) * 16384 + (k & 3) * 32>(s.S, s.Q + 4 * k, dK + (off >> 4), k != 0); });
        wg_commit();
      };
      auto issue_pv = [&](int jv, int accum, bool upper) {
        mbar_wait_c(B(B_VF + (jv & 1)), (vph >> (jv & 1)) & 1);
        vph ^= 1 << (jv & 1);
        wg_fence();
        static_for<4>([&](auto k) { mma_n128_rs<1, k * 2048>(s.O, s.P + 4 * k, dV + (v_slot(jv) >> 4), k == 0 ? accum : 1); });
        wg_commit();
        if (!TRIMPV || upper) {
          if (TRIMPV) wg_fence();
          static_for<4>([&](auto k) { mma_n128_rs<1, (k + 4) * 2048>(s.O, s.P + 16 + 4 * k, dV + (v_slot(jv) >> 4), 1); });
          wg_commit();
        } else {
          asm volatile("wgmma.fence.sync.aligned;\nwgmma.commit_group.sync.aligned;" ::: "memory");
        }
      };
      if (w == 1) bar_arrive(1, 256);
#pragma unroll 1
      for (int half = 0; half < 2; half++) {
        const int head = mt + 16 * half;
        redo = 0;
        float inv[2];
        auto ep_prep = [&]() {
          float l0 = s.l[0] + s.l[1], l1 = s.l[2] + s.l[3];
          l0 += __shfl_xor_sync(~0u, l0, 1); l1 += __shfl_xor_sync(~0u, l1, 1);
          l0 += __shfl_xor_sync(~0u, l0, 2); l1 += __shfl_xor_sync(~0u, l1, 2);
          asm("rcp.approx.ftz.f32 %0, %1;" : "=f"(inv[0]) : "f"(l0));
          asm("rcp.approx.ftz.f32 %0, %1;" : "=f"(inv[1]) : "f"(l1));
          return __any_sync(~0u, !(fminf(l0, l1) >= L_MIN && l0 + l1 <= L_MAX));
        };
        auto ep_out = [&](int qt, auto i0, auto i1) {
          __nv_bfloat16* dst = g_ctx + (size_t)(qt * 128 + wrow + (lane >> 2)) * NQ + head * 128 + (lane & 3) * 8;
#pragma unroll
          for (int i = i0; i < i1; i++) {
            const float* o = s.O + 16 * (i >> 1) + 2 * (i & 1);
            const float c = inv[i & 1];
            asm volatile(CTX_ST " [%0], {%1,%2,%3,%4};" ::"l"(dst + (i & 1) * 8 * NQ + (i >> 1) * 32), "r"(pack_bf16(o[0] * c, o[1] * c)),
                         "r"(pack_bf16(o[4] * c, o[5] * c)), "r"(pack_bf16(o[8] * c, o[9] * c)), "r"(pack_bf16(o[12] * c, o[13] * c)) : "memory");
          }
        };
#pragma unroll 1
        for (int kb = 8; kb < 14; kb++) {
          issue_q(kb, IC<1>{});
          TK(66 + half * 24 + kb - 1);
        }
        TL(1, 20 * half + 0, warp == 4);
        mbar_wait_c(B(B_FULLQ + 2), 1);
        mbar_wait_c(B(B_FULLQ + 3), 1);
        bar_sync(1 + w, 256);
        wg_fence();
        mma_kc(s.S, IC<q_aw(2)>{}, IC<q_aw(2) + UNIT>{}, 1);
        wg_commit();
        wg_wait<1>();
        TK(66 + half * 24 + 13);
        release2(B(B_EMPTYQ + 1));
        wg_fence();
        mma_kc(s.S, IC<q_aw(3)>{}, IC<q_aw(3) + UNIT>{}, 1);
        wg_commit();
        bar_arrive(2 - w, 256);
        bar_sync(6 + w, 128);
        wg_wait<0>();
        TK(66 + half * 24 + 14);
        fence_regs(s.S);
        q_store(s.S);
        q_load(IC<0>{}, IC<8>{});
        TL(1, 20 * half + 1, warp == 4);
        mbar_wait_c(B(B_KF), kph & 1);
        kph ^= 1;
        bar_sync(1 + w, 256);
        fence_regs(s.S); fence_regs(s.O); fence_regs(s.Q);
        wg_fence();
        issue_s(k_slot(0, 0));
        mma_kc(s.O, IC<q_b(2)>{}, IC<q_aw(2) + UNIT>{}, 1);
        mma_kc(s.O, IC<q_b(3)>{}, IC<q_aw(3) + UNIT>{}, 1);
        wg_commit();
        bar_arrive(2 - w, 256);
        wg_wait<1>();
        fence_regs(s.S);
        e_arrive(B(B_KE));
        s.l[0] = s.l[1] = s.l[2] = s.l[3] = 0.f;
        if (gq == 0) {
          if (w == 0) {
            at_mask<0>(s, wrow, lane);
#pragma unroll
            for (int i = 32; i < 64; i++) s.S[i] = -INFINITY;
          } else {
            at_mask<8>(s, wrow - 64, lane);
          }
        }
        at_exp<0, 48>(s);
        at_pack<0, 22>(s);
        sched_fence();
        wg_wait<0>();
        fence_regs(s.O); fence_regs(s.Q);
        release2(B(B_EMPTYQ + 2)); release2(B(B_EMPTYQ + 3));
        at_exp<48, 64>(s);
        at_pack<22, 32>(s);
        q_store(s.O);
        if (gq == 0) q_load(IC<0>{}, IC<8>{});
        TL(1, 20 * half + 2, warp == 4);
        int kr = 1;
        bool kok = false;
        inv[0] = inv[1] = 0.f;
#pragma unroll 1
        for (int j = 1; j < 17; j++) {
          const bool diag = j == gq || j == qa;
          TC(w, j + 17 * half, 0);
          if (!kok) mbar_wait_c(B(B_KF + kr), (kph >> kr) & 1);
          kph ^= 1 << kr;
          if (j == gq + 2) ep_out(gq, IC<0>{}, IC<EP1>{});
          bar_sync(1 + w, 256);
          TC(w, j + 17 * half, 2);
          fence_regs(s.S); fence_regs(s.O); fence_regs(s.P); fence_regs(s.Q);
          const uint32_t ke = B(B_KE + kr), ko = k_slot(j, kr);
          if (++kr == 3) kr = 0;
          auto issue_rest = [&](auto trimmed) {
            TC(w, j + 17 * half, 1);
            at_sum(s);
            if (j == gq + 1) {
              if (ep_prep()) redo = 1;
              s.l[0] = s.l[1] = s.l[2] = s.l[3] = 0.f;
            }
            if (!trimmed && j == gq + 2) {
              ep_out(gq, IC<EP1>{}, IC<8>{});
              if (!__any_sync(~0u, redo)) publish(2 + 2 * half);
              fence_regs(s.O);
            }
            TC(w, j + 17 * half, 3);
            issue_pv(j - 1, j != 1 && j != gq + 2, w == 1 || (j != gq + 1 && j != qa + 1));
            bar_arrive(2 - w, 256);
          };
          auto s_done = [&]() {
            wg_wait<2>();
            TC(w, j + 17 * half, 4);
            fence_regs(s.S); fence_regs(s.Q);
            e_arrive(ke);
            release2(B(B_X + j - 14), j == 14 || j == 15);
          };
          auto pv_half = [&]() { sched_fence(); wg_wait<1>(); fence_regs(s.P); };
          auto pv_done = [&]() {
            sched_fence();
            wg_wait<0>();
            fence_regs(s.O); fence_regs(s.P);
            e_arrive(B(B_VE + ((j - 1) & 1)));
            kok = KTEST && mbar_test(B(B_KF + kr), (kph >> kr) & 1);
          };
          if (diag && w == 0) {
            wg_fence();
            static_for<8>([&](auto k) { mma_n64_rs<(k >> 2) * 16384 + (k & 3) * 32>(s.S, s.Q + 4 * k, dK + (ko >> 4), k != 0); });
            wg_commit();
            issue_rest(IC<1>{});
            s_done();
            at_mask<0>(s, wrow, lane);
            if (DELAY0 == 1) pv_half();
            if (DELAY0 == 2) pv_done();
            static_for<8>([&](auto k) {
              at_exp<4 * k, 4 * k + 4, 32>(s);
              q_load_if(k, j == gq, s.S[4 * k]);
              if (DELAY0 == 0 && k == 3) pv_half();
            });
            at_pack<0, 16>(s);
            if (DELAY0 < 2) pv_done();
            if (SUMV) {
#pragma unroll
              for (int i = 16; i < 32; i++) s.P[i] = 0;
            }
          } else {
            wg_fence();
            issue_s(ko);
            issue_rest(IC<0>{});
            if (!diag) {
              s_done();
              at_exp<0, 4 * SP1>(s);
              pv_half();
              at_exp<4 * SP1, 4 * SP2>(s);
              at_pack<0, 16>(s);
              pv_done();
              release2(B(B_X + 2), j == 16);
              at_exp<4 * SP2, 64>(s);
              at_pack<16, 32>(s);
            } else {
              s_done();
              at_mask<8>(s, wrow - 64, lane);
              static_for<8>([&](auto k) {
                at_exp<7 * k, 7 * k + 7>(s);
                q_load_if(k, j == gq, s.S[7 * k + 3]);
                if (k == 2) pv_half();
                if (k == 5) { at_pack<0, 16>(s); pv_done(); }
              });
              at_exp<56, 64>(s);
              at_pack<16, 32>(s);
            }
          }
          TL(1, 20 * half + 2 + j, warp == 4);
        }
        TK(84 + half * 24);
        bar_sync(1 + w, 256);
        fence_regs(s.S); fence_regs(s.O); fence_regs(s.P);
        issue_pv(16, 1, true);
        at_sum(s);
        if (ep_prep()) redo |= 2;
        TK(85 + half * 24);
        mbar_wait_c(B(half ? B_FULL3 : B_FULLQ), 0);
        wg_fence();
        mma_kc(s.S, IC<0>{}, IC<UNIT>{}, 0);
        mbar_wait_c(B(half ? B_FULL3 + 1 : B_FULLQ + 1), 0);
        wg_fence();
        mma_kb(s.S, (2 - half) * SLOT, (2 - half) * SLOT + UNIT, 1);
        wg_commit();
        if (w == 0 || half == 0) bar_arrive(2 - w, 256);
        TK(86 + half * 24);
        wg_wait<1>();
        TK(87 + half * 24);
        fence_regs(s.O);
        e_arrive(B(B_VE));
        release2(B(B_X + 3));
        fence_regs(s.P);
        {
          uint32_t r;
          asm volatile("mov.u32 %0, %%laneid;" : "=r"(r));
          cdst = g_ctx + (size_t)(qa * 128 + wrow + (r >> 2)) * NQ + head * 128 + (r & 3) * 8;
        }
#pragma unroll
        for (int i = 0; i < 32; i++) {
          const float* o = s.O + 16 * (i >> 3) + 2 * ((i >> 2) & 1) + 4 * (i & 3);
          s.P[i] = pack_bf16(o[0] * inv[(i >> 2) & 1], o[1] * inv[(i >> 2) & 1]);
        }
        fence_regs(s.P);
        if (__builtin_expect(__any_sync(~0u, redo != 0), 0)) {
#pragma unroll
          for (int i = 0; i < 8; i++) put_ctx(i, true);
#pragma unroll 1
          for (int t = 0; t < 2; t++) {
            if (__any_sync(~0u, (redo >> t) & 1)) slow_rows(wq, head, (t ? qa : gq) * 128 + wrow, lane);
          }
          if (__any_sync(~0u, redo & 1)) publish(2 + 2 * half);
#pragma unroll
          for (int i = 0; i < 64; i++) { s.O[i] = 0.f; s.P[i >> 1] = 0; }
          redo = 2;
        }
        TL(1, 20 * half + 19, warp == 4);
        TK(88 + half * 24);
        if (half) break;
        mbar_wait_c(B(B_FULLB), 0);
        TK(89);
        fence_regs(s.O);
        wg_fence();
        mma_kc(s.O, IC<q_b(0)>{}, IC<q_aw(0) + UNIT>{}, 0);
        wg_commit();
        mma_kc(s.O, IC<q_b(1)>{}, IC<q_aw(1) + UNIT>{}, 1);
        wg_commit();
        wg_wait<1>();
        release2(B(B_EMPTYQ));
        put_ctx(0, true);
#pragma unroll 1
        for (int kb = 2; kb < 8; kb++) {
          issue_q(kb, IC<1>{});
          TK(90 + kb - 1);
#pragma unroll
          for (int i = 1; i < 8; i++) put_ctx(i, kb == (i < 7 ? i + 1 : 7));
        }
        publish(3);
      }
    }
    const int wr_ = cw * 16 + (lane & 7) + (lane >> 4) * 8;
    const uint32_t wl = sb + wr_ * 64 + ((((lane >> 3) & 1) ^ ((wr_ >> 1) & 3)) << 4);
    __syncwarp();
    float (&acc)[64] = s.S;
    uint32_t wf[128];
    {
      int st = 2, prev = 1; uint32_t ph = 0;
      auto run = [&](auto k0, auto k1, auto c) {
#pragma unroll 1
        for (int kb = k0; kb < k1; kb++) {
          mbar_wait_c(B(B_FULL3 + st), ph);
          wg_fence();
          mma_kb(acc, r3(st), r3(st) + UNIT, 1);
          wg_commit();
          wg_wait<1>();
          if (k0 == 2) release2(B(B_EMPTY3), kb == 2);
          release2(B(B_EMPTY3 + prev));
          if (c >= 0) {
            constexpr int f = c >= 0 ? 16 * c : 0;
            if (WEF) sched_fence();
            asm volatile("{\n.reg .pred p;\n.reg .b32 t;\nsetp.eq.u32 p, %1, 0;\nlop3.b32 t, %1, %2, %3, 0xE8;\nlop3.b32 t, t, %4, %5, 0xE8;\n"
                         "mad.lo.u32 t, t, %6, %0;\n@p mbarrier.arrive.shared::cta.b64 _, [t];\n}"
                         ::"r"(B(B_WE + (c & 1))), "r"(lane | (kb - k0)), "r"(wf[f]), "r"(wf[f + 4]), "r"(wf[f + 8]), "r"(wf[f + 12]), "r"(zero) : "memory");
          }
          prev = st;
          if (++st == 6) { st = 0; ph ^= 1; }
#pragma unroll
          for (int i = 0; i < 8; i++) if (PUT0 + PUTD * i >= k0 && PUT0 + PUTD * i < k1) put_ctx(i, kb == PUT0 + PUTD * i);
          if (PUT0 + PUTD * 7 >= k0 && PUT0 + PUTD * 7 < k1 && kb == PUT0 + PUTD * 7) publish(5);
          if ((kb & 7) == 7) TL(2, 2 + (kb >> 3), warp == 4);
        }
      };
      static_for<WIN>([&](auto c) {
        run(IC<c == 0 ? 2 : GRAB0 + 8 * c - 8>{}, IC<GRAB0 + 8 * c>{}, IC<c - 1>{});
        if (ffn) mbar_wait_c(B(B_WF + (c & 1)), (c >> 1) & 1);
#pragma unroll
        for (int m = 0; m < 4; m++)
          asm volatile("ldmatrix.sync.aligned.m8n8.x4.trans.shared.b16 {%0,%1,%2,%3}, [%4];"
                       : "=r"(wf[16 * c + 4 * m]), "=r"(wf[16 * c + 4 * m + 1]), "=r"(wf[16 * c + 4 * m + 2]), "=r"(wf[16 * c + 4 * m + 3])
                       : "r"((wl + OFF_STG + (c & 1) * UNIT + (m >> 1) * 8192) ^ ((m & 1) << 5)) : "memory");
      });
      run(IC<GRAB0 + 8 * WIN - 8>{}, IC<64>{}, IC<WIN - 1>{});
    }
    const int r0 = lane >> 2;
    uint32_t hp[32], tb[16];
    mbar_wait_c(B(B_WF + w), ffn ? (WIN >> 1) & 1 : 0);
    mbar_wait_c(B(B_WR), 0);
    mbar_wait_c(B(B_SET2), 0);
#pragma unroll
    for (int j = 0; j < 16; j++) {
      const uint32_t q = stg + r0 * 128 + (lane & 3) * 4 + (j >> 3) * 8192 + (((j & 7) ^ r0) << 4);
      asm volatile("ld.shared.u32 %0, [%1];" : "=r"(hp[2 * j]) : "r"(q) : "memory");
      asm volatile("ld.shared.u32 %0, [%1];" : "=r"(hp[2 * j + 1]) : "r"(q + 1024) : "memory");
      asm volatile("ld.shared.u32 %0, [%1];" : "=r"(tb[j]) : "r"(sb + OFF_MISC + 512 + (r0 & 1) * 256 + (lane & 3) * 4 + j * 16) : "memory");
    }
    wg_wait<0>();
    fence_regs(acc);
    TL(2, 10, warp == 4);
    {
      float d[4] = {0.f, 0.f, 0.f, 0.f}, qa[4] = {0.f, 0.f, 0.f, 0.f}, qb[4] = {0.f, 0.f, 0.f, 0.f};
#pragma unroll
      for (int j = 0; j < 16; j++) {
        hp[2 * j] = hadd2_bf(hp[2 * j], pack_bf16(acc[4 * j], acc[4 * j + 1]));
        hp[2 * j + 1] = hadd2_bf(hp[2 * j + 1], pack_bf16(acc[4 * j + 2], acc[4 * j + 3]));
        if (j & 1) {
          mma16816(d, hp[2 * j - 2], hp[2 * j - 1], hp[2 * j], hp[2 * j + 1], tb[j - 1], tb[j]);
          mma16816(qa, hp[2 * j - 2], hp[2 * j - 1], hp[2 * j], hp[2 * j + 1], hp[2 * j - 2], hp[2 * j]);
          mma16816(qb, hp[2 * j - 2], hp[2 * j - 1], hp[2 * j], hp[2 * j + 1], hp[2 * j - 1], hp[2 * j + 1]);
        }
      }
      const float s2a = __shfl_sync(~0u, (r0 & 1) ? qa[1] : qa[0], r0 * 4 + (r0 >> 1));
      const float s2b = __shfl_sync(~0u, (r0 & 1) ? qb[3] : qb[2], r0 * 4 + (r0 >> 1));
      if ((lane & 3) == 0) {
        __stcg(reinterpret_cast<float4*>(xr + XR_PS + cw * 16 + r0), make_float4(d[0], s2a, d[1], 0.f));
        __stcg(reinterpret_cast<float4*>(xr + XR_PS + cw * 16 + r0 + 8), make_float4(d[2], s2b, d[3], 0.f));
      }
    }
    __syncwarp();
    stage_store_128(stg, lane, hp);
    TL(2, 11, warp == 4);
    __syncwarp();
    uint32_t* keys = reinterpret_cast<uint32_t*>(sp + OFF_MISC);
    {
      uint4 ps[4];
      poll_chunks(ps, g_xr + (mt * 8 + (ct & 1) * 4) * XR_SIZE + XR_PS + (ct >> 1), XR_SIZE);
      TL(2, 12, warp == 4);
      auto F = [](uint32_t u) { return __uint_as_float(u); };
      float s1 = (F(ps[0].x) + F(ps[1].x)) + (F(ps[2].x) + F(ps[3].x)), s2 = (F(ps[0].y) + F(ps[1].y)) + (F(ps[2].y) + F(ps[3].y));
      float s3 = (F(ps[0].z) + F(ps[1].z)) + (F(ps[2].z) + F(ps[3].z));
      s1 += __shfl_xor_sync(~0u, s1, 1); s2 += __shfl_xor_sync(~0u, s2, 1); s3 += __shfl_xor_sync(~0u, s3, 1);
      const float mean = s1 * (1.f / DM);
      float mb, inv;
      ln_round(mean, fmaxf(fmaf(s2, 1.f / DM, -mean * mean), 0.f), mb, inv);
      uint32_t u = pack_bf16((s3 - mb * *reinterpret_cast<const float*>(sp + OFF_MISC + 1024)) * inv, 0.f);
      if (u == 0x8000u) u = 0;
      u = (u & 0x8000u) ? (~u & 0xFFFFu) : (u | 0x8000u);
      const uint32_t key = (u << 16) | (0x7FFFu - (mt * 128 + (ct >> 1)));
      const uint32_t nm2 = pack_bf16(-mb, -mb);
      if (!(ct & 1)) *reinterpret_cast<uint2*>(sp + OFF_RSTAT + (ct >> 1) * 8) = make_uint2(nm2, __float_as_uint(inv));
      const uint32_t c1 = __reduce_max_sync(~0u, key);
      const uint32_t c2 = __reduce_max_sync(~0u, key == c1 ? 0u : key);
      if (lane == 0) __stcg(reinterpret_cast<uint2*>(xr + XR_KEY) + cw, make_uint2(c1, c2));
      const int row = (0x7FFF - (((lane >> 4) ? c2 : c1) & 0x7FFF)) & 15;
      const uint32_t rn = __shfl_sync(~0u, nm2, row * 2);
      const float ri = __shfl_sync(~0u, inv, row * 2);
      const uint4 v = lds128(stg + ((lane & 15) >> 3) * 8192 + row * 128 + (((lane & 7) ^ (row & 7)) << 4));
      __stcg(xr + XR_CAND + cw * 64 + 32 + lane, make_uint4(ln_apply(v.x, rn, ri), ln_apply(v.y, rn, ri), ln_apply(v.z, rn, ri), ln_apply(v.w, rn, ri)));
      __stcg(xr + XR_CAND + cw * 64 + lane, v);
    }
    publish(B_OUT - B_PUB);
    TL(2, 13, warp == 4);
    uint32_t wd[16][4];
    if (cw == 0) {
        uint4 kv[2];
        poll_chunks(kv, g_xr + ((lane >> 1) * 8 + gq) * XR_SIZE + XR_KEY + (lane & 1) * 2, 1);
        const uint32_t a1 = max(kv[0].x, kv[0].z), a2 = max(min(kv[0].x, kv[0].z), max(kv[0].y, kv[0].w));
        const uint32_t b1 = max(kv[1].x, kv[1].z), b2 = max(min(kv[1].x, kv[1].z), max(kv[1].y, kv[1].w));
        const uint32_t k1 = max(a1, b1), k2 = max(min(a1, b1), max(a2, b2));
        const uint32_t m1 = __reduce_max_sync(~0u, k1);
        const uint32_t m2 = __reduce_max_sync(~0u, k1 == m1 ? k2 : k1);
        if (lane == 0) {
          keys[16] = m1; keys[17] = m2;
          mbar_arrive(B(B_OUT2));
        }
    }
    bar_sync(3, 256);
    cluster_arrive();
    const uint32_t top1 = keys[16], top2 = keys[17];
    TL(2, 14, warp == 4);
    const int t0 = 0x7FFF - (top1 & 0x7FFF), t1 = 0x7FFF - (top2 & 0x7FFF);
    auto cand = [&](int second, int chunk) {
      const int tk = second ? t1 : t0;
      return g_xr + ((tk >> 7) * 8 + (chunk >> 4)) * XR_SIZE + XR_CAND + ((tk >> 4) & 7) * 64 + ((second && (t0 >> 4) == (t1 >> 4)) ? 16 : 0) + (chunk & 15);
    };
    if (rid == 127 && ct < C_NUM) g_cnt[ct] = 0;
    if (ffn) {
      const int c8 = ct & 127;
      *reinterpret_cast<uint4*>(sp + OFF_SCR + w * 2064 + c8 * 16) = poll_chunk(cand(w, c8) + 32);
#pragma unroll
      for (int c = WIN; c < 8; c++) {
        const int it = NIT + (c - WIN) / 2;
        if (((c - WIN) & 1) == 0) mbar_wait_c(B(B_FULL3 + it % 6), (it / 6) & 1);
#pragma unroll
        for (int m = 0; m < 4; m++)
          asm volatile("ldmatrix.sync.aligned.m8n8.x4.trans.shared.b16 {%0,%1,%2,%3}, [%4];"
                       : "=r"(wf[16 * c + 4 * m]), "=r"(wf[16 * c + 4 * m + 1]), "=r"(wf[16 * c + 4 * m + 2]), "=r"(wf[16 * c + 4 * m + 3])
                       : "r"((wl + r3(it % 6) + ((c - WIN) & 1) * 16384 + (m >> 1) * 8192) ^ ((m & 1) << 5)) : "memory");
      }
      bar_sync(3, 256);
      TL(2, 15, warp == 4);
      float d[4][4];
#pragma unroll
      for (int m = 0; m < 4; m++) d[m][0] = d[m][1] = d[m][2] = d[m][3] = 0.f;
#pragma unroll
      for (int k = 0; k < 8; k++) {
        const uint8_t* bp = sp + OFF_SCR + (r0 & 1) * 2064 + (k * 128 + cw * 16 + (lane & 3) * 2) * 2;
        const uint32_t b0 = *reinterpret_cast<const uint32_t*>(bp), b1 = *reinterpret_cast<const uint32_t*>(bp + 16);
#pragma unroll
        for (int m = 0; m < 4; m++) mma16816(d[m], wf[16 * k + 4 * m], wf[16 * k + 4 * m + 1], wf[16 * k + 4 * m + 2], wf[16 * k + 4 * m + 3], b0, b1);
      }
      float* red = reinterpret_cast<float*>(sp + OFF_SCR + 8192);
      if ((lane & 3) == 0) {
#pragma unroll
        for (int m = 0; m < 4; m++) {
          *reinterpret_cast<float2*>(red + cw * 128 + (m * 16 + r0) * 2) = make_float2(d[m][0], d[m][1]);
          *reinterpret_cast<float2*>(red + cw * 128 + (m * 16 + 8 + r0) * 2) = make_float2(d[m][2], d[m][3]);
        }
      }
      const int wds = w ? (IT_WD + 1) % 6 : IT_WD % 6;
      mbar_wait_c(B(B_FULL3 + wds), w ? ((IT_WD + 1) / 6) & 1 : (IT_WD / 6) & 1);
#pragma unroll
      for (int i = 0; i < 16; i++) {
        const int k = (i & 1) * 16 + (lane & 7) + (lane >> 4) * 8;
        asm volatile("ldmatrix.sync.aligned.m8n8.x4.trans.shared.b16 {%0,%1,%2,%3}, [%4];"
                     : "=r"(wd[i][0]), "=r"(wd[i][1]), "=r"(wd[i][2]), "=r"(wd[i][3])
                     : "r"(sb + (w ? r3((IT_WD + 1) % 6) : r3(IT_WD % 6)) + (2 * (cw & 3) + (i >> 3)) * 4096 + k * 128 + (((2 * ((i >> 1) & 3) + ((lane >> 3) & 1)) ^ (lane & 7)) << 4)) : "memory");
      }
      bar_sync(3, 256);
      TL(2, 16, warp == 4);
      if (ct < 64) {
        float u = 0.f, gg = 0.f;
#pragma unroll
        for (int i = 0; i < 8; i++) { u += red[i * 128 + ct]; gg += red[i * 128 + 64 + ct]; }
        u = bf_round(u); gg = bf_round(gg);
        const float sg = bf_round(__fdividef(gg, 1.f + __expf(-gg)));
        reinterpret_cast<__nv_bfloat16*>(sp + OFF_MISC + 128)[(ct & 1) * 40 + (ct >> 1)] = __float2bfloat16_rn(sg * u);
      }
      bar_sync(3, 256);
      TL(2, 17, warp == 4);
      const uint32_t* ap = reinterpret_cast<const uint32_t*>(sp + OFF_MISC + 128 + (r0 & 1) * 80 + (lane & 3) * 4);
      const uint32_t a0 = ap[0], a1 = ap[4], a2 = ap[8], a3 = ap[12];
      float2* yp = reinterpret_cast<float2*>(sp + OFF_SCR + 16384) + cw * 128 + r0;
#pragma unroll
      for (int i = 0; i < 8; i++) {
        float y[4] = {0.f, 0.f, 0.f, 0.f};
        mma16816(y, wd[2 * i][0], wd[2 * i][1], wd[2 * i][2], wd[2 * i][3], a0, a1);
        mma16816(y, wd[2 * i + 1][0], wd[2 * i + 1][1], wd[2 * i + 1][2], wd[2 * i + 1][3], a2, a3);
        if ((lane & 3) == 0) { yp[i * 16] = make_float2(y[0], y[1]); yp[i * 16 + 8] = make_float2(y[2], y[3]); }
      }
      __syncwarp();
      uint4* yd = g_xr + (cw * 16 + (lane >> 2)) * XR_SIZE + XR_Y + fid * 4 + (lane & 3);
      __stcg(yd, lds128(sb + OFF_SCR + 16384 + cw * 1024 + lane * 16));
      __stcg(yd + 8 * XR_SIZE, lds128(sb + OFF_SCR + 16384 + cw * 1024 + 512 + lane * 16));
    }
    TL(2, 18, warp == 4);
    TL(2, 38, warp == 11);
    {
      float* red2 = reinterpret_cast<float*>(sp + OFF_SCR + 12288);
      uint4 hv, hx;
      float rs;
      if (cw == 7) {
        hv = poll_chunk(cand(lane & 1, rid));
        hx = poll_chunk(cand(lane & 1, rid) + 32);
        uint32_t u = ((lane & 1) ? top2 : top1) >> 16;
        u = (u & 0x8000u) ? (u & 0x7FFFu) : (~u & 0xFFFFu);
        rs = bf_round(__fdividef(1.f, 1.f + __expf(-__uint_as_float(u << 16))));
        TL(2, 37, rs > -1.f);
      } else {
        uint4 z[2];
        poll_chunks(z, xr + XR_Y + ct * 2, 1);
        __syncwarp();
        TL(2, 30 + cw, true);
        float v[8] = {__uint_as_float(z[0].x), __uint_as_float(z[0].y), __uint_as_float(z[0].z), __uint_as_float(z[0].w),
                      __uint_as_float(z[1].x), __uint_as_float(z[1].y), __uint_as_float(z[1].z), __uint_as_float(z[1].w)};
#pragma unroll
        for (int i = 0; i < 4; i++) { const bool up = lane & 8; v[i] = (up ? v[i + 4] : v[i]) + __shfl_xor_sync(~0u, up ? v[i] : v[i + 4], 8); }
#pragma unroll
        for (int i = 0; i < 2; i++) { const bool up = lane & 4; v[i] = (up ? v[i + 2] : v[i]) + __shfl_xor_sync(~0u, up ? v[i] : v[i + 2], 4); }
        { const bool up = lane & 2; v[0] = (up ? v[1] : v[0]) + __shfl_xor_sync(~0u, up ? v[0] : v[1], 2); }
        v[0] += __shfl_xor_sync(~0u, v[0], 16);
        if (lane < 16) red2[cw * 16 + (lane & 1) * 8 + (lane >> 1)] = v[0];
      }
      bar_sync(3, 256);
      TL(2, 19, warp == 4);
      if (cw == 7) {
        float y = 0.f;
#pragma unroll
        for (int i = 0; i < 7; i++) y += red2[i * 16 + (lane & 15)];
        const uint32_t hw[4] = {hv.x, hv.y, hv.z, hv.w}, hm[4] = {hx.x, hx.y, hx.z, hx.w};
        uint32_t o[4];
#pragma unroll
        for (int e = 0; e < 4; e++) {
          const uint32_t yb = pack_bf16(__shfl_sync(~0u, y, 4 * e + (lane & 1)), __shfl_sync(~0u, y, 4 * e + 2 + (lane & 1)));
          o[e] = hadd2_bf(hw[e], hadd2_bf(hm[e], pack_bf16(bf_lo(yb) * rs, bf_hi(yb) * rs)));
        }
        if (lane < 2) reinterpret_cast<uint4*>(out + (size_t)(lane ? t1 : t0) * DM)[rid] = make_uint4(o[0], o[1], o[2], o[3]);
        TL(2, 21, true);
      }
    }
    TL(2, 20, warp == 4);
    __syncwarp();
    cluster_wait();
  }
}

typedef CUresult (*EncodeFn)(CUtensorMap*, CUtensorMapDataType, cuuint32_t, void*, const cuuint64_t*, const cuuint64_t*, const cuuint32_t*,
                             const cuuint32_t*, CUtensorMapInterleave, CUtensorMapSwizzle, CUtensorMapL2promotion, CUtensorMapFloatOOBfill);
EncodeFn g_enc = nullptr;

void map2(CUtensorMap* m, const void* ptr, uint64_t rows, uint64_t cols, uint32_t bc, uint32_t br) {
  const CUtensorMapSwizzle sw = bc == 64 ? CU_TENSOR_MAP_SWIZZLE_128B : CU_TENSOR_MAP_SWIZZLE_64B;
  cuuint64_t gd[2] = {cols, rows}, gs[1] = {cols * 2};
  cuuint32_t bd[2] = {bc, br}, es[2] = {1, 1};
  g_enc(m, CU_TENSOR_MAP_DATA_TYPE_BFLOAT16, 2, (void*)ptr, gd, gs, bd, es, CU_TENSOR_MAP_INTERLEAVE_NONE, sw,
        CU_TENSOR_MAP_L2_PROMOTION_L2_128B, CU_TENSOR_MAP_FLOAT_OOB_FILL_NONE);
}
void map3(CUtensorMap* m, const void* ptr, uint64_t rows, uint64_t cols, uint32_t br, uint32_t bch) {
  cuuint64_t gd[3] = {64, rows, cols / 64}, gs[2] = {cols * 2, 128};
  cuuint32_t bd[3] = {64, br, bch}, es[3] = {1, 1, 1};
  g_enc(m, CU_TENSOR_MAP_DATA_TYPE_BFLOAT16, 3, (void*)ptr, gd, gs, bd, es, CU_TENSOR_MAP_INTERLEAVE_NONE, CU_TENSOR_MAP_SWIZZLE_128B,
        CU_TENSOR_MAP_L2_PROMOTION_L2_128B, CU_TENSOR_MAP_FLOAT_OOB_FILL_NONE);
}

}

extern "C" void kernel_launch(void* const* d_in, const int* in_sizes, int n_in, void* d_out, int out_size) {
  const __nv_bfloat16* x = (const __nv_bfloat16*)d_in[0];
  const __nv_bfloat16* ckv = (const __nv_bfloat16*)d_in[1];
  const __nv_bfloat16* wq = (const __nv_bfloat16*)d_in[2];
  const __nv_bfloat16* wk = (const __nv_bfloat16*)d_in[3];
  const __nv_bfloat16* wv = (const __nv_bfloat16*)d_in[4];
  const __nv_bfloat16* wo = (const __nv_bfloat16*)d_in[5];
  const __nv_bfloat16* w_r = (const __nv_bfloat16*)d_in[7];
  const __nv_bfloat16* wgate = (const __nv_bfloat16*)d_in[8];
  const __nv_bfloat16* wup = (const __nv_bfloat16*)d_in[9];
  const __nv_bfloat16* wdown = (const __nv_bfloat16*)d_in[10];
  __nv_bfloat16* out = (__nv_bfloat16*)d_out;

  if (!g_enc) {
    void* fn = nullptr;
    cudaDriverEntryPointQueryResult qr;
    cudaGetDriverEntryPoint("cuTensorMapEncodeTiled", &fn, cudaEnableDefault, &qr);
    g_enc = (EncodeFn)fn;
    cudaFuncSetAttribute(fused_kernel, cudaFuncAttributeMaxDynamicSharedMemorySize, SMEM_BYTES);
  }
  void *xn, *kv, *ctx;
  cudaGetSymbolAddress(&xn, g_xn);
  cudaGetSymbolAddress(&kv, g_kv);
  cudaGetSymbolAddress(&ctx, g_ctx);

  Params p;
  map2(&p.xn, xn, SEQ, DM, 64, 64);
  map2(&p.ckv, ckv, SEQ, DC, 64, 128);
  map3(&p.wq, wq, DM, NQ, 64, 2);
  map3(&p.wk, wk, DC, NQ, 64, 2);
  map3(&p.wv, wv, DC, NQ, 64, 2);
  map3(&p.kv_ld, kv, 2 * SEQ, NQ, 128, 2);
  map2(&p.ctx_ld, ctx, SEQ, NQ, 64, 128);
  map3(&p.wo, wo, NQ, DM, 64, 1);
  map3(&p.x, x, SEQ, DM, 64, 2);
  map3(&p.wd, wdown, FF, DM, 32, 8);
  map2(&p.out, out, SEQ, DM, 64, 8);
  map2(&p.wg, wgate, DM, FF, 32, 64);
  map2(&p.wu, wup, DM, FF, 32, 64);
  fused_kernel<<<128, 384, SMEM_BYTES, cudaStreamPerThread>>>(p, x, wq, w_r, wgate, wup, out, 0u);
}
```

```cpp
#include <cuda_runtime.h>
#include <cuda_bf16.h>
#include <cuda.h>
#include <stdint.h>
#include <utility>

#pragma nv_diag_suppress 549
#pragma nv_diag_suppress 177
namespace {

constexpr int SEQ = 2048, DM = 1024, NH = 32, HD = 128, DC = 512, NQ = NH * HD, FF = 3584;

__device__ __align__(1024) __nv_bfloat16 g_xn[SEQ * DM];
__device__ __align__(1024) __nv_bfloat16 g_kv[2 * SEQ * NQ];
__device__ __align__(1024) __nv_bfloat16 g_ctx[SEQ * NQ];
constexpr int XR_PS = 0;
constexpr int XR_KEY = 128;
constexpr int XR_CAND = 136;
constexpr int XR_Y = 648;
constexpr int XR_SIZE = 1104;
__device__ __align__(1024) uint4 g_xr[128 * XR_SIZE];
constexpr int C_LN = 0, C_KV = 16, C_CTX = 32, C_NUM = 64;
__device__ unsigned g_cnt[C_NUM];

#define TL(k, i, cond) do {} while (0)
#define TC(w, g, i) do {} while (0)
#define TL_EXTRA 0
#define TK(i) do {} while (0)

__device__ __forceinline__ uint32_t s2u(const void* p) { return (uint32_t)__cvta_generic_to_shared(p); }
__device__ __forceinline__ void mbar_arrive(uint32_t b) { asm volatile("mbarrier.arrive.shared::cta.b64 _, [%0];" ::"r"(b) : "memory"); }
__device__ __forceinline__ void mbar_arrive_both(uint32_t b, uint32_t lane, bool cond) {
  asm volatile("{\n.reg .pred p;\n.reg .b32 r;\nsetp.lt.u32 p, %1, %2;\nmapa.shared::cluster.u32 r, %0, %1;\n@p mbarrier.arrive.shared::cluster.b64 _, [r];\n}"
               ::"r"(b), "r"(lane), "r"(cond ? 2 : 0) : "memory");
}
__device__ __forceinline__ bool mbar_test(uint32_t b, uint32_t ph) {
  uint32_t ok;
  asm volatile("{\n.reg .pred p;\nmbarrier.test_wait.parity.shared::cta.b64 p, [%1], %2;\nselp.u32 %0, 1, 0, p;\n}" : "=r"(ok) : "r"(b), "r"(ph) : "memory");
  return __all_sync(~0u, ok);
}
__device__ __forceinline__ void mbar_wait(uint32_t b, uint32_t ph) {
  asm volatile(
      "{\n.reg .pred p;\n.reg .u32 n;\nmov.u32 n, 0;\n"
      "LW:\nmbarrier.try_wait.parity.shared::cta.b64 p, [%0], %1, 20000;\n@p bra LD;\n"
      "add.u32 n, n, 1;\nsetp.lt.u32 p, n, 0x40000;\n@p bra LW;\ntrap;\nLD:\n}" ::"r"(b), "r"(ph) : "memory");
}
__device__ __forceinline__ void mbar_wait_u(uint32_t b, uint32_t ph) {
  asm volatile(
      "{\n.reg .pred p;\n.reg .u32 n;\nmov.u32 n, 0;\n"
      "LW:\nmbarrier.try_wait.parity.shared::cta.b64 p, [%0], %1, 20000;\n@p bra.uni LD;\n"
      "add.u32 n, n, 1;\nsetp.lt.u32 p, n, 0x40000;\n@p bra.uni LW;\ntrap;\nLD:\n}" ::"r"(b), "r"(ph) : "memory");
}
__device__ __forceinline__ void mbar_wait_c(uint32_t b, uint32_t ph) {
  asm volatile(
      "{\n.reg .pred p;\n.reg .u32 n;\nmov.u32 n, 0;\n"
      "LW:\nmbarrier.try_wait.parity.shared::cta.b64 p, [%0], %1;\n@p bra.uni LD;\n"
      "add.u32 n, n, 1;\nsetp.lt.u32 p, n, 0x100000;\n@p bra.uni LW;\ntrap;\nLD:\n}" ::"r"(b), "r"(ph) : "memory");
}
template <bool SLEEP = false>
__device__ __forceinline__ void spin_until_ge(const unsigned* p, unsigned target) {
  asm volatile(
      "{\n.reg .pred p, q;\n.reg .u32 n, v;\nmov.u32 n, 0;\nsetp.ne.u32 q, %2, 0;\n"
      "LW:\nld.acquire.gpu.global.u32 v, [%0];\nsetp.ge.u32 p, v, %1;\n@p bra LD;\n@q nanosleep.u32 200;\n"
      "add.u32 n, n, 1;\nsetp.lt.u32 p, n, 0x400000;\n@p bra LW;\ntrap;\nLD:\n}" ::"l"(p), "r"(target), "n"((int)SLEEP) : "memory");
}
template <int N>
__device__ __forceinline__ void poll_chunks(uint4 (&v)[N], const uint4* p, int stride) {
#pragma unroll 1
  for (int n = 0; n < 0x400000; n++) {
    uint32_t m = 0;
#pragma unroll
    for (int i = 0; i < N; i++) {
      asm volatile("ld.relaxed.gpu.global.v4.u32 {%0,%1,%2,%3}, [%4];" : "=r"(v[i].x), "=r"(v[i].y), "=r"(v[i].z), "=r"(v[i].w) : "l"(p + i * stride) : "memory");
    }
#pragma unroll
    for (int i = 0; i < N; i++) m = max(max(m, max(v[i].x, v[i].y)), max(v[i].z, v[i].w));
    if (__all_sync(~0u, m != 0xFFFFFFFFu)) break;
  }
}
__device__ __forceinline__ void fence_async_all() { asm volatile("fence.proxy.async;" ::: "memory"); }
__device__ __forceinline__ void bar_sync(int id, int n) { asm volatile("bar.sync %0, %1;" ::"r"(id), "r"(n) : "memory"); }
__device__ __forceinline__ void bar_arrive(int id, int n) { asm volatile("bar.arrive %0, %1;" ::"r"(id), "r"(n) : "memory"); }
__device__ __forceinline__ void cluster_arrive() { asm volatile("barrier.cluster.arrive.relaxed.aligned;" ::: "memory"); }
__device__ __forceinline__ void cluster_wait() { asm volatile("barrier.cluster.wait.acquire.aligned;" ::: "memory"); }
__device__ __forceinline__ void fence_gpu() { asm volatile("fence.acq_rel.gpu;" ::: "memory"); }
__device__ __forceinline__ void red_add(unsigned* p, unsigned v) { asm volatile("red.relaxed.gpu.global.add.u32 [%0], %1;" ::"l"(p), "r"(v) : "memory"); }
#define ELECT "{\n.reg .pred E;\nelect.sync _|E, 0xFFFFFFFF;\n@E "
__device__ __forceinline__ void e_init(uint32_t b, uint32_t c) { asm volatile(ELECT "mbarrier.init.shared::cta.b64 [%0], %1;\n}" ::"r"(b), "r"(c) : "memory"); }
__device__ __forceinline__ void e_expect(uint32_t b, uint32_t bytes) { asm volatile(ELECT "mbarrier.arrive.expect_tx.shared::cta.b64 _, [%0], %1;\n}" ::"r"(b), "r"(bytes) : "memory"); }
__device__ __forceinline__ void e_arrive(uint32_t b) { asm volatile(ELECT "mbarrier.arrive.shared::cta.b64 _, [%0];\n}" ::"r"(b) : "memory"); }
__device__ __forceinline__ void prefetch_tm(const CUtensorMap* m) { asm volatile(ELECT "prefetch.tensormap [%0];\n}" ::"l"(m) : "memory"); }
__device__ __forceinline__ void tma_ld2(uint32_t dst, const CUtensorMap* m, uint32_t bar, int c0, int c1) {
  asm volatile(ELECT "cp.async.bulk.tensor.2d.shared::cta.global.mbarrier::complete_tx::bytes [%0], [%1, {%3,%4}], [%2];\n}" ::"r"(dst), "l"(m), "r"(bar), "r"(c0), "r"(c1) : "memory");
}
__device__ __forceinline__ void tma_ld3(uint32_t dst, const CUtensorMap* m, uint32_t bar, int c0, int c1, int c2) {
  asm volatile(ELECT "cp.async.bulk.tensor.3d.shared::cta.global.mbarrier::complete_tx::bytes [%0], [%1, {%3,%4,%5}], [%2];\n}" ::"r"(dst), "l"(m), "r"(bar), "r"(c0), "r"(c1), "r"(c2) : "memory");
}
__device__ __forceinline__ void tma_ld2_mc(uint32_t dst, const CUtensorMap* m, uint32_t bar, int c0, int c1, uint16_t mask) {
  asm volatile(ELECT "cp.async.bulk.tensor.2d.shared::cluster.global.mbarrier::complete_tx::bytes.multicast::cluster [%0], [%1, {%3,%4}], [%2], %5;\n}" ::"r"(dst), "l"(m), "r"(bar), "r"(c0), "r"(c1), "h"(mask) : "memory");
}
__device__ __forceinline__ void tma_ld3_mc(uint32_t dst, const CUtensorMap* m, uint32_t bar, int c0, int c1, int c2, uint16_t mask) {
  asm volatile(ELECT "cp.async.bulk.tensor.3d.shared::cluster.global.mbarrier::complete_tx::bytes.multicast::cluster [%0], [%1, {%3,%4,%5}], [%2], %6;\n}" ::"r"(dst), "l"(m), "r"(bar), "r"(c0), "r"(c1), "r"(c2), "h"(mask) : "memory");
}
__device__ __forceinline__ void tma_pf2(const CUtensorMap* m, int c0, int c1) { asm volatile(ELECT "cp.async.bulk.prefetch.tensor.2d.L2.global [%0, {%1,%2}];\n}" ::"l"(m), "r"(c0), "r"(c1) : "memory"); }
__device__ __forceinline__ void tma_pf3(const CUtensorMap* m, int c0, int c1, int c2) { asm volatile(ELECT "cp.async.bulk.prefetch.tensor.3d.L2.global [%0, {%1,%2,%3}];\n}" ::"l"(m), "r"(c0), "r"(c1), "r"(c2) : "memory"); }
__device__ __forceinline__ void sched_fence() { asm volatile("pmevent 0;" ::: "memory"); }
__device__ __forceinline__ void l2_prefetch(const void* p, uint32_t bytes) { asm volatile(ELECT "cp.async.bulk.prefetch.L2.global [%0], %1;\n}" ::"l"(p), "r"(bytes) : "memory"); }

__device__ __forceinline__ void wg_fence() { asm volatile("wgmma.fence.sync.aligned;" ::: "memory"); }
__device__ __forceinline__ void wg_commit() { asm volatile("wgmma.commit_group.sync.aligned;" ::: "memory"); }
template <int N> __device__ __forceinline__ void wg_wait() { asm volatile("wgmma.wait_group.sync.aligned %0;" ::"n"(N) : "memory"); }
template <int N> __device__ __forceinline__ void reg_alloc() { asm volatile("setmaxnreg.inc.sync.aligned.u32 %0;" ::"n"(N)); }
template <int N> __device__ __forceinline__ void reg_dealloc() { asm volatile("setmaxnreg.dec.sync.aligned.u32 %0;" ::"n"(N)); }
template <int N> __device__ __forceinline__ void fence_regs(float (&d)[N]) {
#pragma unroll
  for (int i = 0; i < N; i++) asm volatile("" : "+f"(d[i])::"memory");
}
template <int N> __device__ __forceinline__ void fence_regs(uint32_t (&d)[N]) {
#pragma unroll
  for (int i = 0; i < N; i++) asm volatile("" : "+r"(d[i])::"memory");
}

__device__ __forceinline__ uint32_t mk_desc(uint32_t addr, uint32_t lbo) { return ((addr & 0x3FFFF) >> 4) | ((lbo >> 4) << 16); }

#define R8(b) "+f"(d[b + 0]), "+f"(d[b + 1]), "+f"(d[b + 2]), "+f"(d[b + 3]), "+f"(d[b + 4]), "+f"(d[b + 5]), "+f"(d[b + 6]), "+f"(d[b + 7])
#define REGS64 "%0,%1,%2,%3,%4,%5,%6,%7,%8,%9,%10,%11,%12,%13,%14,%15,%16,%17,%18,%19,%20,%21,%22,%23,%24,%25,%26,%27,%28,%29,%30,%31," \
               "%32,%33,%34,%35,%36,%37,%38,%39,%40,%41,%42,%43,%44,%45,%46,%47,%48,%49,%50,%51,%52,%53,%54,%55,%56,%57,%58,%59,%60,%61,%62,%63"
#define REGS128 REGS64 ",%64,%65,%66,%67,%68,%69,%70,%71,%72,%73,%74,%75,%76,%77,%78,%79,%80,%81,%82,%83,%84,%85,%86,%87,%88,%89,%90,%91,%92,%93,%94,%95," \
               "%96,%97,%98,%99,%100,%101,%102,%103,%104,%105,%106,%107,%108,%109,%110,%111,%112,%113,%114,%115,%116,%117,%118,%119,%120,%121,%122,%123,%124,%125,%126,%127"

#define DESC(d, r, o) "add.u32 t, " r ", " o ";\nmov.b64 " d ", {t, h};\n"
#define MMA_PRE(acc) "{\n.reg .pred p;\n.reg .b32 t, h;\n.reg .b64 da, db;\nmov.b32 h, 0x40000040;\nsetp.ne.b32 p, " acc ", 0;\n"
template <int TB, int OA, int OB>
__device__ __forceinline__ void mma_n256_ss(float (&d)[128], uint32_t a, uint32_t b, int acc) {
  asm volatile(MMA_PRE("%130") DESC("da", "%128", "%132") DESC("db", "%129", "%133")
               "wgmma.mma_async.sync.aligned.m64n256k16.f32.bf16.bf16 {" REGS128 "}, da, db, p, 1, 1, 0, %131;\n}\n"
               : R8(0), R8(8), R8(16), R8(24), R8(32), R8(40), R8(48), R8(56), R8(64), R8(72), R8(80), R8(88), R8(96), R8(104), R8(112), R8(120)
               : "r"(a), "r"(b), "r"(acc), "n"(TB), "n"(OA >> 4), "n"(OB >> 4));
}
template <int TB, int OA, int OB>
__device__ __forceinline__ void mma_n128_ss(float (&d)[64], uint32_t a, uint32_t b, int acc) {
  asm volatile(MMA_PRE("%66") DESC("da", "%64", "%68") DESC("db", "%65", "%69")
               "wgmma.mma_async.sync.aligned.m64n128k16.f32.bf16.bf16 {" REGS64 "}, da, db, p, 1, 1, 0, %67;\n}\n"
               : R8(0), R8(8), R8(16), R8(24), R8(32), R8(40), R8(48), R8(56)
               : "r"(a), "r"(b), "r"(acc), "n"(TB), "n"(OA >> 4), "n"(OB >> 4));
}
template <int TB, int OB>
__device__ __forceinline__ void mma_n128_rs(float (&d)[64], const uint32_t* a, uint32_t b, int acc) {
  asm volatile(MMA_PRE("%69") DESC("db", "%68", "%71")
               "wgmma.mma_async.sync.aligned.m64n128k16.f32.bf16.bf16 {" REGS64 "}, {%64,%65,%66,%67}, db, p, 1, 1, %70;\n}\n"
               : R8(0), R8(8), R8(16), R8(24), R8(32), R8(40), R8(48), R8(56)
               : "r"(a[0]), "r"(a[1]), "r"(a[2]), "r"(a[3]), "r"(b), "r"(acc), "n"(TB), "n"(OB >> 4));
}
template <int OB>
__device__ __forceinline__ void mma_n64_rs(float (&d)[64], const uint32_t* a, uint32_t b, int acc) {
  asm volatile(MMA_PRE("%37") DESC("db", "%36", "%38")
               "wgmma.mma_async.sync.aligned.m64n64k16.f32.bf16.bf16 {%0,%1,%2,%3,%4,%5,%6,%7,%8,%9,%10,%11,%12,%13,%14,%15,%16,%17,%18,%19,%20,%21,"
               "%22,%23,%24,%25,%26,%27,%28,%29,%30,%31}, {%32,%33,%34,%35}, db, p, 1, 1, 0;\n}\n"
               : R8(0), R8(8), R8(16), R8(24)
               : "r"(a[0]), "r"(a[1]), "r"(a[2]), "r"(a[3]), "r"(b), "r"(acc), "n"(OB >> 4));
}
template <int V> struct IC { static constexpr int value = V; __host__ __device__ constexpr operator int() const { return V; } };
template <int N, class F, int... I>
__device__ __forceinline__ void static_for_(F f, std::integer_sequence<int, I...>) { (f(IC<I>{}), ...); }
template <int N, class F>
__device__ __forceinline__ void static_for(F f) { static_for_<N>(f, std::make_integer_sequence<int, N>{}); }
__device__ __forceinline__ uint32_t pack_bf16(float lo, float hi) {
  uint32_t r;
  asm("cvt.rn.bf16x2.f32 %0, %1, %2;" : "=r"(r) : "f"(hi), "f"(lo));
  return r;
}
__device__ __forceinline__ float bf_lo(uint32_t v) { return __uint_as_float(v << 16); }
__device__ __forceinline__ float bf_hi(uint32_t v) { return __uint_as_float(v & 0xFFFF0000u); }
__device__ __forceinline__ float bf_round(float v) { return bf_lo(pack_bf16(v, v)); }
__device__ __forceinline__ void stsm4(uint32_t addr, uint32_t r0, uint32_t r1, uint32_t r2, uint32_t r3) {
  asm volatile("stmatrix.sync.aligned.m8n8.x4.shared.b16 [%0], {%1,%2,%3,%4};" ::"r"(addr), "r"(r0), "r"(r1), "r"(r2), "r"(r3) : "memory");
}
__device__ __forceinline__ uint4 lds128(uint32_t addr) {
  uint4 v;
  asm volatile("ld.shared.v4.u32 {%0,%1,%2,%3}, [%4];" : "=r"(v.x), "=r"(v.y), "=r"(v.z), "=r"(v.w) : "r"(addr));
  return v;
}
__device__ __forceinline__ float ex2(float x) {
  float y;
  asm("ex2.approx.ftz.f32 %0, %1;" : "=f"(y) : "f"(x));
  return y;
}
__device__ __forceinline__ void stage_store_128(uint32_t base, int lane, const uint32_t* pk) {
  const int row = (lane & 7) + ((lane >> 3) & 1) * 8;
  const uint32_t rb = base + row * 128;
  const int hi = lane >> 4;
#pragma unroll
  for (int j = 0; j < 8; j++) {
    const int chunk = 2 * j + hi;
    const uint32_t a = rb + (j >> 2) * 8192 + (((chunk & 7) ^ (lane & 7)) << 4);
    stsm4(a, pk[4 * j + 0], pk[4 * j + 1], pk[4 * j + 2], pk[4 * j + 3]);
  }
}
__device__ __forceinline__ void ln_round(float mean, float var, float& m_bf, float& inv_s) {
  const uint32_t mv = pack_bf16(mean, var);
  m_bf = bf_lo(mv);
  float sq, rc;
  asm("sqrt.approx.f32 %0, %1;" : "=f"(sq) : "f"(bf_round(bf_hi(mv) + 1e-5f)));
  asm("rcp.approx.ftz.f32 %0, %1;" : "=f"(rc) : "f"(bf_round(sq)));
  inv_s = rc;
}
__device__ __forceinline__ uint32_t hadd2_bf(uint32_t a, uint32_t b) {
  uint32_t r;
  asm("add.rn.bf16x2 %0, %1, %2;" : "=r"(r) : "r"(a), "r"(b));
  return r;
}
__device__ __forceinline__ uint32_t ln_apply(uint32_t h, uint32_t nm2, float inv_s) {
  const uint32_t d = hadd2_bf(h, nm2);
  return pack_bf16(bf_lo(d) * inv_s, bf_hi(d) * inv_s);
}
__device__ __forceinline__ void mma16816(float* d, uint32_t a0, uint32_t a1, uint32_t a2, uint32_t a3, uint32_t b0, uint32_t b1) {
  asm volatile("mma.sync.aligned.m16n8k16.row.col.f32.bf16.bf16.f32 {%0,%1,%2,%3}, {%4,%5,%6,%7}, {%8,%9}, {%0,%1,%2,%3};"
               : "+f"(d[0]), "+f"(d[1]), "+f"(d[2]), "+f"(d[3]) : "r"(a0), "r"(a1), "r"(a2), "r"(a3), "r"(b0), "r"(b1));
}

constexpr float AT_C = 0.08838834764831845f * 1.4426950408889634f;
#define L_MIN 2.3283064e-10f
#define L_MAX 1.0995116e12f
#define SP1 6
#define SP2 12
struct AtState {
  float S[64], O[64];
  uint32_t P[32], Q[32];
  float l[4];
};
#define SUMV 0
#define LAG 0
template <int I0, int I1, int N = 64>
__device__ __forceinline__ void at_exp(AtState& s) {
#pragma unroll
  for (int i = I0; i < I1; i++) asm volatile("ex2.approx.ftz.f32 %0, %0;" : "+f"(s.S[i]));
#pragma unroll
  for (int i = I0 > 0 ? I0 - LAG : 0; i < (I1 < N ? I1 - LAG : N); i++) asm volatile("add.f32 %0, %0, %1;" : "+f"(s.l[i & 3]) : "f"(s.S[i]));
}
__device__ __forceinline__ void at_sum(AtState& s) {
}
template <int I0, int I1>
__device__ __forceinline__ void at_pack(AtState& s) {
#pragma unroll
  for (int i = I0; i < I1; i++) asm volatile("cvt.rn.bf16x2.f32 %0, %1, %2;" : "=r"(s.P[i]) : "f"(s.S[2 * i + 1]), "f"(s.S[2 * i]));
}
template <int J0>
__device__ __forceinline__ void at_mask(AtState& s, int r, int lane) {
  const int d = r + (lane >> 2) - (lane & 3) * 2;
#pragma unroll
  for (int j = 0; j < 8; j++) {
    float dummy0 = 0.f, dummy1 = 0.f;
    float& lo0 = j < 7 ? s.S[4 * (J0 + (j < 7 ? j + 1 : j)) + 2] : dummy0;
    float& lo1 = j < 7 ? s.S[4 * (J0 + (j < 7 ? j + 1 : j)) + 3] : dummy1;
    asm("{\n.reg .pred p, q;\nsetp.lt.s32 p, %4, %5;\nsetp.le.s32 q, %4, %5;\n"
        "@p add.f32 %0, %0, 0fFF800000;\n@q add.f32 %1, %1, 0fFF800000;\n@p add.f32 %2, %2, 0fFF800000;\n@q add.f32 %3, %3, 0fFF800000;\n}"
        : "+f"(s.S[4 * (J0 + j)]), "+f"(s.S[4 * (J0 + j) + 1]), "+f"(lo0), "+f"(lo1) : "r"(d), "r"(8 * j));
  }
}
__device__ __forceinline__ uint32_t ld_pair(const __nv_bfloat16* p) {
  uint32_t r;
  asm volatile("{\n.reg .b16 a, b;\nld.global.cg.b16 a, [%1];\nld.global.cg.b16 b, [%1 + 8192];\nmov.b32 %0, {a, b};\n}" : "=r"(r) : "l"(p) : "memory");
  return r;
}
__device__ __forceinline__ uint32_t ld_word(const uint32_t* p) {
  uint32_t r;
  asm volatile("ld.global.cg.b32 %0, [%1];" : "=r"(r) : "l"(p) : "memory");
  return r;
}
__device__ __forceinline__ void slow_rows(const __nv_bfloat16* wq, int head, int row0, int lane) {
  const int r = lane >> 2, c = lane & 3;
  uint32_t q[32];
  float o[32];
#pragma unroll
  for (int i = 0; i < 32; i++) q[i] = 0;
  const uint32_t* xa = reinterpret_cast<const uint32_t*>(g_xn + (size_t)(row0 + r) * DM) + c;
#pragma unroll 1
  for (int h = 0; h < 2; h++) {
    const __nv_bfloat16* wb = wq + (size_t)2 * c * NQ + head * HD + 64 * h + 8 * (r >> 1) + (r & 1);
#pragma unroll
    for (int i = 0; i < 32; i++) o[i] = 0.f;
#pragma unroll 1
    for (int kk = 0; kk < DM / 16; kk++) {
      const uint32_t a0 = ld_word(xa + 8 * kk), a1 = ld_word(xa + 8 * kk + 4 * DM), a2 = ld_word(xa + 8 * kk + 4), a3 = ld_word(xa + 8 * kk + 4 * DM + 4);
#pragma unroll
      for (int n = 0; n < 8; n++) {
        const __nv_bfloat16* b = wb + (size_t)16 * kk * NQ + 32 * (n >> 2) + 2 * (n & 3);
        mma16816(o + 4 * n, a0, a1, a2, a3, ld_pair(b), ld_pair(b + 8 * NQ));
      }
    }
#pragma unroll
    for (int i = 0; i < 16; i++) { q[i] = q[16 + i]; q[16 + i] = pack_bf16(o[2 * i] * AT_C, o[2 * i + 1] * AT_C); }
  }
#pragma unroll 1
  for (int h = 0; h < 2; h++) {
    float m0 = -INFINITY, m1 = -INFINITY, l0 = 0.f, l1 = 0.f;
#pragma unroll
    for (int i = 0; i < 32; i++) o[i] = 0.f;
#pragma unroll 1
    for (int k0 = 0; k0 <= row0; k0 += 16) {
      float e[8] = {0.f, 0.f, 0.f, 0.f, 0.f, 0.f, 0.f, 0.f};
      const uint32_t* kp = reinterpret_cast<const uint32_t*>(g_kv + (size_t)(k0 + r) * NQ + head * HD) + c;
#pragma unroll
      for (int kk = 0; kk < 8; kk++) {
        mma16816(e, q[4 * kk], q[4 * kk + 1], q[4 * kk + 2], q[4 * kk + 3], ld_word(kp + 8 * kk), ld_word(kp + 8 * kk + 4));
        mma16816(e + 4, q[4 * kk], q[4 * kk + 1], q[4 * kk + 2], q[4 * kk + 3], ld_word(kp + 8 * kk + 4 * NQ), ld_word(kp + 8 * kk + 4 * NQ + 4));
      }
      if (k0 == row0) {
#pragma unroll
        for (int i = 0; i < 8; i++) if ((i >> 2) * 8 + 2 * c + (i & 1) > r + (i & 2) * 4) e[i] = -INFINITY;
      }
      float a0 = fmaxf(fmaxf(e[0], e[1]), fmaxf(e[4], e[5])), a1 = fmaxf(fmaxf(e[2], e[3]), fmaxf(e[6], e[7]));
      a0 = fmaxf(a0, __shfl_xor_sync(~0u, a0, 1)); a1 = fmaxf(a1, __shfl_xor_sync(~0u, a1, 1));
      a0 = fmaxf(a0, __shfl_xor_sync(~0u, a0, 2)); a1 = fmaxf(a1, __shfl_xor_sync(~0u, a1, 2));
      a0 = fmaxf(a0, m0); a1 = fmaxf(a1, m1);
      const float sc0 = ex2(m0 - a0), sc1 = ex2(m1 - a1);
      m0 = a0; m1 = a1;
#pragma unroll
      for (int i = 0; i < 8; i++) e[i] = ex2(e[i] - ((i & 2) ? m1 : m0));
      l0 = l0 * sc0 + (e[0] + e[1]) + (e[4] + e[5]);
      l1 = l1 * sc1 + (e[2] + e[3]) + (e[6] + e[7]);
      const uint32_t p0 = pack_bf16(e[0], e[1]), p1 = pack_bf16(e[2], e[3]), p2 = pack_bf16(e[4], e[5]), p3 = pack_bf16(e[6], e[7]);
      const __nv_bfloat16* vp = g_kv + (size_t)(SEQ + k0 + 2 * c) * NQ + head * HD + 64 * h + r;
#pragma unroll
      for (int n = 0; n < 8; n++) {
        o[4 * n] *= sc0; o[4 * n + 1] *= sc0; o[4 * n + 2] *= sc1; o[4 * n + 3] *= sc1;
        mma16816(o + 4 * n, p0, p1, p2, p3, ld_pair(vp + 8 * n), ld_pair(vp + 8 * n + 8 * NQ));
      }
    }
    l0 += __shfl_xor_sync(~0u, l0, 1); l1 += __shfl_xor_sync(~0u, l1, 1);
    l0 += __shfl_xor_sync(~0u, l0, 2); l1 += __shfl_xor_sync(~0u, l1, 2);
#pragma unroll
    for (int i = 0; i < 4; i++) {
      const float* v = o + 16 * (i >> 1) + 2 * (i & 1);
      const float f = __fdividef(1.f, (i & 1) ? l1 : l0);
      *reinterpret_cast<uint4*>(g_ctx + (size_t)(row0 + r + (i & 1) * 8) * NQ + head * HD + 64 * h + (i >> 1) * 32 + c * 8) =
          make_uint4(pack_bf16(v[0] * f, v[1] * f), pack_bf16(v[4] * f, v[5] * f), pack_bf16(v[8] * f, v[9] * f), pack_bf16(v[12] * f, v[13] * f));
    }
  }
}

constexpr int UNIT = 16384, SLOT = 32768;
constexpr int OFF_STG = 2 * SLOT;
__host__ __device__ constexpr int kv_a(int kb) { return (kb < 6 ? kb : 3 * kb - 10) * UNIT; }
__host__ __device__ constexpr int kv_b(int s) { return (s == 2 ? 6 : 9 + 3 * s) * UNIT; }
__host__ __device__ constexpr int q_aw(int s) { return (3 * s + (s & 1)) * UNIT; }
__host__ __device__ constexpr int q_b(int s) { return (3 * s + 2 - 2 * (s & 1)) * UNIT; }
__host__ __device__ constexpr int k_slot(int j, int r) { return (j < 2 ? 2 * j : (r == 2 ? 0 : 3 + r)) * SLOT; }
__host__ __device__ constexpr int v_slot(int j) { return (6 - (j & 1)) * SLOT; }
__host__ __device__ constexpr int r3(int st) { return (st + (st >= 2)) * SLOT; }
constexpr int OFF_BAR = 229376;
constexpr int OFF_MISC = OFF_BAR + 512;
constexpr int SMEM_BYTES = OFF_MISC + 2080 + TL_EXTRA;
constexpr int OFF_RSTAT = OFF_MISC + 1056;
enum : int {
  B_FULL1 = 0, B_FULLQ = 3, B_FULLB = 7, B_KF = 8, B_VF = 11, B_FULL3 = 13, B_WF = 19, B_DEP = 21, B_OUT2 = 26, B_PF = 27, B_SET = 28,
  B_SET2 = 29, B_LNGO = 30, B_WR = 31,
  B_KE = 32, B_VE = 35, B_WE = 37, B_PUB = 39, B_OUT = 45,
  B_EMPTY1 = 46, B_EMPTYQ = 49, B_X = 53, B_EMPTY3 = 57,
  B_NUM = 63
};
constexpr int PRE = 3;
#define LN_PF 99
#define LN_GO 5
#define PFW 9
#define PFX 9
#define PFKV 0
#define SYNC3 0
#define SYNC3A 5
#define SYNC3W 6
#define CTX_ST "st.global.cs.v4.u32"
#define PF3 0
#define PD3 7
#define PFF 0
#define PWAIT mbar_wait_c
#define GRAB0 4
#define SIDE_NS 400
#define REL_AT 3
#define STARTV 2
#define SET_NS 40
#define WRAP 16 - j
#define EP1 3
#define MASKV 0
#define PACE 0
#define TRIMS 1
#define TRIMPV 1
#define KTEST 1
#define DELAY0 1
#define AWAIT mbar_wait_c
#define KWAIT mbar_wait_c
#define PFJ 16
#define PFQ 3
#define PFP 1
#define PFQ0 4
#define PFP0 5
#define PUT0 2
#define PUTD 2
#define NOFFN0 0
#define WEF 1
#define OUTU 1
#define YDLY 0
#define KV_FIRST 1
constexpr int WIN = 6;
constexpr int NIT = 64;
constexpr int NLATE = (8 - WIN) / 2;
constexpr int IT_WD = NIT + NLATE, OFF_SCR = r3((NIT + NLATE + 2) % 6);
#define PF_KB 52
#define PF_CLK 500
#define SET_KB 44
constexpr int OUT_UNROLL = OUTU;
struct Params {
  CUtensorMap xn, ckv, wq, wk, wv, kv_ld, ctx_ld, wo, x, wd, wg, wu;
};

__global__ void __cluster_dims__(2, 1, 1) __launch_bounds__(384, 1)
fused_kernel(const __grid_constant__ Params p, const __nv_bfloat16* __restrict__ x, const __nv_bfloat16* __restrict__ wq,
             const __nv_bfloat16* __restrict__ w_r, const __nv_bfloat16* __restrict__ wgate, const __nv_bfloat16* __restrict__ wup,
             __nv_bfloat16* __restrict__ out, uint32_t zero) {
  extern __shared__ __align__(1024) uint8_t sp[];
  const uint32_t sb = s2u(sp);
  const uint32_t bar = sb + OFF_BAR;
  auto B = [&](int i) { return bar + 8 * i; };
  const int tid = threadIdx.x, warp = __shfl_sync(~0u, tid >> 5, 0), wg = warp >> 2, lane = tid & 31;
  const int cta = blockIdx.x, rank = cta & 1, cl = cta >> 1;
  const int mp = cl < 4 ? 1 : (cl < 36 ? (cl & 7) : (0x3207654 >> (4 * ((cl - 36) % 7))) & 7);
  const int gq = cl < 4 ? 4 + cl : (cl < 36 ? (cl - 4) >> 3 : 4 + (cl - 36) / 7);
  const int mt = 2 * mp + rank;
  const int qa = 15 - gq;
  const int rid = mt * 8 + gq;
  const int fid = mt * 7 + gq - NOFFN0;
  const bool ffn = NOFFN0 ? gq > 0 : gq < 7;
  uint4* const xr = g_xr + rid * XR_SIZE;
  TL(0, 0, warp == 4);
  auto load_pre = [&](int kb) {
    e_expect(B(B_FULL1 + kb), 3 * UNIT);
    tma_ld2(sb + kv_a(kb), &p.ckv, B(B_FULL1 + kb), kb * 64, mt * 128);
    tma_ld3(sb + kv_b(kb) + rank * UNIT, &p.wk, B(B_FULL1 + kb), 0, kb * 64, (gq + KV_FIRST * 8) * 4 + rank * 2);
    tma_ld3(sb + kv_b(kb) + UNIT - rank * UNIT, &p.wk, B(B_FULL1 + kb), 0, kb * 64, (gq + KV_FIRST * 8) * 4 + 2 - rank * 2);
  };
  if (warp == 0) {
    e_init(B(B_FULL1), 1);
    asm volatile("fence.mbarrier_init.release.cluster;" ::: "memory");
    load_pre(0);
#pragma unroll
    for (int kb = 1; kb < PRE; kb++) e_init(B(B_FULL1 + kb), 1);
  } else {
#pragma unroll 1
    for (int i = PRE - 1 + warp; i < B_NUM; i += 11) e_init(B(i), i >= B_EMPTY1 ? 16 : (i >= B_KE ? 8 : (i == B_WR ? 2 : 1)));
  }
  asm volatile("fence.mbarrier_init.release.cluster;" ::: "memory");
  cluster_arrive();
  if (wg == 0) {
    reg_dealloc<40>();
    if (warp == 0) {
#pragma unroll 1
      for (int kb = STARTV ? 1 : 0; kb < PRE; kb++) load_pre(kb);
      if (mt >= 2 * PRE) tma_pf3(&p.wk, 0, (mt >> 1) * 64, (gq + KV_FIRST * 8) * 4 + (mt & 1) * 2);
      if (gq >= PRE) tma_pf2(&p.ckv, gq * 64, mt * 128);
      prefetch_tm(&p.wv); prefetch_tm(&p.wq); prefetch_tm(&p.xn); prefetch_tm(&p.kv_ld);
    }
    __syncwarp();
    cluster_wait();
    auto side_piece = [&](int c, int piece) {
      const uint32_t fb = B(B_WF + (c & 1));
      if (piece == 0) e_expect(fb, UNIT);
      tma_ld2(sb + OFF_STG + (c & 1) * UNIT + piece * 4096, (piece & 2) ? &p.wg : &p.wu, fb, fid * 32, c * 128 + (piece & 1) * 64);
    };
    if (warp == 0) {
      {
        int st = 0; uint32_t ph = 1;
#pragma unroll 1
        for (int i = 0; i < 32; i++) {
          const int t = i >> 3, kb = i & 7;
          if (i >= PRE) {
            const uint32_t fb = B(B_FULL1 + st);
            KWAIT(B(B_EMPTY1 + st), ph);
            e_expect(fb, t == 0 ? 3 * UNIT : 2 * UNIT);
            if (t == 0) tma_ld2(sb + kv_a(kb), &p.ckv, fb, kb * 64, mt * 128);
            tma_ld3_mc(sb + kv_b(st) + rank * UNIT, (t & 1) ? &p.wv : &p.wk, fb, 0, kb * 64, (gq + ((t >> 1) ^ KV_FIRST) * 8) * 4 + rank * 2, 3);
          }
          if (i == LN_PF || i == LN_PF + 1) l2_prefetch(x + (size_t)cta * 16 * DM + (i - LN_PF) * 8 * DM, 16384);
          if (i == LN_GO) e_arrive(B(B_LNGO));
          if (kb == 0 && t < 3) tma_pf3((t & 1) ? &p.wk : &p.wv, 0, (mt >> 1) * 64, (gq + (((t + 1) >> 1) ^ KV_FIRST) * 8) * 4 + (mt & 1) * 2);
          if (kb < 2 && t == 3) tma_pf3(&p.wq, 0, (gq + 8 * kb) * 64, mt * 2);
          if (++st == 3) { st = 0; ph ^= 1; }
        }
        prefetch_tm(&p.ctx_ld); prefetch_tm(&p.wo); prefetch_tm(&p.wd); prefetch_tm(&p.x); prefetch_tm(&p.wg); prefetch_tm(&p.wu);
        PWAIT(B(B_DEP + 0), 0);
        uint32_t kpar = 7, vpar = 3;
        auto load_aw = [&](int kb, int head) {
          const uint32_t d = sb + q_aw(kb & 3), fb = B(B_FULLQ + (kb & 3));
          tma_ld2_mc(d + rank * 8192, &p.xn, fb, kb * 64, gq * 128 + rank * 64, 3);
          tma_ld3(d + UNIT, &p.wq, fb, 0, kb * 64, head * 2);
        };
        auto load_b = [&](int kb, uint32_t fb) { tma_ld2_mc(sb + q_b(kb & 3) + rank * 8192, &p.xn, fb, kb * 64, qa * 128 + rank * 64, 3); };
        auto load3 = [&](int kb, int s) {
          const uint32_t d = sb + r3(s), fb = B(B_FULL3 + s);
          e_expect(fb, SLOT);
          tma_ld2(d, &p.ctx_ld, fb, kb * 64, mt * 128);
          tma_ld3_mc(d + UNIT + rank * 8192, &p.wo, fb, 0, kb * 64, gq * 2 + rank, 3);
        };
#pragma unroll 1
        for (int half = 0; half < 2; half++) {
          const int head = mt + 16 * half;
#pragma unroll 1
          for (int kb = 2 * half; kb < 16; kb++) {
            if (kb >= 4) KWAIT(B(B_EMPTYQ + (kb & 3)), ((kb >> 2) & 1) ^ 1);
            else if (half) PWAIT(B(B_X + 2), 0);
            else if (kb > 0) PWAIT(B(B_EMPTY1 + (kb + 1) % 3), kb == 1);
            e_expect(B(B_FULLQ + (kb & 3)), 3 * UNIT);
            load_aw(kb, head);
            load_b(kb, B(B_FULLQ + (kb & 3)));
          }
          PWAIT(B(B_DEP + 1 + half), 0);
          tma_pf3(&p.kv_ld, 0, 0, head * 2);
          auto load_v = [&](int j) {
            const int r = j & 1;
            AWAIT(B(B_VE + r), (vpar >> r) & 1);
            vpar ^= 1 << r;
            e_expect(B(B_VF + r), SLOT);
            tma_ld3(sb + v_slot(j), &p.kv_ld, B(B_VF + r), 0, SEQ + (j > qa ? WRAP : j) * 128, head * 2);
          };
          int r = 0;
#pragma unroll 1
          for (int j = 0; j < 17; j++) {
            if (j < 2) PWAIT(B(B_EMPTYQ + j), 1);
            if (j == 2) PWAIT(B(B_KE), kpar & 1);
            AWAIT(B(B_KE + r), (kpar >> r) & 1);
            kpar ^= 1 << r;
            e_expect(B(B_KF + r), SLOT);
            tma_ld3(sb + k_slot(j, r), &p.kv_ld, B(B_KF + r), 0, (j > qa ? WRAP : j) * 128, head * 2);
            if (++r == 3) r = 0;
            if (j == 2) PWAIT(B(B_EMPTYQ + 3), 1);
            if (j != 1) load_v(j ? j - 1 : 0);
            if (j == PFJ) {
              if (half == 0) {
                if (PFQ & 1) tma_pf3(&p.wq, 0, (PFQ0 + gq) * 64, (mt + 16) * 2);
                if (PFQ & 2) tma_pf2(&p.xn, (PFQ0 + (mp & 3)) * 64, ((mp & 4) ? qa : gq) * 128 + rank * 64);
              } else {
                PWAIT(B(B_DEP + 3), 0);
                if (PFP & 1) tma_pf3(&p.wo, 0, (PFP0 + mp) * 64, gq * 2 + rank);
                if (PFP & 2) tma_pf2(&p.ctx_ld, (PFP0 + gq) * 64, mt * 128);
              }
            }
            if (half == 0) {
            } else if (ffn && j >= 5 && j < 13) {
              side_piece((j - 5) >> 2, (j - 5) & 3);
            }
          }
          PWAIT(B(B_X + 0), half);
          if (half == 0) {
            for (int kb = 0; kb < 2; kb++) { e_expect(B(B_FULLQ + kb), 2 * UNIT); load_aw(kb, mt + 16); }
          } else {
            load3(0, 0);
          }
          load_v(16);
          PWAIT(B(B_X + 1), half);
          if (half == 0) { e_expect(B(B_FULLB), 2 * UNIT); load_b(0, B(B_FULLB)); load_b(1, B(B_FULLB)); }
        }
        st = 1; ph = 1;
#pragma unroll 1
        for (int kb = 1; kb < 64; kb++) {
          if (kb == 32) PWAIT(B(B_DEP + 4), 0);
          if (kb >= 6) PWAIT(B(B_EMPTY3 + st), ph);
          else if (kb == 3 || kb == 5) PWAIT(B(B_X + (kb + 1) / 2), 1);
          load3(kb, st);
          if (++st == 6) { st = 0; ph ^= 1; }
          if (kb == PF_KB) e_arrive(B(B_PF));
          if (kb == SET_KB) e_arrive(B(B_SET));
          if (kb == 58) l2_prefetch(xr, XR_CAND * 16);
        }
        if (ffn) {
#pragma unroll 1
          for (int j = 0; j < NLATE + 2; j++) {
            PWAIT(B(B_EMPTY3 + st), ph);
            const uint32_t d = sb + r3(st), fb = B(B_FULL3 + st);
            e_expect(fb, SLOT);
            if (j < NLATE) {
#pragma unroll 1
              for (int h = 0; h < 8; h++) tma_ld2(d + h * 4096, (h & 2) ? &p.wg : &p.wu, fb, fid * 32, (WIN + 2 * j + (h >> 2)) * 128 + (h & 1) * 64);
            } else {
              tma_ld3(d, &p.wd, fb, 0, fid * 32, 8 * (j - NLATE));
            }
            if (++st == 6) { st = 0; ph ^= 1; }
          }
        }
        const uint4* kp = g_xr + ((lane >> 1) * 8 + gq) * XR_SIZE + XR_KEY + (lane & 1) * 2;
        PWAIT(B(B_OUT), 0);
        uint4 kv[2];
        poll_chunks(kv, kp, 1);
        const uint32_t a1 = max(kv[0].x, kv[0].z), a2 = max(min(kv[0].x, kv[0].z), max(kv[0].y, kv[0].w));
        const uint32_t b1 = max(kv[1].x, kv[1].z), b2 = max(min(kv[1].x, kv[1].z), max(kv[1].y, kv[1].w));
        const uint32_t k1 = max(a1, b1), k2 = max(min(a1, b1), max(a2, b2));
        const uint32_t m1 = __reduce_max_sync(~0u, k1);
        const uint32_t m2 = __reduce_max_sync(~0u, k1 == m1 ? k2 : k1);
        if (lane == 0) {
          *reinterpret_cast<uint2*>(sp + OFF_MISC) = make_uint2(m1, m2);
          mbar_arrive(B(B_OUT2));
        }
        if (rid == 127) { g_cnt[lane] = 0; g_cnt[32 + lane] = 0; }
      }
    } else {
      if (warp >= 2) {
#pragma unroll 1
        for (int i = tid - 64; i < XR_CAND; i += 64) xr[i] = make_uint4(~0u, ~0u, ~0u, ~0u);
        if (warp == 2) { __syncwarp(); if (lane == 0) mbar_arrive(B(B_WR)); }
      }
      if (warp == 3) {
        float ws = 0.f;
#pragma unroll
        for (int j = 0; j < 4; j++) {
          const uint4 q = __ldg(reinterpret_cast<const uint4*>(w_r) + j * 32 + lane);
          ws += bf_lo(q.x) + bf_hi(q.x) + bf_lo(q.y) + bf_hi(q.y) + bf_lo(q.z) + bf_hi(q.z) + bf_lo(q.w) + bf_hi(q.w);
        }
#pragma unroll
        for (int o = 16; o; o >>= 1) ws += __shfl_xor_sync(~0u, ws, o);
        uint2* tab = reinterpret_cast<uint2*>(sp + OFF_MISC + 512);
        tab[lane] = make_uint2(0x3F803F80u, 0x3F803F80u);
        tab[32 + lane] = __ldg(reinterpret_cast<const uint2*>(w_r + gq * 128) + lane);
        if (lane == 0) *reinterpret_cast<float*>(sp + OFF_MISC + 1024) = ws;
        __syncwarp();
        if (lane == 0) mbar_arrive(B(B_WR));
      }
      __syncwarp();
      mbar_wait_u(B(B_LNGO), 0);
#pragma unroll 1
      for (int r = warp == 2 ? 0 : (warp + 1) >> 1; r < 16; r += 3) {
        const uint4* src = reinterpret_cast<const uint4*>(x + (size_t)(cta * 16 + r) * DM) + lane;
        uint4 v[4];
#pragma unroll
        for (int j = 0; j < 4; j++) v[j] = __ldg(src + j * 32);
        float a0 = 0.f, a1 = 0.f, b0 = 0.f, b1 = 0.f;
#pragma unroll
        for (int j = 0; j < 4; j++) {
          const uint32_t u[4] = {v[j].x, v[j].y, v[j].z, v[j].w};
#pragma unroll
          for (int i = 0; i < 4; i++) { const float a = bf_lo(u[i]), b = bf_hi(u[i]); a0 += a; a1 += b; b0 = fmaf(a, a, b0); b1 = fmaf(b, b, b1); }
        }
        a0 += a1; b0 += b1;
#pragma unroll
        for (int o = 16; o; o >>= 1) { a0 += __shfl_xor_sync(~0u, a0, o); b0 += __shfl_xor_sync(~0u, b0, o); }
        const float mean = a0 * (1.f / DM);
        float mb, inv;
        ln_round(mean, fmaxf(fmaf(b0, 1.f / DM, -mean * mean), 0.f), mb, inv);
        const uint32_t nm2 = pack_bf16(-mb, -mb);
        uint4* dst = reinterpret_cast<uint4*>(g_xn + (size_t)(cta * 16 + r) * DM) + lane;
#pragma unroll
        for (int j = 0; j < 4; j++)
          dst[j * 32] = make_uint4(ln_apply(v[j].x, nm2, inv), ln_apply(v[j].y, nm2, inv), ln_apply(v[j].z, nm2, inv), ln_apply(v[j].w, nm2, inv));
      }
      __syncwarp();
      if (lane == 0) {
        fence_gpu();
        red_add(&g_cnt[C_LN + (cta >> 3)], 1);
        TL(0, 20 + warp, true);
        if (warp == 3) {
          spin_until_ge<true>(&g_cnt[C_LN + gq], 24);
#pragma unroll 1
          for (int i = 0; i < 5; i++) {
            const int c = i == 0 ? C_LN + qa : (i < 3 ? C_KV + (i - 1) * 8 + mp : C_CTX + (i - 3) * 16 + mt);
            spin_until_ge<true>(&g_cnt[c], i == 0 ? 24 : 16);
            fence_async_all();
            mbar_arrive(B(B_DEP + i));
          }
        } else if (warp == 1) {
          mbar_wait(B(B_WR), 0);
#pragma unroll 1
          for (int i = 0; i < 6; i++) {
            const int c = i < 2 ? C_KV + gq + (i ^ KV_FIRST) * 8 : C_CTX + ((i - 2) >> 1) * 16 + ((i & 1) ? qa : gq);
            mbar_wait(B(B_PUB + i), 0);
            fence_gpu();
            red_add(&g_cnt[c], 1);
          }
        }
      }
      __syncwarp();
      if (warp == 2) {
#pragma unroll 1
        for (int c = 2; c < WIN + 2; c++) {
          if (c == WIN + 1) {
            mbar_wait_u(B(B_SET), 0);
#pragma unroll 1
            for (int i = XR_CAND + lane; i < XR_SIZE; i += 32) { xr[i] = make_uint4(~0u, ~0u, ~0u, ~0u); __nanosleep(SET_NS); }
            __syncwarp();
          }
          mbar_wait_u(B(B_WE + (c & 1)), ((c >> 1) & 1) ^ 1);
          if (c >= WIN) {
            e_expect(B(B_WF + (c & 1)), UNIT);
            tma_ld3(sb + OFF_STG + (c & 1) * UNIT, &p.x, B(B_WF + (c & 1)), 0, mt * 128 + (c & 1) * 64, gq * 2);
          } else if (ffn) {
#pragma unroll 1
            for (int i = 0; i < 4; i++) { side_piece(c, i); __nanosleep(SIDE_NS); }
          }
        }
        if (lane == 0) { fence_gpu(); mbar_arrive(B(B_SET2)); }
        __syncwarp();
        mbar_wait_u(B(B_PF), 0);
        uint32_t t0;
        asm volatile("mov.u32 %0, %%clock;" : "=r"(t0));
        constexpr int NF = (8 - WIN) * 4;
#pragma unroll 1
        for (int i = 0; i < NF; i++) {
          const char* a = (const char*)(((i & 2) ? wgate : wup) + (size_t)((WIN + (i >> 2)) * 128 + cta) * FF) + min((i & 1) * 32 + lane, 55) * 128;
          asm volatile("prefetch.global.L2 [%0];" ::"l"(a));
#pragma unroll 1
          for (int n = 0; n < 64; n++) {
            __nanosleep(100);
            uint32_t t;
            asm volatile("mov.u32 %0, %%clock;" : "=r"(t));
            if (t - t0 >= (uint32_t)(i + 1) * PF_CLK) break;
          }
        }
      }
      __syncwarp();
      mbar_wait_u(B(B_OUT), 0);
#pragma unroll OUT_UNROLL
      for (int i = warp - 1; i < 66; i += 3) {
        const int row = 2 * i + (lane >> 4);
        const uint2 rs = *reinterpret_cast<const uint2*>(sp + OFF_RSTAT + (row & 127) * 8);
        const uint4 v = lds128(sb + OFF_STG + ((row >> 6) & 1) * 16384 + ((lane & 15) >> 3) * 8192 + (row & 63) * 128 + (((lane ^ row) & 7) << 4));
        const float inv = __uint_as_float(rs.y);
        if ((int)rs.y >= 0 && row < 128)
          *reinterpret_cast<uint4*>(out + (size_t)(mt * 128 + row) * DM + gq * 128 + (lane & 15) * 8) =
              make_uint4(hadd2_bf(v.x, ln_apply(v.x, rs.x, inv)), hadd2_bf(v.y, ln_apply(v.y, rs.x, inv)),
                         hadd2_bf(v.z, ln_apply(v.z, rs.x, inv)), hadd2_bf(v.w, ln_apply(v.w, rs.x, inv)));
      }
      TL(2, 25, warp == 1);
    }
    __syncwarp();
    cluster_arrive();
    cluster_wait();
  } else {
    reg_alloc<232>();
    cluster_wait();
    const int w = wg - 1, cw = warp - 4, ct = tid - 128;
    const uint32_t stg = sb + OFF_STG + w * 16384 + (cw & 3) * 2048;
    auto publish = [&](int i) { __syncwarp(); e_arrive(B(B_PUB + i)); };
    auto release2 = [&](uint32_t b, bool cond = true) { mbar_arrive_both(b, lane, cond); };
    AtState s;
    const uint32_t dA = mk_desc(sb + w * 8192, 16);
    const uint32_t dW = mk_desc(sb, 8192);
    auto mma_kb = [&](float (&d)[64], uint32_t a, uint32_t b, int accum) {
      static_for<4>([&](auto k) { mma_n128_ss<1, k * 32, k * 2048>(d, dA + (a >> 4), dW + (b >> 4), k == 0 ? accum : 1); });
    };
    auto mma_kc = [&](float (&d)[64], auto a, auto b, int accum) {
      static_for<4>([&](auto k) { mma_n128_ss<1, decltype(a)::value + k * 32, decltype(b)::value + k * 2048>(d, dA, dW, k == 0 ? accum : 1); });
    };
    auto issue_q = [&](int kb, auto accum) {
      const int st = kb & 3;
      mbar_wait_c(B(B_FULLQ + st), (kb >> 2) & 1);
      wg_fence();
      mma_kb(s.S, q_aw(st), q_aw(st) + UNIT, accum);
      wg_commit();
      if (accum) {
        wg_wait<1>();
        release2(B(B_EMPTYQ + ((kb - 1) & 3)));
        wg_fence();
      }
      mma_kb(s.O, q_b(st), q_aw(st) + UNIT, accum);
      wg_commit();
    };
    {
      uint4 pk[16];
      __nv_bfloat16* pdst = g_kv;
      auto put = [&](int i) { __stcs(reinterpret_cast<uint4*>(pdst + (i & 1) * 8 * NQ + (i >> 1) * 32), pk[i]); };
      float acc1[128];
      TL(0, 1, warp == 4);
      int st = 0; uint32_t ph = 0;
      auto issue = [&](int kb, int accum) {
        mbar_wait_c(B(B_FULL1 + st), ph);
        wg_fence();
        static_for<4>([&](auto k) { mma_n256_ss<1, k * 32, k * 2048>(acc1, dA + (kv_a(kb) >> 4), dW + (kv_b(st) >> 4), k == 0 ? accum : 1); });
        wg_commit();
      };
#pragma unroll 1
      for (int t = 0; t < 4; t++) {
        issue(0, 0);
        TL(0, 2 + 2 * t, warp == 4);
        if (t > 0) { put(0); put(1); }
        int prev = st;
        if (++st == 3) { st = 0; ph ^= 1; }
#pragma unroll 1
        for (int kb = 1; kb < 8; kb++) {
          if (kb == 7 && w == 1) bar_sync(5, 256);
          issue(kb, 1);
          if (kb == 7 && w == 0) bar_arrive(5, 256);
          if (t > 0) {
#pragma unroll
            for (int i = 1; i < 8; i++) if (kb == i) { put(2 * i); put(2 * i + 1); }
            if (kb == 7 && t == 2) publish(0);
          }
          wg_wait<1>();
          TK(24 + t * 8 + kb - 1);
          release2(B(B_EMPTY1 + prev));
          prev = st;
          if (++st == 3) { st = 0; ph ^= 1; }
        }
        pdst = g_kv + (size_t)((t & 1) * SEQ + mt * 128 + cw * 16 + (lane >> 2)) * NQ + (gq + ((t >> 1) ^ KV_FIRST) * 8) * 256 + (lane & 3) * 8;
        wg_wait<0>();
        TK(24 + t * 8 + 7);
        fence_regs(acc1);
        release2(B(B_EMPTY1 + prev));
        TL(0, 3 + 2 * t, warp == 4);
#pragma unroll
        for (int a = 0; a < 8; a++)
#pragma unroll
          for (int h = 0; h < 2; h++)
            pk[2 * a + h] = make_uint4(pack_bf16(acc1[16 * a + 2 * h], acc1[16 * a + 2 * h + 1]), pack_bf16(acc1[16 * a + 4 + 2 * h], acc1[16 * a + 5 + 2 * h]),
                                       pack_bf16(acc1[16 * a + 8 + 2 * h], acc1[16 * a + 9 + 2 * h]), pack_bf16(acc1[16 * a + 12 + 2 * h], acc1[16 * a + 13 + 2 * h]));
      }
      issue_q(0, IC<0>{});
      TL(0, 10, warp == 4);
      put(0); put(1);
#pragma unroll 1
      for (int kb = 1; kb < 8; kb++) {
        issue_q(kb, IC<1>{});
        TK(66 + kb - 1);
#pragma unroll
        for (int i = 1; i < 8; i++) if (kb == i) { put(2 * i); put(2 * i + 1); }
      }
      publish(1);
      TL(0, 11, warp == 4);
    }
    __nv_bfloat16* cdst;
    uint32_t redo = 0;
    auto put_ctx = [&](int i, bool cond) {
      asm volatile("{\n.reg .pred p;\nsetp.ne.u32 p, %5, 0;\n@p " CTX_ST " [%0], {%1,%2,%3,%4};\n}" ::"l"(cdst + (i & 1) * 8 * NQ + (i >> 1) * 32),
                   "r"(s.P[4 * i]), "r"(s.P[4 * i + 1]), "r"(s.P[4 * i + 2]), "r"(s.P[4 * i + 3]), "r"((uint32_t)(cond && !(redo & 2))) : "memory");
    };
    {
      const int wrow = cw * 16;
      const uint32_t dK = mk_desc(sb, 16), dV = mk_desc(sb, 16384);
      uint32_t kph = 0, vph = 0;
      auto q_store = [&](const float (&d)[64]) {
        const int r0 = lane >> 2;
        const uint32_t a = sb + SLOT + (wrow + r0) * 128 + (((lane & 3) ^ (((r0 & 1) << 2) | (r0 >> 1))) << 4);
#pragma unroll
        for (int i = 0; i < 8; i++) {
          const float* o = d + 16 * (i >> 1) + 2 * (i & 1);
          asm volatile("st.shared.v4.u32 [%0], {%1,%2,%3,%4};" ::"r"((a ^ ((i & 2) << 5)) + (i >> 2) * UNIT + (i & 1) * 1024),
                       "r"(pack_bf16(o[0] * AT_C, o[1] * AT_C)), "r"(pack_bf16(o[4] * AT_C, o[5] * AT_C)),
                       "r"(pack_bf16(o[8] * AT_C, o[9] * AT_C)), "r"(pack_bf16(o[12] * AT_C, o[13] * AT_C)) : "memory");
        }
        __syncwarp();
      };
      auto q_load = [&](auto k0, auto k1) {
        const uint32_t a = sb + SLOT + (wrow + (lane & 15)) * 128 + (((lane >> 4) ^ (((lane & 1) << 2) | ((lane >> 1) & 3))) << 4);
#pragma unroll
        for (int k = k0; k < k1; k++)
          asm volatile("ldmatrix.sync.aligned.m8n8.x4.shared.b16 {%0,%1,%2,%3}, [%4];"
                       : "=r"(s.Q[4 * k]), "=r"(s.Q[4 * k + 1]), "=r"(s.Q[4 * k + 2]), "=r"(s.Q[4 * k + 3]) : "r"((a ^ ((k & 3) << 5)) + (k >> 2) * UNIT) : "memory");
      };
      auto q_load_if = [&](auto k, bool cond, float after) {
        const uint32_t a = sb + SLOT + (wrow + (lane & 15)) * 128 + (((lane >> 4) ^ (((lane & 1) << 2) | ((lane >> 1) & 3))) << 4);
        asm volatile("{\n.reg .pred p;\nsetp.ne.u32 p, %5, 0;\n@p ldmatrix.sync.aligned.m8n8.x4.shared.b16 {%0,%1,%2,%3}, [%4];\n}"
                     : "+r"(s.Q[4 * k]), "+r"(s.Q[4 * k + 1]), "+r"(s.Q[4 * k + 2]), "+r"(s.Q[4 * k + 3])
                     : "r"((a ^ ((k & 3) << 5)) + (k >> 2) * UNIT + (__float_as_uint(after) >> 31)), "r"((uint32_t)cond) : "memory");
      };
      auto issue_s = [&](uint32_t off) {
        static_for<8>([&](auto k) { mma_n128_rs<0, (k >> 2) * 16384 + (k & 3) * 32>(s.S, s.Q + 4 * k, dK + (off >> 4), k != 0); });
        wg_commit();
      };
      auto issue_pv = [&](int jv, int accum, bool upper) {
        mbar_wait_c(B(B_VF + (jv & 1)), (vph >> (jv & 1)) & 1);
        vph ^= 1 << (jv & 1);
        wg_fence();
        static_for<4>([&](auto k) { mma_n128_rs<1, k * 2048>(s.O, s.P + 4 * k, dV + (v_slot(jv) >> 4), k == 0 ? accum : 1); });
        wg_commit();
        if (!TRIMPV || upper) {
          if (TRIMPV) wg_fence();
          static_for<4>([&](auto k) { mma_n128_rs<1, (k + 4) * 2048>(s.O, s.P + 16 + 4 * k, dV + (v_slot(jv) >> 4), 1); });
          wg_commit();
        } else {
          asm volatile("wgmma.fence.sync.aligned;\nwgmma.commit_group.sync.aligned;" ::: "memory");
        }
      };
      if (w == 1) bar_arrive(1, 256);
#pragma unroll 1
      for (int half = 0; half < 2; half++) {
        const int head = mt + 16 * half;
        redo = 0;
        float inv[2];
        auto ep_prep = [&]() {
          float l0 = s.l[0] + s.l[1], l1 = s.l[2] + s.l[3];
          l0 += __shfl_xor_sync(~0u, l0, 1); l1 += __shfl_xor_sync(~0u, l1, 1);
          l0 += __shfl_xor_sync(~0u, l0, 2); l1 += __shfl_xor_sync(~0u, l1, 2);
          asm("rcp.approx.ftz.f32 %0, %1;" : "=f"(inv[0]) : "f"(l0));
          asm("rcp.approx.ftz.f32 %0, %1;" : "=f"(inv[1]) : "f"(l1));
          return __any_sync(~0u, !(fminf(l0, l1) >= L_MIN && l0 + l1 <= L_MAX));
        };
        auto ep_out = [&](int qt, auto i0, auto i1) {
          __nv_bfloat16* dst = g_ctx + (size_t)(qt * 128 + wrow + (lane >> 2)) * NQ + head * 128 + (lane & 3) * 8;
#pragma unroll
          for (int i = i0; i < i1; i++) {
            const float* o = s.O + 16 * (i >> 1) + 2 * (i & 1);
            const float c = inv[i & 1];
            asm volatile(CTX_ST " [%0], {%1,%2,%3,%4};" ::"l"(dst + (i & 1) * 8 * NQ + (i >> 1) * 32), "r"(pack_bf16(o[0] * c, o[1] * c)),
                         "r"(pack_bf16(o[4] * c, o[5] * c)), "r"(pack_bf16(o[8] * c, o[9] * c)), "r"(pack_bf16(o[12] * c, o[13] * c)) : "memory");
          }
        };
#pragma unroll 1
        for (int kb = 8; kb < 14; kb++) {
          issue_q(kb, IC<1>{});
          TK(66 + half * 24 + kb - 1);
        }
        TL(1, 20 * half + 0, warp == 4);
        mbar_wait_c(B(B_FULLQ + 2), 1);
        mbar_wait_c(B(B_FULLQ + 3), 1);
        bar_sync(1 + w, 256);
        wg_fence();
        mma_kc(s.S, IC<q_aw(2)>{}, IC<q_aw(2) + UNIT>{}, 1);
        wg_commit();
        wg_wait<1>();
        TK(66 + half * 24 + 13);
        release2(B(B_EMPTYQ + 1));
        wg_fence();
        mma_kc(s.S, IC<q_aw(3)>{}, IC<q_aw(3) + UNIT>{}, 1);
        wg_commit();
        bar_arrive(2 - w, 256);
        bar_sync(6 + w, 128);
        wg_wait<0>();
        TK(66 + half * 24 + 14);
        fence_regs(s.S);
        q_store(s.S);
        q_load(IC<0>{}, IC<8>{});
        TL(1, 20 * half + 1, warp == 4);
        mbar_wait_c(B(B_KF), kph & 1);
        kph ^= 1;
        bar_sync(1 + w, 256);
        fence_regs(s.S); fence_regs(s.O); fence_regs(s.Q);
        wg_fence();
        issue_s(k_slot(0, 0));
        mma_kc(s.O, IC<q_b(2)>{}, IC<q_aw(2) + UNIT>{}, 1);
        mma_kc(s.O, IC<q_b(3)>{}, IC<q_aw(3) + UNIT>{}, 1);
        wg_commit();
        bar_arrive(2 - w, 256);
        wg_wait<1>();
        fence_regs(s.S);
        e_arrive(B(B_KE));
        s.l[0] = s.l[1] = s.l[2] = s.l[3] = 0.f;
        if (gq == 0) {
          if (w == 0) {
            at_mask<0>(s, wrow, lane);
#pragma unroll
            for (int i = 32; i < 64; i++) s.S[i] = -INFINITY;
          } else {
            at_mask<8>(s, wrow - 64, lane);
          }
        }
        at_exp<0, 48>(s);
        at_pack<0, 22>(s);
        sched_fence();
        wg_wait<0>();
        fence_regs(s.O); fence_regs(s.Q);
        release2(B(B_EMPTYQ + 2)); release2(B(B_EMPTYQ + 3));
        at_exp<48, 64>(s);
        at_pack<22, 32>(s);
        q_store(s.O);
        if (gq == 0) q_load(IC<0>{}, IC<8>{});
        TL(1, 20 * half + 2, warp == 4);
        int kr = 1;
        bool kok = false;
        inv[0] = inv[1] = 0.f;
#pragma unroll 1
        for (int j = 1; j < 17; j++) {
          const bool diag = j == gq || j == qa;
          TC(w, j + 17 * half, 0);
          if (!kok) mbar_wait_c(B(B_KF + kr), (kph >> kr) & 1);
          kph ^= 1 << kr;
          if (j == gq + 2) ep_out(gq, IC<0>{}, IC<EP1>{});
          bar_sync(1 + w, 256);
          TC(w, j + 17 * half, 2);
          fence_regs(s.S); fence_regs(s.O); fence_regs(s.P); fence_regs(s.Q);
          const uint32_t ke = B(B_KE + kr), ko = k_slot(j, kr);
          if (++kr == 3) kr = 0;
          auto issue_rest = [&](auto trimmed) {
            TC(w, j + 17 * half, 1);
            at_sum(s);
            if (j == gq + 1) {
              if (ep_prep()) redo = 1;
              s.l[0] = s.l[1] = s.l[2] = s.l[3] = 0.f;
            }
            if (!trimmed && j == gq + 2) {
              ep_out(gq, IC<EP1>{}, IC<8>{});
              if (!__any_sync(~0u, redo)) publish(2 + 2 * half);
              fence_regs(s.O);
            }
            TC(w, j + 17 * half, 3);
            issue_pv(j - 1, j != 1 && j != gq + 2, w == 1 || (j != gq + 1 && j != qa + 1));
            bar_arrive(2 - w, 256);
          };
          auto s_done = [&]() {
            wg_wait<2>();
            TC(w, j + 17 * half, 4);
            fence_regs(s.S); fence_regs(s.Q);
            e_arrive(ke);
            release2(B(B_X + j - 14), j == 14 || j == 15);
          };
          auto pv_half = [&]() { sched_fence(); wg_wait<1>(); fence_regs(s.P); };
          auto pv_done = [&]() {
            sched_fence();
            wg_wait<0>();
            fence_regs(s.O); fence_regs(s.P);
            e_arrive(B(B_VE + ((j - 1) & 1)));
            kok = KTEST && mbar_test(B(B_KF + kr), (kph >> kr) & 1);
          };
          if (diag && w == 0) {
            wg_fence();
            static_for<8>([&](auto k) { mma_n64_rs<(k >> 2) * 16384 + (k & 3) * 32>(s.S, s.Q + 4 * k, dK + (ko >> 4), k != 0); });
            wg_commit();
            issue_rest(IC<1>{});
            s_done();
            at_mask<0>(s, wrow, lane);
            if (DELAY0 == 1) pv_half();
            if (DELAY0 == 2) pv_done();
            static_for<8>([&](auto k) {
              at_exp<4 * k, 4 * k + 4, 32>(s);
              q_load_if(k, j == gq, s.S[4 * k]);
              if (DELAY0 == 0 && k == 3) pv_half();
            });
            at_pack<0, 16>(s);
            if (DELAY0 < 2) pv_done();
            if (SUMV) {
#pragma unroll
              for (int i = 16; i < 32; i++) s.P[i] = 0;
            }
          } else {
            wg_fence();
            issue_s(ko);
            issue_rest(IC<0>{});
            if (!diag) {
              s_done();
              at_exp<0, 4 * SP1>(s);
              pv_half();
              at_exp<4 * SP1, 4 * SP2>(s);
              at_pack<0, 16>(s);
              pv_done();
              release2(B(B_X + 2), j == 16);
              at_exp<4 * SP2, 64>(s);
              at_pack<16, 32>(s);
            } else {
              s_done();
              at_mask<8>(s, wrow - 64, lane);
              static_for<8>([&](auto k) {
                at_exp<7 * k, 7 * k + 7>(s);
                q_load_if(k, j == gq, s.S[7 * k + 3]);
                if (k == 2) pv_half();
                if (k == 5) { at_pack<0, 16>(s); pv_done(); }
              });
              at_exp<56, 64>(s);
              at_pack<16, 32>(s);
            }
          }
          TL(1, 20 * half + 2 + j, warp == 4);
        }
        TK(84 + half * 24);
        bar_sync(1 + w, 256);
        fence_regs(s.S); fence_regs(s.O); fence_regs(s.P);
        issue_pv(16, 1, true);
        at_sum(s);
        if (ep_prep()) redo |= 2;
        TK(85 + half * 24);
        mbar_wait_c(B(half ? B_FULL3 : B_FULLQ), 0);
        wg_fence();
        mma_kc(s.S, IC<0>{}, IC<UNIT>{}, 0);
        mbar_wait_c(B(half ? B_FULL3 + 1 : B_FULLQ + 1), 0);
        wg_fence();
        mma_kb(s.S, (2 - half) * SLOT, (2 - half) * SLOT + UNIT, 1);
        wg_commit();
        if (w == 0 || half == 0) bar_arrive(2 - w, 256);
        TK(86 + half * 24);
        wg_wait<1>();
        TK(87 + half * 24);
        fence_regs(s.O);
        e_arrive(B(B_VE));
        release2(B(B_X + 3));
        fence_regs(s.P);
        {
          uint32_t r;
          asm volatile("mov.u32 %0, %%laneid;" : "=r"(r));
          cdst = g_ctx + (size_t)(qa * 128 + wrow + (r >> 2)) * NQ + head * 128 + (r & 3) * 8;
        }
#pragma unroll
        for (int i = 0; i < 32; i++) {
          const float* o = s.O + 16 * (i >> 3) + 2 * ((i >> 2) & 1) + 4 * (i & 3);
          s.P[i] = pack_bf16(o[0] * inv[(i >> 2) & 1], o[1] * inv[(i >> 2) & 1]);
        }
        fence_regs(s.P);
        if (__builtin_expect(__any_sync(~0u, redo != 0), 0)) {
#pragma unroll
          for (int i = 0; i < 8; i++) put_ctx(i, true);
#pragma unroll 1
          for (int t = 0; t < 2; t++) {
            if (__any_sync(~0u, (redo >> t) & 1)) slow_rows(wq, head, (t ? qa : gq) * 128 + wrow, lane);
          }
          if (__any_sync(~0u, redo & 1)) publish(2 + 2 * half);
#pragma unroll
          for (int i = 0; i < 64; i++) { s.O[i] = 0.f; s.P[i >> 1] = 0; }
          redo = 2;
        }
        TL(1, 20 * half + 19, warp == 4);
        TK(88 + half * 24);
        if (half) break;
        mbar_wait_c(B(B_FULLB), 0);
        TK(89);
        fence_regs(s.O);
        wg_fence();
        mma_kc(s.O, IC<q_b(0)>{}, IC<q_aw(0) + UNIT>{}, 0);
        wg_commit();
        mma_kc(s.O, IC<q_b(1)>{}, IC<q_aw(1) + UNIT>{}, 1);
        wg_commit();
        wg_wait<1>();
        release2(B(B_EMPTYQ));
        put_ctx(0, true);
#pragma unroll 1
        for (int kb = 2; kb < 8; kb++) {
          issue_q(kb, IC<1>{});
          TK(90 + kb - 1);
#pragma unroll
          for (int i = 1; i < 8; i++) put_ctx(i, kb == (i < 7 ? i + 1 : 7));
        }
        publish(3);
      }
    }
    const int wr_ = w * 64 + (lane & 7) + (lane >> 4) * 8;
    const uint32_t wl = sb + ((lane >> 3) & 1) * 8192 + wr_ * 64 + (((cw ^ (wr_ >> 1)) & 3) << 4);
    __syncwarp();
    float (&acc)[64] = s.S;
    uint32_t wf[128];
    auto grab = [&](auto c, uint32_t off) {
#pragma unroll
      for (int m = 0; m < 4; m++)
        asm volatile("ldmatrix.sync.aligned.m8n8.x4.trans.shared.b16 {%0,%1,%2,%3}, [%4];"
                     : "=r"(wf[16 * c + 4 * m]), "=r"(wf[16 * c + 4 * m + 1]), "=r"(wf[16 * c + 4 * m + 2]), "=r"(wf[16 * c + 4 * m + 3])
                     : "r"(wl + off + m * 1024) : "memory");
    };
    {
      int st = 2, prev = 1; uint32_t ph = 0;
      auto run = [&](auto k0, auto k1, auto c) {
#pragma unroll 1
        for (int kb = k0; kb < k1; kb++) {
          mbar_wait_c(B(B_FULL3 + st), ph);
          wg_fence();
          mma_kb(acc, r3(st), r3(st) + UNIT, 1);
          wg_commit();
          wg_wait<1>();
          if (k0 == 2) release2(B(B_EMPTY3), kb == 2);
          release2(B(B_EMPTY3 + prev));
          if (c >= 0 && kb == k0) {
            constexpr int f = c >= 0 ? 16 * c : 0;
            asm volatile("{\n.reg .pred p;\n.reg .b32 t;\nsetp.eq.u32 p, %1, 0;\nlop3.b32 t, %1, %2, %3, 0xE8;\nlop3.b32 t, t, %4, %5, 0xE8;\n"
                         "mad.lo.u32 t, t, %6, %0;\n@p mbarrier.arrive.shared::cta.b64 _, [t];\n}"
                         ::"r"(B(B_WE + (c & 1))), "r"(lane), "r"(wf[f]), "r"(wf[f + 4]), "r"(wf[f + 8]), "r"(wf[f + 12]), "r"(zero) : "memory");
          }
          prev = st;
          if (++st == 6) { st = 0; ph ^= 1; }
#pragma unroll
          for (int i = 0; i < 8; i++) if (PUT0 + PUTD * i >= k0 && PUT0 + PUTD * i < k1) put_ctx(i, kb == PUT0 + PUTD * i);
          if (PUT0 + PUTD * 7 >= k0 && PUT0 + PUTD * 7 < k1 && kb == PUT0 + PUTD * 7) publish(5);
          if ((kb & 7) == 7) TL(2, 2 + (kb >> 3), warp == 4);
        }
      };
      static_for<WIN>([&](auto c) {
        run(IC<c == 0 ? 2 : GRAB0 + 8 * c - 8>{}, IC<GRAB0 + 8 * c>{}, IC<c - 1>{});
        if (ffn) mbar_wait_c(B(B_WF + (c & 1)), (c >> 1) & 1);
        grab(c, OFF_STG + (c & 1) * UNIT);
      });
      run(IC<GRAB0 + 8 * WIN - 8>{}, IC<64>{}, IC<WIN - 1>{});
    }
    const int r0 = lane >> 2;
    uint32_t hp[32], tb[16];
    mbar_wait_c(B(B_WF + w), ffn ? (WIN >> 1) & 1 : 0);
    mbar_wait_c(B(B_WR), 0);
    mbar_wait_c(B(B_SET2), 0);
#pragma unroll
    for (int j = 0; j < 16; j++) {
      const uint32_t q = stg + r0 * 128 + (lane & 3) * 4 + (j >> 3) * 8192 + (((j & 7) ^ r0) << 4);
      asm volatile("ld.shared.u32 %0, [%1];" : "=r"(hp[2 * j]) : "r"(q) : "memory");
      asm volatile("ld.shared.u32 %0, [%1];" : "=r"(hp[2 * j + 1]) : "r"(q + 1024) : "memory");
      asm volatile("ld.shared.u32 %0, [%1];" : "=r"(tb[j]) : "r"(sb + OFF_MISC + 512 + (r0 & 1) * 256 + (lane & 3) * 4 + j * 16) : "memory");
    }
    wg_wait<0>();
    fence_regs(acc);
    TL(2, 10, warp == 4);
    {
      float d[4] = {0.f, 0.f, 0.f, 0.f}, qa[4] = {0.f, 0.f, 0.f, 0.f}, qb[4] = {0.f, 0.f, 0.f, 0.f};
#pragma unroll
      for (int j = 0; j < 16; j++) {
        hp[2 * j] = hadd2_bf(hp[2 * j], pack_bf16(acc[4 * j], acc[4 * j + 1]));
        hp[2 * j + 1] = hadd2_bf(hp[2 * j + 1], pack_bf16(acc[4 * j + 2], acc[4 * j + 3]));
        if (j & 1) {
          mma16816(d, hp[2 * j - 2], hp[2 * j - 1], hp[2 * j], hp[2 * j + 1], tb[j - 1], tb[j]);
          mma16816(qa, hp[2 * j - 2], hp[2 * j - 1], hp[2 * j], hp[2 * j + 1], hp[2 * j - 2], hp[2 * j]);
          mma16816(qb, hp[2 * j - 2], hp[2 * j - 1], hp[2 * j], hp[2 * j + 1], hp[2 * j - 1], hp[2 * j + 1]);
        }
      }
      const float s2a = __shfl_sync(~0u, (r0 & 1) ? qa[1] : qa[0], r0 * 4 + (r0 >> 1));
      const float s2b = __shfl_sync(~0u, (r0 & 1) ? qb[3] : qb[2], r0 * 4 + (r0 >> 1));
      if ((lane & 3) == 0) {
        __stcg(reinterpret_cast<float4*>(xr + XR_PS + cw * 16 + r0), make_float4(d[0], s2a, d[1], 0.f));
        __stcg(reinterpret_cast<float4*>(xr + XR_PS + cw * 16 + r0 + 8), make_float4(d[2], s2b, d[3], 0.f));
      }
    }
    __syncwarp();
    stage_store_128(stg, lane, hp);
    TL(2, 11, warp == 4);
    __syncwarp();
    uint4 cout;
    uint32_t ckey;
    {
      uint4 ps[4];
      const float wsum = *reinterpret_cast<const float*>(sp + OFF_MISC + 1024);
      poll_chunks(ps, g_xr + (mt * 8 + (ct & 1) * 4) * XR_SIZE + XR_PS + (ct >> 1), XR_SIZE);
      TL(2, 12, warp == 4);
      auto F = [](uint32_t u) { return __uint_as_float(u); };
      float s1 = (F(ps[0].x) + F(ps[1].x)) + (F(ps[2].x) + F(ps[3].x)), s2 = (F(ps[0].y) + F(ps[1].y)) + (F(ps[2].y) + F(ps[3].y));
      float s3 = (F(ps[0].z) + F(ps[1].z)) + (F(ps[2].z) + F(ps[3].z));
      s1 += __shfl_xor_sync(~0u, s1, 1); s2 += __shfl_xor_sync(~0u, s2, 1); s3 += __shfl_xor_sync(~0u, s3, 1);
      const float mean = s1 * (1.f / DM);
      float mb, inv;
      ln_round(mean, fmaxf(fmaf(s2, 1.f / DM, -mean * mean), 0.f), mb, inv);
      uint32_t u = pack_bf16((s3 - mb * wsum) * inv, 0.f);
      if (u == 0x8000u) u = 0;
      u = (u & 0x8000u) ? (~u & 0xFFFFu) : (u | 0x8000u);
      const uint32_t key = (u << 16) | (0x7FFFu - (mt * 128 + (ct >> 1)));
      const uint32_t nm2 = pack_bf16(-mb, -mb);
      const uint32_t c1 = __reduce_max_sync(~0u, key);
      const uint32_t c2 = __reduce_max_sync(~0u, key == c1 ? 0u : key);
      if (lane == 0) __stcg(reinterpret_cast<uint2*>(xr + XR_KEY) + cw, make_uint2(c1, c2));
      if (!(ct & 1)) *reinterpret_cast<uint2*>(sp + OFF_RSTAT + (ct >> 1) * 8) = make_uint2(nm2, __float_as_uint(inv) | (key >= c2 ? 0x80000000u : 0u));
      ckey = (lane >> 4) ? c2 : c1;
      const int row = (0x7FFF - (ckey & 0x7FFF)) & 15;
      const uint32_t rn = __shfl_sync(~0u, nm2, row * 2);
      const float ri = __shfl_sync(~0u, inv, row * 2);
      const uint4 v = lds128(stg + ((lane & 15) >> 3) * 8192 + row * 128 + (((lane & 7) ^ (row & 7)) << 4));
      const uint4 n = make_uint4(ln_apply(v.x, rn, ri), ln_apply(v.y, rn, ri), ln_apply(v.z, rn, ri), ln_apply(v.w, rn, ri));
      __stcg(xr + XR_CAND + cw * 64 + 32 + lane, n);
      __stcg(xr + XR_CAND + cw * 64 + lane, v);
      cdst = out + (size_t)(0x7FFF - (ckey & 0x7FFF)) * DM + gq * 128 + (lane & 15) * 8;
      cout = make_uint4(hadd2_bf(v.x, n.x), hadd2_bf(v.y, n.y), hadd2_bf(v.z, n.z), hadd2_bf(v.w, n.w));
    }
    publish(B_OUT - B_PUB);
    cluster_arrive();
    TL(2, 13, warp == 4);
    uint32_t wd[16][4];
    if (ffn) {
      static_for<8 - WIN>([&](auto i) {
        constexpr int it = NIT + i / 2;
        if ((i & 1) == 0) mbar_wait_c(B(B_FULL3 + it % 6), (it / 6) & 1);
        grab(IC<WIN + i>{}, r3(it % 6) + (i & 1) * UNIT);
      });
      mbar_wait_c(B(B_FULL3 + (w ? (IT_WD + 1) % 6 : IT_WD % 6)), w ? ((IT_WD + 1) / 6) & 1 : (IT_WD / 6) & 1);
#pragma unroll
      for (int i = 0; i < 16; i++) {
        const int k = (i & 1) * 16 + (lane & 7) + (lane >> 4) * 8;
        asm volatile("ldmatrix.sync.aligned.m8n8.x4.trans.shared.b16 {%0,%1,%2,%3}, [%4];"
                     : "=r"(wd[i][0]), "=r"(wd[i][1]), "=r"(wd[i][2]), "=r"(wd[i][3])
                     : "r"(sb + (w ? r3((IT_WD + 1) % 6) : r3(IT_WD % 6)) + (2 * (cw & 3) + (i >> 3)) * 4096 + k * 128 + (((2 * ((i >> 1) & 3) + ((lane >> 3) & 1)) ^ (lane & 7)) << 4)) : "memory");
      }
    }
    mbar_wait_c(B(B_OUT2), 0);
    const uint2 top = *reinterpret_cast<const uint2*>(sp + OFF_MISC);
    TL(2, 14, warp == 4);
    const int t0 = 0x7FFF - (top.x & 0x7FFF), t1 = 0x7FFF - (top.y & 0x7FFF);
    auto cand = [&](int second, int chunk) {
      const int tk = second ? t1 : t0;
      return g_xr + ((tk >> 7) * 8 + (chunk >> 4)) * XR_SIZE + XR_CAND + ((tk >> 4) & 7) * 64 + ((second && (t0 >> 4) == (t1 >> 4)) ? 16 : 0) + (chunk & 15);
    };
    const int fc = 16 * (rid >> 1) + 4 * (rid & 1) + (lane & 3) + 8 * (lane >> 4), ft = (lane >> 3) & 1;
    uint32_t fh, fn;
    {
      const uint4* pc = cand(w, ct & 127) + 32;
      const uint16_t* pf = reinterpret_cast<const uint16_t*>(cand(ft, fc >> 3)) + (fc & 7);
      uint4 v;
#pragma unroll 1
      for (int n = 0; n < 0x400000; n++) {
        asm volatile("ld.relaxed.gpu.global.v4.u32 {%0,%1,%2,%3}, [%4];" : "=r"(v.x), "=r"(v.y), "=r"(v.z), "=r"(v.w) : "l"(pc) : "memory");
        asm volatile("ld.relaxed.gpu.global.u16 %0, [%1];" : "=r"(fh) : "l"(pf) : "memory");
        asm volatile("ld.relaxed.gpu.global.u16 %0, [%1 + 512];" : "=r"(fn) : "l"(pf) : "memory");
        if (__all_sync(~0u, max(max(v.x, v.y), max(v.z, v.w)) != 0xFFFFFFFFu && max(fh, fn) != 0xFFFFu)) break;
      }
      const int blk = (ct & 127) >> 2;
      const uint32_t a = sb + OFF_SCR + w * 2112 + blk * 64 + (((blk >> 1) & 3) << 4) + (ct & 3) * 4;
      asm volatile("st.shared.u32 [%0], %1;" ::"r"(a), "r"(v.x) : "memory");
      asm volatile("st.shared.u32 [%0], %1;" ::"r"(a ^ 16), "r"(v.y) : "memory");
      asm volatile("st.shared.u32 [%0], %1;" ::"r"(a ^ 32), "r"(v.z) : "memory");
      asm volatile("st.shared.u32 [%0], %1;" ::"r"(a ^ 48), "r"(v.w) : "memory");
    }
    asm volatile("{\n.reg .pred p;\nsetp.lt.u32 p, %5, %6;\n@p st.global.v4.u32 [%0], {%1,%2,%3,%4};\n}" ::"l"(cdst), "r"(cout.x), "r"(cout.y), "r"(cout.z),
                 "r"(cout.w), "r"(ckey), "r"(top.y) : "memory");
    if (ffn) {
      bar_sync(3, 256);
      TL(2, 15, warp == 4);
      float d[2][4] = {{0.f, 0.f, 0.f, 0.f}, {0.f, 0.f, 0.f, 0.f}};
      const uint32_t xb = sb + OFF_SCR + (r0 & 1) * 2112 + w * 128 + (((lane ^ w) & 3) << 4);
#pragma unroll
      for (int i = 0; i < 16; i++) {
        const uint4 b = lds128((xb ^ ((i & 2) << 4)) + (i >> 1) * 256 + (i & 1) * 64);
        mma16816(d[0], wf[8 * i], wf[8 * i + 1], wf[8 * i + 2], wf[8 * i + 3], b.x, b.y);
        mma16816(d[1], wf[8 * i + 4], wf[8 * i + 5], wf[8 * i + 6], wf[8 * i + 7], b.z, b.w);
      }
      float2* red = reinterpret_cast<float2*>(sp + OFF_SCR + 8192);
      if (!(lane & 2))
        red[(w * 2 + (lane & 1)) * 32 + (cw & 3) * 8 + r0] = (lane & 1) ? make_float2(d[0][1] + d[1][1], d[0][3] + d[1][3]) : make_float2(d[0][0] + d[1][0], d[0][2] + d[1][2]);
      bar_sync(3, 256);
      TL(2, 16, warp == 4);
      const uint32_t ra = sb + OFF_SCR + 8192 + (r0 & 1) * 256 + (r0 >> 1) * 64 + (lane & 3) * 16;
      const uint4 p0 = lds128(ra), p1 = lds128(ra + 512);
      auto act = [](uint32_t u0, uint32_t u1, uint32_t g0, uint32_t g1) {
        const uint32_t ug = pack_bf16(__uint_as_float(u0) + __uint_as_float(u1), __uint_as_float(g0) + __uint_as_float(g1));
        const float g = bf_hi(ug);
        return bf_round(__fdividef(g, 1.f + __expf(-g))) * bf_lo(ug);
      };
      const uint32_t av = pack_bf16(act(p0.x, p1.x, p0.y, p1.y), act(p0.z, p1.z, p0.w, p1.w));
      uint32_t b[4];
#pragma unroll
      for (int i = 0; i < 4; i++) b[i] = __shfl_sync(~0u, av, 8 * i + (lane & 7));
      TL(2, 17, warp == 4);
      float y[2][4] = {{0.f, 0.f, 0.f, 0.f}, {0.f, 0.f, 0.f, 0.f}};
#pragma unroll
      for (int c = 0; c < 4; c++) {
        const bool on = (lane >> 3) == c;
        const uint32_t b0 = on ? b[0] : 0, b1 = on ? b[1] : 0, b2 = on ? b[2] : 0, b3 = on ? b[3] : 0;
#pragma unroll
        for (int a = 0; a < 2; a++) {
          const int i = 8 * a + 2 * c;
          mma16816(y[a], wd[i][0], wd[i][1], wd[i][2], wd[i][3], b0, b1);
          mma16816(y[a], wd[i + 1][0], wd[i + 1][1], wd[i + 1][2], wd[i + 1][3], b2, b3);
        }
      }
      float4* yd = reinterpret_cast<float4*>(g_xr + (cw * 16 + (lane & 3) * 2 + (lane >> 4)) * XR_SIZE + XR_Y + fid * 4 + (r0 & 3));
      __stcg(yd, make_float4(y[0][0], y[0][1], y[0][2], y[0][3]));
      __stcg(yd + 8 * XR_SIZE, make_float4(y[1][0], y[1][1], y[1][2], y[1][3]));
    }
    TL(2, 18, warp == 4);
    if (cw == 0) {
      uint32_t u = (ft ? top.y : top.x) >> 16;
      u = (u & 0x8000u) ? (u & 0x7FFFu) : (~u & 0xFFFFu);
      float rs = bf_round(__fdividef(1.f, 1.f + __expf(-__uint_as_float(u << 16))));
      uint16_t* op = reinterpret_cast<uint16_t*>(out) + (size_t)(ft ? t1 : t0) * DM + fc;
      asm volatile("" : "+l"(op), "+f"(rs));
      if (YDLY) __nanosleep(YDLY);
      float v[4];
#pragma unroll 1
      for (int n = 0; n < 0x400000; n++) {
        float4 z[14];
#pragma unroll
        for (int i = 0; i < 14; i++)
          asm volatile("ld.relaxed.gpu.global.v4.f32 {%0,%1,%2,%3}, [%4];" : "=f"(z[i].x), "=f"(z[i].y), "=f"(z[i].z), "=f"(z[i].w) : "l"(xr + XR_Y + lane + 32 * i) : "memory");
        float a[4] = {z[0].x, z[0].y, z[0].z, z[0].w}, b[4] = {z[1].x, z[1].y, z[1].z, z[1].w};
#pragma unroll
        for (int i = 2; i < 14; i += 2) {
          a[0] += z[i].x; a[1] += z[i].y; a[2] += z[i].z; a[3] += z[i].w;
          b[0] += z[i + 1].x; b[1] += z[i + 1].y; b[2] += z[i + 1].z; b[3] += z[i + 1].w;
        }
#pragma unroll
        for (int i = 0; i < 4; i++) v[i] = a[i] + b[i];
        const float t = (v[0] + v[1]) + (v[2] + v[3]);
        if (__all_sync(~0u, t == t)) break;
        uint32_t m = 0;
#pragma unroll
        for (int i = 0; i < 14; i++) m = max(max(m, max(__float_as_uint(z[i].x), __float_as_uint(z[i].y))), max(__float_as_uint(z[i].z), __float_as_uint(z[i].w)));
        if (__all_sync(~0u, m != 0xFFFFFFFFu)) break;
      }
      TL(2, 30, true);
      const bool hi = lane & 16, odd = lane & 8;
      const float a0 = (hi ? v[2] : v[0]) + __shfl_xor_sync(~0u, hi ? v[0] : v[2], 16), a1 = (hi ? v[3] : v[1]) + __shfl_xor_sync(~0u, hi ? v[1] : v[3], 16);
      float yv = (odd ? a1 : a0) + __shfl_xor_sync(~0u, odd ? a0 : a1, 8);
      yv += __shfl_xor_sync(~0u, yv, 4);
      const uint32_t o = hadd2_bf(fh, hadd2_bf(fn, pack_bf16(bf_round(yv) * rs, 0.f)));
      if (!(lane & 4)) *op = (uint16_t)o;
      TL(2, 21, true);
    }
    TL(2, 20, warp == 4);
    __syncwarp();
    cluster_wait();
  }
}

typedef CUresult (*EncodeFn)(CUtensorMap*, CUtensorMapDataType, cuuint32_t, void*, const cuuint64_t*, const cuuint64_t*, const cuuint32_t*,
                             const cuuint32_t*, CUtensorMapInterleave, CUtensorMapSwizzle, CUtensorMapL2promotion, CUtensorMapFloatOOBfill);
EncodeFn g_enc = nullptr;

void map2(CUtensorMap* m, const void* ptr, uint64_t rows, uint64_t cols, uint32_t bc, uint32_t br) {
  const CUtensorMapSwizzle sw = bc == 64 ? CU_TENSOR_MAP_SWIZZLE_128B : CU_TENSOR_MAP_SWIZZLE_64B;
  cuuint64_t gd[2] = {cols, rows}, gs[1] = {cols * 2};
  cuuint32_t bd[2] = {bc, br}, es[2] = {1, 1};
  g_enc(m, CU_TENSOR_MAP_DATA_TYPE_BFLOAT16, 2, (void*)ptr, gd, gs, bd, es, CU_TENSOR_MAP_INTERLEAVE_NONE, sw,
        CU_TENSOR_MAP_L2_PROMOTION_L2_128B, CU_TENSOR_MAP_FLOAT_OOB_FILL_NONE);
}
void map3(CUtensorMap* m, const void* ptr, uint64_t rows, uint64_t cols, uint32_t br, uint32_t bch) {
  cuuint64_t gd[3] = {64, rows, cols / 64}, gs[2] = {cols * 2, 128};
  cuuint32_t bd[3] = {64, br, bch}, es[3] = {1, 1, 1};
  g_enc(m, CU_TENSOR_MAP_DATA_TYPE_BFLOAT16, 3, (void*)ptr, gd, gs, bd, es, CU_TENSOR_MAP_INTERLEAVE_NONE, CU_TENSOR_MAP_SWIZZLE_128B,
        CU_TENSOR_MAP_L2_PROMOTION_L2_128B, CU_TENSOR_MAP_FLOAT_OOB_FILL_NONE);
}

}

extern "C" void kernel_launch(void* const* d_in, const int* in_sizes, int n_in, void* d_out, int out_size) {
  const __nv_bfloat16* x = (const __nv_bfloat16*)d_in[0];
  const __nv_bfloat16* ckv = (const __nv_bfloat16*)d_in[1];
  const __nv_bfloat16* wq = (const __nv_bfloat16*)d_in[2];
  const __nv_bfloat16* wk = (const __nv_bfloat16*)d_in[3];
  const __nv_bfloat16* wv = (const __nv_bfloat16*)d_in[4];
  const __nv_bfloat16* wo = (const __nv_bfloat16*)d_in[5];
  const __nv_bfloat16* w_r = (const __nv_bfloat16*)d_in[7];
  const __nv_bfloat16* wgate = (const __nv_bfloat16*)d_in[8];
  const __nv_bfloat16* wup = (const __nv_bfloat16*)d_in[9];
  const __nv_bfloat16* wdown = (const __nv_bfloat16*)d_in[10];
  __nv_bfloat16* out = (__nv_bfloat16*)d_out;

  if (!g_enc) {
    void* fn = nullptr;
    cudaDriverEntryPointQueryResult qr;
    cudaGetDriverEntryPoint("cuTensorMapEncodeTiled", &fn, cudaEnableDefault, &qr);
    g_enc = (EncodeFn)fn;
    cudaFuncSetAttribute(fused_kernel, cudaFuncAttributeMaxDynamicSharedMemorySize, SMEM_BYTES);
  }
  void *xn, *kv, *ctx;
  cudaGetSymbolAddress(&xn, g_xn);
  cudaGetSymbolAddress(&kv, g_kv);
  cudaGetSymbolAddress(&ctx, g_ctx);

  Params p;
  map2(&p.xn, xn, SEQ, DM, 64, 64);
  map2(&p.ckv, ckv, SEQ, DC, 64, 128);
  map3(&p.wq, wq, DM, NQ, 64, 2);
  map3(&p.wk, wk, DC, NQ, 64, 2);
  map3(&p.wv, wv, DC, NQ, 64, 2);
  map3(&p.kv_ld, kv, 2 * SEQ, NQ, 128, 2);
  map2(&p.ctx_ld, ctx, SEQ, NQ, 64, 128);
  map3(&p.wo, wo, NQ, DM, 64, 1);
  map3(&p.x, x, SEQ, DM, 64, 2);
  map3(&p.wd, wdown, FF, DM, 32, 8);
  map2(&p.wg, wgate, DM, FF, 32, 64);
  map2(&p.wu, wup, DM, FF, 32, 64);
  fused_kernel<<<128, 384, SMEM_BYTES, cudaStreamPerThread>>>(p, x, wq, w_r, wgate, wup, out, 0u);
}
```

```cpp
#include <cuda_runtime.h>
#include <cuda_bf16.h>
#include <cuda.h>
#include <stdint.h>
#include <utility>

#pragma nv_diag_suppress 549
#pragma nv_diag_suppress 177
namespace {

constexpr int SEQ = 2048, DM = 1024, NH = 32, HD = 128, DC = 512, NQ = NH * HD, FF = 3584;

__device__ __align__(1024) __nv_bfloat16 g_xn[SEQ * DM];
__device__ __align__(1024) __nv_bfloat16 g_kv[2 * SEQ * NQ];
__device__ __align__(1024) __nv_bfloat16 g_ctx[SEQ * NQ];
constexpr int XR_PS = 0;
constexpr int XR_KEY = 128;
constexpr int XR_CAND = 136;
constexpr int XR_Y = 648;
constexpr int XR_SIZE = 1104;
__device__ __align__(1024) uint4 g_xr[128 * XR_SIZE];
constexpr int C_LN = 0, C_KV = 16, C_CTX = 32, C_NUM = 64;
__device__ unsigned g_cnt[C_NUM];

#define TL(k, i, cond) do {} while (0)
#define TC(w, g, i) do {} while (0)
#define TL_EXTRA 0
#define TK(i) do {} while (0)

__device__ __forceinline__ uint32_t s2u(const void* p) { return (uint32_t)__cvta_generic_to_shared(p); }
__device__ __forceinline__ void mbar_arrive(uint32_t b) { asm volatile("mbarrier.arrive.shared::cta.b64 _, [%0];" ::"r"(b) : "memory"); }
__device__ __forceinline__ void mbar_arrive_both(uint32_t b, uint32_t lane, bool cond) {
  asm volatile("{\n.reg .pred p;\n.reg .b32 r;\nsetp.lt.u32 p, %1, %2;\nmapa.shared::cluster.u32 r, %0, %1;\n@p mbarrier.arrive.shared::cluster.b64 _, [r];\n}"
               ::"r"(b), "r"(lane), "r"(cond ? 2 : 0) : "memory");
}
__device__ __forceinline__ bool mbar_test(uint32_t b, uint32_t ph) {
  uint32_t ok;
  asm volatile("{\n.reg .pred p;\nmbarrier.test_wait.parity.shared::cta.b64 p, [%1], %2;\nselp.u32 %0, 1, 0, p;\n}" : "=r"(ok) : "r"(b), "r"(ph) : "memory");
  return __all_sync(~0u, ok);
}
__device__ __forceinline__ void mbar_wait(uint32_t b, uint32_t ph) {
  asm volatile(
      "{\n.reg .pred p;\n.reg .u32 n;\nmov.u32 n, 0;\n"
      "LW:\nmbarrier.try_wait.parity.shared::cta.b64 p, [%0], %1, 20000;\n@p bra LD;\n"
      "add.u32 n, n, 1;\nsetp.lt.u32 p, n, 0x40000;\n@p bra LW;\ntrap;\nLD:\n}" ::"r"(b), "r"(ph) : "memory");
}
__device__ __forceinline__ void mbar_wait_u(uint32_t b, uint32_t ph) {
  asm volatile(
      "{\n.reg .pred p;\n.reg .u32 n;\nmov.u32 n, 0;\n"
      "LW:\nmbarrier.try_wait.parity.shared::cta.b64 p, [%0], %1, 20000;\n@p bra.uni LD;\n"
      "add.u32 n, n, 1;\nsetp.lt.u32 p, n, 0x40000;\n@p bra.uni LW;\ntrap;\nLD:\n}" ::"r"(b), "r"(ph) : "memory");
}
__device__ __forceinline__ void mbar_wait_c(uint32_t b, uint32_t ph) {
  asm volatile(
      "{\n.reg .pred p;\n.reg .u32 n;\nmov.u32 n, 0;\n"
      "LW:\nmbarrier.try_wait.parity.shared::cta.b64 p, [%0], %1;\n@p bra.uni LD;\n"
      "add.u32 n, n, 1;\nsetp.lt.u32 p, n, 0x100000;\n@p bra.uni LW;\ntrap;\nLD:\n}" ::"r"(b), "r"(ph) : "memory");
}
template <bool SLEEP = false>
__device__ __forceinline__ void spin_until_ge(const unsigned* p, unsigned target) {
  asm volatile(
      "{\n.reg .pred p, q;\n.reg .u32 n, v;\nmov.u32 n, 0;\nsetp.ne.u32 q, %2, 0;\n"
      "LW:\nld.acquire.gpu.global.u32 v, [%0];\nsetp.ge.u32 p, v, %1;\n@p bra LD;\n@q nanosleep.u32 200;\n"
      "add.u32 n, n, 1;\nsetp.lt.u32 p, n, 0x400000;\n@p bra LW;\ntrap;\nLD:\n}" ::"l"(p), "r"(target), "n"((int)SLEEP) : "memory");
}
template <int N>
__device__ __forceinline__ void poll_chunks(uint4 (&v)[N], const uint4* p, int stride) {
#pragma unroll 1
  for (int n = 0; n < 0x400000; n++) {
    uint32_t m = 0;
#pragma unroll
    for (int i = 0; i < N; i++) {
      asm volatile("ld.relaxed.gpu.global.v4.u32 {%0,%1,%2,%3}, [%4];" : "=r"(v[i].x), "=r"(v[i].y), "=r"(v[i].z), "=r"(v[i].w) : "l"(p + i * stride) : "memory");
    }
#pragma unroll
    for (int i = 0; i < N; i++) m = max(max(m, max(v[i].x, v[i].y)), max(v[i].z, v[i].w));
    if (__all_sync(~0u, m != 0xFFFFFFFFu)) break;
  }
}
__device__ __forceinline__ void spin_clk(uint32_t n) {
  asm volatile("{\n.reg .pred p;\n.reg .u32 a, b;\nmov.u32 a, %%clock;\nLW:\nmov.u32 b, %%clock;\nsub.u32 b, b, a;\nsetp.lt.u32 p, b, %0;\n@p bra.uni LW;\n}" ::"r"(n) : "memory");
}
__device__ __forceinline__ void fence_async_all() { asm volatile("fence.proxy.async;" ::: "memory"); }
__device__ __forceinline__ void bar_sync(int id, int n) { asm volatile("bar.sync %0, %1;" ::"r"(id), "r"(n) : "memory"); }
__device__ __forceinline__ void bar_arrive(int id, int n) { asm volatile("bar.arrive %0, %1;" ::"r"(id), "r"(n) : "memory"); }
__device__ __forceinline__ void cluster_arrive() { asm volatile("barrier.cluster.arrive.relaxed.aligned;" ::: "memory"); }
__device__ __forceinline__ void cluster_wait() { asm volatile("barrier.cluster.wait.acquire.aligned;" ::: "memory"); }
__device__ __forceinline__ void fence_gpu() { asm volatile("fence.acq_rel.gpu;" ::: "memory"); }
__device__ __forceinline__ void red_add(unsigned* p, unsigned v) { asm volatile("red.relaxed.gpu.global.add.u32 [%0], %1;" ::"l"(p), "r"(v) : "memory"); }
#define ELECT "{\n.reg .pred E;\nelect.sync _|E, 0xFFFFFFFF;\n@E "
__device__ __forceinline__ void e_init(uint32_t b, uint32_t c) { asm volatile(ELECT "mbarrier.init.shared::cta.b64 [%0], %1;\n}" ::"r"(b), "r"(c) : "memory"); }
__device__ __forceinline__ void e_expect(uint32_t b, uint32_t bytes) { asm volatile(ELECT "mbarrier.arrive.expect_tx.shared::cta.b64 _, [%0], %1;\n}" ::"r"(b), "r"(bytes) : "memory"); }
__device__ __forceinline__ void e_arrive(uint32_t b) { asm volatile(ELECT "mbarrier.arrive.shared::cta.b64 _, [%0];\n}" ::"r"(b) : "memory"); }
__device__ __forceinline__ void prefetch_tm(const CUtensorMap* m) { asm volatile(ELECT "prefetch.tensormap [%0];\n}" ::"l"(m) : "memory"); }
__device__ __forceinline__ void tma_ld2(uint32_t dst, const CUtensorMap* m, uint32_t bar, int c0, int c1) {
  asm volatile(ELECT "cp.async.bulk.tensor.2d.shared::cta.global.mbarrier::complete_tx::bytes [%0], [%1, {%3,%4}], [%2];\n}" ::"r"(dst), "l"(m), "r"(bar), "r"(c0), "r"(c1) : "memory");
}
__device__ __forceinline__ void tma_ld3(uint32_t dst, const CUtensorMap* m, uint32_t bar, int c0, int c1, int c2) {
  asm volatile(ELECT "cp.async.bulk.tensor.3d.shared::cta.global.mbarrier::complete_tx::bytes [%0], [%1, {%3,%4,%5}], [%2];\n}" ::"r"(dst), "l"(m), "r"(bar), "r"(c0), "r"(c1), "r"(c2) : "memory");
}
__device__ __forceinline__ void tma_ld2_mc(uint32_t dst, const CUtensorMap* m, uint32_t bar, int c0, int c1, uint16_t mask) {
  asm volatile(ELECT "cp.async.bulk.tensor.2d.shared::cluster.global.mbarrier::complete_tx::bytes.multicast::cluster [%0], [%1, {%3,%4}], [%2], %5;\n}" ::"r"(dst), "l"(m), "r"(bar), "r"(c0), "r"(c1), "h"(mask) : "memory");
}
__device__ __forceinline__ void tma_ld3_mc(uint32_t dst, const CUtensorMap* m, uint32_t bar, int c0, int c1, int c2, uint16_t mask) {
  asm volatile(ELECT "cp.async.bulk.tensor.3d.shared::cluster.global.mbarrier::complete_tx::bytes.multicast::cluster [%0], [%1, {%3,%4,%5}], [%2], %6;\n}" ::"r"(dst), "l"(m), "r"(bar), "r"(c0), "r"(c1), "r"(c2), "h"(mask) : "memory");
}
__device__ __forceinline__ void tma_pf2(const CUtensorMap* m, int c0, int c1) { asm volatile(ELECT "cp.async.bulk.prefetch.tensor.2d.L2.global [%0, {%1,%2}];\n}" ::"l"(m), "r"(c0), "r"(c1) : "memory"); }
__device__ __forceinline__ void tma_pf3(const CUtensorMap* m, int c0, int c1, int c2) { asm volatile(ELECT "cp.async.bulk.prefetch.tensor.3d.L2.global [%0, {%1,%2,%3}];\n}" ::"l"(m), "r"(c0), "r"(c1), "r"(c2) : "memory"); }
__device__ __forceinline__ void sched_fence() { asm volatile("pmevent 0;" ::: "memory"); }
__device__ __forceinline__ void l2_prefetch(const void* p, uint32_t bytes) { asm volatile(ELECT "cp.async.bulk.prefetch.L2.global [%0], %1;\n}" ::"l"(p), "r"(bytes) : "memory"); }

__device__ __forceinline__ void wg_fence() { asm volatile("wgmma.fence.sync.aligned;" ::: "memory"); }
__device__ __forceinline__ void wg_commit() { asm volatile("wgmma.commit_group.sync.aligned;" ::: "memory"); }
template <int N> __device__ __forceinline__ void wg_wait() { asm volatile("wgmma.wait_group.sync.aligned %0;" ::"n"(N) : "memory"); }
template <int N> __device__ __forceinline__ void reg_alloc() { asm volatile("setmaxnreg.inc.sync.aligned.u32 %0;" ::"n"(N)); }
template <int N> __device__ __forceinline__ void reg_dealloc() { asm volatile("setmaxnreg.dec.sync.aligned.u32 %0;" ::"n"(N)); }
template <int N> __device__ __forceinline__ void fence_regs(float (&d)[N]) {
#pragma unroll
  for (int i = 0; i < N; i++) asm volatile("" : "+f"(d[i])::"memory");
}
template <int N> __device__ __forceinline__ void fence_regs(uint32_t (&d)[N]) {
#pragma unroll
  for (int i = 0; i < N; i++) asm volatile("" : "+r"(d[i])::"memory");
}

__device__ __forceinline__ uint32_t mk_desc(uint32_t addr, uint32_t lbo) { return ((addr & 0x3FFFF) >> 4) | ((lbo >> 4) << 16); }

#define R8(b) "+f"(d[b + 0]), "+f"(d[b + 1]), "+f"(d[b + 2]), "+f"(d[b + 3]), "+f"(d[b + 4]), "+f"(d[b + 5]), "+f"(d[b + 6]), "+f"(d[b + 7])
#define REGS64 "%0,%1,%2,%3,%4,%5,%6,%7,%8,%9,%10,%11,%12,%13,%14,%15,%16,%17,%18,%19,%20,%21,%22,%23,%24,%25,%26,%27,%28,%29,%30,%31," \
               "%32,%33,%34,%35,%36,%37,%38,%39,%40,%41,%42,%43,%44,%45,%46,%47,%48,%49,%50,%51,%52,%53,%54,%55,%56,%57,%58,%59,%60,%61,%62,%63"
#define REGS128 REGS64 ",%64,%65,%66,%67,%68,%69,%70,%71,%72,%73,%74,%75,%76,%77,%78,%79,%80,%81,%82,%83,%84,%85,%86,%87,%88,%89,%90,%91,%92,%93,%94,%95," \
               "%96,%97,%98,%99,%100,%101,%102,%103,%104,%105,%106,%107,%108,%109,%110,%111,%112,%113,%114,%115,%116,%117,%118,%119,%120,%121,%122,%123,%124,%125,%126,%127"

#define DESC(d, r, o) "add.u32 t, " r ", " o ";\nmov.b64 " d ", {t, h};\n"
#define MMA_PRE(acc) "{\n.reg .pred p;\n.reg .b32 t, h;\n.reg .b64 da, db;\nmov.b32 h, 0x40000040;\nsetp.ne.b32 p, " acc ", 0;\n"
template <int TB, int OA, int OB>
__device__ __forceinline__ void mma_n256_ss(float (&d)[128], uint32_t a, uint32_t b, int acc) {
  asm volatile(MMA_PRE("%130") DESC("da", "%128", "%132") DESC("db", "%129", "%133")
               "wgmma.mma_async.sync.aligned.m64n256k16.f32.bf16.bf16 {" REGS128 "}, da, db, p, 1, 1, 0, %131;\n}\n"
               : R8(0), R8(8), R8(16), R8(24), R8(32), R8(40), R8(48), R8(56), R8(64), R8(72), R8(80), R8(88), R8(96), R8(104), R8(112), R8(120)
               : "r"(a), "r"(b), "r"(acc), "n"(TB), "n"(OA >> 4), "n"(OB >> 4));
}
template <int TB, int OA, int OB>
__device__ __forceinline__ void mma_n128_ss(float (&d)[64], uint32_t a, uint32_t b, int acc) {
  asm volatile(MMA_PRE("%66") DESC("da", "%64", "%68") DESC("db", "%65", "%69")
               "wgmma.mma_async.sync.aligned.m64n128k16.f32.bf16.bf16 {" REGS64 "}, da, db, p, 1, 1, 0, %67;\n}\n"
               : R8(0), R8(8), R8(16), R8(24), R8(32), R8(40), R8(48), R8(56)
               : "r"(a), "r"(b), "r"(acc), "n"(TB), "n"(OA >> 4), "n"(OB >> 4));
}
template <int TB, int OB>
__device__ __forceinline__ void mma_n128_rs(float (&d)[64], const uint32_t* a, uint32_t b, int acc) {
  asm volatile(MMA_PRE("%69") DESC("db", "%68", "%71")
               "wgmma.mma_async.sync.aligned.m64n128k16.f32.bf16.bf16 {" REGS64 "}, {%64,%65,%66,%67}, db, p, 1, 1, %70;\n}\n"
               : R8(0), R8(8), R8(16), R8(24), R8(32), R8(40), R8(48), R8(56)
               : "r"(a[0]), "r"(a[1]), "r"(a[2]), "r"(a[3]), "r"(b), "r"(acc), "n"(TB), "n"(OB >> 4));
}
template <int OB>
__device__ __forceinline__ void mma_n64_rs(float (&d)[64], const uint32_t* a, uint32_t b, int acc) {
  asm volatile(MMA_PRE("%37") DESC("db", "%36", "%38")
               "wgmma.mma_async.sync.aligned.m64n64k16.f32.bf16.bf16 {%0,%1,%2,%3,%4,%5,%6,%7,%8,%9,%10,%11,%12,%13,%14,%15,%16,%17,%18,%19,%20,%21,"
               "%22,%23,%24,%25,%26,%27,%28,%29,%30,%31}, {%32,%33,%34,%35}, db, p, 1, 1, 0;\n}\n"
               : R8(0), R8(8), R8(16), R8(24)
               : "r"(a[0]), "r"(a[1]), "r"(a[2]), "r"(a[3]), "r"(b), "r"(acc), "n"(OB >> 4));
}
template <int V> struct IC { static constexpr int value = V; __host__ __device__ constexpr operator int() const { return V; } };
template <int N, class F, int... I>
__device__ __forceinline__ void static_for_(F f, std::integer_sequence<int, I...>) { (f(IC<I>{}), ...); }
template <int N, class F>
__device__ __forceinline__ void static_for(F f) { static_for_<N>(f, std::make_integer_sequence<int, N>{}); }
__device__ __forceinline__ uint32_t pack_bf16(float lo, float hi) {
  uint32_t r;
  asm("cvt.rn.bf16x2.f32 %0, %1, %2;" : "=r"(r) : "f"(hi), "f"(lo));
  return r;
}
__device__ __forceinline__ float bf_lo(uint32_t v) { return __uint_as_float(v << 16); }
__device__ __forceinline__ float bf_hi(uint32_t v) { return __uint_as_float(v & 0xFFFF0000u); }
__device__ __forceinline__ float bf_round(float v) { return bf_lo(pack_bf16(v, v)); }
__device__ __forceinline__ void stsm4(uint32_t addr, uint32_t r0, uint32_t r1, uint32_t r2, uint32_t r3) {
  asm volatile("stmatrix.sync.aligned.m8n8.x4.shared.b16 [%0], {%1,%2,%3,%4};" ::"r"(addr), "r"(r0), "r"(r1), "r"(r2), "r"(r3) : "memory");
}
__device__ __forceinline__ uint4 lds128(uint32_t addr) {
  uint4 v;
  asm volatile("ld.shared.v4.u32 {%0,%1,%2,%3}, [%4];" : "=r"(v.x), "=r"(v.y), "=r"(v.z), "=r"(v.w) : "r"(addr));
  return v;
}
__device__ __forceinline__ float ex2(float x) {
  float y;
  asm("ex2.approx.ftz.f32 %0, %1;" : "=f"(y) : "f"(x));
  return y;
}
__device__ __forceinline__ void stage_store_128(uint32_t base, int lane, const uint32_t* pk) {
  const int row = (lane & 7) + ((lane >> 3) & 1) * 8;
  const uint32_t rb = base + row * 128;
  const int hi = lane >> 4;
#pragma unroll
  for (int j = 0; j < 8; j++) {
    const int chunk = 2 * j + hi;
    const uint32_t a = rb + (j >> 2) * 8192 + (((chunk & 7) ^ (lane & 7)) << 4);
    stsm4(a, pk[4 * j + 0], pk[4 * j + 1], pk[4 * j + 2], pk[4 * j + 3]);
  }
}
__device__ __forceinline__ void ln_round(float mean, float var, float& m_bf, float& inv_s) {
  const uint32_t mv = pack_bf16(mean, var);
  m_bf = bf_lo(mv);
  float sq, rc;
  asm("sqrt.approx.f32 %0, %1;" : "=f"(sq) : "f"(bf_round(bf_hi(mv) + 1e-5f)));
  asm("rcp.approx.ftz.f32 %0, %1;" : "=f"(rc) : "f"(bf_round(sq)));
  inv_s = rc;
}
__device__ __forceinline__ uint32_t hadd2_bf(uint32_t a, uint32_t b) {
  uint32_t r;
  asm("add.rn.bf16x2 %0, %1, %2;" : "=r"(r) : "r"(a), "r"(b));
  return r;
}
__device__ __forceinline__ uint32_t ln_apply(uint32_t h, uint32_t nm2, float inv_s) {
  const uint32_t d = hadd2_bf(h, nm2);
  return pack_bf16(bf_lo(d) * inv_s, bf_hi(d) * inv_s);
}
__device__ __forceinline__ void mma16816(float* d, uint32_t a0, uint32_t a1, uint32_t a2, uint32_t a3, uint32_t b0, uint32_t b1) {
  asm volatile("mma.sync.aligned.m16n8k16.row.col.f32.bf16.bf16.f32 {%0,%1,%2,%3}, {%4,%5,%6,%7}, {%8,%9}, {%0,%1,%2,%3};"
               : "+f"(d[0]), "+f"(d[1]), "+f"(d[2]), "+f"(d[3]) : "r"(a0), "r"(a1), "r"(a2), "r"(a3), "r"(b0), "r"(b1));
}

constexpr float AT_C = 0.08838834764831845f * 1.4426950408889634f;
#define L_MIN 2.3283064e-10f
#define L_MAX 1.0995116e12f
#define SP1 6
#define SP2 12
struct AtState {
  float S[64], O[64];
  uint32_t P[32], Q[32];
  float l[4];
};
#define LAG 0
template <int I0, int I1, int N = 64>
__device__ __forceinline__ void at_exp(AtState& s) {
#pragma unroll
  for (int i = I0; i < I1; i++) asm volatile("ex2.approx.ftz.f32 %0, %0;" : "+f"(s.S[i]));
#pragma unroll
  for (int i = I0 > 0 ? I0 - LAG : 0; i < (I1 < N ? I1 - LAG : N); i++) asm volatile("add.f32 %0, %0, %1;" : "+f"(s.l[i & 3]) : "f"(s.S[i]));
}
template <int I0, int I1>
__device__ __forceinline__ void at_pack(AtState& s) {
#pragma unroll
  for (int i = I0; i < I1; i++) asm volatile("cvt.rn.bf16x2.f32 %0, %1, %2;" : "=r"(s.P[i]) : "f"(s.S[2 * i + 1]), "f"(s.S[2 * i]));
}
template <int J0>
__device__ __forceinline__ void at_mask(AtState& s, int r, int lane) {
  const int d = r + (lane >> 2) - (lane & 3) * 2;
#pragma unroll
  for (int j = 0; j < 8; j++) {
    float dummy0 = 0.f, dummy1 = 0.f;
    float& lo0 = j < 7 ? s.S[4 * (J0 + (j < 7 ? j + 1 : j)) + 2] : dummy0;
    float& lo1 = j < 7 ? s.S[4 * (J0 + (j < 7 ? j + 1 : j)) + 3] : dummy1;
    asm("{\n.reg .pred p, q;\nsetp.lt.s32 p, %4, %5;\nsetp.le.s32 q, %4, %5;\n"
        "@p add.f32 %0, %0, 0fFF800000;\n@q add.f32 %1, %1, 0fFF800000;\n@p add.f32 %2, %2, 0fFF800000;\n@q add.f32 %3, %3, 0fFF800000;\n}"
        : "+f"(s.S[4 * (J0 + j)]), "+f"(s.S[4 * (J0 + j) + 1]), "+f"(lo0), "+f"(lo1) : "r"(d), "r"(8 * j));
  }
}
__device__ __forceinline__ uint32_t ld_pair(const __nv_bfloat16* p) {
  uint32_t r;
  asm volatile("{\n.reg .b16 a, b;\nld.global.cg.b16 a, [%1];\nld.global.cg.b16 b, [%1 + 8192];\nmov.b32 %0, {a, b};\n}" : "=r"(r) : "l"(p) : "memory");
  return r;
}
__device__ __forceinline__ uint32_t ld_word(const uint32_t* p) {
  uint32_t r;
  asm volatile("ld.global.cg.b32 %0, [%1];" : "=r"(r) : "l"(p) : "memory");
  return r;
}
__device__ __forceinline__ void slow_rows(const __nv_bfloat16* wq, int head, int row0, int lane) {
  const int r = lane >> 2, c = lane & 3;
  uint32_t q[32];
  float o[32];
#pragma unroll
  for (int i = 0; i < 32; i++) q[i] = 0;
  const uint32_t* xa = reinterpret_cast<const uint32_t*>(g_xn + (size_t)(row0 + r) * DM) + c;
#pragma unroll 1
  for (int h = 0; h < 2; h++) {
    const __nv_bfloat16* wb = wq + (size_t)2 * c * NQ + head * HD + 64 * h + 8 * (r >> 1) + (r & 1);
#pragma unroll
    for (int i = 0; i < 32; i++) o[i] = 0.f;
#pragma unroll 1
    for (int kk = 0; kk < DM / 16; kk++) {
      const uint32_t a0 = ld_word(xa + 8 * kk), a1 = ld_word(xa + 8 * kk + 4 * DM), a2 = ld_word(xa + 8 * kk + 4), a3 = ld_word(xa + 8 * kk + 4 * DM + 4);
#pragma unroll
      for (int n = 0; n < 8; n++) {
        const __nv_bfloat16* b = wb + (size_t)16 * kk * NQ + 32 * (n >> 2) + 2 * (n & 3);
        mma16816(o + 4 * n, a0, a1, a2, a3, ld_pair(b), ld_pair(b + 8 * NQ));
      }
    }
#pragma unroll
    for (int i = 0; i < 16; i++) { q[i] = q[16 + i]; q[16 + i] = pack_bf16(o[2 * i] * AT_C, o[2 * i + 1] * AT_C); }
  }
#pragma unroll 1
  for (int h = 0; h < 2; h++) {
    float m0 = -INFINITY, m1 = -INFINITY, l0 = 0.f, l1 = 0.f;
#pragma unroll
    for (int i = 0; i < 32; i++) o[i] = 0.f;
#pragma unroll 1
    for (int k0 = 0; k0 <= row0; k0 += 16) {
      float e[8] = {0.f, 0.f, 0.f, 0.f, 0.f, 0.f, 0.f, 0.f};
      const uint32_t* kp = reinterpret_cast<const uint32_t*>(g_kv + (size_t)(k0 + r) * NQ + head * HD) + c;
#pragma unroll
      for (int kk = 0; kk < 8; kk++) {
        mma16816(e, q[4 * kk], q[4 * kk + 1], q[4 * kk + 2], q[4 * kk + 3], ld_word(kp + 8 * kk), ld_word(kp + 8 * kk + 4));
        mma16816(e + 4, q[4 * kk], q[4 * kk + 1], q[4 * kk + 2], q[4 * kk + 3], ld_word(kp + 8 * kk + 4 * NQ), ld_word(kp + 8 * kk + 4 * NQ + 4));
      }
      if (k0 == row0) {
#pragma unroll
        for (int i = 0; i < 8; i++) if ((i >> 2) * 8 + 2 * c + (i & 1) > r + (i & 2) * 4) e[i] = -INFINITY;
      }
      float a0 = fmaxf(fmaxf(e[0], e[1]), fmaxf(e[4], e[5])), a1 = fmaxf(fmaxf(e[2], e[3]), fmaxf(e[6], e[7]));
      a0 = fmaxf(a0, __shfl_xor_sync(~0u, a0, 1)); a1 = fmaxf(a1, __shfl_xor_sync(~0u, a1, 1));
      a0 = fmaxf(a0, __shfl_xor_sync(~0u, a0, 2)); a1 = fmaxf(a1, __shfl_xor_sync(~0u, a1, 2));
      a0 = fmaxf(a0, m0); a1 = fmaxf(a1, m1);
      const float sc0 = ex2(m0 - a0), sc1 = ex2(m1 - a1);
      m0 = a0; m1 = a1;
#pragma unroll
      for (int i = 0; i < 8; i++) e[i] = ex2(e[i] - ((i & 2) ? m1 : m0));
      l0 = l0 * sc0 + (e[0] + e[1]) + (e[4] + e[5]);
      l1 = l1 * sc1 + (e[2] + e[3]) + (e[6] + e[7]);
      const uint32_t p0 = pack_bf16(e[0], e[1]), p1 = pack_bf16(e[2], e[3]), p2 = pack_bf16(e[4], e[5]), p3 = pack_bf16(e[6], e[7]);
      const __nv_bfloat16* vp = g_kv + (size_t)(SEQ + k0 + 2 * c) * NQ + head * HD + 64 * h + r;
#pragma unroll
      for (int n = 0; n < 8; n++) {
        o[4 * n] *= sc0; o[4 * n + 1] *= sc0; o[4 * n + 2] *= sc1; o[4 * n + 3] *= sc1;
        mma16816(o + 4 * n, p0, p1, p2, p3, ld_pair(vp + 8 * n), ld_pair(vp + 8 * n + 8 * NQ));
      }
    }
    l0 += __shfl_xor_sync(~0u, l0, 1); l1 += __shfl_xor_sync(~0u, l1, 1);
    l0 += __shfl_xor_sync(~0u, l0, 2); l1 += __shfl_xor_sync(~0u, l1, 2);
#pragma unroll
    for (int i = 0; i < 4; i++) {
      const float* v = o + 16 * (i >> 1) + 2 * (i & 1);
      const float f = __fdividef(1.f, (i & 1) ? l1 : l0);
      *reinterpret_cast<uint4*>(g_ctx + (size_t)(row0 + r + (i & 1) * 8) * NQ + head * HD + 64 * h + (i >> 1) * 32 + c * 8) =
          make_uint4(pack_bf16(v[0] * f, v[1] * f), pack_bf16(v[4] * f, v[5] * f), pack_bf16(v[8] * f, v[9] * f), pack_bf16(v[12] * f, v[13] * f));
    }
  }
}

constexpr int UNIT = 16384, SLOT = 32768;
constexpr int OFF_STG = 2 * SLOT;
__host__ __device__ constexpr int kv_a(int kb) { return (kb < 6 ? kb : 3 * kb - 10) * UNIT; }
__host__ __device__ constexpr int kv_b(int s) { return (s == 2 ? 6 : 9 + 3 * s) * UNIT; }
__host__ __device__ constexpr int q_aw(int s) { return (3 * s + (s & 1)) * UNIT; }
__host__ __device__ constexpr int q_b(int s) { return (3 * s + 2 - 2 * (s & 1)) * UNIT; }
__host__ __device__ constexpr int k_slot(int j, int r) { return (j < 2 ? 2 * j : (r == 2 ? 0 : 3 + r)) * SLOT; }
__host__ __device__ constexpr int v_slot(int j) { return (6 - (j & 1)) * SLOT; }
__host__ __device__ constexpr int r3(int st) { return ((0x654130 >> (4 * st)) & 7) * SLOT; }
constexpr int OFF_BAR = 229376;
constexpr int OFF_MISC = OFF_BAR + 512;
constexpr int SMEM_BYTES = OFF_MISC + 2080 + TL_EXTRA;
constexpr int OFF_RSTAT = OFF_MISC + 1056;
enum : int {
  B_FULL1 = 0, B_FULLQ = 3, B_FULLB = 7, B_KF = 8, B_VF = 11, B_FULL3 = 13, B_WF = 19, B_DEP = 21, B_OUT2 = 26, B_PF = 27, B_SET = 28,
  B_SET2 = 29, B_LNGO = 30, B_WR = 31,
  B_KE = 32, B_VE = 35, B_WE = 37, B_PUB = 39, B_OUT = 45,
  B_EMPTY1 = 46, B_EMPTYQ = 49, B_X = 53, B_EMPTY3 = 57,
  B_NUM = 63
};
constexpr int PRE = 3;
#define LN_PF 99
#define LN_GO 5
#define PFW 9
#define PFX 9
#define PFKV 0
#define SYNC3 0
#define SYNC3A 5
#define SYNC3W 6
#define CTX_ST "st.global.cs.v4.u32"
#define PF3 0
#define PD3 7
#define PFF 0
#define PWAIT mbar_wait_c
#define GRAB0 4
#define SIDE_NS 400
#define REL_AT 3
#define STARTV 2
#define SET_NS 40
#define WRAP 16 - j
#define EP1 3
#define MASKV 0
#define PACE 0
#define TRIMS 1
#define TRIMPV 1
#define KTEST 1
#define DELAY0 1
#define AWAIT mbar_wait_c
#define KWAIT mbar_wait_c
#define PFJ 16
#define PFQ 3
#define PFP 1
#define PFQ0 4
#define PFP0 5
#define PUT0 2
#define PUTD 2
#define NOFFN0 0
#define WEF 1
#define OUTU 1
#define YDLY 800
#define YDLY0 1500
#define PDLY 250
#define KV_FIRST 1
constexpr int WIN = 6;
constexpr int NIT = 64;
constexpr int NLATE = (8 - WIN) / 2;
constexpr int IT_WD = NIT + NLATE, OFF_SCR = r3((NIT + NLATE + 2) % 6);
#define PF_KB 52
#define PF_CLK 500
#define SET_KB 44
constexpr int OUT_UNROLL = OUTU;
struct Params {
  CUtensorMap xn, ckv, wq, wk, wv, kv_ld, ctx_ld, wo, x, wd, wg, wu;
};

__global__ void __cluster_dims__(2, 1, 1) __launch_bounds__(384, 1)
fused_kernel(const __grid_constant__ Params p, const __nv_bfloat16* __restrict__ x, const __nv_bfloat16* __restrict__ wq,
             const __nv_bfloat16* __restrict__ w_r, const __nv_bfloat16* __restrict__ wgate, const __nv_bfloat16* __restrict__ wup,
             __nv_bfloat16* __restrict__ out, uint32_t zero) {
  extern __shared__ __align__(1024) uint8_t sp[];
  const uint32_t sb = s2u(sp);
  const uint32_t bar = sb + OFF_BAR;
  auto B = [&](int i) { return bar + 8 * i; };
  const int tid = threadIdx.x, warp = __shfl_sync(~0u, tid >> 5, 0), wg = warp >> 2, lane = tid & 31;
  const int cta = blockIdx.x, rank = cta & 1, cl = cta >> 1;
  const int mp = cl < 4 ? 1 : (cl < 36 ? (cl & 7) : (0x3207654 >> (4 * ((cl - 36) % 7))) & 7);
  const int gq = cl < 4 ? 4 + cl : (cl < 36 ? (cl - 4) >> 3 : 4 + (cl - 36) / 7);
  const int mt = 2 * mp + rank;
  const int qa = 15 - gq;
  const int ta = gq ? gq : 15, tb = 15 - ta;
  const int rid = mt * 8 + gq;
  const int fid = mt * 7 + gq - NOFFN0;
  const bool ffn = NOFFN0 ? gq > 0 : gq < 7;
  TL(0, 0, warp == 4);
  auto load_pre = [&](int kb) {
    e_expect(B(B_FULL1 + kb), 3 * UNIT);
    tma_ld2(sb + kv_a(kb), &p.ckv, B(B_FULL1 + kb), kb * 64, mt * 128);
    tma_ld3(sb + kv_b(kb) + rank * UNIT, &p.wk, B(B_FULL1 + kb), 0, kb * 64, (gq + KV_FIRST * 8) * 4 + rank * 2);
    tma_ld3(sb + kv_b(kb) + UNIT - rank * UNIT, &p.wk, B(B_FULL1 + kb), 0, kb * 64, (gq + KV_FIRST * 8) * 4 + 2 - rank * 2);
  };
  if (warp == 0) {
    e_init(B(B_FULL1), 1);
    asm volatile("fence.mbarrier_init.release.cluster;" ::: "memory");
    load_pre(0);
#pragma unroll
    for (int kb = 1; kb < PRE; kb++) e_init(B(B_FULL1 + kb), 1);
  } else {
#pragma unroll 1
    for (int i = PRE - 1 + warp; i < B_NUM; i += 11) e_init(B(i), i >= B_EMPTY1 ? 16 : (i >= B_KE ? 8 : (i == B_WR ? 2 : 1)));
  }
  asm volatile("fence.mbarrier_init.release.cluster;" ::: "memory");
  cluster_arrive();
  if (wg == 0) {
    reg_dealloc<40>();
    uint4* const xr = g_xr + rid * XR_SIZE;
    if (warp == 0) {
#pragma unroll 1
      for (int kb = STARTV ? 1 : 0; kb < PRE; kb++) load_pre(kb);
      if (mt >= 2 * PRE) tma_pf3(&p.wk, 0, (mt >> 1) * 64, (gq + KV_FIRST * 8) * 4 + (mt & 1) * 2);
      if (gq >= PRE) tma_pf2(&p.ckv, gq * 64, mt * 128);
      prefetch_tm(&p.wv); prefetch_tm(&p.wq); prefetch_tm(&p.xn); prefetch_tm(&p.kv_ld);
    }
    __syncwarp();
    cluster_wait();
    auto side_piece = [&](int c, int piece) {
      const uint32_t fb = B(B_WF + (c & 1));
      if (piece == 0) e_expect(fb, UNIT);
      tma_ld2(sb + OFF_STG + (c & 1) * UNIT + piece * 4096, (piece & 2) ? &p.wg : &p.wu, fb, fid * 32, c * 128 + (piece & 1) * 64);
    };
    if (warp == 0) {
      {
        int st = 0; uint32_t ph = 1;
#pragma unroll 1
        for (int i = 0; i < 32; i++) {
          const int t = i >> 3, kb = i & 7;
          if (i >= PRE) {
            const uint32_t fb = B(B_FULL1 + st);
            KWAIT(B(B_EMPTY1 + st), ph);
            e_expect(fb, t == 0 ? 3 * UNIT : 2 * UNIT);
            if (t == 0) tma_ld2(sb + kv_a(kb), &p.ckv, fb, kb * 64, mt * 128);
            tma_ld3_mc(sb + kv_b(st) + rank * UNIT, (t & 1) ? &p.wv : &p.wk, fb, 0, kb * 64, (gq + ((t >> 1) ^ KV_FIRST) * 8) * 4 + rank * 2, 3);
          }
          if (i == LN_PF || i == LN_PF + 1) l2_prefetch(x + (size_t)cta * 16 * DM + (i - LN_PF) * 8 * DM, 16384);
          if (i == LN_GO) e_arrive(B(B_LNGO));
          if (kb == 0 && t < 3) tma_pf3((t & 1) ? &p.wk : &p.wv, 0, (mt >> 1) * 64, (gq + (((t + 1) >> 1) ^ KV_FIRST) * 8) * 4 + (mt & 1) * 2);
          if (kb < 2 && t == 3) tma_pf3(&p.wq, 0, (gq + 8 * kb) * 64, mt * 2);
          if (++st == 3) { st = 0; ph ^= 1; }
        }
        prefetch_tm(&p.ctx_ld); prefetch_tm(&p.wo); prefetch_tm(&p.wd); prefetch_tm(&p.x); prefetch_tm(&p.wg); prefetch_tm(&p.wu);
        PWAIT(B(B_DEP + 0), 0);
        uint32_t kpar = 7, vpar = 3;
        auto load_aw = [&](int kb, int head) {
          const uint32_t d = sb + q_aw(kb & 3), fb = B(B_FULLQ + (kb & 3));
          tma_ld2_mc(d + rank * 8192, &p.xn, fb, kb * 64, ta * 128 + rank * 64, 3);
          tma_ld3(d + UNIT, &p.wq, fb, 0, kb * 64, head * 2);
        };
        auto load_b = [&](int kb, uint32_t fb) { tma_ld2_mc(sb + q_b(kb & 3) + rank * 8192, &p.xn, fb, kb * 64, tb * 128 + rank * 64, 3); };
        auto load3 = [&](int kb, int s) {
          const uint32_t d = sb + r3(s), fb = B(B_FULL3 + s);
          e_expect(fb, SLOT);
          tma_ld2(d, &p.ctx_ld, fb, kb * 64, mt * 128);
          tma_ld3_mc(d + UNIT + rank * 8192, &p.wo, fb, 0, kb * 64, gq * 2 + rank, 3);
        };
#pragma unroll 1
        for (int half = 0; half < 2; half++) {
          const int head = mt + 16 * half;
#pragma unroll 1
          for (int kb = 2 * half; kb < 16; kb++) {
            if (kb >= 4) KWAIT(B(B_EMPTYQ + (kb & 3)), ((kb >> 2) & 1) ^ 1);
            else if (half) PWAIT(B(B_X + 2), 0);
            else if (kb > 0) PWAIT(B(B_EMPTY1 + (kb + 1) % 3), kb == 1);
            e_expect(B(B_FULLQ + (kb & 3)), 3 * UNIT);
            load_aw(kb, head);
            load_b(kb, B(B_FULLQ + (kb & 3)));
          }
          PWAIT(B(B_DEP + 1 + half), 0);
          tma_pf3(&p.kv_ld, 0, 0, head * 2);
          auto load_v = [&](int j) {
            const int r = j & 1;
            AWAIT(B(B_VE + r), (vpar >> r) & 1);
            vpar ^= 1 << r;
            e_expect(B(B_VF + r), SLOT);
            tma_ld3(sb + v_slot(j), &p.kv_ld, B(B_VF + r), 0, SEQ + (j > qa ? WRAP : j) * 128, head * 2);
          };
          int r = 0;
#pragma unroll 1
          for (int j = 0; j < 17; j++) {
            if (j < 2) PWAIT(B(B_EMPTYQ + j), 1);
            if (j == 2) PWAIT(B(B_KE), kpar & 1);
            AWAIT(B(B_KE + r), (kpar >> r) & 1);
            kpar ^= 1 << r;
            e_expect(B(B_KF + r), SLOT);
            tma_ld3(sb + k_slot(j, r), &p.kv_ld, B(B_KF + r), 0, (j > qa ? WRAP : j) * 128, head * 2);
            if (++r == 3) r = 0;
            if (j == 2) PWAIT(B(B_EMPTYQ + 3), 1);
            if (j != 1) load_v(j ? j - 1 : 0);
            if (j == PFJ) {
              if (half == 0) {
                if (PFQ & 1) tma_pf3(&p.wq, 0, (PFQ0 + gq) * 64, (mt + 16) * 2);
                if (PFQ & 2) tma_pf2(&p.xn, (PFQ0 + (mp & 3)) * 64, ((mp & 4) ? qa : gq) * 128 + rank * 64);
              } else {
                PWAIT(B(B_DEP + 3), 0);
                if (PFP & 1) tma_pf3(&p.wo, 0, (PFP0 + mp) * 64, gq * 2 + rank);
                if (PFP & 2) tma_pf2(&p.ctx_ld, (PFP0 + gq) * 64, mt * 128);
              }
            }
            if (half == 0) {
            } else if (ffn && j >= 5 && j < 13) {
              side_piece((j - 5) >> 2, (j - 5) & 3);
            }
          }
          PWAIT(B(B_X + 0), half);
          if (half == 0) {
            for (int kb = 0; kb < 2; kb++) { e_expect(B(B_FULLQ + kb), 2 * UNIT); load_aw(kb, mt + 16); }
          } else {
            load3(0, 0);
          }
          PWAIT(B(B_X + 1), half);
          if (half) load3(1, 1);
          load_v(16);
          if (gq == 0) PWAIT(B(B_X + 2), half);
          if (half == 0) { e_expect(B(B_FULLB), 2 * UNIT); load_b(0, B(B_FULLB)); load_b(1, B(B_FULLB)); }
        }
        st = 2; ph = 1;
#pragma unroll 1
        for (int kb = 2; kb < 64; kb++) {
          if (kb == 32) PWAIT(B(B_DEP + 4), 0);
          if (kb >= 6) PWAIT(B(B_EMPTY3 + st), ph);
          else if (kb == 3 || kb == 5) PWAIT(B(B_X + (kb + 1) / 2), 1);
          load3(kb, st);
          if (++st == 6) { st = 0; ph ^= 1; }
          if (kb == PF_KB) e_arrive(B(B_PF));
          if (kb == SET_KB) e_arrive(B(B_SET));
          if (kb == 58) l2_prefetch(xr, XR_CAND * 16);
        }
        if (ffn) {
#pragma unroll 1
          for (int j = 0; j < NLATE + 2; j++) {
            PWAIT(B(B_EMPTY3 + st), ph);
            const uint32_t d = sb + r3(st), fb = B(B_FULL3 + st);
            e_expect(fb, SLOT);
            if (j < NLATE) {
#pragma unroll 1
              for (int h = 0; h < 8; h++) tma_ld2(d + h * 4096, (h & 2) ? &p.wg : &p.wu, fb, fid * 32, (WIN + 2 * j + (h >> 2)) * 128 + (h & 1) * 64);
            } else {
              tma_ld3(d, &p.wd, fb, 0, fid * 32, 8 * (j - NLATE));
            }
            if (++st == 6) { st = 0; ph ^= 1; }
          }
        }
        const uint4* kp = g_xr + ((lane >> 1) * 8 + gq) * XR_SIZE + XR_KEY + (lane & 1) * 2;
        PWAIT(B(B_OUT), 0);
        uint4 kv[2];
        poll_chunks(kv, kp, 1);
        const uint32_t a1 = max(kv[0].x, kv[0].z), a2 = max(min(kv[0].x, kv[0].z), max(kv[0].y, kv[0].w));
        const uint32_t b1 = max(kv[1].x, kv[1].z), b2 = max(min(kv[1].x, kv[1].z), max(kv[1].y, kv[1].w));
        const uint32_t k1 = max(a1, b1), k2 = max(min(a1, b1), max(a2, b2));
        const uint32_t m1 = __reduce_max_sync(~0u, k1);
        const uint32_t m2 = __reduce_max_sync(~0u, k1 == m1 ? k2 : k1);
        if (lane == 0) {
          *reinterpret_cast<uint2*>(sp + OFF_MISC) = make_uint2(m1, m2);
          mbar_arrive(B(B_OUT2));
        }
        if (rid == 127) { g_cnt[lane] = 0; g_cnt[32 + lane] = 0; }
      }
    } else {
      if (warp >= 2) {
#pragma unroll 1
        for (int i = tid - 64; i < XR_CAND; i += 64) xr[i] = make_uint4(~0u, ~0u, ~0u, ~0u);
        if (warp == 2) { __syncwarp(); if (lane == 0) mbar_arrive(B(B_WR)); }
      }
      if (warp == 3) {
        float ws = 0.f;
#pragma unroll
        for (int j = 0; j < 4; j++) {
          const uint4 q = __ldg(reinterpret_cast<const uint4*>(w_r) + j * 32 + lane);
          ws += bf_lo(q.x) + bf_hi(q.x) + bf_lo(q.y) + bf_hi(q.y) + bf_lo(q.z) + bf_hi(q.z) + bf_lo(q.w) + bf_hi(q.w);
        }
#pragma unroll
        for (int o = 16; o; o >>= 1) ws += __shfl_xor_sync(~0u, ws, o);
        uint2* tab = reinterpret_cast<uint2*>(sp + OFF_MISC + 512);
        tab[lane] = make_uint2(0x3F803F80u, 0x3F803F80u);
        tab[32 + lane] = __ldg(reinterpret_cast<const uint2*>(w_r + gq * 128) + lane);
        if (lane == 0) *reinterpret_cast<float*>(sp + OFF_MISC + 1024) = ws;
        __syncwarp();
        if (lane == 0) mbar_arrive(B(B_WR));
      }
      __syncwarp();
      mbar_wait_u(B(B_LNGO), 0);
#pragma unroll 1
      for (int r = warp == 2 ? 0 : (warp + 1) >> 1; r < 16; r += 3) {
        const uint4* src = reinterpret_cast<const uint4*>(x + (size_t)(cta * 16 + r) * DM) + lane;
        uint4 v[4];
#pragma unroll
        for (int j = 0; j < 4; j++) v[j] = __ldg(src + j * 32);
        float a0 = 0.f, a1 = 0.f, b0 = 0.f, b1 = 0.f;
#pragma unroll
        for (int j = 0; j < 4; j++) {
          const uint32_t u[4] = {v[j].x, v[j].y, v[j].z, v[j].w};
#pragma unroll
          for (int i = 0; i < 4; i++) { const float a = bf_lo(u[i]), b = bf_hi(u[i]); a0 += a; a1 += b; b0 = fmaf(a, a, b0); b1 = fmaf(b, b, b1); }
        }
        a0 += a1; b0 += b1;
#pragma unroll
        for (int o = 16; o; o >>= 1) { a0 += __shfl_xor_sync(~0u, a0, o); b0 += __shfl_xor_sync(~0u, b0, o); }
        const float mean = a0 * (1.f / DM);
        float mb, inv;
        ln_round(mean, fmaxf(fmaf(b0, 1.f / DM, -mean * mean), 0.f), mb, inv);
        const uint32_t nm2 = pack_bf16(-mb, -mb);
        uint4* dst = reinterpret_cast<uint4*>(g_xn + (size_t)(cta * 16 + r) * DM) + lane;
#pragma unroll
        for (int j = 0; j < 4; j++)
          dst[j * 32] = make_uint4(ln_apply(v[j].x, nm2, inv), ln_apply(v[j].y, nm2, inv), ln_apply(v[j].z, nm2, inv), ln_apply(v[j].w, nm2, inv));
      }
      __syncwarp();
      if (lane == 0) {
        fence_gpu();
        red_add(&g_cnt[C_LN + (cta >> 3)], 1);
        TL(0, 20 + warp, true);
        if (warp == 3) {
          spin_until_ge<true>(&g_cnt[C_LN + gq], 24);
#pragma unroll 1
          for (int i = 0; i < 5; i++) {
            const int c = i == 0 ? C_LN + qa : (i < 3 ? C_KV + (i - 1) * 8 + mp : C_CTX + (i - 3) * 16 + mt);
            spin_until_ge<true>(&g_cnt[c], i == 0 ? 24 : 16);
            fence_async_all();
            mbar_arrive(B(B_DEP + i));
          }
        } else if (warp == 1) {
          mbar_wait(B(B_WR), 0);
#pragma unroll 1
          for (int i = 0; i < 6; i++) {
            const int c = i < 2 ? C_KV + gq + (i ^ KV_FIRST) * 8 : C_CTX + ((i - 2) >> 1) * 16 + ((i & 1) ? tb : ta);
            mbar_wait(B(B_PUB + i), 0);
            fence_gpu();
            red_add(&g_cnt[c], 1);
          }
        }
      }
      __syncwarp();
      if (warp == 2) {
#pragma unroll 1
        for (int c = 2; c < WIN + 2; c++) {
          if (c == WIN + 1) {
            mbar_wait_u(B(B_SET), 0);
#pragma unroll 1
            for (int i = XR_CAND + lane; i < XR_SIZE; i += 32) { xr[i] = make_uint4(~0u, ~0u, ~0u, ~0u); __nanosleep(SET_NS); }
            __syncwarp();
          }
          mbar_wait_u(B(B_WE + (c & 1)), ((c >> 1) & 1) ^ 1);
          if (c >= WIN) {
            e_expect(B(B_WF + (c & 1)), UNIT);
            tma_ld3(sb + OFF_STG + (c & 1) * UNIT, &p.x, B(B_WF + (c & 1)), 0, mt * 128 + (c & 1) * 64, gq * 2);
          } else if (ffn) {
#pragma unroll 1
            for (int i = 0; i < 4; i++) { side_piece(c, i); __nanosleep(SIDE_NS); }
          }
        }
        if (lane == 0) { fence_gpu(); mbar_arrive(B(B_SET2)); }
        __syncwarp();
        mbar_wait_u(B(B_PF), 0);
        uint32_t t0;
        asm volatile("mov.u32 %0, %%clock;" : "=r"(t0));
        constexpr int NF = (8 - WIN) * 4;
#pragma unroll 1
        for (int i = 0; i < NF; i++) {
          const char* a = (const char*)(((i & 2) ? wgate : wup) + (size_t)((WIN + (i >> 2)) * 128 + cta) * FF) + min((i & 1) * 32 + lane, 55) * 128;
          asm volatile("prefetch.global.L2 [%0];" ::"l"(a));
#pragma unroll 1
          for (int n = 0; n < 64; n++) {
            __nanosleep(100);
            uint32_t t;
            asm volatile("mov.u32 %0, %%clock;" : "=r"(t));
            if (t - t0 >= (uint32_t)(i + 1) * PF_CLK) break;
          }
        }
      }
      __syncwarp();
      mbar_wait_u(B(B_OUT), 0);
#pragma unroll OUT_UNROLL
      for (int i = warp - 1; i < 66; i += 3) {
        const int row = 2 * i + (lane >> 4);
        const uint2 rs = *reinterpret_cast<const uint2*>(sp + OFF_RSTAT + (row & 127) * 8);
        const uint4 v = lds128(sb + OFF_STG + ((row >> 6) & 1) * 16384 + ((lane & 15) >> 3) * 8192 + (row & 63) * 128 + (((lane ^ row) & 7) << 4));
        const float inv = __uint_as_float(rs.y);
        if ((int)rs.y >= 0 && row < 128)
          *reinterpret_cast<uint4*>(out + (size_t)(mt * 128 + row) * DM + gq * 128 + (lane & 15) * 8) =
              make_uint4(hadd2_bf(v.x, ln_apply(v.x, rs.x, inv)), hadd2_bf(v.y, ln_apply(v.y, rs.x, inv)),
                         hadd2_bf(v.z, ln_apply(v.z, rs.x, inv)), hadd2_bf(v.w, ln_apply(v.w, rs.x, inv)));
      }
      TL(2, 25, warp == 1);
    }
    __syncwarp();
    cluster_arrive();
    cluster_wait();
  } else {
    reg_alloc<232>();
    cluster_wait();
    const int w = wg - 1, cw = warp - 4, ct = tid - 128;
    const uint32_t stg = sb + OFF_STG + w * 16384 + (cw & 3) * 2048;
    auto publish = [&](int i) { __syncwarp(); e_arrive(B(B_PUB + i)); };
    auto release2 = [&](uint32_t b, bool cond = true) { mbar_arrive_both(b, lane, cond); };
    AtState s;
    const uint32_t dA = mk_desc(sb + w * 8192, 16);
    const uint32_t dW = mk_desc(sb, 8192);
    auto mma_kb = [&](float (&d)[64], uint32_t a, uint32_t b, int accum) {
      static_for<4>([&](auto k) { mma_n128_ss<1, k * 32, k * 2048>(d, dA + (a >> 4), dW + (b >> 4), k == 0 ? accum : 1); });
    };
    auto mma_kc = [&](float (&d)[64], auto a, auto b, int accum) {
      static_for<4>([&](auto k) { mma_n128_ss<1, decltype(a)::value + k * 32, decltype(b)::value + k * 2048>(d, dA, dW, k == 0 ? accum : 1); });
    };
    auto issue_q = [&](int kb, auto accum) {
      const int st = kb & 3;
      mbar_wait_c(B(B_FULLQ + st), (kb >> 2) & 1);
      wg_fence();
      mma_kb(s.S, q_aw(st), q_aw(st) + UNIT, accum);
      wg_commit();
      if (accum) {
        wg_wait<1>();
        release2(B(B_EMPTYQ + ((kb - 1) & 3)));
        wg_fence();
      }
      mma_kb(s.O, q_b(st), q_aw(st) + UNIT, accum);
      wg_commit();
    };
    {
      uint4 pk[16];
      __nv_bfloat16* pdst = g_kv;
      auto put = [&](int i) { __stcs(reinterpret_cast<uint4*>(pdst + (i & 1) * 8 * NQ + (i >> 1) * 32), pk[i]); };
      float acc1[128];
      TL(0, 1, warp == 4);
      int st = 0; uint32_t ph = 0;
      auto issue = [&](int kb, int accum) {
        mbar_wait_c(B(B_FULL1 + st), ph);
        wg_fence();
        static_for<4>([&](auto k) { mma_n256_ss<1, k * 32, k * 2048>(acc1, dA + (kv_a(kb) >> 4), dW + (kv_b(st) >> 4), k == 0 ? accum : 1); });
        wg_commit();
      };
#pragma unroll 1
      for (int t = 0; t < 4; t++) {
        issue(0, 0);
        TL(0, 2 + 2 * t, warp == 4);
        if (t > 0) { put(0); put(1); }
        int prev = st;
        if (++st == 3) { st = 0; ph ^= 1; }
#pragma unroll 1
        for (int kb = 1; kb < 8; kb++) {
          if (kb == 7 && w == 1) bar_sync(5, 256);
          issue(kb, 1);
          if (kb == 7 && w == 0) bar_arrive(5, 256);
          if (t > 0) {
#pragma unroll
            for (int i = 1; i < 8; i++) if (kb == i) { put(2 * i); put(2 * i + 1); }
            if (kb == 7 && t == 2) publish(0);
          }
          wg_wait<1>();
          TK(24 + t * 8 + kb - 1);
          release2(B(B_EMPTY1 + prev));
          prev = st;
          if (++st == 3) { st = 0; ph ^= 1; }
        }
        pdst = g_kv + (size_t)((t & 1) * SEQ + mt * 128 + cw * 16 + (lane >> 2)) * NQ + (gq + ((t >> 1) ^ KV_FIRST) * 8) * 256 + (lane & 3) * 8;
        wg_wait<0>();
        TK(24 + t * 8 + 7);
        fence_regs(acc1);
        release2(B(B_EMPTY1 + prev));
        TL(0, 3 + 2 * t, warp == 4);
#pragma unroll
        for (int a = 0; a < 8; a++)
#pragma unroll
          for (int h = 0; h < 2; h++)
            pk[2 * a + h] = make_uint4(pack_bf16(acc1[16 * a + 2 * h], acc1[16 * a + 2 * h + 1]), pack_bf16(acc1[16 * a + 4 + 2 * h], acc1[16 * a + 5 + 2 * h]),
                                       pack_bf16(acc1[16 * a + 8 + 2 * h], acc1[16 * a + 9 + 2 * h]), pack_bf16(acc1[16 * a + 12 + 2 * h], acc1[16 * a + 13 + 2 * h]));
      }
      issue_q(0, IC<0>{});
      TL(0, 10, warp == 4);
      put(0); put(1);
#pragma unroll 1
      for (int kb = 1; kb < 8; kb++) {
        issue_q(kb, IC<1>{});
        TK(66 + kb - 1);
#pragma unroll
        for (int i = 1; i < 8; i++) if (kb == i) { put(2 * i); put(2 * i + 1); }
      }
      publish(1);
      TL(0, 11, warp == 4);
    }
    __nv_bfloat16* cdst;
    uint32_t redo = 0;
    auto put_ctx = [&](int i, bool cond) {
      asm volatile("{\n.reg .pred p;\nsetp.ne.u32 p, %5, 0;\n@p " CTX_ST " [%0], {%1,%2,%3,%4};\n}" ::"l"(cdst + (i & 1) * 8 * NQ + (i >> 1) * 32),
                   "r"(s.P[4 * i]), "r"(s.P[4 * i + 1]), "r"(s.P[4 * i + 2]), "r"(s.P[4 * i + 3]), "r"((uint32_t)(cond && !(redo & 2))) : "memory");
    };
    {
      const int wrow = cw * 16;
      const uint32_t dK = mk_desc(sb, 16), dV = mk_desc(sb, 16384);
      uint32_t kph = 0, vph = 0;
      auto q_store = [&](const float (&d)[64]) {
        const int r0 = lane >> 2;
        const uint32_t a = sb + SLOT + (wrow + r0) * 128 + (((lane & 3) ^ (((r0 & 1) << 2) | (r0 >> 1))) << 4);
#pragma unroll
        for (int i = 0; i < 8; i++) {
          const float* o = d + 16 * (i >> 1) + 2 * (i & 1);
          asm volatile("st.shared.v4.u32 [%0], {%1,%2,%3,%4};" ::"r"((a ^ ((i & 2) << 5)) + (i >> 2) * UNIT + (i & 1) * 1024),
                       "r"(pack_bf16(o[0] * AT_C, o[1] * AT_C)), "r"(pack_bf16(o[4] * AT_C, o[5] * AT_C)),
                       "r"(pack_bf16(o[8] * AT_C, o[9] * AT_C)), "r"(pack_bf16(o[12] * AT_C, o[13] * AT_C)) : "memory");
        }
        __syncwarp();
      };
      auto q_load = [&](auto k0, auto k1) {
        const uint32_t a = sb + SLOT + (wrow + (lane & 15)) * 128 + (((lane >> 4) ^ (((lane & 1) << 2) | ((lane >> 1) & 3))) << 4);
#pragma unroll
        for (int k = k0; k < k1; k++)
          asm volatile("ldmatrix.sync.aligned.m8n8.x4.shared.b16 {%0,%1,%2,%3}, [%4];"
                       : "=r"(s.Q[4 * k]), "=r"(s.Q[4 * k + 1]), "=r"(s.Q[4 * k + 2]), "=r"(s.Q[4 * k + 3]) : "r"((a ^ ((k & 3) << 5)) + (k >> 2) * UNIT) : "memory");
      };
      auto q_load_if = [&](auto k, bool cond, float after) {
        const uint32_t a = sb + SLOT + (wrow + (lane & 15)) * 128 + (((lane >> 4) ^ (((lane & 1) << 2) | ((lane >> 1) & 3))) << 4);
        asm volatile("{\n.reg .pred p;\nsetp.ne.u32 p, %5, 0;\n@p ldmatrix.sync.aligned.m8n8.x4.shared.b16 {%0,%1,%2,%3}, [%4];\n}"
                     : "+r"(s.Q[4 * k]), "+r"(s.Q[4 * k + 1]), "+r"(s.Q[4 * k + 2]), "+r"(s.Q[4 * k + 3])
                     : "r"((a ^ ((k & 3) << 5)) + (k >> 2) * UNIT + (__float_as_uint(after) >> 31)), "r"((uint32_t)cond) : "memory");
      };
      auto issue_s = [&](uint32_t off) {
        static_for<8>([&](auto k) { mma_n128_rs<0, (k >> 2) * 16384 + (k & 3) * 32>(s.S, s.Q + 4 * k, dK + (off >> 4), k != 0); });
        wg_commit();
      };
      auto issue_pv = [&](int jv, int accum, bool upper) {
        mbar_wait_c(B(B_VF + (jv & 1)), (vph >> (jv & 1)) & 1);
        vph ^= 1 << (jv & 1);
        wg_fence();
        static_for<4>([&](auto k) { mma_n128_rs<1, k * 2048>(s.O, s.P + 4 * k, dV + (v_slot(jv) >> 4), k == 0 ? accum : 1); });
        wg_commit();
        if (!TRIMPV || upper) {
          if (TRIMPV) wg_fence();
          static_for<4>([&](auto k) { mma_n128_rs<1, (k + 4) * 2048>(s.O, s.P + 16 + 4 * k, dV + (v_slot(jv) >> 4), 1); });
          wg_commit();
        } else {
          asm volatile("wgmma.fence.sync.aligned;\nwgmma.commit_group.sync.aligned;" ::: "memory");
        }
      };
      if (w == 1) bar_arrive(1, 256);
#pragma unroll 1
      for (int half = 0; half < 2; half++) {
        const int head = mt + 16 * half;
        redo = 0;
        float inv[2];
        auto ep_prep = [&]() {
          float l0 = s.l[0] + s.l[1], l1 = s.l[2] + s.l[3];
          l0 += __shfl_xor_sync(~0u, l0, 1); l1 += __shfl_xor_sync(~0u, l1, 1);
          l0 += __shfl_xor_sync(~0u, l0, 2); l1 += __shfl_xor_sync(~0u, l1, 2);
          asm("rcp.approx.ftz.f32 %0, %1;" : "=f"(inv[0]) : "f"(l0));
          asm("rcp.approx.ftz.f32 %0, %1;" : "=f"(inv[1]) : "f"(l1));
          return __any_sync(~0u, !(fminf(l0, l1) >= L_MIN && l0 + l1 <= L_MAX));
        };
        auto ep_out = [&](auto i0, auto i1) {
          __nv_bfloat16* dst = g_ctx + (size_t)(ta * 128 + wrow + (lane >> 2)) * NQ + head * 128 + (lane & 3) * 8;
#pragma unroll
          for (int i = i0; i < i1; i++) {
            const float* o = s.O + 16 * (i >> 1) + 2 * (i & 1);
            const float c = inv[i & 1];
            asm volatile(CTX_ST " [%0], {%1,%2,%3,%4};" ::"l"(dst + (i & 1) * 8 * NQ + (i >> 1) * 32), "r"(pack_bf16(o[0] * c, o[1] * c)),
                         "r"(pack_bf16(o[4] * c, o[5] * c)), "r"(pack_bf16(o[8] * c, o[9] * c)), "r"(pack_bf16(o[12] * c, o[13] * c)) : "memory");
          }
        };
        auto ep_rest = [&]() {
          ep_out(IC<EP1>{}, IC<8>{});
          if (!__any_sync(~0u, redo)) publish(2 + 2 * half);
          fence_regs(s.O);
        };
#pragma unroll 1
        for (int kb = 8; kb < 14; kb++) {
          issue_q(kb, IC<1>{});
          TK(66 + half * 24 + kb - 1);
        }
        TL(1, 20 * half + 0, warp == 4);
        mbar_wait_c(B(B_FULLQ + 2), 1);
        mbar_wait_c(B(B_FULLQ + 3), 1);
        bar_sync(1 + w, 256);
        wg_fence();
        mma_kc(s.S, IC<q_aw(2)>{}, IC<q_aw(2) + UNIT>{}, 1);
        wg_commit();
        wg_wait<1>();
        TK(66 + half * 24 + 13);
        release2(B(B_EMPTYQ + 1));
        wg_fence();
        mma_kc(s.S, IC<q_aw(3)>{}, IC<q_aw(3) + UNIT>{}, 1);
        wg_commit();
        bar_arrive(2 - w, 256);
        bar_sync(6 + w, 128);
        wg_wait<0>();
        TK(66 + half * 24 + 14);
        fence_regs(s.S);
        q_store(s.S);
        q_load(IC<0>{}, IC<8>{});
        TL(1, 20 * half + 1, warp == 4);
        mbar_wait_c(B(B_KF), kph & 1);
        kph ^= 1;
        bar_sync(1 + w, 256);
        fence_regs(s.S); fence_regs(s.O); fence_regs(s.Q);
        wg_fence();
        issue_s(k_slot(0, 0));
        mma_kc(s.O, IC<q_b(2)>{}, IC<q_aw(2) + UNIT>{}, 1);
        mma_kc(s.O, IC<q_b(3)>{}, IC<q_aw(3) + UNIT>{}, 1);
        wg_commit();
        bar_arrive(2 - w, 256);
        wg_wait<1>();
        fence_regs(s.S);
        e_arrive(B(B_KE));
        s.l[0] = s.l[1] = s.l[2] = s.l[3] = 0.f;
        at_exp<0, 48>(s);
        at_pack<0, 22>(s);
        sched_fence();
        wg_wait<0>();
        fence_regs(s.O); fence_regs(s.Q);
        release2(B(B_EMPTYQ + 2)); release2(B(B_EMPTYQ + 3));
        at_exp<48, 64>(s);
        at_pack<22, 32>(s);
        q_store(s.O);
        TL(1, 20 * half + 2, warp == 4);
        int kr = 1;
        bool kok = false;
        inv[0] = inv[1] = 0.f;
        const int db = gq ? qa : 16;
#pragma unroll 1
        for (int j = 1; j < 17; j++) {
          const bool diag = j == ta || j == db;
          TC(w, j + 17 * half, 0);
          if (!kok) mbar_wait_c(B(B_KF + kr), (kph >> kr) & 1);
          kph ^= 1 << kr;
          if (j == ta + 2) ep_out(IC<0>{}, IC<EP1>{});
          bar_sync(1 + w, 256);
          TC(w, j + 17 * half, 2);
          fence_regs(s.S); fence_regs(s.O); fence_regs(s.P); fence_regs(s.Q);
          const uint32_t ke = B(B_KE + kr), ko = k_slot(j, kr);
          if (++kr == 3) kr = 0;
          auto issue_rest = [&](auto trimmed) {
            TC(w, j + 17 * half, 1);
            if (j == ta + 1) {
              if (ep_prep()) redo = 1;
              s.l[0] = s.l[1] = s.l[2] = s.l[3] = 0.f;
            }
            if (!trimmed && j == ta + 2) ep_rest();
            TC(w, j + 17 * half, 3);
            issue_pv(j - 1, j != 1 && j != ta + 2, w == 1 || (j != ta + 1 && j != db + 1));
            bar_arrive(2 - w, 256);
          };
          auto s_done = [&]() {
            wg_wait<2>();
            TC(w, j + 17 * half, 4);
            fence_regs(s.S); fence_regs(s.Q);
            e_arrive(ke);
            release2(B(B_X + j - 14), j == 14 || j == 15);
          };
          auto pv_half = [&]() { sched_fence(); wg_wait<1>(); fence_regs(s.P); };
          auto pv_done = [&]() {
            sched_fence();
            wg_wait<0>();
            fence_regs(s.O); fence_regs(s.P);
            e_arrive(B(B_VE + ((j - 1) & 1)));
            release2(B(B_X + 2), j == 16);
            kok = KTEST && mbar_test(B(B_KF + kr), (kph >> kr) & 1);
          };
          if (diag && w == 0) {
            wg_fence();
            static_for<8>([&](auto k) { mma_n64_rs<(k >> 2) * 16384 + (k & 3) * 32>(s.S, s.Q + 4 * k, dK + (ko >> 4), k != 0); });
            wg_commit();
            issue_rest(IC<1>{});
            s_done();
            at_mask<0>(s, wrow, lane);
            if (DELAY0 == 1) pv_half();
            if (DELAY0 == 2) pv_done();
            static_for<8>([&](auto k) {
              at_exp<4 * k, 4 * k + 4, 32>(s);
              q_load_if(k, j == ta, s.S[4 * k]);
              if (DELAY0 == 0 && k == 3) pv_half();
            });
            at_pack<0, 16>(s);
            if (DELAY0 < 2) pv_done();
          } else {
            wg_fence();
            issue_s(ko);
            issue_rest(IC<0>{});
            if (!diag) {
              s_done();
              at_exp<0, 4 * SP1>(s);
              pv_half();
              at_exp<4 * SP1, 4 * SP2>(s);
              at_pack<0, 16>(s);
              pv_done();
              at_exp<4 * SP2, 64>(s);
              at_pack<16, 32>(s);
            } else {
              s_done();
              at_mask<8>(s, wrow - 64, lane);
              static_for<8>([&](auto k) {
                at_exp<7 * k, 7 * k + 7>(s);
                q_load_if(k, j == ta, s.S[7 * k + 3]);
                if (k == 2) pv_half();
                if (k == 5) { at_pack<0, 16>(s); pv_done(); }
              });
              at_exp<56, 64>(s);
              at_pack<16, 32>(s);
            }
          }
          TL(1, 20 * half + 2 + j, warp == 4);
        }
        TK(84 + half * 24);
        mbar_wait_c(B(half ? B_FULL3 : B_FULLQ), 0);
        if (gq == 0) ep_out(IC<0>{}, IC<EP1>{});
        bar_sync(1 + w, 256);
        fence_regs(s.S); fence_regs(s.O); fence_regs(s.P);
        wg_fence();
        mma_kc(s.S, IC<0>{}, IC<UNIT>{}, 0);
        mbar_wait_c(B(half ? B_FULL3 + 1 : B_FULLQ + 1), 0);
        wg_fence();
        mma_kb(s.S, (2 + half) * SLOT, (2 + half) * SLOT + UNIT, 1);
        wg_commit();
        TK(85 + half * 24);
        if (gq == 0) ep_rest();
        issue_pv(16, gq != 0, w == 1 || gq != 0);
        if (w == 0 || half == 0) bar_arrive(2 - w, 256);
        TK(86 + half * 24);
        wg_wait<2>();
        release2(B(B_EMPTY3), half); release2(B(B_EMPTY3 + 1), half);
        if (ep_prep()) redo |= 2;
        sched_fence();
        wg_wait<0>();
        TK(87 + half * 24);
        fence_regs(s.S);
        fence_regs(s.O);
        e_arrive(B(B_VE));
        release2(B(B_X + 3));
        fence_regs(s.P);
        {
          uint32_t r;
          asm volatile("mov.u32 %0, %%laneid;" : "=r"(r));
          cdst = g_ctx + (size_t)(tb * 128 + wrow + (r >> 2)) * NQ + head * 128 + (r & 3) * 8;
        }
#pragma unroll
        for (int i = 0; i < 32; i++) {
          const float* o = s.O + 16 * (i >> 3) + 2 * ((i >> 2) & 1) + 4 * (i & 3);
          s.P[i] = pack_bf16(o[0] * inv[(i >> 2) & 1], o[1] * inv[(i >> 2) & 1]);
        }
        fence_regs(s.P);
        if (__builtin_expect(__any_sync(~0u, redo != 0), 0)) {
#pragma unroll
          for (int i = 0; i < 8; i++) put_ctx(i, true);
#pragma unroll 1
          for (int t = 0; t < 2; t++) {
            if (__any_sync(~0u, (redo >> t) & 1)) slow_rows(wq, head, (t ? tb : ta) * 128 + wrow, lane);
          }
          if (__any_sync(~0u, redo & 1)) publish(2 + 2 * half);
#pragma unroll
          for (int i = 0; i < 64; i++) { s.O[i] = 0.f; s.P[i >> 1] = 0; }
          redo = 2;
        }
        TL(1, 20 * half + 19, warp == 4);
        TK(88 + half * 24);
        if (half) break;
        mbar_wait_c(B(B_FULLB), 0);
        TK(89);
        fence_regs(s.O);
        wg_fence();
        mma_kc(s.O, IC<q_b(0)>{}, IC<q_aw(0) + UNIT>{}, 0);
        wg_commit();
        mma_kc(s.O, IC<q_b(1)>{}, IC<q_aw(1) + UNIT>{}, 1);
        wg_commit();
        wg_wait<1>();
        release2(B(B_EMPTYQ));
        put_ctx(0, true);
#pragma unroll 1
        for (int kb = 2; kb < 8; kb++) {
          issue_q(kb, IC<1>{});
          TK(90 + kb - 1);
#pragma unroll
          for (int i = 1; i < 8; i++) put_ctx(i, kb == (i < 7 ? i + 1 : 7));
        }
        publish(3);
      }
    }
    const int wr_ = w * 64 + (lane & 7) + (lane >> 4) * 8;
    const uint32_t wl = sb + ((lane >> 3) & 1) * 8192 + wr_ * 64 + (((cw ^ (wr_ >> 1)) & 3) << 4);
    __syncwarp();
    float (&acc)[64] = s.S;
    uint32_t wf[128];
    auto grab = [&](auto c, uint32_t off) {
#pragma unroll
      for (int m = 0; m < 4; m++)
        asm volatile("ldmatrix.sync.aligned.m8n8.x4.trans.shared.b16 {%0,%1,%2,%3}, [%4];"
                     : "=r"(wf[16 * c + 4 * m]), "=r"(wf[16 * c + 4 * m + 1]), "=r"(wf[16 * c + 4 * m + 2]), "=r"(wf[16 * c + 4 * m + 3])
                     : "r"(wl + off + m * 1024) : "memory");
    };
    {
      int st = 2, prev = 1; uint32_t ph = 0;
      auto run = [&](auto k0, auto k1, auto c) {
#pragma unroll 1
        for (int kb = k0; kb < k1; kb++) {
          mbar_wait_c(B(B_FULL3 + st), ph);
          wg_fence();
          mma_kb(acc, r3(st), r3(st) + UNIT, 1);
          wg_commit();
          wg_wait<1>();
          release2(B(B_EMPTY3 + prev), k0 != 2 || kb != 2);
          if (c >= 0 && kb == k0) {
            constexpr int f = c >= 0 ? 16 * c : 0;
            asm volatile("{\n.reg .pred p;\n.reg .b32 t;\nsetp.eq.u32 p, %1, 0;\nlop3.b32 t, %1, %2, %3, 0xE8;\nlop3.b32 t, t, %4, %5, 0xE8;\n"
                         "mad.lo.u32 t, t, %6, %0;\n@p mbarrier.arrive.shared::cta.b64 _, [t];\n}"
                         ::"r"(B(B_WE + (c & 1))), "r"(lane), "r"(wf[f]), "r"(wf[f + 4]), "r"(wf[f + 8]), "r"(wf[f + 12]), "r"(zero) : "memory");
          }
          prev = st;
          if (++st == 6) { st = 0; ph ^= 1; }
#pragma unroll
          for (int i = 0; i < 8; i++) if (PUT0 + PUTD * i >= k0 && PUT0 + PUTD * i < k1) put_ctx(i, kb == PUT0 + PUTD * i);
          if (PUT0 + PUTD * 7 >= k0 && PUT0 + PUTD * 7 < k1 && kb == PUT0 + PUTD * 7) publish(5);
          if ((kb & 7) == 7) TL(2, 2 + (kb >> 3), warp == 4);
        }
      };
      static_for<WIN>([&](auto c) {
        run(IC<c == 0 ? 2 : GRAB0 + 8 * c - 8>{}, IC<GRAB0 + 8 * c>{}, IC<c - 1>{});
        if (ffn) mbar_wait_c(B(B_WF + (c & 1)), (c >> 1) & 1);
        grab(c, OFF_STG + (c & 1) * UNIT);
      });
      run(IC<GRAB0 + 8 * WIN - 8>{}, IC<64>{}, IC<WIN - 1>{});
    }
    uint4* const xr = g_xr + (rid + zero) * XR_SIZE;
    const int r0 = lane >> 2;
    uint32_t hp[32], rt[16];
    mbar_wait_c(B(B_WF + w), ffn ? (WIN >> 1) & 1 : 0);
    mbar_wait_c(B(B_WR), 0);
    mbar_wait_c(B(B_SET2), 0);
#pragma unroll
    for (int j = 0; j < 16; j++) {
      const uint32_t q = stg + r0 * 128 + (lane & 3) * 4 + (j >> 3) * 8192 + (((j & 7) ^ r0) << 4);
      asm volatile("ld.shared.u32 %0, [%1];" : "=r"(hp[2 * j]) : "r"(q) : "memory");
      asm volatile("ld.shared.u32 %0, [%1];" : "=r"(hp[2 * j + 1]) : "r"(q + 1024) : "memory");
      asm volatile("ld.shared.u32 %0, [%1];" : "=r"(rt[j]) : "r"(sb + OFF_MISC + 512 + (r0 & 1) * 256 + (lane & 3) * 4 + j * 16) : "memory");
    }
    wg_wait<0>();
    fence_regs(acc);
    TL(2, 10, warp == 4);
    {
      float d[4] = {0.f, 0.f, 0.f, 0.f}, qa[4] = {0.f, 0.f, 0.f, 0.f}, qb[4] = {0.f, 0.f, 0.f, 0.f};
#pragma unroll
      for (int j = 0; j < 16; j++) {
        hp[2 * j] = hadd2_bf(hp[2 * j], pack_bf16(acc[4 * j], acc[4 * j + 1]));
        hp[2 * j + 1] = hadd2_bf(hp[2 * j + 1], pack_bf16(acc[4 * j + 2], acc[4 * j + 3]));
        if (j & 1) {
          mma16816(d, hp[2 * j - 2], hp[2 * j - 1], hp[2 * j], hp[2 * j + 1], rt[j - 1], rt[j]);
          mma16816(qa, hp[2 * j - 2], hp[2 * j - 1], hp[2 * j], hp[2 * j + 1], hp[2 * j - 2], hp[2 * j]);
          mma16816(qb, hp[2 * j - 2], hp[2 * j - 1], hp[2 * j], hp[2 * j + 1], hp[2 * j - 1], hp[2 * j + 1]);
        }
      }
      const float s2a = __shfl_sync(~0u, (r0 & 1) ? qa[1] : qa[0], r0 * 4 + (r0 >> 1));
      const float s2b = __shfl_sync(~0u, (r0 & 1) ? qb[3] : qb[2], r0 * 4 + (r0 >> 1));
      if ((lane & 3) == 0) {
        __stcg(reinterpret_cast<float4*>(xr + XR_PS + cw * 16 + r0), make_float4(d[0], s2a, d[1], 0.f));
        __stcg(reinterpret_cast<float4*>(xr + XR_PS + cw * 16 + r0 + 8), make_float4(d[2], s2b, d[3], 0.f));
      }
    }
    __syncwarp();
    stage_store_128(stg, lane, hp);
    TL(2, 11, warp == 4);
    __syncwarp();
    uint4 cout;
    uint32_t ckey;
    {
      uint4 ps[4];
      const float wsum = *reinterpret_cast<const float*>(sp + OFF_MISC + 1024);
      if (PDLY) spin_clk(PDLY);
      poll_chunks(ps, g_xr + (mt * 8 + (ct & 1) * 4) * XR_SIZE + XR_PS + (ct >> 1), XR_SIZE);
      TL(2, 12, warp == 4);
      auto F = [](uint32_t u) { return __uint_as_float(u); };
      float s1 = (F(ps[0].x) + F(ps[1].x)) + (F(ps[2].x) + F(ps[3].x)), s2 = (F(ps[0].y) + F(ps[1].y)) + (F(ps[2].y) + F(ps[3].y));
      float s3 = (F(ps[0].z) + F(ps[1].z)) + (F(ps[2].z) + F(ps[3].z));
      s1 += __shfl_xor_sync(~0u, s1, 1); s2 += __shfl_xor_sync(~0u, s2, 1); s3 += __shfl_xor_sync(~0u, s3, 1);
      const float mean = s1 * (1.f / DM);
      float mb, inv;
      ln_round(mean, fmaxf(fmaf(s2, 1.f / DM, -mean * mean), 0.f), mb, inv);
      uint32_t u = pack_bf16((s3 - mb * wsum) * inv, 0.f);
      if (u == 0x8000u) u = 0;
      u = (u & 0x8000u) ? (~u & 0xFFFFu) : (u | 0x8000u);
      const uint32_t key = (u << 16) | (0x7FFFu - (mt * 128 + (ct >> 1)));
      const uint32_t nm2 = pack_bf16(-mb, -mb);
      const uint32_t c1 = __reduce_max_sync(~0u, key);
      const uint32_t c2 = __reduce_max_sync(~0u, key == c1 ? 0u : key);
      if (lane == 0) __stcg(reinterpret_cast<uint2*>(xr + XR_KEY) + cw, make_uint2(c1, c2));
      if (!(ct & 1)) *reinterpret_cast<uint2*>(sp + OFF_RSTAT + (ct >> 1) * 8) = make_uint2(nm2, __float_as_uint(inv) | (key >= c2 ? 0x80000000u : 0u));
      ckey = (lane >> 4) ? c2 : c1;
      const int row = (0x7FFF - (ckey & 0x7FFF)) & 15;
      const uint32_t rn = __shfl_sync(~0u, nm2, row * 2);
      const float ri = __shfl_sync(~0u, inv, row * 2);
      const uint4 v = lds128(stg + ((lane & 15) >> 3) * 8192 + row * 128 + (((lane & 7) ^ (row & 7)) << 4));
      const uint4 n = make_uint4(ln_apply(v.x, rn, ri), ln_apply(v.y, rn, ri), ln_apply(v.z, rn, ri), ln_apply(v.w, rn, ri));
      __stcg(xr + XR_CAND + cw * 64 + 32 + lane, n);
      __stcg(xr + XR_CAND + cw * 64 + lane, v);
      cdst = out + (size_t)(0x7FFF - (ckey & 0x7FFF)) * DM + gq * 128 + (lane & 15) * 8;
      cout = make_uint4(hadd2_bf(v.x, n.x), hadd2_bf(v.y, n.y), hadd2_bf(v.z, n.z), hadd2_bf(v.w, n.w));
    }
    publish(B_OUT - B_PUB);
    cluster_arrive();
    TL(2, 13, warp == 4);
    uint32_t wd[16][4];
    if (ffn) {
      static_for<8 - WIN>([&](auto i) {
        constexpr int it = NIT + i / 2;
        if ((i & 1) == 0) mbar_wait_c(B(B_FULL3 + it % 6), (it / 6) & 1);
        grab(IC<WIN + i>{}, r3(it % 6) + (i & 1) * UNIT);
      });
      mbar_wait_c(B(B_FULL3 + (w ? (IT_WD + 1) % 6 : IT_WD % 6)), w ? ((IT_WD + 1) / 6) & 1 : (IT_WD / 6) & 1);
#pragma unroll
      for (int i = 0; i < 16; i++) {
        const int k = (i & 1) * 16 + (lane & 7) + (lane >> 4) * 8;
        asm volatile("ldmatrix.sync.aligned.m8n8.x4.trans.shared.b16 {%0,%1,%2,%3}, [%4];"
                     : "=r"(wd[i][0]), "=r"(wd[i][1]), "=r"(wd[i][2]), "=r"(wd[i][3])
                     : "r"(sb + (w ? r3((IT_WD + 1) % 6) : r3(IT_WD % 6)) + (2 * (cw & 3) + (i >> 3)) * 4096 + k * 128 + (((2 * ((i >> 1) & 3) + ((lane >> 3) & 1)) ^ (lane & 7)) << 4)) : "memory");
      }
    }
    mbar_wait_c(B(B_OUT2), 0);
    const uint2 top = *reinterpret_cast<const uint2*>(sp + OFF_MISC);
    TL(2, 14, warp == 4);
    const int t0 = 0x7FFF - (top.x & 0x7FFF), t1 = 0x7FFF - (top.y & 0x7FFF);
    auto cand = [&](int second, int chunk) {
      const int tk = second ? t1 : t0;
      return g_xr + ((tk >> 7) * 8 + (chunk >> 4)) * XR_SIZE + XR_CAND + ((tk >> 4) & 7) * 64 + ((second && (t0 >> 4) == (t1 >> 4)) ? 16 : 0) + (chunk & 15);
    };
    const int fc = 16 * (rid >> 1) + 4 * (rid & 1) + (lane & 3) + 8 * (lane >> 4), ft = (lane >> 3) & 1;
    uint32_t fh, fn;
    {
      const uint4* pc = cand(w, ct & 127) + 32;
      const uint16_t* pf = reinterpret_cast<const uint16_t*>(cand(ft, fc >> 3)) + (fc & 7);
      uint4 v;
#pragma unroll 1
      for (int n = 0; n < 0x400000; n++) {
        asm volatile("ld.relaxed.gpu.global.v4.u32 {%0,%1,%2,%3}, [%4];" : "=r"(v.x), "=r"(v.y), "=r"(v.z), "=r"(v.w) : "l"(pc) : "memory");
        asm volatile("ld.relaxed.gpu.global.u16 %0, [%1];" : "=r"(fh) : "l"(pf) : "memory");
        asm volatile("ld.relaxed.gpu.global.u16 %0, [%1 + 512];" : "=r"(fn) : "l"(pf) : "memory");
        if (__all_sync(~0u, max(max(v.x, v.y), max(v.z, v.w)) != 0xFFFFFFFFu && max(fh, fn) != 0xFFFFu)) break;
      }
      const int blk = (ct & 127) >> 2;
      const uint32_t a = sb + OFF_SCR + w * 2112 + blk * 64 + (((blk >> 1) & 3) << 4) + (ct & 3) * 4;
      asm volatile("st.shared.u32 [%0], %1;" ::"r"(a), "r"(v.x) : "memory");
      asm volatile("st.shared.u32 [%0], %1;" ::"r"(a ^ 16), "r"(v.y) : "memory");
      asm volatile("st.shared.u32 [%0], %1;" ::"r"(a ^ 32), "r"(v.z) : "memory");
      asm volatile("st.shared.u32 [%0], %1;" ::"r"(a ^ 48), "r"(v.w) : "memory");
    }
    asm volatile("{\n.reg .pred p;\nsetp.lt.u32 p, %5, %6;\n@p st.global.v4.u32 [%0], {%1,%2,%3,%4};\n}" ::"l"(cdst), "r"(cout.x), "r"(cout.y), "r"(cout.z),
                 "r"(cout.w), "r"(ckey), "r"(top.y) : "memory");
    if (ffn) {
      bar_sync(3, 256);
      TL(2, 15, warp == 4);
      float d[2][4] = {{0.f, 0.f, 0.f, 0.f}, {0.f, 0.f, 0.f, 0.f}};
      const uint32_t xb = sb + OFF_SCR + (r0 & 1) * 2112 + w * 128 + (((lane ^ w) & 3) << 4);
#pragma unroll
      for (int i = 0; i < 16; i++) {
        const uint4 b = lds128((xb ^ ((i & 2) << 4)) + (i >> 1) * 256 + (i & 1) * 64);
        mma16816(d[0], wf[8 * i], wf[8 * i + 1], wf[8 * i + 2], wf[8 * i + 3], b.x, b.y);
        mma16816(d[1], wf[8 * i + 4], wf[8 * i + 5], wf[8 * i + 6], wf[8 * i + 7], b.z, b.w);
      }
      float2* red = reinterpret_cast<float2*>(sp + OFF_SCR + 8192);
      if (!(lane & 2))
        red[(w * 2 + (lane & 1)) * 32 + (cw & 3) * 8 + r0] = (lane & 1) ? make_float2(d[0][1] + d[1][1], d[0][3] + d[1][3]) : make_float2(d[0][0] + d[1][0], d[0][2] + d[1][2]);
      bar_sync(3, 256);
      TL(2, 16, warp == 4);
      const uint32_t ra = sb + OFF_SCR + 8192 + (r0 & 1) * 256 + (r0 >> 1) * 64 + (lane & 3) * 16;
      const uint4 p0 = lds128(ra), p1 = lds128(ra + 512);
      auto act = [](uint32_t u0, uint32_t u1, uint32_t g0, uint32_t g1) {
        const uint32_t ug = pack_bf16(__uint_as_float(u0) + __uint_as_float(u1), __uint_as_float(g0) + __uint_as_float(g1));
        const float g = bf_hi(ug);
        return bf_round(__fdividef(g, 1.f + __expf(-g))) * bf_lo(ug);
      };
      const uint32_t av = pack_bf16(act(p0.x, p1.x, p0.y, p1.y), act(p0.z, p1.z, p0.w, p1.w));
      uint32_t b[4];
#pragma unroll
      for (int i = 0; i < 4; i++) b[i] = __shfl_sync(~0u, av, 8 * i + (lane & 7));
      TL(2, 17, warp == 4);
      float y[2][4] = {{0.f, 0.f, 0.f, 0.f}, {0.f, 0.f, 0.f, 0.f}};
#pragma unroll
      for (int c = 0; c < 4; c++) {
        const bool on = (lane >> 3) == c;
        const uint32_t b0 = on ? b[0] : 0, b1 = on ? b[1] : 0, b2 = on ? b[2] : 0, b3 = on ? b[3] : 0;
#pragma unroll
        for (int a = 0; a < 2; a++) {
          const int i = 8 * a + 2 * c;
          mma16816(y[a], wd[i][0], wd[i][1], wd[i][2], wd[i][3], b0, b1);
          mma16816(y[a], wd[i + 1][0], wd[i + 1][1], wd[i + 1][2], wd[i + 1][3], b2, b3);
        }
      }
      float4* yd = reinterpret_cast<float4*>(g_xr + (cw * 16 + (lane & 3) * 2 + (lane >> 4)) * XR_SIZE + XR_Y + fid * 4 + (r0 & 3));
      __stcg(yd, make_float4(y[0][0], y[0][1], y[0][2], y[0][3]));
      __stcg(yd + 8 * XR_SIZE, make_float4(y[1][0], y[1][1], y[1][2], y[1][3]));
    }
    TL(2, 18, warp == 4);
    if (cw == 0) {
      uint32_t u = (ft ? top.y : top.x) >> 16;
      u = (u & 0x8000u) ? (u & 0x7FFFu) : (~u & 0xFFFFu);
      float rs = bf_round(__fdividef(1.f, 1.f + __expf(-__uint_as_float(u << 16))));
      uint16_t* op = reinterpret_cast<uint16_t*>(out) + (size_t)(ft ? t1 : t0) * DM + fc;
      asm volatile("" : "+l"(op), "+f"(rs));
      spin_clk(ffn ? YDLY : YDLY + YDLY0);
      float v[4];
#pragma unroll 1
      for (int n = 0; n < 0x400000; n++) {
        float4 z[14];
#pragma unroll
        for (int i = 0; i < 14; i++)
          asm volatile("ld.relaxed.gpu.global.v4.f32 {%0,%1,%2,%3}, [%4];" : "=f"(z[i].x), "=f"(z[i].y), "=f"(z[i].z), "=f"(z[i].w) : "l"(xr + XR_Y + lane + 32 * i) : "memory");
        float a[4] = {z[0].x, z[0].y, z[0].z, z[0].w}, b[4] = {z[1].x, z[1].y, z[1].z, z[1].w};
#pragma unroll
        for (int i = 2; i < 14; i += 2) {
          a[0] += z[i].x; a[1] += z[i].y; a[2] += z[i].z; a[3] += z[i].w;
          b[0] += z[i + 1].x; b[1] += z[i + 1].y; b[2] += z[i + 1].z; b[3] += z[i + 1].w;
        }
#pragma unroll
        for (int i = 0; i < 4; i++) v[i] = a[i] + b[i];
        const float t = (v[0] + v[1]) + (v[2] + v[3]);
        if (__all_sync(~0u, t == t)) break;
        uint32_t m = 0;
#pragma unroll
        for (int i = 0; i < 14; i++) m = max(max(m, max(__float_as_uint(z[i].x), __float_as_uint(z[i].y))), max(__float_as_uint(z[i].z), __float_as_uint(z[i].w)));
        if (__all_sync(~0u, m != 0xFFFFFFFFu)) break;
      }
      TL(2, 30, true);
      const bool hi = lane & 16, odd = lane & 8;
      const float a0 = (hi ? v[2] : v[0]) + __shfl_xor_sync(~0u, hi ? v[0] : v[2], 16), a1 = (hi ? v[3] : v[1]) + __shfl_xor_sync(~0u, hi ? v[1] : v[3], 16);
      float yv = (odd ? a1 : a0) + __shfl_xor_sync(~0u, odd ? a0 : a1, 8);
      yv += __shfl_xor_sync(~0u, yv, 4);
      const uint32_t o = hadd2_bf(fh, hadd2_bf(fn, pack_bf16(bf_round(yv) * rs, 0.f)));
      if (!(lane & 4)) *op = (uint16_t)o;
      TL(2, 21, true);
    }
    TL(2, 20, warp == 4);
    __syncwarp();
    cluster_wait();
  }
}

typedef CUresult (*EncodeFn)(CUtensorMap*, CUtensorMapDataType, cuuint32_t, void*, const cuuint64_t*, const cuuint64_t*, const cuuint32_t*,
                             const cuuint32_t*, CUtensorMapInterleave, CUtensorMapSwizzle, CUtensorMapL2promotion, CUtensorMapFloatOOBfill);
EncodeFn g_enc = nullptr;

void map2(CUtensorMap* m, const void* ptr, uint64_t rows, uint64_t cols, uint32_t bc, uint32_t br) {
  const CUtensorMapSwizzle sw = bc == 64 ? CU_TENSOR_MAP_SWIZZLE_128B : CU_TENSOR_MAP_SWIZZLE_64B;
  cuuint64_t gd[2] = {cols, rows}, gs[1] = {cols * 2};
  cuuint32_t bd[2] = {bc, br}, es[2] = {1, 1};
  g_enc(m, CU_TENSOR_MAP_DATA_TYPE_BFLOAT16, 2, (void*)ptr, gd, gs, bd, es, CU_TENSOR_MAP_INTERLEAVE_NONE, sw,
        CU_TENSOR_MAP_L2_PROMOTION_L2_128B, CU_TENSOR_MAP_FLOAT_OOB_FILL_NONE);
}
void map3(CUtensorMap* m, const void* ptr, uint64_t rows, uint64_t cols, uint32_t br, uint32_t bch) {
  cuuint64_t gd[3] = {64, rows, cols / 64}, gs[2] = {cols * 2, 128};
  cuuint32_t bd[3] = {64, br, bch}, es[3] = {1, 1, 1};
  g_enc(m, CU_TENSOR_MAP_DATA_TYPE_BFLOAT16, 3, (void*)ptr, gd, gs, bd, es, CU_TENSOR_MAP_INTERLEAVE_NONE, CU_TENSOR_MAP_SWIZZLE_128B,
        CU_TENSOR_MAP_L2_PROMOTION_L2_128B, CU_TENSOR_MAP_FLOAT_OOB_FILL_NONE);
}

}

extern "C" void kernel_launch(void* const* d_in, const int* in_sizes, int n_in, void* d_out, int out_size) {
  const __nv_bfloat16* x = (const __nv_bfloat16*)d_in[0];
  const __nv_bfloat16* ckv = (const __nv_bfloat16*)d_in[1];
  const __nv_bfloat16* wq = (const __nv_bfloat16*)d_in[2];
  const __nv_bfloat16* wk = (const __nv_bfloat16*)d_in[3];
  const __nv_bfloat16* wv = (const __nv_bfloat16*)d_in[4];
  const __nv_bfloat16* wo = (const __nv_bfloat16*)d_in[5];
  const __nv_bfloat16* w_r = (const __nv_bfloat16*)d_in[7];
  const __nv_bfloat16* wgate = (const __nv_bfloat16*)d_in[8];
  const __nv_bfloat16* wup = (const __nv_bfloat16*)d_in[9];
  const __nv_bfloat16* wdown = (const __nv_bfloat16*)d_in[10];
  __nv_bfloat16* out = (__nv_bfloat16*)d_out;

  if (!g_enc) {
    void* fn = nullptr;
    cudaDriverEntryPointQueryResult qr;
    cudaGetDriverEntryPoint("cuTensorMapEncodeTiled", &fn, cudaEnableDefault, &qr);
    g_enc = (EncodeFn)fn;
    cudaFuncSetAttribute(fused_kernel, cudaFuncAttributeMaxDynamicSharedMemorySize, SMEM_BYTES);
  }
  void *xn, *kv, *ctx;
  cudaGetSymbolAddress(&xn, g_xn);
  cudaGetSymbolAddress(&kv, g_kv);
  cudaGetSymbolAddress(&ctx, g_ctx);

  Params p;
  map2(&p.xn, xn, SEQ, DM, 64, 64);
  map2(&p.ckv, ckv, SEQ, DC, 64, 128);
  map3(&p.wq, wq, DM, NQ, 64, 2);
  map3(&p.wk, wk, DC, NQ, 64, 2);
  map3(&p.wv, wv, DC, NQ, 64, 2);
  map3(&p.kv_ld, kv, 2 * SEQ, NQ, 128, 2);
  map2(&p.ctx_ld, ctx, SEQ, NQ, 64, 128);
  map3(&p.wo, wo, NQ, DM, 64, 1);
  map3(&p.x, x, SEQ, DM, 64, 2);
  map3(&p.wd, wdown, FF, DM, 32, 8);
  map2(&p.wg, wgate, DM, FF, 32, 64);
  map2(&p.wu, wup, DM, FF, 32, 64);
  fused_kernel<<<128, 384, SMEM_BYTES, cudaStreamPerThread>>>(p, x, wq, w_r, wgate, wup, out, 0u);
}
```

```cpp
#include <cuda_runtime.h>
#include <cuda_bf16.h>
#include <cuda.h>
#include <stdint.h>
#include <utility>

#pragma nv_diag_suppress 549
#pragma nv_diag_suppress 177
namespace {

constexpr int SEQ = 2048, DM = 1024, NH = 32, HD = 128, DC = 512, NQ = NH * HD, FF = 3584;

__device__ __align__(1024) __nv_bfloat16 g_xn[SEQ * DM];
__device__ __align__(1024) __nv_bfloat16 g_kv[2 * SEQ * NQ];
__device__ __align__(1024) __nv_bfloat16 g_ctx[SEQ * NQ];
constexpr int XR_PS = 0;
constexpr int XR_KEY = 128;
constexpr int XR_CAND = 136;
constexpr int XR_Y = 648;
constexpr int XR_SIZE = 1104;
__device__ __align__(1024) uint4 g_xr[128 * XR_SIZE];
constexpr int C_LN = 0, C_KV = 16, C_CTX = 32, C_NUM = 64;
__device__ unsigned g_cnt[C_NUM];

#define TL(k, i, cond) do {} while (0)
#define TC(w, g, i) do {} while (0)
#define TL_EXTRA 0
#define TK(i) do {} while (0)

__device__ __forceinline__ uint32_t s2u(const void* p) { return (uint32_t)__cvta_generic_to_shared(p); }
__device__ __forceinline__ void mbar_arrive(uint32_t b) { asm volatile("mbarrier.arrive.shared::cta.b64 _, [%0];" ::"r"(b) : "memory"); }
__device__ __forceinline__ void mbar_arrive_both(uint32_t b, uint32_t lane, bool cond) {
  asm volatile("{\n.reg .pred p;\n.reg .b32 r;\nsetp.lt.u32 p, %1, %2;\nmapa.shared::cluster.u32 r, %0, %1;\n@p mbarrier.arrive.shared::cluster.b64 _, [r];\n}"
               ::"r"(b), "r"(lane), "r"(cond ? 2 : 0) : "memory");
}
__device__ __forceinline__ bool mbar_test(uint32_t b, uint32_t ph) {
  uint32_t ok;
  asm volatile("{\n.reg .pred p;\nmbarrier.test_wait.parity.shared::cta.b64 p, [%1], %2;\nselp.u32 %0, 1, 0, p;\n}" : "=r"(ok) : "r"(b), "r"(ph) : "memory");
  return __all_sync(~0u, ok);
}
__device__ __forceinline__ void mbar_wait(uint32_t b, uint32_t ph) {
  asm volatile(
      "{\n.reg .pred p;\n.reg .u32 n;\nmov.u32 n, 0;\n"
      "LW:\nmbarrier.try_wait.parity.shared::cta.b64 p, [%0], %1, 20000;\n@p bra LD;\n"
      "add.u32 n, n, 1;\nsetp.lt.u32 p, n, 0x40000;\n@p bra LW;\ntrap;\nLD:\n}" ::"r"(b), "r"(ph) : "memory");
}
__device__ __forceinline__ void mbar_wait_u(uint32_t b, uint32_t ph) {
  asm volatile(
      "{\n.reg .pred p;\n.reg .u32 n;\nmov.u32 n, 0;\n"
      "LW:\nmbarrier.try_wait.parity.shared::cta.b64 p, [%0], %1, 20000;\n@p bra.uni LD;\n"
      "add.u32 n, n, 1;\nsetp.lt.u32 p, n, 0x40000;\n@p bra.uni LW;\ntrap;\nLD:\n}" ::"r"(b), "r"(ph) : "memory");
}
__device__ __forceinline__ void mbar_wait_c(uint32_t b, uint32_t ph) {
  asm volatile(
      "{\n.reg .pred p;\n.reg .u32 n;\nmov.u32 n, 0;\n"
      "LW:\nmbarrier.try_wait.parity.shared::cta.b64 p, [%0], %1;\n@p bra.uni LD;\n"
      "add.u32 n, n, 1;\nsetp.lt.u32 p, n, 0x100000;\n@p bra.uni LW;\ntrap;\nLD:\n}" ::"r"(b), "r"(ph) : "memory");
}
template <bool SLEEP = false>
__device__ __forceinline__ void spin_until_ge(const unsigned* p, unsigned target) {
  asm volatile(
      "{\n.reg .pred p, q;\n.reg .u32 n, v;\nmov.u32 n, 0;\nsetp.ne.u32 q, %2, 0;\n"
      "LW:\nld.acquire.gpu.global.u32 v, [%0];\nsetp.ge.u32 p, v, %1;\n@p bra LD;\n@q nanosleep.u32 200;\n"
      "add.u32 n, n, 1;\nsetp.lt.u32 p, n, 0x400000;\n@p bra LW;\ntrap;\nLD:\n}" ::"l"(p), "r"(target), "n"((int)SLEEP) : "memory");
}
template <int N>
__device__ __forceinline__ void poll_chunks(uint4 (&v)[N], const uint4* p, int stride) {
#pragma unroll 1
  for (int n = 0; n < 0x400000; n++) {
    uint32_t m = 0;
#pragma unroll
    for (int i = 0; i < N; i++) {
      asm volatile("ld.relaxed.gpu.global.v4.u32 {%0,%1,%2,%3}, [%4];" : "=r"(v[i].x), "=r"(v[i].y), "=r"(v[i].z), "=r"(v[i].w) : "l"(p + i * stride) : "memory");
    }
#pragma unroll
    for (int i = 0; i < N; i++) m = max(max(m, max(v[i].x, v[i].y)), max(v[i].z, v[i].w));
    if (__all_sync(~0u, m != 0xFFFFFFFFu)) break;
  }
}
__device__ __forceinline__ void spin_clk(uint32_t n) {
  asm volatile("{\n.reg .pred p;\n.reg .u32 a, b;\nmov.u32 a, %%clock;\nLW:\nmov.u32 b, %%clock;\nsub.u32 b, b, a;\nsetp.lt.u32 p, b, %0;\n@p bra.uni LW;\n}" ::"r"(n) : "memory");
}
__device__ __forceinline__ int fresh_lane() {
  int r;
  asm volatile("mov.u32 %0, %%laneid;" : "=r"(r));
  return r;
}
__device__ __forceinline__ void fence_async_all() { asm volatile("fence.proxy.async;" ::: "memory"); }
__device__ __forceinline__ void bar_sync(int id, int n) { asm volatile("bar.sync %0, %1;" ::"r"(id), "r"(n) : "memory"); }
__device__ __forceinline__ void bar_arrive(int id, int n) { asm volatile("bar.arrive %0, %1;" ::"r"(id), "r"(n) : "memory"); }
__device__ __forceinline__ void cluster_arrive() { asm volatile("barrier.cluster.arrive.relaxed.aligned;" ::: "memory"); }
__device__ __forceinline__ void cluster_wait() { asm volatile("barrier.cluster.wait.acquire.aligned;" ::: "memory"); }
__device__ __forceinline__ void fence_gpu() { asm volatile("fence.acq_rel.gpu;" ::: "memory"); }
__device__ __forceinline__ void red_add(unsigned* p, unsigned v) { asm volatile("red.relaxed.gpu.global.add.u32 [%0], %1;" ::"l"(p), "r"(v) : "memory"); }
#define ELECT "{\n.reg .pred E;\nelect.sync _|E, 0xFFFFFFFF;\n@E "
__device__ __forceinline__ void e_init(uint32_t b, uint32_t c) { asm volatile(ELECT "mbarrier.init.shared::cta.b64 [%0], %1;\n}" ::"r"(b), "r"(c) : "memory"); }
__device__ __forceinline__ void e_expect(uint32_t b, uint32_t bytes) { asm volatile(ELECT "mbarrier.arrive.expect_tx.shared::cta.b64 _, [%0], %1;\n}" ::"r"(b), "r"(bytes) : "memory"); }
__device__ __forceinline__ void e_arrive(uint32_t b) { asm volatile(ELECT "mbarrier.arrive.shared::cta.b64 _, [%0];\n}" ::"r"(b) : "memory"); }
__device__ __forceinline__ void prefetch_tm(const CUtensorMap* m) { asm volatile(ELECT "prefetch.tensormap [%0];\n}" ::"l"(m) : "memory"); }
__device__ __forceinline__ void tma_ld2(uint32_t dst, const CUtensorMap* m, uint32_t bar, int c0, int c1) {
  asm volatile(ELECT "cp.async.bulk.tensor.2d.shared::cta.global.mbarrier::complete_tx::bytes [%0], [%1, {%3,%4}], [%2];\n}" ::"r"(dst), "l"(m), "r"(bar), "r"(c0), "r"(c1) : "memory");
}
__device__ __forceinline__ void tma_ld3(uint32_t dst, const CUtensorMap* m, uint32_t bar, int c0, int c1, int c2) {
  asm volatile(ELECT "cp.async.bulk.tensor.3d.shared::cta.global.mbarrier::complete_tx::bytes [%0], [%1, {%3,%4,%5}], [%2];\n}" ::"r"(dst), "l"(m), "r"(bar), "r"(c0), "r"(c1), "r"(c2) : "memory");
}
__device__ __forceinline__ void tma_ld2_mc(uint32_t dst, const CUtensorMap* m, uint32_t bar, int c0, int c1, uint16_t mask) {
  asm volatile(ELECT "cp.async.bulk.tensor.2d.shared::cluster.global.mbarrier::complete_tx::bytes.multicast::cluster [%0], [%1, {%3,%4}], [%2], %5;\n}" ::"r"(dst), "l"(m), "r"(bar), "r"(c0), "r"(c1), "h"(mask) : "memory");
}
__device__ __forceinline__ void tma_ld3_mc(uint32_t dst, const CUtensorMap* m, uint32_t bar, int c0, int c1, int c2, uint16_t mask) {
  asm volatile(ELECT "cp.async.bulk.tensor.3d.shared::cluster.global.mbarrier::complete_tx::bytes.multicast::cluster [%0], [%1, {%3,%4,%5}], [%2], %6;\n}" ::"r"(dst), "l"(m), "r"(bar), "r"(c0), "r"(c1), "r"(c2), "h"(mask) : "memory");
}
__device__ __forceinline__ uint64_t policy_evict_first() {
  uint64_t p;
  asm("createpolicy.fractional.L2::evict_first.b64 %0, 1.0;" : "=l"(p));
  return p;
}
__device__ __forceinline__ void tma_ld2_ef(uint32_t dst, const CUtensorMap* m, uint32_t bar, int c0, int c1) {
  asm volatile(ELECT "cp.async.bulk.tensor.2d.shared::cta.global.mbarrier::complete_tx::bytes.L2::cache_hint [%0], [%1, {%3,%4}], [%2], %5;\n}" ::"r"(dst), "l"(m), "r"(bar), "r"(c0), "r"(c1), "l"(policy_evict_first()) : "memory");
}
__device__ __forceinline__ void tma_ld3_ef(uint32_t dst, const CUtensorMap* m, uint32_t bar, int c0, int c1, int c2) {
  asm volatile(ELECT "cp.async.bulk.tensor.3d.shared::cta.global.mbarrier::complete_tx::bytes.L2::cache_hint [%0], [%1, {%3,%4,%5}], [%2], %6;\n}" ::"r"(dst), "l"(m), "r"(bar), "r"(c0), "r"(c1), "r"(c2), "l"(policy_evict_first()) : "memory");
}
__device__ __forceinline__ void tma_ld3_mc_ef(uint32_t dst, const CUtensorMap* m, uint32_t bar, int c0, int c1, int c2, uint16_t mask) {
  asm volatile(ELECT "cp.async.bulk.tensor.3d.shared::cluster.global.mbarrier::complete_tx::bytes.multicast::cluster.L2::cache_hint [%0], [%1, {%3,%4,%5}], [%2], %6, %7;\n}" ::"r"(dst), "l"(m), "r"(bar), "r"(c0), "r"(c1), "r"(c2), "h"(mask), "l"(policy_evict_first()) : "memory");
}
__device__ __forceinline__ void tma_pf2(const CUtensorMap* m, int c0, int c1) { asm volatile(ELECT "cp.async.bulk.prefetch.tensor.2d.L2.global [%0, {%1,%2}];\n}" ::"l"(m), "r"(c0), "r"(c1) : "memory"); }
__device__ __forceinline__ void tma_pf3(const CUtensorMap* m, int c0, int c1, int c2) { asm volatile(ELECT "cp.async.bulk.prefetch.tensor.3d.L2.global [%0, {%1,%2,%3}];\n}" ::"l"(m), "r"(c0), "r"(c1), "r"(c2) : "memory"); }
__device__ __forceinline__ void sched_fence() { asm volatile("pmevent 0;" ::: "memory"); }
__device__ __forceinline__ void l2_prefetch(const void* p, uint32_t bytes) { asm volatile(ELECT "cp.async.bulk.prefetch.L2.global [%0], %1;\n}" ::"l"(p), "r"(bytes) : "memory"); }

__device__ __forceinline__ void wg_fence() { asm volatile("wgmma.fence.sync.aligned;" ::: "memory"); }
__device__ __forceinline__ void wg_commit() { asm volatile("wgmma.commit_group.sync.aligned;" ::: "memory"); }
template <int N> __device__ __forceinline__ void wg_wait() { asm volatile("wgmma.wait_group.sync.aligned %0;" ::"n"(N) : "memory"); }
template <int N> __device__ __forceinline__ void reg_alloc() { asm volatile("setmaxnreg.inc.sync.aligned.u32 %0;" ::"n"(N)); }
template <int N> __device__ __forceinline__ void reg_dealloc() { asm volatile("setmaxnreg.dec.sync.aligned.u32 %0;" ::"n"(N)); }
template <int N> __device__ __forceinline__ void fence_regs(float (&d)[N]) {
#pragma unroll
  for (int i = 0; i < N; i++) asm volatile("" : "+f"(d[i])::"memory");
}
template <int N> __device__ __forceinline__ void fence_regs(uint32_t (&d)[N]) {
#pragma unroll
  for (int i = 0; i < N; i++) asm volatile("" : "+r"(d[i])::"memory");
}

__device__ __forceinline__ uint32_t mk_desc(uint32_t addr, uint32_t lbo) { return ((addr & 0x3FFFF) >> 4) | ((lbo >> 4) << 16); }

#define R8(b) "+f"(d[b + 0]), "+f"(d[b + 1]), "+f"(d[b + 2]), "+f"(d[b + 3]), "+f"(d[b + 4]), "+f"(d[b + 5]), "+f"(d[b + 6]), "+f"(d[b + 7])
#define REGS64 "%0,%1,%2,%3,%4,%5,%6,%7,%8,%9,%10,%11,%12,%13,%14,%15,%16,%17,%18,%19,%20,%21,%22,%23,%24,%25,%26,%27,%28,%29,%30,%31," \
               "%32,%33,%34,%35,%36,%37,%38,%39,%40,%41,%42,%43,%44,%45,%46,%47,%48,%49,%50,%51,%52,%53,%54,%55,%56,%57,%58,%59,%60,%61,%62,%63"
#define REGS128 REGS64 ",%64,%65,%66,%67,%68,%69,%70,%71,%72,%73,%74,%75,%76,%77,%78,%79,%80,%81,%82,%83,%84,%85,%86,%87,%88,%89,%90,%91,%92,%93,%94,%95," \
               "%96,%97,%98,%99,%100,%101,%102,%103,%104,%105,%106,%107,%108,%109,%110,%111,%112,%113,%114,%115,%116,%117,%118,%119,%120,%121,%122,%123,%124,%125,%126,%127"

#define DESC(d, r, o) "add.u32 t, " r ", " o ";\nmov.b64 " d ", {t, h};\n"
#define MMA_PRE(acc) "{\n.reg .pred p;\n.reg .b32 t, h;\n.reg .b64 da, db;\nmov.b32 h, 0x40000040;\nsetp.ne.b32 p, " acc ", 0;\n"
template <int TB, int OA, int OB>
__device__ __forceinline__ void mma_n256_ss(float (&d)[128], uint32_t a, uint32_t b, int acc) {
  asm volatile(MMA_PRE("%130") DESC("da", "%128", "%132") DESC("db", "%129", "%133")
               "wgmma.mma_async.sync.aligned.m64n256k16.f32.bf16.bf16 {" REGS128 "}, da, db, p, 1, 1, 0, %131;\n}\n"
               : R8(0), R8(8), R8(16), R8(24), R8(32), R8(40), R8(48), R8(56), R8(64), R8(72), R8(80), R8(88), R8(96), R8(104), R8(112), R8(120)
               : "r"(a), "r"(b), "r"(acc), "n"(TB), "n"(OA >> 4), "n"(OB >> 4));
}
template <int TB, int OA, int OB>
__device__ __forceinline__ void mma_n128_ss(float (&d)[64], uint32_t a, uint32_t b, int acc) {
  asm volatile(MMA_PRE("%66") DESC("da", "%64", "%68") DESC("db", "%65", "%69")
               "wgmma.mma_async.sync.aligned.m64n128k16.f32.bf16.bf16 {" REGS64 "}, da, db, p, 1, 1, 0, %67;\n}\n"
               : R8(0), R8(8), R8(16), R8(24), R8(32), R8(40), R8(48), R8(56)
               : "r"(a), "r"(b), "r"(acc), "n"(TB), "n"(OA >> 4), "n"(OB >> 4));
}
template <int TB, int OB>
__device__ __forceinline__ void mma_n128_rs(float (&d)[64], const uint32_t* a, uint32_t b, int acc) {
  asm volatile(MMA_PRE("%69") DESC("db", "%68", "%71")
               "wgmma.mma_async.sync.aligned.m64n128k16.f32.bf16.bf16 {" REGS64 "}, {%64,%65,%66,%67}, db, p, 1, 1, %70;\n}\n"
               : R8(0), R8(8), R8(16), R8(24), R8(32), R8(40), R8(48), R8(56)
               : "r"(a[0]), "r"(a[1]), "r"(a[2]), "r"(a[3]), "r"(b), "r"(acc), "n"(TB), "n"(OB >> 4));
}
template <int OB>
__device__ __forceinline__ void mma_n64_rs(float (&d)[64], const uint32_t* a, uint32_t b, int acc) {
  asm volatile(MMA_PRE("%37") DESC("db", "%36", "%38")
               "wgmma.mma_async.sync.aligned.m64n64k16.f32.bf16.bf16 {%0,%1,%2,%3,%4,%5,%6,%7,%8,%9,%10,%11,%12,%13,%14,%15,%16,%17,%18,%19,%20,%21,"
               "%22,%23,%24,%25,%26,%27,%28,%29,%30,%31}, {%32,%33,%34,%35}, db, p, 1, 1, 0;\n}\n"
               : R8(0), R8(8), R8(16), R8(24)
               : "r"(a[0]), "r"(a[1]), "r"(a[2]), "r"(a[3]), "r"(b), "r"(acc), "n"(OB >> 4));
}
template <int V> struct IC { static constexpr int value = V; __host__ __device__ constexpr operator int() const { return V; } };
template <int N, class F, int... I>
__device__ __forceinline__ void static_for_(F f, std::integer_sequence<int, I...>) { (f(IC<I>{}), ...); }
template <int N, class F>
__device__ __forceinline__ void static_for(F f) { static_for_<N>(f, std::make_integer_sequence<int, N>{}); }
__device__ __forceinline__ uint32_t pack_bf16(float lo, float hi) {
  uint32_t r;
  asm("cvt.rn.bf16x2.f32 %0, %1, %2;" : "=r"(r) : "f"(hi), "f"(lo));
  return r;
}
__device__ __forceinline__ float bf_lo(uint32_t v) { return __uint_as_float(v << 16); }
__device__ __forceinline__ float bf_hi(uint32_t v) { return __uint_as_float(v & 0xFFFF0000u); }
__device__ __forceinline__ float bf_round(float v) { return bf_lo(pack_bf16(v, v)); }
__device__ __forceinline__ void stsm4(uint32_t addr, uint32_t r0, uint32_t r1, uint32_t r2, uint32_t r3) {
  asm volatile("stmatrix.sync.aligned.m8n8.x4.shared.b16 [%0], {%1,%2,%3,%4};" ::"r"(addr), "r"(r0), "r"(r1), "r"(r2), "r"(r3) : "memory");
}
__device__ __forceinline__ uint4 lds128(uint32_t addr) {
  uint4 v;
  asm volatile("ld.shared.v4.u32 {%0,%1,%2,%3}, [%4];" : "=r"(v.x), "=r"(v.y), "=r"(v.z), "=r"(v.w) : "r"(addr));
  return v;
}
__device__ __forceinline__ float ex2(float x) {
  float y;
  asm("ex2.approx.ftz.f32 %0, %1;" : "=f"(y) : "f"(x));
  return y;
}
__device__ __forceinline__ void stage_store_128(uint32_t base, int lane, const uint32_t* pk) {
  const int row = (lane & 7) + ((lane >> 3) & 1) * 8;
  const uint32_t rb = base + row * 128;
  const int hi = lane >> 4;
#pragma unroll
  for (int j = 0; j < 8; j++) {
    const int chunk = 2 * j + hi;
    const uint32_t a = rb + (j >> 2) * 8192 + (((chunk & 7) ^ (lane & 7)) << 4);
    stsm4(a, pk[4 * j + 0], pk[4 * j + 1], pk[4 * j + 2], pk[4 * j + 3]);
  }
}
__device__ __forceinline__ void ln_round(float mean, float var, float& m_bf, float& inv_s) {
  const uint32_t mv = pack_bf16(mean, var);
  m_bf = bf_lo(mv);
  float sq, rc;
  asm("sqrt.approx.f32 %0, %1;" : "=f"(sq) : "f"(bf_round(bf_hi(mv) + 1e-5f)));
  asm("rcp.approx.ftz.f32 %0, %1;" : "=f"(rc) : "f"(bf_round(sq)));
  inv_s = rc;
}
__device__ __forceinline__ uint32_t hadd2_bf(uint32_t a, uint32_t b) {
  uint32_t r;
  asm("add.rn.bf16x2 %0, %1, %2;" : "=r"(r) : "r"(a), "r"(b));
  return r;
}
__device__ __forceinline__ uint32_t ln_apply(uint32_t h, uint32_t nm2, float inv_s) {
  const uint32_t d = hadd2_bf(h, nm2);
  return pack_bf16(bf_lo(d) * inv_s, bf_hi(d) * inv_s);
}
__device__ __forceinline__ void mma16816(float* d, uint32_t a0, uint32_t a1, uint32_t a2, uint32_t a3, uint32_t b0, uint32_t b1) {
  asm volatile("mma.sync.aligned.m16n8k16.row.col.f32.bf16.bf16.f32 {%0,%1,%2,%3}, {%4,%5,%6,%7}, {%8,%9}, {%0,%1,%2,%3};"
               : "+f"(d[0]), "+f"(d[1]), "+f"(d[2]), "+f"(d[3]) : "r"(a0), "r"(a1), "r"(a2), "r"(a3), "r"(b0), "r"(b1));
}

constexpr float AT_C = 0.08838834764831845f * 1.4426950408889634f;
#define L_MIN 2.3283064e-10f
#define L_MAX 1.0995116e12f
#define SP1 6
#define SP2 12
struct AtState {
  float S[64], O[64];
  uint32_t P[32], Q[32];
  float l[4];
};
#define LAG 0
template <int I0, int I1, int N = 64>
__device__ __forceinline__ void at_exp(AtState& s) {
#pragma unroll
  for (int i = I0; i < I1; i++) asm volatile("ex2.approx.ftz.f32 %0, %0;" : "+f"(s.S[i]));
#pragma unroll
  for (int i = I0 > 0 ? I0 - LAG : 0; i < (I1 < N ? I1 - LAG : N); i++) asm volatile("add.f32 %0, %0, %1;" : "+f"(s.l[i & 3]) : "f"(s.S[i]));
}
template <int I0, int I1>
__device__ __forceinline__ void at_pack(AtState& s) {
#pragma unroll
  for (int i = I0; i < I1; i++) asm volatile("cvt.rn.bf16x2.f32 %0, %1, %2;" : "=r"(s.P[i]) : "f"(s.S[2 * i + 1]), "f"(s.S[2 * i]));
}
template <int J0>
__device__ __forceinline__ void at_mask(AtState& s, int r, int lane) {
  const int d = r + (lane >> 2) - (lane & 3) * 2;
#pragma unroll
  for (int j = 0; j < 8; j++) {
    float dummy0 = 0.f, dummy1 = 0.f;
    float& lo0 = j < 7 ? s.S[4 * (J0 + (j < 7 ? j + 1 : j)) + 2] : dummy0;
    float& lo1 = j < 7 ? s.S[4 * (J0 + (j < 7 ? j + 1 : j)) + 3] : dummy1;
    asm("{\n.reg .pred p, q;\nsetp.lt.s32 p, %4, %5;\nsetp.le.s32 q, %4, %5;\n"
        "@p add.f32 %0, %0, 0fFF800000;\n@q add.f32 %1, %1, 0fFF800000;\n@p add.f32 %2, %2, 0fFF800000;\n@q add.f32 %3, %3, 0fFF800000;\n}"
        : "+f"(s.S[4 * (J0 + j)]), "+f"(s.S[4 * (J0 + j) + 1]), "+f"(lo0), "+f"(lo1) : "r"(d), "r"(8 * j));
  }
}
__device__ __forceinline__ uint32_t ld_pair(const __nv_bfloat16* p) {
  uint32_t r;
  asm volatile("{\n.reg .b16 a, b;\nld.global.cg.b16 a, [%1];\nld.global.cg.b16 b, [%1 + 8192];\nmov.b32 %0, {a, b};\n}" : "=r"(r) : "l"(p) : "memory");
  return r;
}
__device__ __forceinline__ uint32_t ld_word(const uint32_t* p) {
  uint32_t r;
  asm volatile("ld.global.cg.b32 %0, [%1];" : "=r"(r) : "l"(p) : "memory");
  return r;
}
__device__ __forceinline__ void slow_rows(const __nv_bfloat16* wq, int head, int row0) {
  const int lane = fresh_lane(), r = lane >> 2, c = lane & 3;
  uint32_t q[32];
  float o[32];
#pragma unroll
  for (int i = 0; i < 32; i++) q[i] = 0;
  const uint32_t* xa = reinterpret_cast<const uint32_t*>(g_xn + (size_t)(row0 + r) * DM) + c;
#pragma unroll 1
  for (int h = 0; h < 2; h++) {
    const __nv_bfloat16* wb = wq + (size_t)2 * c * NQ + head * HD + 64 * h + 8 * (r >> 1) + (r & 1);
#pragma unroll
    for (int i = 0; i < 32; i++) o[i] = 0.f;
#pragma unroll 1
    for (int kk = 0; kk < DM / 16; kk++) {
      const uint32_t a0 = ld_word(xa + 8 * kk), a1 = ld_word(xa + 8 * kk + 4 * DM), a2 = ld_word(xa + 8 * kk + 4), a3 = ld_word(xa + 8 * kk + 4 * DM + 4);
#pragma unroll
      for (int n = 0; n < 8; n++) {
        const __nv_bfloat16* b = wb + (size_t)16 * kk * NQ + 32 * (n >> 2) + 2 * (n & 3);
        mma16816(o + 4 * n, a0, a1, a2, a3, ld_pair(b), ld_pair(b + 8 * NQ));
      }
    }
#pragma unroll
    for (int i = 0; i < 16; i++) { q[i] = q[16 + i]; q[16 + i] = pack_bf16(o[2 * i] * AT_C, o[2 * i + 1] * AT_C); }
  }
#pragma unroll 1
  for (int h = 0; h < 2; h++) {
    float m0 = -INFINITY, m1 = -INFINITY, l0 = 0.f, l1 = 0.f;
#pragma unroll
    for (int i = 0; i < 32; i++) o[i] = 0.f;
#pragma unroll 1
    for (int k0 = 0; k0 <= row0; k0 += 16) {
      float e[8] = {0.f, 0.f, 0.f, 0.f, 0.f, 0.f, 0.f, 0.f};
      const uint32_t* kp = reinterpret_cast<const uint32_t*>(g_kv + (size_t)(k0 + r) * NQ + head * HD) + c;
#pragma unroll
      for (int kk = 0; kk < 8; kk++) {
        mma16816(e, q[4 * kk], q[4 * kk + 1], q[4 * kk + 2], q[4 * kk + 3], ld_word(kp + 8 * kk), ld_word(kp + 8 * kk + 4));
        mma16816(e + 4, q[4 * kk], q[4 * kk + 1], q[4 * kk + 2], q[4 * kk + 3], ld_word(kp + 8 * kk + 4 * NQ), ld_word(kp + 8 * kk + 4 * NQ + 4));
      }
      if (k0 == row0) {
#pragma unroll
        for (int i = 0; i < 8; i++) if ((i >> 2) * 8 + 2 * c + (i & 1) > r + (i & 2) * 4) e[i] = -INFINITY;
      }
      float a0 = fmaxf(fmaxf(e[0], e[1]), fmaxf(e[4], e[5])), a1 = fmaxf(fmaxf(e[2], e[3]), fmaxf(e[6], e[7]));
      a0 = fmaxf(a0, __shfl_xor_sync(~0u, a0, 1)); a1 = fmaxf(a1, __shfl_xor_sync(~0u, a1, 1));
      a0 = fmaxf(a0, __shfl_xor_sync(~0u, a0, 2)); a1 = fmaxf(a1, __shfl_xor_sync(~0u, a1, 2));
      a0 = fmaxf(a0, m0); a1 = fmaxf(a1, m1);
      const float sc0 = ex2(m0 - a0), sc1 = ex2(m1 - a1);
      m0 = a0; m1 = a1;
#pragma unroll
      for (int i = 0; i < 8; i++) e[i] = ex2(e[i] - ((i & 2) ? m1 : m0));
      l0 = l0 * sc0 + (e[0] + e[1]) + (e[4] + e[5]);
      l1 = l1 * sc1 + (e[2] + e[3]) + (e[6] + e[7]);
      const uint32_t p0 = pack_bf16(e[0], e[1]), p1 = pack_bf16(e[2], e[3]), p2 = pack_bf16(e[4], e[5]), p3 = pack_bf16(e[6], e[7]);
      const __nv_bfloat16* vp = g_kv + (size_t)(SEQ + k0 + 2 * c) * NQ + head * HD + 64 * h + r;
#pragma unroll
      for (int n = 0; n < 8; n++) {
        o[4 * n] *= sc0; o[4 * n + 1] *= sc0; o[4 * n + 2] *= sc1; o[4 * n + 3] *= sc1;
        mma16816(o + 4 * n, p0, p1, p2, p3, ld_pair(vp + 8 * n), ld_pair(vp + 8 * n + 8 * NQ));
      }
    }
    l0 += __shfl_xor_sync(~0u, l0, 1); l1 += __shfl_xor_sync(~0u, l1, 1);
    l0 += __shfl_xor_sync(~0u, l0, 2); l1 += __shfl_xor_sync(~0u, l1, 2);
#pragma unroll
    for (int i = 0; i < 4; i++) {
      const float* v = o + 16 * (i >> 1) + 2 * (i & 1);
      const float f = __fdividef(1.f, (i & 1) ? l1 : l0);
      *reinterpret_cast<uint4*>(g_ctx + (size_t)(row0 + r + (i & 1) * 8) * NQ + head * HD + 64 * h + (i >> 1) * 32 + c * 8) =
          make_uint4(pack_bf16(v[0] * f, v[1] * f), pack_bf16(v[4] * f, v[5] * f), pack_bf16(v[8] * f, v[9] * f), pack_bf16(v[12] * f, v[13] * f));
    }
  }
}

constexpr int UNIT = 16384, SLOT = 32768;
constexpr int OFF_SIDE = 2 * SLOT;
__host__ __device__ constexpr int kv_a(int kb) { return (kb < 6 ? kb : 3 * kb - 10) * UNIT; }
__host__ __device__ constexpr int kv_b(int s) { return (s == 2 ? 6 : 9 + 3 * s) * UNIT; }
__host__ __device__ constexpr int q_aw(int s) { return (3 * s + (s & 1)) * UNIT; }
__host__ __device__ constexpr int q_b(int s) { return (3 * s + 2 - 2 * (s & 1)) * UNIT; }
__host__ __device__ constexpr int k_slot(int j, int r) { return (j < 2 ? 2 * j : (r == 2 ? 0 : 3 + r)) * SLOT; }
__host__ __device__ constexpr int v_slot(int j) { return (6 - (j & 1)) * SLOT; }
__host__ __device__ constexpr int r3(int st) { return ((0x654130 >> (4 * st)) & 7) * SLOT; }
constexpr int OFF_BAR = 229376;
constexpr int OFF_MISC = OFF_BAR + 512;
constexpr int SMEM_BYTES = OFF_MISC + 2080 + TL_EXTRA;
constexpr int OFF_RSTAT = OFF_MISC + 1056;
enum : int {
  B_FULL1 = 0, B_FULLQ = 3, B_FULLB = 7, B_KF = 8, B_VF = 11, B_FULL3 = 13, B_WF = 19, B_DEP = 21, B_OUT2 = 26, B_PF = 27, B_SET = 28,
  B_SET2 = 29, B_LNGO = 30, B_WR = 31,
  B_KE = 32, B_VE = 35, B_WE = 37, B_PUB = 39, B_OUT = 45,
  B_EMPTY1 = 46, B_EMPTYQ = 49, B_X = 53, B_EMPTY3 = 57,
  B_NUM = 63
};
constexpr int PRE = 3;
#define LN_PF 99
#define LN_GO 5
#define PFW 9
#define PFX 9
#define PFKV 0
#define SYNC3 0
#define SYNC3A 5
#define SYNC3W 6
#define CTX_ST "st.global.cs.v4.u32"
#define PF3 0
#define PD3 7
#define PFF 0
#define PWAIT mbar_wait_c
#define GRAB0 4
#define SIDE_NS 400
#define REL_AT 3
#define STARTV 2
#define SET_NS 40
#define WRAP 16 - j
#define EP1 3
#define MASKV 0
#define PACE 0
#define TRIMS 1
#define TRIMPV 1
#define KTEST 1
#define DELAY0 1
#define AWAIT mbar_wait_c
#define KWAIT mbar_wait_c
#define PFJ 16
#define PFQ 3
#define PFP 1
#define PFQ0 4
#define PFP0 5
#define PUT0 2
#define PUTD 2
#define NOFFN0 0
#define WEF 1
#define OUTU 1
#define YDLY 800
#define YDLY0 1500
#define PDLY 250
#define LATEW 0
#define PFD 7
#define EFM 1
#define PFC 0
#define PFO 2
#define KV_FIRST 1
constexpr int WIN = 6;
constexpr int OFF_STG = r3(0), OFF_SCR = r3(1);
#define PF_KB 54
#define PF_NS 300
#define GRABD 6
#define XGRAB 44
#define SET_KB 44
constexpr int OUT_UNROLL = OUTU;
struct Params {
  CUtensorMap xn, ckv, wq, wk, wv, kv_ld, ctx_ld, wo, x, wd, wg, wu;
};

__global__ void __cluster_dims__(2, 1, 1) __launch_bounds__(384, 1)
fused_kernel(const __grid_constant__ Params p, const __nv_bfloat16* __restrict__ x, const __nv_bfloat16* __restrict__ wq,
             const __nv_bfloat16* __restrict__ w_r, const __nv_bfloat16* __restrict__ wdown,
             __nv_bfloat16* __restrict__ out, uint32_t zero) {
  extern __shared__ __align__(1024) uint8_t sp[];
  const uint32_t sb = s2u(sp);
  const uint32_t bar = sb + OFF_BAR;
  auto B = [&](int i) { return bar + 8 * i; };
  const int tid = threadIdx.x, warp = __shfl_sync(~0u, tid >> 5, 0), wg = warp >> 2, lane = tid & 31;
  const int cta = blockIdx.x, rank = cta & 1, cl = cta >> 1;
  const int mp = cl < 4 ? 1 : (cl < 36 ? (cl & 7) : (0x3207654 >> (4 * ((cl - 36) % 7))) & 7);
  const int gq = cl < 4 ? 4 + cl : (cl < 36 ? (cl - 4) >> 3 : 4 + (cl - 36) / 7);
  const int mt = 2 * mp + rank;
  const int qa = 15 - gq;
  const int ta = gq ? gq : 15, tb = 15 - ta;
  const int rid = mt * 8 + gq;
  const int fid = mt * 7 + gq - NOFFN0;
  const bool ffn = NOFFN0 ? gq > 0 : gq < 7;
  TL(0, 0, warp == 4);
  auto load_pre = [&](int kb) {
    e_expect(B(B_FULL1 + kb), 3 * UNIT);
    tma_ld2(sb + kv_a(kb), &p.ckv, B(B_FULL1 + kb), kb * 64, mt * 128);
    tma_ld3(sb + kv_b(kb) + rank * UNIT, &p.wk, B(B_FULL1 + kb), 0, kb * 64, (gq + KV_FIRST * 8) * 4 + rank * 2);
    tma_ld3(sb + kv_b(kb) + UNIT - rank * UNIT, &p.wk, B(B_FULL1 + kb), 0, kb * 64, (gq + KV_FIRST * 8) * 4 + 2 - rank * 2);
  };
  if (warp == 0) {
    e_init(B(B_FULL1), 1);
    asm volatile("fence.mbarrier_init.release.cluster;" ::: "memory");
    load_pre(0);
#pragma unroll
    for (int kb = 1; kb < PRE; kb++) e_init(B(B_FULL1 + kb), 1);
  } else {
#pragma unroll 1
    for (int i = PRE - 1 + warp; i < B_NUM; i += 11) e_init(B(i), i >= B_EMPTY1 ? 16 : (i >= B_KE ? 8 : (i == B_WR ? 2 : 1)));
  }
  asm volatile("fence.mbarrier_init.release.cluster;" ::: "memory");
  cluster_arrive();
  const int rid0 = rid, warp0 = warp;
  if (wg == 0) {
    reg_dealloc<40>();
    uint4* const xr = g_xr + rid * XR_SIZE;
    if (warp == 0) {
#pragma unroll 1
      for (int kb = STARTV ? 1 : 0; kb < PRE; kb++) load_pre(kb);
      if (mt >= 2 * PRE) tma_pf3(&p.wk, 0, (mt >> 1) * 64, (gq + KV_FIRST * 8) * 4 + (mt & 1) * 2);
      if (gq >= PRE) tma_pf2(&p.ckv, gq * 64, mt * 128);
      prefetch_tm(&p.wv); prefetch_tm(&p.wq); prefetch_tm(&p.xn); prefetch_tm(&p.kv_ld);
    }
    __syncwarp();
    cluster_wait();
    auto side_piece = [&](int c, int piece) {
      const uint32_t fb = B(B_WF + (c & 1));
      if (piece == 0) e_expect(fb, UNIT);
      ((EFM & 1) ? tma_ld2_ef : tma_ld2)(sb + OFF_SIDE + (c & 1) * UNIT + piece * 4096, (piece & 2) ? &p.wg : &p.wu, fb, fid * 32, c * 128 + (piece & 1) * 64);
    };
    if (warp == 0) {
      {
        int st = 0; uint32_t ph = 1;
#pragma unroll 1
        for (int i = 0; i < 32; i++) {
          const int t = i >> 3, kb = i & 7;
          if (i >= PRE) {
            const uint32_t fb = B(B_FULL1 + st);
            KWAIT(B(B_EMPTY1 + st), ph);
            e_expect(fb, t == 0 ? 3 * UNIT : 2 * UNIT);
            if (t == 0) tma_ld2(sb + kv_a(kb), &p.ckv, fb, kb * 64, mt * 128);
            ((EFM & 16) ? tma_ld3_mc_ef : tma_ld3_mc)(sb + kv_b(st) + rank * UNIT, (t & 1) ? &p.wv : &p.wk, fb, 0, kb * 64, (gq + ((t >> 1) ^ KV_FIRST) * 8) * 4 + rank * 2, 3);
          }
          if (i == LN_PF || i == LN_PF + 1) l2_prefetch(x + (size_t)cta * 16 * DM + (i - LN_PF) * 8 * DM, 16384);
          if (i == LN_GO) e_arrive(B(B_LNGO));
          if (kb == 0 && t < 3) tma_pf3((t & 1) ? &p.wk : &p.wv, 0, (mt >> 1) * 64, (gq + (((t + 1) >> 1) ^ KV_FIRST) * 8) * 4 + (mt & 1) * 2);
          if (kb < 2 && t == 3) tma_pf3(&p.wq, 0, (gq + 8 * kb) * 64, mt * 2);
          if (++st == 3) { st = 0; ph ^= 1; }
        }
        prefetch_tm(&p.ctx_ld); prefetch_tm(&p.wo); prefetch_tm(&p.wd); prefetch_tm(&p.x); prefetch_tm(&p.wg); prefetch_tm(&p.wu);
        PWAIT(B(B_DEP + 0), 0);
        uint32_t kpar = 7, vpar = 3;
        auto load_aw = [&](int kb, int head) {
          const uint32_t d = sb + q_aw(kb & 3), fb = B(B_FULLQ + (kb & 3));
          tma_ld2_mc(d + rank * 8192, &p.xn, fb, kb * 64, ta * 128 + rank * 64, 3);
          ((EFM & 16) ? tma_ld3_ef : tma_ld3)(d + UNIT, &p.wq, fb, 0, kb * 64, head * 2);
        };
        auto load_b = [&](int kb, uint32_t fb) { tma_ld2_mc(sb + q_b(kb & 3) + rank * 8192, &p.xn, fb, kb * 64, tb * 128 + rank * 64, 3); };
        auto load3 = [&](int kb, int s) {
          const uint32_t d = sb + r3(s), fb = B(B_FULL3 + s);
          e_expect(fb, SLOT);
          ((EFM & 4) ? tma_ld2_ef : tma_ld2)(d, &p.ctx_ld, fb, kb * 64, mt * 128);
          ((EFM & 2) ? tma_ld3_mc_ef : tma_ld3_mc)(d + UNIT + rank * 8192, &p.wo, fb, 0, kb * 64, gq * 2 + rank, 3);
        };
#pragma unroll 1
        for (int half = 0; half < 2; half++) {
          const int head = mt + 16 * half;
#pragma unroll 1
          for (int kb = 2 * half; kb < 16; kb++) {
            if (kb >= 4) KWAIT(B(B_EMPTYQ + (kb & 3)), ((kb >> 2) & 1) ^ 1);
            else if (half) PWAIT(B(B_X + 2), 0);
            else if (kb > 0) PWAIT(B(B_EMPTY1 + (kb + 1) % 3), kb == 1);
            e_expect(B(B_FULLQ + (kb & 3)), 3 * UNIT);
            load_aw(kb, head);
            load_b(kb, B(B_FULLQ + (kb & 3)));
          }
          PWAIT(B(B_DEP + 1 + half), 0);
          tma_pf3(&p.kv_ld, 0, 0, head * 2);
          auto load_v = [&](int j) {
            const int r = j & 1;
            AWAIT(B(B_VE + r), (vpar >> r) & 1);
            vpar ^= 1 << r;
            e_expect(B(B_VF + r), SLOT);
            ((EFM & 8) ? tma_ld3_ef : tma_ld3)(sb + v_slot(j), &p.kv_ld, B(B_VF + r), 0, SEQ + (j > qa ? WRAP : j) * 128, head * 2);
          };
          int r = 0;
#pragma unroll 1
          for (int j = 0; j < 17; j++) {
            if (j < 2) PWAIT(B(B_EMPTYQ + j), 1);
            if (j == 2) PWAIT(B(B_KE), kpar & 1);
            AWAIT(B(B_KE + r), (kpar >> r) & 1);
            kpar ^= 1 << r;
            e_expect(B(B_KF + r), SLOT);
            ((EFM & 8) ? tma_ld3_ef : tma_ld3)(sb + k_slot(j, r), &p.kv_ld, B(B_KF + r), 0, (j > qa ? WRAP : j) * 128, head * 2);
            if (++r == 3) r = 0;
            if (j == 2) PWAIT(B(B_EMPTYQ + 3), 1);
            if (j != 1) load_v(j ? j - 1 : 0);
            if (j == PFJ) {
              if (half == 0) {
                if (PFQ & 1) tma_pf3(&p.wq, 0, (PFQ0 + gq) * 64, (mt + 16) * 2);
                if (PFQ & 2) tma_pf2(&p.xn, (PFQ0 + (mp & 3)) * 64, ((mp & 4) ? qa : gq) * 128 + rank * 64);
              } else {
                PWAIT(B(B_DEP + 3), 0);
                if (PFP & 1) tma_pf3(&p.wo, 0, (PFP0 + mp) * 64, gq * 2 + rank);
                if (PFP & 2) tma_pf2(&p.ctx_ld, (PFP0 + gq) * 64, mt * 128);
              }
            }
            if (half && j >= 17 - PFC && ffn) tma_pf2(((j - 1) & 2) ? &p.wg : &p.wu, fid * 32, (2 + ((j - 17 + PFC) >> 2)) * 128 + ((j - 1) & 1) * 64);
            if (half && j >= 16 - PFO && j < 16) tma_pf3(&p.wo, 0, (PFP0 + mp + 8 * (16 - j)) * 64, gq * 2 + rank);
            if (half == 0) {
            } else if (ffn && j >= 5 && j < 13) {
              side_piece((j - 5) >> 2, (j - 5) & 3);
            }
          }
          PWAIT(B(B_X + 0), half);
          if (half == 0) {
            for (int kb = 0; kb < 2; kb++) { e_expect(B(B_FULLQ + kb), 2 * UNIT); load_aw(kb, mt + 16); }
          } else {
            load3(0, 0);
          }
          PWAIT(B(B_X + 1), half);
          if (half) load3(1, 1);
          load_v(16);
          if (gq == 0) PWAIT(B(B_X + 2), half);
          if (half == 0) { e_expect(B(B_FULLB), 2 * UNIT); load_b(0, B(B_FULLB)); load_b(1, B(B_FULLB)); }
        }
        st = 2; ph = 1;
#pragma unroll 1
        for (int kb = 2; kb < 64; kb++) {
          if (kb == 32) PWAIT(B(B_DEP + 4), 0);
          if (kb >= 6) PWAIT(B(B_EMPTY3 + st), ph);
          else if (kb == 3 || kb == 5) PWAIT(B(B_X + (kb + 1) / 2), 1);
          load3(kb, st);
          if (++st == 6) { st = 0; ph ^= 1; }
          if (kb == PF_KB) e_arrive(B(B_PF));
          if (kb == SET_KB) e_arrive(B(B_SET));
          if (kb == 58) l2_prefetch(xr, XR_CAND * 16);
        }
        if (ffn) {
#pragma unroll 1
          for (int j = 0; j < 2; j++) {
            PWAIT(B(B_EMPTY3 + 4 + j), 1);
            e_expect(B(B_FULL3 + 4 + j), SLOT);
            tma_ld3(sb + r3(4 + j), &p.wd, B(B_FULL3 + 4 + j), 0, fid * 32, 8 * j);
          }
        }
        const uint4* kp = g_xr + ((lane >> 1) * 8 + gq) * XR_SIZE + XR_KEY + (lane & 1) * 2;
        PWAIT(B(B_OUT), 0);
        uint4 kv[2];
        poll_chunks(kv, kp, 1);
        const uint32_t a1 = max(kv[0].x, kv[0].z), a2 = max(min(kv[0].x, kv[0].z), max(kv[0].y, kv[0].w));
        const uint32_t b1 = max(kv[1].x, kv[1].z), b2 = max(min(kv[1].x, kv[1].z), max(kv[1].y, kv[1].w));
        const uint32_t k1 = max(a1, b1), k2 = max(min(a1, b1), max(a2, b2));
        const uint32_t m1 = __reduce_max_sync(~0u, k1);
        const uint32_t m2 = __reduce_max_sync(~0u, k1 == m1 ? k2 : k1);
        if (lane == 0) {
          *reinterpret_cast<uint2*>(sp + OFF_MISC) = make_uint2(m1, m2);
          mbar_arrive(B(B_OUT2));
        }
        if (rid == 127) { g_cnt[lane] = 0; g_cnt[32 + lane] = 0; }
      }
    } else {
      if (warp >= 2) {
#pragma unroll 1
        for (int i = tid - 64; i < XR_CAND; i += 64) xr[i] = make_uint4(~0u, ~0u, ~0u, ~0u);
        if (warp == 2) { __syncwarp(); if (lane == 0) mbar_arrive(B(B_WR)); }
      }
      if (warp == 3) {
        float ws = 0.f;
#pragma unroll
        for (int j = 0; j < 4; j++) {
          const uint4 q = __ldg(reinterpret_cast<const uint4*>(w_r) + j * 32 + lane);
          ws += bf_lo(q.x) + bf_hi(q.x) + bf_lo(q.y) + bf_hi(q.y) + bf_lo(q.z) + bf_hi(q.z) + bf_lo(q.w) + bf_hi(q.w);
        }
#pragma unroll
        for (int o = 16; o; o >>= 1) ws += __shfl_xor_sync(~0u, ws, o);
        uint2* tab = reinterpret_cast<uint2*>(sp + OFF_MISC + 512);
        tab[lane] = make_uint2(0x3F803F80u, 0x3F803F80u);
        tab[32 + lane] = __ldg(reinterpret_cast<const uint2*>(w_r + gq * 128) + lane);
        if (lane == 0) *reinterpret_cast<float*>(sp + OFF_MISC + 1024) = ws;
        __syncwarp();
        if (lane == 0) mbar_arrive(B(B_WR));
      }
      __syncwarp();
      mbar_wait_u(B(B_LNGO), 0);
#pragma unroll 1
      for (int r = warp == 2 ? 0 : (warp + 1) >> 1; r < 16; r += 3) {
        const uint4* src = reinterpret_cast<const uint4*>(x + (size_t)(cta * 16 + r) * DM) + lane;
        uint4 v[4];
#pragma unroll
        for (int j = 0; j < 4; j++) v[j] = __ldg(src + j * 32);
        float a0 = 0.f, a1 = 0.f, b0 = 0.f, b1 = 0.f;
#pragma unroll
        for (int j = 0; j < 4; j++) {
          const uint32_t u[4] = {v[j].x, v[j].y, v[j].z, v[j].w};
#pragma unroll
          for (int i = 0; i < 4; i++) { const float a = bf_lo(u[i]), b = bf_hi(u[i]); a0 += a; a1 += b; b0 = fmaf(a, a, b0); b1 = fmaf(b, b, b1); }
        }
        a0 += a1; b0 += b1;
#pragma unroll
        for (int o = 16; o; o >>= 1) { a0 += __shfl_xor_sync(~0u, a0, o); b0 += __shfl_xor_sync(~0u, b0, o); }
        const float mean = a0 * (1.f / DM);
        float mb, inv;
        ln_round(mean, fmaxf(fmaf(b0, 1.f / DM, -mean * mean), 0.f), mb, inv);
        const uint32_t nm2 = pack_bf16(-mb, -mb);
        uint4* dst = reinterpret_cast<uint4*>(g_xn + (size_t)(cta * 16 + r) * DM) + lane;
#pragma unroll
        for (int j = 0; j < 4; j++) {
          dst[j * 32] = make_uint4(ln_apply(v[j].x, nm2, inv), ln_apply(v[j].y, nm2, inv), ln_apply(v[j].z, nm2, inv), ln_apply(v[j].w, nm2, inv));
          sched_fence();
        }
      }
      __syncwarp();
      if (lane == 0) {
        fence_gpu();
        red_add(&g_cnt[C_LN + (cta >> 3)], 1);
        TL(0, 20 + warp, true);
        if (warp == 3) {
          spin_until_ge<true>(&g_cnt[C_LN + gq], 24);
#pragma unroll 1
          for (int i = 0; i < 5; i++) {
            const int c = i == 0 ? C_LN + qa : (i < 3 ? C_KV + (i - 1) * 8 + mp : C_CTX + (i - 3) * 16 + mt);
            spin_until_ge<true>(&g_cnt[c], i == 0 ? 24 : 16);
            fence_async_all();
            mbar_arrive(B(B_DEP + i));
          }
        } else if (warp == 1) {
          mbar_wait(B(B_WR), 0);
#pragma unroll 1
          for (int i = 0; i < 6; i++) {
            const int c = i < 2 ? C_KV + gq + (i ^ KV_FIRST) * 8 : C_CTX + ((i - 2) >> 1) * 16 + ((i & 1) ? tb : ta);
            mbar_wait(B(B_PUB + i), 0);
            fence_gpu();
            red_add(&g_cnt[c], 1);
          }
        }
      }
      __syncwarp();
      if (warp == 2) {
#pragma unroll 1
        for (int c = 2; c < WIN + 4; c++) {
          mbar_wait_u(B(B_WE + (c & 1)), ((c >> 1) & 1) ^ 1);
          if (c == WIN || c == WIN + 1) {
            e_expect(B(B_WF + (c & 1)), UNIT);
            ((EFM & 1) ? tma_ld3_ef : tma_ld3)(sb + OFF_SIDE + (c & 1) * UNIT, &p.x, B(B_WF + (c & 1)), 0, mt * 128 + (c & 1) * 64, gq * 2);
          } else if (ffn) {
#pragma unroll 1
            for (int i = 0; i < 4; i++) { side_piece(c < WIN ? c : c - 2, i); __nanosleep(SIDE_NS); }
          }
        }
      } else if (warp == 1) {
        mbar_wait_u(B(B_SET), 0);
#pragma unroll 1
        for (int i = XR_CAND + lane; i < XR_SIZE; i += 32) { xr[i] = make_uint4(~0u, ~0u, ~0u, ~0u); __nanosleep(SET_NS); }
        __syncwarp();
        if (lane == 0) { fence_gpu(); mbar_arrive(B(B_SET2)); }
      } else {
        mbar_wait_u(B(B_PF), 0);
#pragma unroll 1
        for (int i = 0; i < PFD; i++) {
          asm volatile("prefetch.global.L2 [%0];" ::"l"((const char*)wdown + (size_t)cta * 57344 + (i * 32 + lane) * 128));
          __nanosleep(PF_NS);
        }
      }
      __syncwarp();
      mbar_wait_u(B(B_OUT), 0);
#pragma unroll OUT_UNROLL
      for (int i = warp - 1; i < 66; i += 3) {
        const int row = 2 * i + (lane >> 4);
        const uint2 rs = *reinterpret_cast<const uint2*>(sp + OFF_RSTAT + (row & 127) * 8);
        const uint4 v = lds128(sb + OFF_STG + ((row >> 6) & 1) * 16384 + ((lane & 15) >> 3) * 8192 + (row & 63) * 128 + (((lane ^ row) & 7) << 4));
        const float inv = __uint_as_float(rs.y);
        if ((int)rs.y >= 0 && row < 128)
          *reinterpret_cast<uint4*>(out + (size_t)(mt * 128 + row) * DM + gq * 128 + (lane & 15) * 8) =
              make_uint4(hadd2_bf(v.x, ln_apply(v.x, rs.x, inv)), hadd2_bf(v.y, ln_apply(v.y, rs.x, inv)),
                         hadd2_bf(v.z, ln_apply(v.z, rs.x, inv)), hadd2_bf(v.w, ln_apply(v.w, rs.x, inv)));
      }
      TL(2, 25, warp == 1);
    }
    __syncwarp();
    cluster_arrive();
    cluster_wait();
  } else {
    reg_alloc<232>();
    const int rid_c = rid0 + zero, warp_c = warp0 + zero;
    const int lane = fresh_lane(), rid = rid_c, mt = rid >> 3, gq = rid & 7, qa = 15 - gq, ta = gq ? gq : 15, tb = 15 - ta;
    const int warp = warp_c, cw = warp - 4, w = cw >> 2;
    cluster_wait();
    auto publish = [&](int i) { __syncwarp(); e_arrive(B(B_PUB + i)); };
    auto release2 = [&](uint32_t b, bool cond = true) { mbar_arrive_both(b, lane, cond); };
    AtState s;
    const uint32_t dA = mk_desc(sb + w * 8192, 16);
    const uint32_t dW = mk_desc(sb, 8192);
    auto mma_kb = [&](float (&d)[64], uint32_t a, uint32_t b, int accum) {
      static_for<4>([&](auto k) { mma_n128_ss<1, k * 32, k * 2048>(d, dA + (a >> 4), dW + (b >> 4), k == 0 ? accum : 1); });
    };
    auto mma_kc = [&](float (&d)[64], auto a, auto b, int accum) {
      static_for<4>([&](auto k) { mma_n128_ss<1, decltype(a)::value + k * 32, decltype(b)::value + k * 2048>(d, dA, dW, k == 0 ? accum : 1); });
    };
    auto issue_q = [&](int kb, auto accum) {
      const int st = kb & 3;
      mbar_wait_c(B(B_FULLQ + st), (kb >> 2) & 1);
      wg_fence();
      mma_kb(s.S, q_aw(st), q_aw(st) + UNIT, accum);
      wg_commit();
      if (accum) {
        wg_wait<1>();
        release2(B(B_EMPTYQ + ((kb - 1) & 3)));
        wg_fence();
      }
      mma_kb(s.O, q_b(st), q_aw(st) + UNIT, accum);
      wg_commit();
    };
    {
      uint4 pk[16];
      __nv_bfloat16* pdst = g_kv;
      auto put = [&](int i) { __stcs(reinterpret_cast<uint4*>(pdst + (i & 1) * 8 * NQ + (i >> 1) * 32), pk[i]); };
      float acc1[128];
      TL(0, 1, warp == 4);
      int st = 0; uint32_t ph = 0;
      auto issue = [&](int kb, int accum) {
        mbar_wait_c(B(B_FULL1 + st), ph);
        wg_fence();
        static_for<4>([&](auto k) { mma_n256_ss<1, k * 32, k * 2048>(acc1, dA + (kv_a(kb) >> 4), dW + (kv_b(st) >> 4), k == 0 ? accum : 1); });
        wg_commit();
      };
#pragma unroll 1
      for (int t = 0; t < 4; t++) {
        issue(0, 0);
        TL(0, 2 + 2 * t, warp == 4);
        if (t > 0) { put(0); put(1); }
        int prev = st;
        if (++st == 3) { st = 0; ph ^= 1; }
#pragma unroll 1
        for (int kb = 1; kb < 8; kb++) {
          if (kb == 7 && w == 1) bar_sync(5, 256);
          issue(kb, 1);
          if (kb == 7 && w == 0) bar_arrive(5, 256);
          if (t > 0) {
#pragma unroll
            for (int i = 1; i < 8; i++) if (kb == i) { put(2 * i); put(2 * i + 1); }
            if (kb == 7 && t == 2) publish(0);
          }
          wg_wait<1>();
          TK(24 + t * 8 + kb - 1);
          release2(B(B_EMPTY1 + prev));
          prev = st;
          if (++st == 3) { st = 0; ph ^= 1; }
        }
        pdst = g_kv + (size_t)((t & 1) * SEQ + mt * 128 + cw * 16 + (lane >> 2)) * NQ + (gq + ((t >> 1) ^ KV_FIRST) * 8) * 256 + (lane & 3) * 8;
        wg_wait<0>();
        TK(24 + t * 8 + 7);
        fence_regs(acc1);
        release2(B(B_EMPTY1 + prev));
        TL(0, 3 + 2 * t, warp == 4);
#pragma unroll
        for (int a = 0; a < 8; a++)
#pragma unroll
          for (int h = 0; h < 2; h++)
            pk[2 * a + h] = make_uint4(pack_bf16(acc1[16 * a + 2 * h], acc1[16 * a + 2 * h + 1]), pack_bf16(acc1[16 * a + 4 + 2 * h], acc1[16 * a + 5 + 2 * h]),
                                       pack_bf16(acc1[16 * a + 8 + 2 * h], acc1[16 * a + 9 + 2 * h]), pack_bf16(acc1[16 * a + 12 + 2 * h], acc1[16 * a + 13 + 2 * h]));
      }
      issue_q(0, IC<0>{});
      TL(0, 10, warp == 4);
      put(0); put(1);
#pragma unroll 1
      for (int kb = 1; kb < 8; kb++) {
        issue_q(kb, IC<1>{});
        TK(66 + kb - 1);
#pragma unroll
        for (int i = 1; i < 8; i++) if (kb == i) { put(2 * i); put(2 * i + 1); }
      }
      publish(1);
      TL(0, 11, warp == 4);
    }
    __nv_bfloat16* cdst;
    uint32_t redo = 0;
    auto put_ctx = [&](int i, bool cond) {
      asm volatile("{\n.reg .pred p;\nsetp.ne.u32 p, %5, 0;\n@p " CTX_ST " [%0], {%1,%2,%3,%4};\n}" ::"l"(cdst + (i & 1) * 8 * NQ + (i >> 1) * 32),
                   "r"(s.P[4 * i]), "r"(s.P[4 * i + 1]), "r"(s.P[4 * i + 2]), "r"(s.P[4 * i + 3]), "r"((uint32_t)(cond && !(redo & 2))) : "memory");
    };
    {
      const int wrow = cw * 16;
      const uint32_t dK = mk_desc(sb, 16), dV = mk_desc(sb, 16384);
      uint32_t kph = 0, vph = 0;
      auto q_store = [&](const float (&d)[64]) {
        const int r0 = lane >> 2;
        const uint32_t a = sb + SLOT + (wrow + r0) * 128 + (((lane & 3) ^ (((r0 & 1) << 2) | (r0 >> 1))) << 4);
#pragma unroll
        for (int i = 0; i < 8; i++) {
          const float* o = d + 16 * (i >> 1) + 2 * (i & 1);
          asm volatile("st.shared.v4.u32 [%0], {%1,%2,%3,%4};" ::"r"((a ^ ((i & 2) << 5)) + (i >> 2) * UNIT + (i & 1) * 1024),
                       "r"(pack_bf16(o[0] * AT_C, o[1] * AT_C)), "r"(pack_bf16(o[4] * AT_C, o[5] * AT_C)),
                       "r"(pack_bf16(o[8] * AT_C, o[9] * AT_C)), "r"(pack_bf16(o[12] * AT_C, o[13] * AT_C)) : "memory");
        }
        __syncwarp();
      };
      auto q_load = [&](auto k0, auto k1) {
        const uint32_t a = sb + SLOT + (wrow + (lane & 15)) * 128 + (((lane >> 4) ^ (((lane & 1) << 2) | ((lane >> 1) & 3))) << 4);
#pragma unroll
        for (int k = k0; k < k1; k++)
          asm volatile("ldmatrix.sync.aligned.m8n8.x4.shared.b16 {%0,%1,%2,%3}, [%4];"
                       : "=r"(s.Q[4 * k]), "=r"(s.Q[4 * k + 1]), "=r"(s.Q[4 * k + 2]), "=r"(s.Q[4 * k + 3]) : "r"((a ^ ((k & 3) << 5)) + (k >> 2) * UNIT) : "memory");
      };
      auto q_load_if = [&](auto k, bool cond, float after) {
        const uint32_t a = sb + SLOT + (wrow + (lane & 15)) * 128 + (((lane >> 4) ^ (((lane & 1) << 2) | ((lane >> 1) & 3))) << 4);
        asm volatile("{\n.reg .pred p;\nsetp.ne.u32 p, %5, 0;\n@p ldmatrix.sync.aligned.m8n8.x4.shared.b16 {%0,%1,%2,%3}, [%4];\n}"
                     : "+r"(s.Q[4 * k]), "+r"(s.Q[4 * k + 1]), "+r"(s.Q[4 * k + 2]), "+r"(s.Q[4 * k + 3])
                     : "r"((a ^ ((k & 3) << 5)) + (k >> 2) * UNIT + (__float_as_uint(after) >> 31)), "r"((uint32_t)cond) : "memory");
      };
      auto issue_s = [&](uint32_t off) {
        static_for<8>([&](auto k) { mma_n128_rs<0, (k >> 2) * 16384 + (k & 3) * 32>(s.S, s.Q + 4 * k, dK + (off >> 4), k != 0); });
        wg_commit();
      };
      auto issue_pv = [&](int jv, int accum, bool upper) {
        mbar_wait_c(B(B_VF + (jv & 1)), (vph >> (jv & 1)) & 1);
        vph ^= 1 << (jv & 1);
        wg_fence();
        static_for<4>([&](auto k) { mma_n128_rs<1, k * 2048>(s.O, s.P + 4 * k, dV + (v_slot(jv) >> 4), k == 0 ? accum : 1); });
        wg_commit();
        if (!TRIMPV || upper) {
          if (TRIMPV) wg_fence();
          static_for<4>([&](auto k) { mma_n128_rs<1, (k + 4) * 2048>(s.O, s.P + 16 + 4 * k, dV + (v_slot(jv) >> 4), 1); });
          wg_commit();
        } else {
          asm volatile("wgmma.fence.sync.aligned;\nwgmma.commit_group.sync.aligned;" ::: "memory");
        }
      };
      if (w == 1) bar_arrive(1, 256);
#pragma unroll 1
      for (int half = 0; half < 2; half++) {
        const int head = mt + 16 * half;
        redo = 0;
        float inv[2];
        auto ep_prep = [&]() {
          float l0 = s.l[0] + s.l[1], l1 = s.l[2] + s.l[3];
          l0 += __shfl_xor_sync(~0u, l0, 1); l1 += __shfl_xor_sync(~0u, l1, 1);
          l0 += __shfl_xor_sync(~0u, l0, 2); l1 += __shfl_xor_sync(~0u, l1, 2);
          asm("rcp.approx.ftz.f32 %0, %1;" : "=f"(inv[0]) : "f"(l0));
          asm("rcp.approx.ftz.f32 %0, %1;" : "=f"(inv[1]) : "f"(l1));
          return __any_sync(~0u, !(fminf(l0, l1) >= L_MIN && l0 + l1 <= L_MAX));
        };
        auto ep_out = [&](auto i0, auto i1) {
          __nv_bfloat16* dst = g_ctx + (size_t)(ta * 128 + wrow + (lane >> 2)) * NQ + head * 128 + (lane & 3) * 8;
#pragma unroll
          for (int i = i0; i < i1; i++) {
            const float* o = s.O + 16 * (i >> 1) + 2 * (i & 1);
            const float c = inv[i & 1];
            asm volatile(CTX_ST " [%0], {%1,%2,%3,%4};" ::"l"(dst + (i & 1) * 8 * NQ + (i >> 1) * 32), "r"(pack_bf16(o[0] * c, o[1] * c)),
                         "r"(pack_bf16(o[4] * c, o[5] * c)), "r"(pack_bf16(o[8] * c, o[9] * c)), "r"(pack_bf16(o[12] * c, o[13] * c)) : "memory");
          }
        };
        auto ep_rest = [&]() {
          ep_out(IC<EP1>{}, IC<8>{});
          if (!__any_sync(~0u, redo)) publish(2 + 2 * half);
          fence_regs(s.O);
        };
#pragma unroll 1
        for (int kb = 8; kb < 14; kb++) {
          issue_q(kb, IC<1>{});
          TK(66 + half * 24 + kb - 1);
        }
        TL(1, 20 * half + 0, warp == 4);
        mbar_wait_c(B(B_FULLQ + 2), 1);
        mbar_wait_c(B(B_FULLQ + 3), 1);
        bar_sync(1 + w, 256);
        wg_fence();
        mma_kc(s.S, IC<q_aw(2)>{}, IC<q_aw(2) + UNIT>{}, 1);
        wg_commit();
        wg_wait<1>();
        TK(66 + half * 24 + 13);
        release2(B(B_EMPTYQ + 1));
        wg_fence();
        mma_kc(s.S, IC<q_aw(3)>{}, IC<q_aw(3) + UNIT>{}, 1);
        wg_commit();
        bar_arrive(2 - w, 256);
        bar_sync(6 + w, 128);
        wg_wait<0>();
        TK(66 + half * 24 + 14);
        fence_regs(s.S);
        q_store(s.S);
        q_load(IC<0>{}, IC<8>{});
        TL(1, 20 * half + 1, warp == 4);
        mbar_wait_c(B(B_KF), kph & 1);
        kph ^= 1;
        bar_sync(1 + w, 256);
        fence_regs(s.S); fence_regs(s.O); fence_regs(s.Q);
        wg_fence();
        issue_s(k_slot(0, 0));
        mma_kc(s.O, IC<q_b(2)>{}, IC<q_aw(2) + UNIT>{}, 1);
        mma_kc(s.O, IC<q_b(3)>{}, IC<q_aw(3) + UNIT>{}, 1);
        wg_commit();
        bar_arrive(2 - w, 256);
        wg_wait<1>();
        fence_regs(s.S);
        e_arrive(B(B_KE));
        s.l[0] = s.l[1] = s.l[2] = s.l[3] = 0.f;
        at_exp<0, 48>(s);
        at_pack<0, 22>(s);
        sched_fence();
        wg_wait<0>();
        fence_regs(s.O); fence_regs(s.Q);
        release2(B(B_EMPTYQ + 2)); release2(B(B_EMPTYQ + 3));
        at_exp<48, 64>(s);
        at_pack<22, 32>(s);
        q_store(s.O);
        TL(1, 20 * half + 2, warp == 4);
        int kr = 1;
        bool kok = false;
        inv[0] = inv[1] = 0.f;
        const int db = gq ? qa : 16;
#pragma unroll 1
        for (int j = 1; j < 17; j++) {
          const bool diag = j == ta || j == db;
          TC(w, j + 17 * half, 0);
          if (!kok) mbar_wait_c(B(B_KF + kr), (kph >> kr) & 1);
          kph ^= 1 << kr;
          if (j == ta + 2) ep_out(IC<0>{}, IC<EP1>{});
          bar_sync(1 + w, 256);
          TC(w, j + 17 * half, 2);
          fence_regs(s.S); fence_regs(s.O); fence_regs(s.P); fence_regs(s.Q);
          const uint32_t ke = B(B_KE + kr), ko = k_slot(j, kr);
          if (++kr == 3) kr = 0;
          auto issue_rest = [&](auto trimmed) {
            TC(w, j + 17 * half, 1);
            if (j == ta + 1) {
              if (ep_prep()) redo = 1;
              s.l[0] = s.l[1] = s.l[2] = s.l[3] = 0.f;
            }
            if (!trimmed && j == ta + 2) ep_rest();
            TC(w, j + 17 * half, 3);
            issue_pv(j - 1, j != 1 && j != ta + 2, w == 1 || (j != ta + 1 && j != db + 1));
            bar_arrive(2 - w, 256);
          };
          auto s_done = [&]() {
            wg_wait<2>();
            TC(w, j + 17 * half, 4);
            fence_regs(s.S); fence_regs(s.Q);
            e_arrive(ke);
            release2(B(B_X + j - 14), j == 14 || j == 15);
          };
          auto pv_half = [&]() { sched_fence(); wg_wait<1>(); fence_regs(s.P); };
          auto pv_done = [&]() {
            sched_fence();
            wg_wait<0>();
            fence_regs(s.O); fence_regs(s.P);
            e_arrive(B(B_VE + ((j - 1) & 1)));
            release2(B(B_X + 2), j == 16);
            kok = KTEST && mbar_test(B(B_KF + kr), (kph >> kr) & 1);
          };
          if (diag && w == 0) {
            wg_fence();
            static_for<8>([&](auto k) { mma_n64_rs<(k >> 2) * 16384 + (k & 3) * 32>(s.S, s.Q + 4 * k, dK + (ko >> 4), k != 0); });
            wg_commit();
            issue_rest(IC<1>{});
            s_done();
            at_mask<0>(s, wrow, lane);
            if (DELAY0 == 1) pv_half();
            if (DELAY0 == 2) pv_done();
            static_for<8>([&](auto k) {
              at_exp<4 * k, 4 * k + 4, 32>(s);
              q_load_if(k, j == ta, s.S[4 * k]);
              if (DELAY0 == 0 && k == 3) pv_half();
            });
            at_pack<0, 16>(s);
            if (DELAY0 < 2) pv_done();
          } else {
            wg_fence();
            issue_s(ko);
            issue_rest(IC<0>{});
            if (!diag) {
              s_done();
              at_exp<0, 4 * SP1>(s);
              pv_half();
              at_exp<4 * SP1, 4 * SP2>(s);
              at_pack<0, 16>(s);
              pv_done();
              at_exp<4 * SP2, 64>(s);
              at_pack<16, 32>(s);
            } else {
              s_done();
              at_mask<8>(s, wrow - 64, lane);
              static_for<8>([&](auto k) {
                at_exp<7 * k, 7 * k + 7>(s);
                q_load_if(k, j == ta, s.S[7 * k + 3]);
                if (k == 2) pv_half();
                if (k == 5) { at_pack<0, 16>(s); pv_done(); }
              });
              at_exp<56, 64>(s);
              at_pack<16, 32>(s);
            }
          }
          TL(1, 20 * half + 2 + j, warp == 4);
        }
        TK(84 + half * 24);
        mbar_wait_c(B(half ? B_FULL3 : B_FULLQ), 0);
        if (gq == 0) ep_out(IC<0>{}, IC<EP1>{});
        bar_sync(1 + w, 256);
        fence_regs(s.S); fence_regs(s.O); fence_regs(s.P);
        wg_fence();
        mma_kc(s.S, IC<0>{}, IC<UNIT>{}, 0);
        mbar_wait_c(B(half ? B_FULL3 + 1 : B_FULLQ + 1), 0);
        wg_fence();
        mma_kb(s.S, (2 + half) * SLOT, (2 + half) * SLOT + UNIT, 1);
        wg_commit();
        TK(85 + half * 24);
        if (gq == 0) ep_rest();
        issue_pv(16, gq != 0, w == 1 || gq != 0);
        if (w == 0 || half == 0) bar_arrive(2 - w, 256);
        TK(86 + half * 24);
        wg_wait<2>();
        release2(B(B_EMPTY3), half); release2(B(B_EMPTY3 + 1), half);
        if (ep_prep()) redo |= 2;
        sched_fence();
        wg_wait<0>();
        TK(87 + half * 24);
        fence_regs(s.S);
        fence_regs(s.O);
        e_arrive(B(B_VE));
        release2(B(B_X + 3));
        fence_regs(s.P);
        {
          const int r = fresh_lane();
          cdst = g_ctx + (size_t)(tb * 128 + wrow + (r >> 2)) * NQ + head * 128 + (r & 3) * 8;
        }
#pragma unroll
        for (int i = 0; i < 32; i++) {
          const float* o = s.O + 16 * (i >> 3) + 2 * ((i >> 2) & 1) + 4 * (i & 3);
          s.P[i] = pack_bf16(o[0] * inv[(i >> 2) & 1], o[1] * inv[(i >> 2) & 1]);
        }
        fence_regs(s.P);
        if (__builtin_expect(__any_sync(~0u, redo != 0), 0)) {
#pragma unroll
          for (int i = 0; i < 8; i++) put_ctx(i, true);
#pragma unroll 1
          for (int t = 0; t < 2; t++) {
            if (__any_sync(~0u, (redo >> t) & 1)) slow_rows(wq, head, (t ? tb : ta) * 128 + wrow);
          }
          if (__any_sync(~0u, redo & 1)) publish(2 + 2 * half);
#pragma unroll
          for (int i = 0; i < 64; i++) { s.O[i] = 0.f; s.P[i >> 1] = 0; }
          redo = 2;
        }
        TL(1, 20 * half + 19, warp == 4);
        TK(88 + half * 24);
        if (half) break;
        mbar_wait_c(B(B_FULLB), 0);
        TK(89);
        fence_regs(s.O);
        wg_fence();
        mma_kc(s.O, IC<q_b(0)>{}, IC<q_aw(0) + UNIT>{}, 0);
        wg_commit();
        mma_kc(s.O, IC<q_b(1)>{}, IC<q_aw(1) + UNIT>{}, 1);
        wg_commit();
        wg_wait<1>();
        release2(B(B_EMPTYQ));
        put_ctx(0, true);
#pragma unroll 1
        for (int kb = 2; kb < 8; kb++) {
          issue_q(kb, IC<1>{});
          TK(90 + kb - 1);
#pragma unroll
          for (int i = 1; i < 8; i++) put_ctx(i, kb == (i < 7 ? i + 1 : 7));
        }
        publish(3);
      }
    }
    const int rid_ = rid + zero, cw_ = cw + zero;
    {
    const int lane = fresh_lane(), rid = rid_, mt = rid >> 3, gq = rid & 7, cw = cw_, w = cw >> 2, ct = cw * 32 + lane;
    const int fid = mt * 7 + gq - NOFFN0;
    const bool ffn = NOFFN0 ? gq > 0 : gq < 7;
    const uint32_t stg = sb + OFF_STG + w * 16384 + (cw & 3) * 2048;
    const int wr_ = w * 64 + (lane & 7) + (lane >> 4) * 8;
    const uint32_t wl = sb + ((lane >> 3) & 1) * 8192 + wr_ * 64 + (((cw ^ (wr_ >> 1)) & 3) << 4);
    __syncwarp();
    float (&acc)[64] = s.S;
    uint32_t wf[128];
    auto grab = [&](auto c, uint32_t off) {
#pragma unroll
      for (int m = 0; m < 4; m++)
        asm volatile("ldmatrix.sync.aligned.m8n8.x4.trans.shared.b16 {%0,%1,%2,%3}, [%4];"
                     : "=r"(wf[16 * c + 4 * m]), "=r"(wf[16 * c + 4 * m + 1]), "=r"(wf[16 * c + 4 * m + 2]), "=r"(wf[16 * c + 4 * m + 3])
                     : "r"(wl + off + m * 1024) : "memory");
    };
    const int r0 = lane >> 2;
    uint32_t hp[32], rt[16];
    {
      int st = 2, prev = 1; uint32_t ph = 0;
      auto run = [&](auto k0, auto k1, auto back) {
#pragma unroll 1
        for (int kb = k0; kb < k1; kb++) {
          mbar_wait_c(B(B_FULL3 + st), ph);
          wg_fence();
          mma_kb(acc, r3(st), r3(st) + UNIT, 1);
          wg_commit();
          wg_wait<1>();
          release2(B(B_EMPTY3 + prev), k0 != 2 || kb != 2);
          if (kb == k0) back();
          prev = st;
          if (++st == 6) { st = 0; ph ^= 1; }
#pragma unroll
          for (int i = 0; i < 8; i++) if (PUT0 + PUTD * i >= k0 && PUT0 + PUTD * i < k1) put_ctx(i, kb == PUT0 + PUTD * i);
          if (PUT0 + PUTD * 7 >= k0 && PUT0 + PUTD * 7 < k1 && kb == PUT0 + PUTD * 7) publish(5);
          if ((kb & 7) == 7) TL(2, 2 + (kb >> 3), warp == 4);
        }
      };
      auto hand = [&](uint32_t b, int n, uint32_t f0, uint32_t f1, uint32_t f2, uint32_t f3) {
        asm volatile("{\n.reg .pred p;\n.reg .b32 t;\nsetp.lt.u32 p, %1, %7;\nlop3.b32 t, %1, %2, %3, 0xE8;\nlop3.b32 t, t, %4, %5, 0xE8;\n"
                     "mad.lo.u32 t, t, %6, %0;\n@p mbarrier.arrive.shared::cta.b64 _, [t];\n}"
                     ::"r"(b + 8 * lane), "r"(lane), "r"(f0), "r"(f1), "r"(f2), "r"(f3), "r"(zero), "r"(n) : "memory");
      };
      static_for<WIN + 1>([&](auto c) {
        run(IC<c == 0 ? 2 : GRAB0 + GRABD * (c - 1)>{}, IC<(c < WIN ? GRAB0 + GRABD * c : XGRAB)>{}, [&]() {
          constexpr int f = c > 0 ? 16 * (c - 1) : 0;
          if (c > 0) hand(B(B_WE + ((c - 1) & 1)), 1, wf[f], wf[f + 4], wf[f + 8], wf[f + 12]);
        });
        if (c < WIN) {
          if (ffn) mbar_wait_c(B(B_WF + (c & 1)), (c >> 1) & 1);
          grab(IC<(c < WIN ? c : 0)>{}, OFF_SIDE + (c & 1) * UNIT);
        }
      });
      mbar_wait_c(B(B_WF), ffn ? (WIN >> 1) & 1 : 0);
      mbar_wait_c(B(B_WF + 1), ffn ? (WIN >> 1) & 1 : 0);
      mbar_wait_c(B(B_WR), 0);
      const uint32_t xa = sb + OFF_SIDE + w * UNIT + (cw & 3) * 2048 + (lane & 15) * 128 + (((lane >> 4) ^ (lane & 7)) << 4);
#pragma unroll
      for (int j = 0; j < 8; j++)
        asm volatile("ldmatrix.sync.aligned.m8n8.x4.shared.b16 {%0,%1,%2,%3}, [%4];"
                     : "=r"(hp[4 * j]), "=r"(hp[4 * j + 1]), "=r"(hp[4 * j + 2]), "=r"(hp[4 * j + 3]) : "r"((xa ^ ((j & 3) << 5)) + (j >> 2) * 8192) : "memory");
      run(IC<XGRAB>{}, IC<XGRAB + 2>{}, [&]() { hand(B(B_WE), 2, hp[0] ^ hp[4], hp[8] ^ hp[12], hp[16] ^ hp[20], hp[24] ^ hp[28]); });
#pragma unroll
      for (int j = 0; j < 4; j++)
        asm volatile("ldmatrix.sync.aligned.m8n8.x4.shared.b16 {%0,%1,%2,%3}, [%4];"
                     : "=r"(rt[4 * j]), "=r"(rt[4 * j + 1]), "=r"(rt[4 * j + 2]), "=r"(rt[4 * j + 3])
                     : "r"(sb + OFF_MISC + 512 + (lane & 1) * 256 + (lane >> 3) * 16 + j * 64) : "memory");
      run(IC<XGRAB + 2>{}, IC<64>{}, []() {});
    }
    uint4* const xr = g_xr + rid * XR_SIZE;
    mbar_wait_c(B(B_SET2), 0);
    mbar_wait_c(B(B_EMPTY3), 0);
    wg_wait<0>();
    fence_regs(acc);
    TL(2, 10, warp == 4);
    {
      float d[4] = {0.f, 0.f, 0.f, 0.f}, qa[4] = {0.f, 0.f, 0.f, 0.f}, qb[4] = {0.f, 0.f, 0.f, 0.f};
#pragma unroll
      for (int j = 0; j < 16; j++) {
        hp[2 * j] = hadd2_bf(hp[2 * j], pack_bf16(acc[4 * j], acc[4 * j + 1]));
        hp[2 * j + 1] = hadd2_bf(hp[2 * j + 1], pack_bf16(acc[4 * j + 2], acc[4 * j + 3]));
        if (j & 1) {
          mma16816(d, hp[2 * j - 2], hp[2 * j - 1], hp[2 * j], hp[2 * j + 1], rt[j - 1], rt[j]);
          mma16816(qa, hp[2 * j - 2], hp[2 * j - 1], hp[2 * j], hp[2 * j + 1], hp[2 * j - 2], hp[2 * j]);
          mma16816(qb, hp[2 * j - 2], hp[2 * j - 1], hp[2 * j], hp[2 * j + 1], hp[2 * j - 1], hp[2 * j + 1]);
        }
      }
      const float s2a = __shfl_sync(~0u, (r0 & 1) ? qa[1] : qa[0], r0 * 4 + (r0 >> 1));
      const float s2b = __shfl_sync(~0u, (r0 & 1) ? qb[3] : qb[2], r0 * 4 + (r0 >> 1));
      if ((lane & 3) == 0) {
        __stcg(reinterpret_cast<float4*>(xr + XR_PS + cw * 16 + r0), make_float4(d[0], s2a, d[1], 0.f));
        __stcg(reinterpret_cast<float4*>(xr + XR_PS + cw * 16 + r0 + 8), make_float4(d[2], s2b, d[3], 0.f));
      }
    }
    __syncwarp();
    stage_store_128(stg, lane, hp);
    TL(2, 11, warp == 4);
    __syncwarp();
    uint4 cout;
    uint32_t ckey;
    {
      uint4 ps[4];
      const float wsum = *reinterpret_cast<const float*>(sp + OFF_MISC + 1024);
      if (PDLY) spin_clk(PDLY);
      poll_chunks(ps, g_xr + (mt * 8 + (ct & 1) * 4) * XR_SIZE + XR_PS + (ct >> 1), XR_SIZE);
      TL(2, 12, warp == 4);
      auto F = [](uint32_t u) { return __uint_as_float(u); };
      float s1 = (F(ps[0].x) + F(ps[1].x)) + (F(ps[2].x) + F(ps[3].x)), s2 = (F(ps[0].y) + F(ps[1].y)) + (F(ps[2].y) + F(ps[3].y));
      float s3 = (F(ps[0].z) + F(ps[1].z)) + (F(ps[2].z) + F(ps[3].z));
      s1 += __shfl_xor_sync(~0u, s1, 1); s2 += __shfl_xor_sync(~0u, s2, 1); s3 += __shfl_xor_sync(~0u, s3, 1);
      const float mean = s1 * (1.f / DM);
      float mb, inv;
      ln_round(mean, fmaxf(fmaf(s2, 1.f / DM, -mean * mean), 0.f), mb, inv);
      uint32_t u = pack_bf16((s3 - mb * wsum) * inv, 0.f);
      if (u == 0x8000u) u = 0;
      u = (u & 0x8000u) ? (~u & 0xFFFFu) : (u | 0x8000u);
      const uint32_t key = (u << 16) | (0x7FFFu - (mt * 128 + (ct >> 1)));
      const uint32_t nm2 = pack_bf16(-mb, -mb);
      const uint32_t c1 = __reduce_max_sync(~0u, key);
      const uint32_t c2 = __reduce_max_sync(~0u, key == c1 ? 0u : key);
      if (lane == 0) __stcg(reinterpret_cast<uint2*>(xr + XR_KEY) + cw, make_uint2(c1, c2));
      if (!(ct & 1)) *reinterpret_cast<uint2*>(sp + OFF_RSTAT + (ct >> 1) * 8) = make_uint2(nm2, __float_as_uint(inv) | (key >= c2 ? 0x80000000u : 0u));
      ckey = (lane >> 4) ? c2 : c1;
      const int row = (0x7FFF - (ckey & 0x7FFF)) & 15;
      const uint32_t rn = __shfl_sync(~0u, nm2, row * 2);
      const float ri = __shfl_sync(~0u, inv, row * 2);
      const uint4 v = lds128(stg + ((lane & 15) >> 3) * 8192 + row * 128 + (((lane & 7) ^ (row & 7)) << 4));
      const uint4 n = make_uint4(ln_apply(v.x, rn, ri), ln_apply(v.y, rn, ri), ln_apply(v.z, rn, ri), ln_apply(v.w, rn, ri));
      __stcg(xr + XR_CAND + cw * 64 + 32 + lane, n);
      __stcg(xr + XR_CAND + cw * 64 + lane, v);
      cdst = out + (size_t)(0x7FFF - (ckey & 0x7FFF)) * DM + gq * 128 + (lane & 15) * 8;
      cout = make_uint4(hadd2_bf(v.x, n.x), hadd2_bf(v.y, n.y), hadd2_bf(v.z, n.z), hadd2_bf(v.w, n.w));
    }
    publish(B_OUT - B_PUB);
    cluster_arrive();
    TL(2, 13, warp == 4);
    uint32_t wd[16][4];
    if (ffn) {
      static_for<2>([&](auto i) {
        mbar_wait_c(B(B_WF + i), ((WIN >> 1) & 1) ^ 1);
        grab(IC<WIN + i>{}, OFF_SIDE + i * UNIT);
      });
      mbar_wait_c(B(B_FULL3 + 4 + w), 0);
#pragma unroll
      for (int i = 0; i < 16; i++) {
        const int k = (i & 1) * 16 + (lane & 7) + (lane >> 4) * 8;
        asm volatile("ldmatrix.sync.aligned.m8n8.x4.trans.shared.b16 {%0,%1,%2,%3}, [%4];"
                     : "=r"(wd[i][0]), "=r"(wd[i][1]), "=r"(wd[i][2]), "=r"(wd[i][3])
                     : "r"(sb + r3(4) + w * SLOT + (2 * (cw & 3) + (i >> 3)) * 4096 + k * 128 + (((2 * ((i >> 1) & 3) + ((lane >> 3) & 1)) ^ (lane & 7)) << 4)) : "memory");
      }
    }
    mbar_wait_c(B(B_OUT2), 0);
    const uint2 top = *reinterpret_cast<const uint2*>(sp + OFF_MISC);
    TL(2, 14, warp == 4);
    const int t0 = 0x7FFF - (top.x & 0x7FFF), t1 = 0x7FFF - (top.y & 0x7FFF);
    auto cand = [&](int second, int chunk) {
      const int tk = second ? t1 : t0;
      return g_xr + ((tk >> 7) * 8 + (chunk >> 4)) * XR_SIZE + XR_CAND + ((tk >> 4) & 7) * 64 + ((second && (t0 >> 4) == (t1 >> 4)) ? 16 : 0) + (chunk & 15);
    };
    const int fc = 16 * (rid >> 1) + 4 * (rid & 1) + (lane & 3) + 8 * (lane >> 4), ft = (lane >> 3) & 1;
    uint32_t fh, fn;
    {
      const uint4* pc = cand(w, ct & 127) + 32;
      const uint16_t* pf = reinterpret_cast<const uint16_t*>(cand(ft, fc >> 3)) + (fc & 7);
      uint4 v;
#pragma unroll 1
      for (int n = 0; n < 0x400000; n++) {
        asm volatile("ld.relaxed.gpu.global.v4.u32 {%0,%1,%2,%3}, [%4];" : "=r"(v.x), "=r"(v.y), "=r"(v.z), "=r"(v.w) : "l"(pc) : "memory");
        asm volatile("ld.relaxed.gpu.global.u16 %0, [%1];" : "=r"(fh) : "l"(pf) : "memory");
        asm volatile("ld.relaxed.gpu.global.u16 %0, [%1 + 512];" : "=r"(fn) : "l"(pf) : "memory");
        if (__all_sync(~0u, max(max(v.x, v.y), max(v.z, v.w)) != 0xFFFFFFFFu && max(fh, fn) != 0xFFFFu)) break;
      }
      const int blk = (ct & 127) >> 2;
      const uint32_t a = sb + OFF_SCR + w * 2112 + blk * 64 + (((blk >> 1) & 3) << 4) + (ct & 3) * 4;
      asm volatile("st.shared.u32 [%0], %1;" ::"r"(a), "r"(v.x) : "memory");
      asm volatile("st.shared.u32 [%0], %1;" ::"r"(a ^ 16), "r"(v.y) : "memory");
      asm volatile("st.shared.u32 [%0], %1;" ::"r"(a ^ 32), "r"(v.z) : "memory");
      asm volatile("st.shared.u32 [%0], %1;" ::"r"(a ^ 48), "r"(v.w) : "memory");
    }
    asm volatile("{\n.reg .pred p;\nsetp.lt.u32 p, %5, %6;\n@p st.global.v4.u32 [%0], {%1,%2,%3,%4};\n}" ::"l"(cdst), "r"(cout.x), "r"(cout.y), "r"(cout.z),
                 "r"(cout.w), "r"(ckey), "r"(top.y) : "memory");
    if (ffn) {
      bar_sync(3, 256);
      TL(2, 15, warp == 4);
      float d[2][4] = {{0.f, 0.f, 0.f, 0.f}, {0.f, 0.f, 0.f, 0.f}};
      const uint32_t xb = sb + OFF_SCR + (r0 & 1) * 2112 + w * 128 + (((lane ^ w) & 3) << 4);
#pragma unroll
      for (int i = 0; i < 16; i++) {
        const uint4 b = lds128((xb ^ ((i & 2) << 4)) + (i >> 1) * 256 + (i & 1) * 64);
        mma16816(d[0], wf[8 * i], wf[8 * i + 1], wf[8 * i + 2], wf[8 * i + 3], b.x, b.y);
        mma16816(d[1], wf[8 * i + 4], wf[8 * i + 5], wf[8 * i + 6], wf[8 * i + 7], b.z, b.w);
      }
      float2* red = reinterpret_cast<float2*>(sp + OFF_SCR + 8192);
      if (!(lane & 2))
        red[(w * 2 + (lane & 1)) * 32 + (cw & 3) * 8 + r0] = (lane & 1) ? make_float2(d[0][1] + d[1][1], d[0][3] + d[1][3]) : make_float2(d[0][0] + d[1][0], d[0][2] + d[1][2]);
      bar_sync(3, 256);
      TL(2, 16, warp == 4);
      const uint32_t ra = sb + OFF_SCR + 8192 + (r0 & 1) * 256 + (r0 >> 1) * 64 + (lane & 3) * 16;
      const uint4 p0 = lds128(ra), p1 = lds128(ra + 512);
      auto act = [](uint32_t u0, uint32_t u1, uint32_t g0, uint32_t g1) {
        const uint32_t ug = pack_bf16(__uint_as_float(u0) + __uint_as_float(u1), __uint_as_float(g0) + __uint_as_float(g1));
        const float g = bf_hi(ug);
        return bf_round(__fdividef(g, 1.f + __expf(-g))) * bf_lo(ug);
      };
      const uint32_t av = pack_bf16(act(p0.x, p1.x, p0.y, p1.y), act(p0.z, p1.z, p0.w, p1.w));
      uint32_t b[4];
#pragma unroll
      for (int i = 0; i < 4; i++) b[i] = __shfl_sync(~0u, av, 8 * i + (lane & 7));
      TL(2, 17, warp == 4);
      float y[2][4] = {{0.f, 0.f, 0.f, 0.f}, {0.f, 0.f, 0.f, 0.f}};
#pragma unroll
      for (int c = 0; c < 4; c++) {
        const bool on = (lane >> 3) == c;
        const uint32_t b0 = on ? b[0] : 0, b1 = on ? b[1] : 0, b2 = on ? b[2] : 0, b3 = on ? b[3] : 0;
#pragma unroll
        for (int a = 0; a < 2; a++) {
          const int i = 8 * a + 2 * c;
          mma16816(y[a], wd[i][0], wd[i][1], wd[i][2], wd[i][3], b0, b1);
          mma16816(y[a], wd[i + 1][0], wd[i + 1][1], wd[i + 1][2], wd[i + 1][3], b2, b3);
        }
      }
      float4* yd = reinterpret_cast<float4*>(g_xr + (cw * 16 + (lane & 3) * 2 + (lane >> 4)) * XR_SIZE + XR_Y + fid * 4 + (r0 & 3));
      __stcg(yd, make_float4(y[0][0], y[0][1], y[0][2], y[0][3]));
      __stcg(yd + 8 * XR_SIZE, make_float4(y[1][0], y[1][1], y[1][2], y[1][3]));
    }
    TL(2, 18, warp == 4);
    if (cw == 0) {
      uint32_t u = (ft ? top.y : top.x) >> 16;
      u = (u & 0x8000u) ? (u & 0x7FFFu) : (~u & 0xFFFFu);
      float rs = bf_round(__fdividef(1.f, 1.f + __expf(-__uint_as_float(u << 16))));
      uint16_t* op = reinterpret_cast<uint16_t*>(out) + (size_t)(ft ? t1 : t0) * DM + fc;
      asm volatile("" : "+l"(op), "+f"(rs));
      spin_clk(ffn ? YDLY : YDLY + YDLY0);
      float v[4];
#pragma unroll 1
      for (int n = 0; n < 0x400000; n++) {
        float4 z[14];
#pragma unroll
        for (int i = 0; i < 14; i++)
          asm volatile("ld.relaxed.gpu.global.v4.f32 {%0,%1,%2,%3}, [%4];" : "=f"(z[i].x), "=f"(z[i].y), "=f"(z[i].z), "=f"(z[i].w) : "l"(xr + XR_Y + lane + 32 * i) : "memory");
        float a[4] = {z[0].x, z[0].y, z[0].z, z[0].w}, b[4] = {z[1].x, z[1].y, z[1].z, z[1].w};
#pragma unroll
        for (int i = 2; i < 14; i += 2) {
          a[0] += z[i].x; a[1] += z[i].y; a[2] += z[i].z; a[3] += z[i].w;
          b[0] += z[i + 1].x; b[1] += z[i + 1].y; b[2] += z[i + 1].z; b[3] += z[i + 1].w;
        }
#pragma unroll
        for (int i = 0; i < 4; i++) v[i] = a[i] + b[i];
        const float t = (v[0] + v[1]) + (v[2] + v[3]);
        if (__all_sync(~0u, t == t)) break;
        uint32_t m = 0;
#pragma unroll
        for (int i = 0; i < 14; i++) m = max(max(m, max(__float_as_uint(z[i].x), __float_as_uint(z[i].y))), max(__float_as_uint(z[i].z), __float_as_uint(z[i].w)));
        if (__all_sync(~0u, m != 0xFFFFFFFFu)) break;
      }
      TL(2, 30, true);
      const bool hi = lane & 16, odd = lane & 8;
      const float a0 = (hi ? v[2] : v[0]) + __shfl_xor_sync(~0u, hi ? v[0] : v[2], 16), a1 = (hi ? v[3] : v[1]) + __shfl_xor_sync(~0u, hi ? v[1] : v[3], 16);
      float yv = (odd ? a1 : a0) + __shfl_xor_sync(~0u, odd ? a0 : a1, 8);
      yv += __shfl_xor_sync(~0u, yv, 4);
      const uint32_t o = hadd2_bf(fh, hadd2_bf(fn, pack_bf16(bf_round(yv) * rs, 0.f)));
      if (!(lane & 4)) *op = (uint16_t)o;
      TL(2, 21, true);
    }
    TL(2, 20, warp == 4);
    }
    __syncwarp();
    cluster_wait();
  }
}

typedef CUresult (*EncodeFn)(CUtensorMap*, CUtensorMapDataType, cuuint32_t, void*, const cuuint64_t*, const cuuint64_t*, const cuuint32_t*,
                             const cuuint32_t*, CUtensorMapInterleave, CUtensorMapSwizzle, CUtensorMapL2promotion, CUtensorMapFloatOOBfill);
EncodeFn g_enc = nullptr;

void map2(CUtensorMap* m, const void* ptr, uint64_t rows, uint64_t cols, uint32_t bc, uint32_t br) {
  const CUtensorMapSwizzle sw = bc == 64 ? CU_TENSOR_MAP_SWIZZLE_128B : CU_TENSOR_MAP_SWIZZLE_64B;
  cuuint64_t gd[2] = {cols, rows}, gs[1] = {cols * 2};
  cuuint32_t bd[2] = {bc, br}, es[2] = {1, 1};
  g_enc(m, CU_TENSOR_MAP_DATA_TYPE_BFLOAT16, 2, (void*)ptr, gd, gs, bd, es, CU_TENSOR_MAP_INTERLEAVE_NONE, sw,
        CU_TENSOR_MAP_L2_PROMOTION_L2_128B, CU_TENSOR_MAP_FLOAT_OOB_FILL_NONE);
}
void map3(CUtensorMap* m, const void* ptr, uint64_t rows, uint64_t cols, uint32_t br, uint32_t bch) {
  cuuint64_t gd[3] = {64, rows, cols / 64}, gs[2] = {cols * 2, 128};
  cuuint32_t bd[3] = {64, br, bch}, es[3] = {1, 1, 1};
  g_enc(m, CU_TENSOR_MAP_DATA_TYPE_BFLOAT16, 3, (void*)ptr, gd, gs, bd, es, CU_TENSOR_MAP_INTERLEAVE_NONE, CU_TENSOR_MAP_SWIZZLE_128B,
        CU_TENSOR_MAP_L2_PROMOTION_L2_128B, CU_TENSOR_MAP_FLOAT_OOB_FILL_NONE);
}

}

extern "C" void kernel_launch(void* const* d_in, const int* in_sizes, int n_in, void* d_out, int out_size) {
  const __nv_bfloat16* x = (const __nv_bfloat16*)d_in[0];
  const __nv_bfloat16* ckv = (const __nv_bfloat16*)d_in[1];
  const __nv_bfloat16* wq = (const __nv_bfloat16*)d_in[2];
  const __nv_bfloat16* wk = (const __nv_bfloat16*)d_in[3];
  const __nv_bfloat16* wv = (const __nv_bfloat16*)d_in[4];
  const __nv_bfloat16* wo = (const __nv_bfloat16*)d_in[5];
  const __nv_bfloat16* w_r = (const __nv_bfloat16*)d_in[7];
  const __nv_bfloat16* wgate = (const __nv_bfloat16*)d_in[8];
  const __nv_bfloat16* wup = (const __nv_bfloat16*)d_in[9];
  const __nv_bfloat16* wdown = (const __nv_bfloat16*)d_in[10];
  __nv_bfloat16* out = (__nv_bfloat16*)d_out;

  if (!g_enc) {
    void* fn = nullptr;
    cudaDriverEntryPointQueryResult qr;
    cudaGetDriverEntryPoint("cuTensorMapEncodeTiled", &fn, cudaEnableDefault, &qr);
    g_enc = (EncodeFn)fn;
    cudaFuncSetAttribute(fused_kernel, cudaFuncAttributeMaxDynamicSharedMemorySize, SMEM_BYTES);
  }
  void *xn, *kv, *ctx;
  cudaGetSymbolAddress(&xn, g_xn);
  cudaGetSymbolAddress(&kv, g_kv);
  cudaGetSymbolAddress(&ctx, g_ctx);

  Params p;
  map2(&p.xn, xn, SEQ, DM, 64, 64);
  map2(&p.ckv, ckv, SEQ, DC, 64, 128);
  map3(&p.wq, wq, DM, NQ, 64, 2);
  map3(&p.wk, wk, DC, NQ, 64, 2);
  map3(&p.wv, wv, DC, NQ, 64, 2);
  map3(&p.kv_ld, kv, 2 * SEQ, NQ, 128, 2);
  map2(&p.ctx_ld, ctx, SEQ, NQ, 64, 128);
  map3(&p.wo, wo, NQ, DM, 64, 1);
  map3(&p.x, x, SEQ, DM, 64, 2);
  map3(&p.wd, wdown, FF, DM, 32, 8);
  map2(&p.wg, wgate, DM, FF, 32, 64);
  map2(&p.wu, wup, DM, FF, 32, 64);
  fused_kernel<<<128, 384, SMEM_BYTES, cudaStreamPerThread>>>(p, x, wq, w_r, wdown, out, 0u);
}
```

```cpp
#include <cuda_runtime.h>
#include <cuda_bf16.h>
#include <cuda.h>
#include <stdint.h>
#include <utility>

#pragma nv_diag_suppress 549
#pragma nv_diag_suppress 177
namespace {

constexpr int SEQ = 2048, DM = 1024, NH = 32, HD = 128, DC = 512, NQ = NH * HD, FF = 3584;

__device__ __align__(1024) __nv_bfloat16 g_xn[SEQ * DM];
__device__ __align__(1024) __nv_bfloat16 g_kv[2 * SEQ * NQ];
__device__ __align__(1024) __nv_bfloat16 g_ctx[SEQ * NQ];
constexpr int XR_PS = 0;
constexpr int XR_KEY = 128;
constexpr int XR_CAND = 136;
constexpr int XR_Y = 648;
constexpr int XR_SIZE = 1104;
__device__ __align__(1024) uint4 g_xr[128 * XR_SIZE];
constexpr int C_LN = 0, C_KV = 16, C_CTX = 32, C_NUM = 64;
__device__ unsigned g_cnt[C_NUM];

#define TL(k, i, cond) do {} while (0)
#define TC(w, g, i) do {} while (0)
#define TL_EXTRA 0
#define TK(i) do {} while (0)

__device__ __forceinline__ uint32_t s2u(const void* p) { return (uint32_t)__cvta_generic_to_shared(p); }
__device__ __forceinline__ void mbar_arrive(uint32_t b) { asm volatile("mbarrier.arrive.shared::cta.b64 _, [%0];" ::"r"(b) : "memory"); }
__device__ __forceinline__ void mbar_arrive_both(uint32_t b, uint32_t lane, bool cond) {
  asm volatile("{\n.reg .pred p;\n.reg .b32 r;\nsetp.lt.u32 p, %1, %2;\nmapa.shared::cluster.u32 r, %0, %1;\n@p mbarrier.arrive.shared::cluster.b64 _, [r];\n}"
               ::"r"(b), "r"(lane), "r"(cond ? 2 : 0) : "memory");
}
__device__ __forceinline__ bool mbar_test(uint32_t b, uint32_t ph) {
  uint32_t ok;
  asm volatile("{\n.reg .pred p;\nmbarrier.test_wait.parity.shared::cta.b64 p, [%1], %2;\nselp.u32 %0, 1, 0, p;\n}" : "=r"(ok) : "r"(b), "r"(ph) : "memory");
  return __all_sync(~0u, ok);
}
__device__ __forceinline__ void mbar_wait(uint32_t b, uint32_t ph) {
  asm volatile(
      "{\n.reg .pred p;\n.reg .u32 n;\nmov.u32 n, 0;\n"
      "LW:\nmbarrier.try_wait.parity.shared::cta.b64 p, [%0], %1, 20000;\n@p bra LD;\n"
      "add.u32 n, n, 1;\nsetp.lt.u32 p, n, 0x40000;\n@p bra LW;\ntrap;\nLD:\n}" ::"r"(b), "r"(ph) : "memory");
}
__device__ __forceinline__ void mbar_wait_u(uint32_t b, uint32_t ph) {
  asm volatile(
      "{\n.reg .pred p;\n.reg .u32 n;\nmov.u32 n, 0;\n"
      "LW:\nmbarrier.try_wait.parity.shared::cta.b64 p, [%0], %1, 20000;\n@p bra.uni LD;\n"
      "add.u32 n, n, 1;\nsetp.lt.u32 p, n, 0x40000;\n@p bra.uni LW;\ntrap;\nLD:\n}" ::"r"(b), "r"(ph) : "memory");
}
__device__ __forceinline__ void mbar_wait_c(uint32_t b, uint32_t ph) {
  asm volatile(
      "{\n.reg .pred p;\n.reg .u32 n;\nmov.u32 n, 0;\n"
      "LW:\nmbarrier.try_wait.parity.shared::cta.b64 p, [%0], %1;\n@p bra.uni LD;\n"
      "add.u32 n, n, 1;\nsetp.lt.u32 p, n, 0x100000;\n@p bra.uni LW;\ntrap;\nLD:\n}" ::"r"(b), "r"(ph) : "memory");
}
template <bool SLEEP = false>
__device__ __forceinline__ void spin_until_ge(const unsigned* p, unsigned target) {
  asm volatile(
      "{\n.reg .pred p, q;\n.reg .u32 n, v;\nmov.u32 n, 0;\nsetp.ne.u32 q, %2, 0;\n"
      "LW:\nld.acquire.gpu.global.u32 v, [%0];\nsetp.ge.u32 p, v, %1;\n@p bra LD;\n@q nanosleep.u32 200;\n"
      "add.u32 n, n, 1;\nsetp.lt.u32 p, n, 0x400000;\n@p bra LW;\ntrap;\nLD:\n}" ::"l"(p), "r"(target), "n"((int)SLEEP) : "memory");
}
template <int N>
__device__ __forceinline__ void poll_chunks(uint4 (&v)[N], const uint4* p, int stride) {
#pragma unroll 1
  for (int n = 0; n < 0x400000; n++) {
    uint32_t m = 0;
#pragma unroll
    for (int i = 0; i < N; i++) {
      asm volatile("ld.relaxed.gpu.global.v4.u32 {%0,%1,%2,%3}, [%4];" : "=r"(v[i].x), "=r"(v[i].y), "=r"(v[i].z), "=r"(v[i].w) : "l"(p + i * stride) : "memory");
    }
#pragma unroll
    for (int i = 0; i < N; i++) m = max(max(m, max(v[i].x, v[i].y)), max(v[i].z, v[i].w));
    if (__all_sync(~0u, m != 0xFFFFFFFFu)) break;
  }
}
__device__ __forceinline__ void spin_clk(uint32_t n) {
  asm volatile("{\n.reg .pred p;\n.reg .u32 a, b;\nmov.u32 a, %%clock;\nLW:\nmov.u32 b, %%clock;\nsub.u32 b, b, a;\nsetp.lt.u32 p, b, %0;\n@p bra.uni LW;\n}" ::"r"(n) : "memory");
}
__device__ __forceinline__ int fresh_lane() {
  int r;
  asm volatile("mov.u32 %0, %%laneid;" : "=r"(r));
  return r;
}
__device__ __forceinline__ void fence_async_all() { asm volatile("fence.proxy.async;" ::: "memory"); }
__device__ __forceinline__ void bar_sync(int id, int n) { asm volatile("bar.sync %0, %1;" ::"r"(id), "r"(n) : "memory"); }
__device__ __forceinline__ void bar_arrive(int id, int n) { asm volatile("bar.arrive %0, %1;" ::"r"(id), "r"(n) : "memory"); }
__device__ __forceinline__ void cluster_arrive() { asm volatile("barrier.cluster.arrive.relaxed.aligned;" ::: "memory"); }
__device__ __forceinline__ void cluster_wait() { asm volatile("barrier.cluster.wait.acquire.aligned;" ::: "memory"); }
__device__ __forceinline__ void fence_gpu() { asm volatile("fence.acq_rel.gpu;" ::: "memory"); }
__device__ __forceinline__ void red_add(unsigned* p, unsigned v) { asm volatile("red.relaxed.gpu.global.add.u32 [%0], %1;" ::"l"(p), "r"(v) : "memory"); }
#define ELECT "{\n.reg .pred E;\nelect.sync _|E, 0xFFFFFFFF;\n@E "
__device__ __forceinline__ void e_init(uint32_t b, uint32_t c) { asm volatile(ELECT "mbarrier.init.shared::cta.b64 [%0], %1;\n}" ::"r"(b), "r"(c) : "memory"); }
__device__ __forceinline__ void e_expect(uint32_t b, uint32_t bytes) { asm volatile(ELECT "mbarrier.arrive.expect_tx.shared::cta.b64 _, [%0], %1;\n}" ::"r"(b), "r"(bytes) : "memory"); }
__device__ __forceinline__ void e_arrive(uint32_t b) { asm volatile(ELECT "mbarrier.arrive.shared::cta.b64 _, [%0];\n}" ::"r"(b) : "memory"); }
__device__ __forceinline__ void prefetch_tm(const CUtensorMap* m) { asm volatile(ELECT "prefetch.tensormap [%0];\n}" ::"l"(m) : "memory"); }
__device__ __forceinline__ void tma_ld2(uint32_t dst, const CUtensorMap* m, uint32_t bar, int c0, int c1) {
  asm volatile(ELECT "cp.async.bulk.tensor.2d.shared::cta.global.mbarrier::complete_tx::bytes [%0], [%1, {%3,%4}], [%2];\n}" ::"r"(dst), "l"(m), "r"(bar), "r"(c0), "r"(c1) : "memory");
}
__device__ __forceinline__ void tma_ld3(uint32_t dst, const CUtensorMap* m, uint32_t bar, int c0, int c1, int c2) {
  asm volatile(ELECT "cp.async.bulk.tensor.3d.shared::cta.global.mbarrier::complete_tx::bytes [%0], [%1, {%3,%4,%5}], [%2];\n}" ::"r"(dst), "l"(m), "r"(bar), "r"(c0), "r"(c1), "r"(c2) : "memory");
}
__device__ __forceinline__ void tma_ld2_mc(uint32_t dst, const CUtensorMap* m, uint32_t bar, int c0, int c1, uint16_t mask) {
  asm volatile(ELECT "cp.async.bulk.tensor.2d.shared::cluster.global.mbarrier::complete_tx::bytes.multicast::cluster [%0], [%1, {%3,%4}], [%2], %5;\n}" ::"r"(dst), "l"(m), "r"(bar), "r"(c0), "r"(c1), "h"(mask) : "memory");
}
__device__ __forceinline__ void tma_ld3_mc(uint32_t dst, const CUtensorMap* m, uint32_t bar, int c0, int c1, int c2, uint16_t mask) {
  asm volatile(ELECT "cp.async.bulk.tensor.3d.shared::cluster.global.mbarrier::complete_tx::bytes.multicast::cluster [%0], [%1, {%3,%4,%5}], [%2], %6;\n}" ::"r"(dst), "l"(m), "r"(bar), "r"(c0), "r"(c1), "r"(c2), "h"(mask) : "memory");
}
__device__ __forceinline__ uint64_t policy_evict_first() {
  uint64_t p;
  asm("createpolicy.fractional.L2::evict_first.b64 %0, 1.0;" : "=l"(p));
  return p;
}
__device__ __forceinline__ void tma_ld2_ef(uint32_t dst, const CUtensorMap* m, uint32_t bar, int c0, int c1) {
  asm volatile(ELECT "cp.async.bulk.tensor.2d.shared::cta.global.mbarrier::complete_tx::bytes.L2::cache_hint [%0], [%1, {%3,%4}], [%2], %5;\n}" ::"r"(dst), "l"(m), "r"(bar), "r"(c0), "r"(c1), "l"(policy_evict_first()) : "memory");
}
__device__ __forceinline__ void tma_ld3_ef(uint32_t dst, const CUtensorMap* m, uint32_t bar, int c0, int c1, int c2) {
  asm volatile(ELECT "cp.async.bulk.tensor.3d.shared::cta.global.mbarrier::complete_tx::bytes.L2::cache_hint [%0], [%1, {%3,%4,%5}], [%2], %6;\n}" ::"r"(dst), "l"(m), "r"(bar), "r"(c0), "r"(c1), "r"(c2), "l"(policy_evict_first()) : "memory");
}
__device__ __forceinline__ void tma_ld3_mc_ef(uint32_t dst, const CUtensorMap* m, uint32_t bar, int c0, int c1, int c2, uint16_t mask) {
  asm volatile(ELECT "cp.async.bulk.tensor.3d.shared::cluster.global.mbarrier::complete_tx::bytes.multicast::cluster.L2::cache_hint [%0], [%1, {%3,%4,%5}], [%2], %6, %7;\n}" ::"r"(dst), "l"(m), "r"(bar), "r"(c0), "r"(c1), "r"(c2), "h"(mask), "l"(policy_evict_first()) : "memory");
}
__device__ __forceinline__ void tma_pf2(const CUtensorMap* m, int c0, int c1) { asm volatile(ELECT "cp.async.bulk.prefetch.tensor.2d.L2.global [%0, {%1,%2}];\n}" ::"l"(m), "r"(c0), "r"(c1) : "memory"); }
__device__ __forceinline__ void tma_pf3(const CUtensorMap* m, int c0, int c1, int c2) { asm volatile(ELECT "cp.async.bulk.prefetch.tensor.3d.L2.global [%0, {%1,%2,%3}];\n}" ::"l"(m), "r"(c0), "r"(c1), "r"(c2) : "memory"); }
__device__ __forceinline__ void sched_fence() { asm volatile("pmevent 0;" ::: "memory"); }
__device__ __forceinline__ void l2_prefetch(const void* p, uint32_t bytes) { asm volatile(ELECT "cp.async.bulk.prefetch.L2.global [%0], %1;\n}" ::"l"(p), "r"(bytes) : "memory"); }

__device__ __forceinline__ void wg_fence() { asm volatile("wgmma.fence.sync.aligned;" ::: "memory"); }
__device__ __forceinline__ void wg_commit() { asm volatile("wgmma.commit_group.sync.aligned;" ::: "memory"); }
template <int N> __device__ __forceinline__ void wg_wait() { asm volatile("wgmma.wait_group.sync.aligned %0;" ::"n"(N) : "memory"); }
template <int N> __device__ __forceinline__ void reg_alloc() { asm volatile("setmaxnreg.inc.sync.aligned.u32 %0;" ::"n"(N)); }
template <int N> __device__ __forceinline__ void reg_dealloc() { asm volatile("setmaxnreg.dec.sync.aligned.u32 %0;" ::"n"(N)); }
template <int N> __device__ __forceinline__ void fence_regs(float (&d)[N]) {
#pragma unroll
  for (int i = 0; i < N; i++) asm volatile("" : "+f"(d[i])::"memory");
}
template <int N> __device__ __forceinline__ void fence_regs(uint32_t (&d)[N]) {
#pragma unroll
  for (int i = 0; i < N; i++) asm volatile("" : "+r"(d[i])::"memory");
}

__device__ __forceinline__ uint32_t mk_desc(uint32_t addr, uint32_t lbo) { return ((addr & 0x3FFFF) >> 4) | ((lbo >> 4) << 16); }

#define R8(b) "+f"(d[b + 0]), "+f"(d[b + 1]), "+f"(d[b + 2]), "+f"(d[b + 3]), "+f"(d[b + 4]), "+f"(d[b + 5]), "+f"(d[b + 6]), "+f"(d[b + 7])
#define REGS64 "%0,%1,%2,%3,%4,%5,%6,%7,%8,%9,%10,%11,%12,%13,%14,%15,%16,%17,%18,%19,%20,%21,%22,%23,%24,%25,%26,%27,%28,%29,%30,%31," \
               "%32,%33,%34,%35,%36,%37,%38,%39,%40,%41,%42,%43,%44,%45,%46,%47,%48,%49,%50,%51,%52,%53,%54,%55,%56,%57,%58,%59,%60,%61,%62,%63"
#define REGS128 REGS64 ",%64,%65,%66,%67,%68,%69,%70,%71,%72,%73,%74,%75,%76,%77,%78,%79,%80,%81,%82,%83,%84,%85,%86,%87,%88,%89,%90,%91,%92,%93,%94,%95," \
               "%96,%97,%98,%99,%100,%101,%102,%103,%104,%105,%106,%107,%108,%109,%110,%111,%112,%113,%114,%115,%116,%117,%118,%119,%120,%121,%122,%123,%124,%125,%126,%127"

#define DESC(d, r, o) "add.u32 t, " r ", " o ";\nmov.b64 " d ", {t, h};\n"
#define MMA_PRE(acc) "{\n.reg .pred p;\n.reg .b32 t, h;\n.reg .b64 da, db;\nmov.b32 h, 0x40000040;\nsetp.ne.b32 p, " acc ", 0;\n"
template <int TB, int OA, int OB>
__device__ __forceinline__ void mma_n256_ss(float (&d)[128], uint32_t a, uint32_t b, int acc) {
  asm volatile(MMA_PRE("%130") DESC("da", "%128", "%132") DESC("db", "%129", "%133")
               "wgmma.mma_async.sync.aligned.m64n256k16.f32.bf16.bf16 {" REGS128 "}, da, db, p, 1, 1, 0, %131;\n}\n"
               : R8(0), R8(8), R8(16), R8(24), R8(32), R8(40), R8(48), R8(56), R8(64), R8(72), R8(80), R8(88), R8(96), R8(104), R8(112), R8(120)
               : "r"(a), "r"(b), "r"(acc), "n"(TB), "n"(OA >> 4), "n"(OB >> 4));
}
template <int TB, int OA, int OB>
__device__ __forceinline__ void mma_n128_ss(float (&d)[64], uint32_t a, uint32_t b, int acc) {
  asm volatile(MMA_PRE("%66") DESC("da", "%64", "%68") DESC("db", "%65", "%69")
               "wgmma.mma_async.sync.aligned.m64n128k16.f32.bf16.bf16 {" REGS64 "}, da, db, p, 1, 1, 0, %67;\n}\n"
               : R8(0), R8(8), R8(16), R8(24), R8(32), R8(40), R8(48), R8(56)
               : "r"(a), "r"(b), "r"(acc), "n"(TB), "n"(OA >> 4), "n"(OB >> 4));
}
template <int TB, int OB>
__device__ __forceinline__ void mma_n128_rs(float (&d)[64], const uint32_t* a, uint32_t b, int acc) {
  asm volatile(MMA_PRE("%69") DESC("db", "%68", "%71")
               "wgmma.mma_async.sync.aligned.m64n128k16.f32.bf16.bf16 {" REGS64 "}, {%64,%65,%66,%67}, db, p, 1, 1, %70;\n}\n"
               : R8(0), R8(8), R8(16), R8(24), R8(32), R8(40), R8(48), R8(56)
               : "r"(a[0]), "r"(a[1]), "r"(a[2]), "r"(a[3]), "r"(b), "r"(acc), "n"(TB), "n"(OB >> 4));
}
template <int OB>
__device__ __forceinline__ void mma_n64_rs(float (&d)[64], const uint32_t* a, uint32_t b, int acc) {
  asm volatile(MMA_PRE("%37") DESC("db", "%36", "%38")
               "wgmma.mma_async.sync.aligned.m64n64k16.f32.bf16.bf16 {%0,%1,%2,%3,%4,%5,%6,%7,%8,%9,%10,%11,%12,%13,%14,%15,%16,%17,%18,%19,%20,%21,"
               "%22,%23,%24,%25,%26,%27,%28,%29,%30,%31}, {%32,%33,%34,%35}, db, p, 1, 1, 0;\n}\n"
               : R8(0), R8(8), R8(16), R8(24)
               : "r"(a[0]), "r"(a[1]), "r"(a[2]), "r"(a[3]), "r"(b), "r"(acc), "n"(OB >> 4));
}
template <int V> struct IC { static constexpr int value = V; __host__ __device__ constexpr operator int() const { return V; } };
template <int N, class F, int... I>
__device__ __forceinline__ void static_for_(F f, std::integer_sequence<int, I...>) { (f(IC<I>{}), ...); }
template <int N, class F>
__device__ __forceinline__ void static_for(F f) { static_for_<N>(f, std::make_integer_sequence<int, N>{}); }
__device__ __forceinline__ uint32_t pack_bf16(float lo, float hi) {
  uint32_t r;
  asm("cvt.rn.bf16x2.f32 %0, %1, %2;" : "=r"(r) : "f"(hi), "f"(lo));
  return r;
}
__device__ __forceinline__ float bf_lo(uint32_t v) { return __uint_as_float(v << 16); }
__device__ __forceinline__ float bf_hi(uint32_t v) { return __uint_as_float(v & 0xFFFF0000u); }
__device__ __forceinline__ float bf_round(float v) { return bf_lo(pack_bf16(v, v)); }
__device__ __forceinline__ void stsm4(uint32_t addr, uint32_t r0, uint32_t r1, uint32_t r2, uint32_t r3) {
  asm volatile("stmatrix.sync.aligned.m8n8.x4.shared.b16 [%0], {%1,%2,%3,%4};" ::"r"(addr), "r"(r0), "r"(r1), "r"(r2), "r"(r3) : "memory");
}
__device__ __forceinline__ uint4 lds128(uint32_t addr) {
  uint4 v;
  asm volatile("ld.shared.v4.u32 {%0,%1,%2,%3}, [%4];" : "=r"(v.x), "=r"(v.y), "=r"(v.z), "=r"(v.w) : "r"(addr));
  return v;
}
__device__ __forceinline__ float ex2(float x) {
  float y;
  asm("ex2.approx.ftz.f32 %0, %1;" : "=f"(y) : "f"(x));
  return y;
}
__device__ __forceinline__ void stage_store_128(uint32_t base, int lane, const uint32_t* pk) {
  const int row = (lane & 7) + ((lane >> 3) & 1) * 8;
  const uint32_t rb = base + row * 128;
  const int hi = lane >> 4;
#pragma unroll
  for (int j = 0; j < 8; j++) {
    const int chunk = 2 * j + hi;
    const uint32_t a = rb + (j >> 2) * 8192 + (((chunk & 7) ^ (lane & 7)) << 4);
    stsm4(a, pk[4 * j + 0], pk[4 * j + 1], pk[4 * j + 2], pk[4 * j + 3]);
  }
}
__device__ __forceinline__ void ln_round(float mean, float var, float& m_bf, float& inv_s) {
  const uint32_t mv = pack_bf16(mean, var);
  m_bf = bf_lo(mv);
  float sq, rc;
  asm("sqrt.approx.f32 %0, %1;" : "=f"(sq) : "f"(bf_round(bf_hi(mv) + 1e-5f)));
  asm("rcp.approx.ftz.f32 %0, %1;" : "=f"(rc) : "f"(bf_round(sq)));
  inv_s = rc;
}
__device__ __forceinline__ uint32_t hadd2_bf(uint32_t a, uint32_t b) {
  uint32_t r;
  asm("add.rn.bf16x2 %0, %1, %2;" : "=r"(r) : "r"(a), "r"(b));
  return r;
}
__device__ __forceinline__ uint32_t ln_apply(uint32_t h, uint32_t nm2, float inv_s) {
  const uint32_t d = hadd2_bf(h, nm2);
  return pack_bf16(bf_lo(d) * inv_s, bf_hi(d) * inv_s);
}
__device__ __forceinline__ void mma16816(float* d, uint32_t a0, uint32_t a1, uint32_t a2, uint32_t a3, uint32_t b0, uint32_t b1) {
  asm volatile("mma.sync.aligned.m16n8k16.row.col.f32.bf16.bf16.f32 {%0,%1,%2,%3}, {%4,%5,%6,%7}, {%8,%9}, {%0,%1,%2,%3};"
               : "+f"(d[0]), "+f"(d[1]), "+f"(d[2]), "+f"(d[3]) : "r"(a0), "r"(a1), "r"(a2), "r"(a3), "r"(b0), "r"(b1));
}

constexpr float AT_C = 0.08838834764831845f * 1.4426950408889634f;
#define L_MIN 2.3283064e-10f
#define L_MAX 1.0995116e12f
#define SP1 6
#define SP2 12
struct AtState {
  float S[64], O[64];
  uint32_t P[32], Q[32];
  float l[4];
};
#define LAG 0
template <int I0, int I1, int N = 64>
__device__ __forceinline__ void at_exp(AtState& s) {
#pragma unroll
  for (int i = I0; i < I1; i++) asm volatile("ex2.approx.ftz.f32 %0, %0;" : "+f"(s.S[i]));
#pragma unroll
  for (int i = I0 > 0 ? I0 - LAG : 0; i < (I1 < N ? I1 - LAG : N); i++) asm volatile("add.f32 %0, %0, %1;" : "+f"(s.l[i & 3]) : "f"(s.S[i]));
}
template <int I0, int I1>
__device__ __forceinline__ void at_pack(AtState& s) {
#pragma unroll
  for (int i = I0; i < I1; i++) asm volatile("cvt.rn.bf16x2.f32 %0, %1, %2;" : "=r"(s.P[i]) : "f"(s.S[2 * i + 1]), "f"(s.S[2 * i]));
}
template <int J0>
__device__ __forceinline__ void at_mask(AtState& s, int r, int lane) {
  const int d = r + (lane >> 2) - (lane & 3) * 2;
#pragma unroll
  for (int j = 0; j < 8; j++) {
    float dummy0 = 0.f, dummy1 = 0.f;
    float& lo0 = j < 7 ? s.S[4 * (J0 + (j < 7 ? j + 1 : j)) + 2] : dummy0;
    float& lo1 = j < 7 ? s.S[4 * (J0 + (j < 7 ? j + 1 : j)) + 3] : dummy1;
    asm("{\n.reg .pred p, q;\nsetp.lt.s32 p, %4, %5;\nsetp.le.s32 q, %4, %5;\n"
        "@p add.f32 %0, %0, 0fFF800000;\n@q add.f32 %1, %1, 0fFF800000;\n@p add.f32 %2, %2, 0fFF800000;\n@q add.f32 %3, %3, 0fFF800000;\n}"
        : "+f"(s.S[4 * (J0 + j)]), "+f"(s.S[4 * (J0 + j) + 1]), "+f"(lo0), "+f"(lo1) : "r"(d), "r"(8 * j));
  }
}
__device__ __forceinline__ uint32_t ld_pair(const __nv_bfloat16* p) {
  uint32_t r;
  asm volatile("{\n.reg .b16 a, b;\nld.global.cg.b16 a, [%1];\nld.global.cg.b16 b, [%1 + 8192];\nmov.b32 %0, {a, b};\n}" : "=r"(r) : "l"(p) : "memory");
  return r;
}
__device__ __forceinline__ uint32_t ld_word(const uint32_t* p) {
  uint32_t r;
  asm volatile("ld.global.cg.b32 %0, [%1];" : "=r"(r) : "l"(p) : "memory");
  return r;
}
__device__ __forceinline__ void slow_rows(const __nv_bfloat16* wq, int head, int row0) {
  const int lane = fresh_lane(), r = lane >> 2, c = lane & 3;
  uint32_t q[32];
  float o[32];
#pragma unroll
  for (int i = 0; i < 32; i++) q[i] = 0;
  const uint32_t* xa = reinterpret_cast<const uint32_t*>(g_xn + (size_t)(row0 + r) * DM) + c;
#pragma unroll 1
  for (int h = 0; h < 2; h++) {
    const __nv_bfloat16* wb = wq + (size_t)2 * c * NQ + head * HD + 64 * h + 8 * (r >> 1) + (r & 1);
#pragma unroll
    for (int i = 0; i < 32; i++) o[i] = 0.f;
#pragma unroll 1
    for (int kk = 0; kk < DM / 16; kk++) {
      const uint32_t a0 = ld_word(xa + 8 * kk), a1 = ld_word(xa + 8 * kk + 4 * DM), a2 = ld_word(xa + 8 * kk + 4), a3 = ld_word(xa + 8 * kk + 4 * DM + 4);
#pragma unroll
      for (int n = 0; n < 8; n++) {
        const __nv_bfloat16* b = wb + (size_t)16 * kk * NQ + 32 * (n >> 2) + 2 * (n & 3);
        mma16816(o + 4 * n, a0, a1, a2, a3, ld_pair(b), ld_pair(b + 8 * NQ));
      }
    }
#pragma unroll
    for (int i = 0; i < 16; i++) { q[i] = q[16 + i]; q[16 + i] = pack_bf16(o[2 * i] * AT_C, o[2 * i + 1] * AT_C); }
  }
#pragma unroll 1
  for (int h = 0; h < 2; h++) {
    float m0 = -INFINITY, m1 = -INFINITY, l0 = 0.f, l1 = 0.f;
#pragma unroll
    for (int i = 0; i < 32; i++) o[i] = 0.f;
#pragma unroll 1
    for (int k0 = 0; k0 <= row0; k0 += 16) {
      float e[8] = {0.f, 0.f, 0.f, 0.f, 0.f, 0.f, 0.f, 0.f};
      const uint32_t* kp = reinterpret_cast<const uint32_t*>(g_kv + (size_t)(k0 + r) * NQ + head * HD) + c;
#pragma unroll
      for (int kk = 0; kk < 8; kk++) {
        mma16816(e, q[4 * kk], q[4 * kk + 1], q[4 * kk + 2], q[4 * kk + 3], ld_word(kp + 8 * kk), ld_word(kp + 8 * kk + 4));
        mma16816(e + 4, q[4 * kk], q[4 * kk + 1], q[4 * kk + 2], q[4 * kk + 3], ld_word(kp + 8 * kk + 4 * NQ), ld_word(kp + 8 * kk + 4 * NQ + 4));
      }
      if (k0 == row0) {
#pragma unroll
        for (int i = 0; i < 8; i++) if ((i >> 2) * 8 + 2 * c + (i & 1) > r + (i & 2) * 4) e[i] = -INFINITY;
      }
      float a0 = fmaxf(fmaxf(e[0], e[1]), fmaxf(e[4], e[5])), a1 = fmaxf(fmaxf(e[2], e[3]), fmaxf(e[6], e[7]));
      a0 = fmaxf(a0, __shfl_xor_sync(~0u, a0, 1)); a1 = fmaxf(a1, __shfl_xor_sync(~0u, a1, 1));
      a0 = fmaxf(a0, __shfl_xor_sync(~0u, a0, 2)); a1 = fmaxf(a1, __shfl_xor_sync(~0u, a1, 2));
      a0 = fmaxf(a0, m0); a1 = fmaxf(a1, m1);
      const float sc0 = ex2(m0 - a0), sc1 = ex2(m1 - a1);
      m0 = a0; m1 = a1;
#pragma unroll
      for (int i = 0; i < 8; i++) e[i] = ex2(e[i] - ((i & 2) ? m1 : m0));
      l0 = l0 * sc0 + (e[0] + e[1]) + (e[4] + e[5]);
      l1 = l1 * sc1 + (e[2] + e[3]) + (e[6] + e[7]);
      const uint32_t p0 = pack_bf16(e[0], e[1]), p1 = pack_bf16(e[2], e[3]), p2 = pack_bf16(e[4], e[5]), p3 = pack_bf16(e[6], e[7]);
      const __nv_bfloat16* vp = g_kv + (size_t)(SEQ + k0 + 2 * c) * NQ + head * HD + 64 * h + r;
#pragma unroll
      for (int n = 0; n < 8; n++) {
        o[4 * n] *= sc0; o[4 * n + 1] *= sc0; o[4 * n + 2] *= sc1; o[4 * n + 3] *= sc1;
        mma16816(o + 4 * n, p0, p1, p2, p3, ld_pair(vp + 8 * n), ld_pair(vp + 8 * n + 8 * NQ));
      }
    }
    l0 += __shfl_xor_sync(~0u, l0, 1); l1 += __shfl_xor_sync(~0u, l1, 1);
    l0 += __shfl_xor_sync(~0u, l0, 2); l1 += __shfl_xor_sync(~0u, l1, 2);
#pragma unroll
    for (int i = 0; i < 4; i++) {
      const float* v = o + 16 * (i >> 1) + 2 * (i & 1);
      const float f = __fdividef(1.f, (i & 1) ? l1 : l0);
      *reinterpret_cast<uint4*>(g_ctx + (size_t)(row0 + r + (i & 1) * 8) * NQ + head * HD + 64 * h + (i >> 1) * 32 + c * 8) =
          make_uint4(pack_bf16(v[0] * f, v[1] * f), pack_bf16(v[4] * f, v[5] * f), pack_bf16(v[8] * f, v[9] * f), pack_bf16(v[12] * f, v[13] * f));
    }
  }
}

constexpr int UNIT = 16384, SLOT = 32768;
constexpr int OFF_SIDE = 2 * SLOT;
__host__ __device__ constexpr int kv_a(int kb) { return (kb < 6 ? kb : 3 * kb - 10) * UNIT; }
__host__ __device__ constexpr int kv_b(int s) { return (s == 2 ? 6 : 9 + 3 * s) * UNIT; }
__host__ __device__ constexpr int q_aw(int s) { return (3 * s + (s & 1)) * UNIT; }
__host__ __device__ constexpr int q_b(int s) { return (3 * s + 2 - 2 * (s & 1)) * UNIT; }
__host__ __device__ constexpr int k_slot(int j, int r) { return (j < 2 ? 2 * j : (r == 2 ? 0 : 3 + r)) * SLOT; }
__host__ __device__ constexpr int v_slot(int j) { return (6 - (j & 1)) * SLOT; }
__host__ __device__ constexpr int r3(int st) { return ((0x654130 >> (4 * st)) & 7) * SLOT; }
constexpr int OFF_BAR = 229376;
constexpr int OFF_MISC = OFF_BAR + 512;
constexpr int SMEM_BYTES = OFF_MISC + 2080 + TL_EXTRA;
constexpr int OFF_RSTAT = OFF_MISC + 1056;
enum : int {
  B_FULL1 = 0, B_FULLQ = 3, B_FULLB = 7, B_KF = 8, B_VF = 11, B_FULL3 = 13, B_WF = 19, B_DEP = 21, B_OUT2 = 26, B_PF = 27, B_SET = 28,
  B_SET2 = 29, B_LNGO = 30, B_WR = 31,
  B_KE = 32, B_VE = 35, B_WE = 37, B_PUB = 39, B_OUT = 45,
  B_EMPTY1 = 46, B_EMPTYQ = 49, B_X = 53, B_EMPTY3 = 57,
  B_NUM = 63
};
#define PREN 3
#define PFS PREN
constexpr int PRE = PREN;
#define LN_PF 99
#define LN_GO 4
#define PFW 9
#define PFX 9
#define PFKV 0
#define SYNC3 0
#define SYNC3A 5
#define SYNC3W 6
#define CTX_ST "st.global.cs.v4.u32"
#define PF3 0
#define PD3 7
#define PFF 0
#define PWAIT mbar_wait_c
#define GRAB0 4
#define SIDE_NS 400
#define REL_AT 3
#define STARTV 2
#define SET_NS 40
#define WRAP 16 - j
#define EP1 3
#define MASKV 0
#define PACE 0
#define TRIMS 1
#define TRIMPV 1
#define KTEST 1
#define DELAY0 1
#define AWAIT mbar_wait_c
#define KWAIT mbar_wait_c
#define PFJ 16
#define PFQ 3
#define PFP 1
#define PFQ0 4
#define PFP0 5
#define PUT0 2
#define PUTD 2
#define NOFFN0 0
#define WEF 1
#define OUTU 1
#define YDLY 800
#define YDLY0 1500
#define PDLY 250
#define LATEW 0
#define PFD 7
#define EFM 1
#define PFC 0
#define PFO 2
#define LNF 1
#define TMPF 0
#define DPF 1
#define NPF 0
#define NPF0 4
#define KV_FIRST 1
constexpr int WIN = 6;
constexpr int OFF_STG = r3(0), OFF_SCR = r3(1);
#define PF_KB 54
#define PF_NS 300
#define GRABD 6
#define XGRAB 44
#define SET_KB 44
constexpr int OUT_UNROLL = OUTU;
struct Params {
  CUtensorMap xn, ckv, wq, wk, wv, kv_ld, ctx_ld, wo, x, wd, wg, wu;
};

__global__ void __cluster_dims__(2, 1, 1) __launch_bounds__(384, 1)
fused_kernel(uint32_t zero, const __nv_bfloat16* __restrict__ x, __nv_bfloat16* g_kv, __nv_bfloat16* g_ctx, uint4* g_xr,
             __nv_bfloat16* __restrict__ out, __nv_bfloat16* g_xn, unsigned* g_cnt, const __nv_bfloat16* __restrict__ w_r,
             const __nv_bfloat16* __restrict__ wdown, const __nv_bfloat16* __restrict__ wq, const __grid_constant__ Params p) {
  extern __shared__ __align__(1024) uint8_t sp[];
  const uint32_t sb = s2u(sp);
  const uint32_t bar = sb + OFF_BAR;
  auto B = [&](int i) { return bar + 8 * i; };
  const int tid = threadIdx.x, warp = __shfl_sync(~0u, tid >> 5, 0), wg = warp >> 2, lane = tid & 31;
  if (TMPF == 1 && warp == 0) { prefetch_tm(&p.wk); prefetch_tm(&p.ckv); }
  if (TMPF == 2 && warp == 1) prefetch_tm(&p.wk);
  if (TMPF == 3 && tid == 32) { asm volatile("prefetch.global.L2 [%0];" ::"l"(&p.wk)); }
  const int cta = blockIdx.x, rank = cta & 1, cl = cta >> 1;
  const int mp = cl < 4 ? 1 : (cl < 36 ? (cl & 7) : (0x3207654 >> (4 * ((cl - 36) % 7))) & 7);
  const int gq = cl < 4 ? 4 + cl : (cl < 36 ? (cl - 4) >> 3 : 4 + (cl - 36) / 7);
  const int mt = 2 * mp + rank;
  const int qa = 15 - gq;
  const int ta = gq ? gq : 15, tb = 15 - ta;
  const int rid = mt * 8 + gq;
  const int fid = mt * 7 + gq - NOFFN0;
  const bool ffn = NOFFN0 ? gq > 0 : gq < 7;
  TL(0, 0, warp == 4);
  auto load_pre = [&](int kb) {
    e_expect(B(B_FULL1 + kb), 3 * UNIT);
    tma_ld2(sb + kv_a(kb), &p.ckv, B(B_FULL1 + kb), kb * 64, mt * 128);
    tma_ld3(sb + kv_b(kb) + rank * UNIT, &p.wk, B(B_FULL1 + kb), 0, kb * 64, (gq + KV_FIRST * 8) * 4 + rank * 2);
    tma_ld3(sb + kv_b(kb) + UNIT - rank * UNIT, &p.wk, B(B_FULL1 + kb), 0, kb * 64, (gq + KV_FIRST * 8) * 4 + 2 - rank * 2);
  };
  if (warp == 0) {
    e_init(B(B_FULL1), 1);
    asm volatile("fence.mbarrier_init.release.cluster;" ::: "memory");
    TL(0, 16, true);
    load_pre(0);
    TL(0, 17, true);
#pragma unroll
    for (int kb = 1; kb < PRE; kb++) e_init(B(B_FULL1 + kb), 1);
  } else {
#pragma unroll 1
    for (int i = PRE - 1 + warp; i < B_NUM; i += 11) e_init(B(i), i >= B_EMPTY1 ? 16 : (i >= B_KE ? 8 : (i == B_WR ? 2 : 1)));
  }
  asm volatile("fence.mbarrier_init.release.cluster;" ::: "memory");
  cluster_arrive();
  const int rid0 = rid, warp0 = warp;
  if (wg == 0) {
    reg_dealloc<40>();
    if (warp == 0) {
      TL(0, 12, true);
#pragma unroll 1
      for (int kb = 1; kb < PRE; kb++) { load_pre(kb); TL(0, 12 + kb, true); }
      if (mt >= 2 * PFS) tma_pf3(&p.wk, 0, (mt >> 1) * 64, (gq + KV_FIRST * 8) * 4 + (mt & 1) * 2);
      if (gq >= PFS) tma_pf2(&p.ckv, gq * 64, mt * 128);
      TL(0, 15, true);
      if (DPF == 0) { prefetch_tm(&p.wv); prefetch_tm(&p.wq); prefetch_tm(&p.xn); prefetch_tm(&p.kv_ld); }
    }
    TL(0, 18, warp == 0);
    __syncwarp();
    cluster_wait();
    uint4* const xr = g_xr + rid * XR_SIZE;
    auto side_piece = [&](int c, int piece) {
      const uint32_t fb = B(B_WF + (c & 1));
      if (piece == 0) e_expect(fb, UNIT);
      ((EFM & 1) ? tma_ld2_ef : tma_ld2)(sb + OFF_SIDE + (c & 1) * UNIT + piece * 4096, (piece & 2) ? &p.wg : &p.wu, fb, fid * 32, c * 128 + (piece & 1) * 64);
    };
    if (warp == 0) {
      {
        int st = 0; uint32_t ph = 1;
#pragma unroll 1
        for (int i = 0; i < 32; i++) {
          const int t = i >> 3, kb = i & 7;
          if (i >= PRE) {
            const uint32_t fb = B(B_FULL1 + st);
            KWAIT(B(B_EMPTY1 + st), ph);
            e_expect(fb, t == 0 ? 3 * UNIT : 2 * UNIT);
            if (t == 0) tma_ld2(sb + kv_a(kb), &p.ckv, fb, kb * 64, mt * 128);
            ((EFM & 16) ? tma_ld3_mc_ef : tma_ld3_mc)(sb + kv_b(st) + rank * UNIT, (t & 1) ? &p.wv : &p.wk, fb, 0, kb * 64, (gq + ((t >> 1) ^ KV_FIRST) * 8) * 4 + rank * 2, 3);
          }
          if (i == LN_PF || i == LN_PF + 1) l2_prefetch(x + (size_t)cta * 16 * DM + (i - LN_PF) * 8 * DM, 16384);
          if (i == LN_GO) e_arrive(B(B_LNGO));
          if (DPF && i == 12) { prefetch_tm(&p.wq); prefetch_tm(&p.xn); prefetch_tm(&p.kv_ld); }
          if (kb == (t ? NPF : NPF0) && t < 3) tma_pf3((t & 1) ? &p.wk : &p.wv, 0, (mt >> 1) * 64, (gq + (((t + 1) >> 1) ^ KV_FIRST) * 8) * 4 + (mt & 1) * 2);
          if (kb < 2 && t == 3) tma_pf3(&p.wq, 0, (gq + 8 * kb) * 64, mt * 2);
          if (++st == 3) { st = 0; ph ^= 1; }
        }
        prefetch_tm(&p.ctx_ld); prefetch_tm(&p.wo); prefetch_tm(&p.wd); prefetch_tm(&p.x); prefetch_tm(&p.wg); prefetch_tm(&p.wu);
        PWAIT(B(B_DEP + 0), 0);
        uint32_t kpar = 7, vpar = 3;
        auto load_aw = [&](int kb, int head) {
          const uint32_t d = sb + q_aw(kb & 3), fb = B(B_FULLQ + (kb & 3));
          tma_ld2_mc(d + rank * 8192, &p.xn, fb, kb * 64, ta * 128 + rank * 64, 3);
          ((EFM & 16) ? tma_ld3_ef : tma_ld3)(d + UNIT, &p.wq, fb, 0, kb * 64, head * 2);
        };
        auto load_b = [&](int kb, uint32_t fb) { tma_ld2_mc(sb + q_b(kb & 3) + rank * 8192, &p.xn, fb, kb * 64, tb * 128 + rank * 64, 3); };
        auto load3 = [&](int kb, int s) {
          const uint32_t d = sb + r3(s), fb = B(B_FULL3 + s);
          e_expect(fb, SLOT);
          ((EFM & 4) ? tma_ld2_ef : tma_ld2)(d, &p.ctx_ld, fb, kb * 64, mt * 128);
          ((EFM & 2) ? tma_ld3_mc_ef : tma_ld3_mc)(d + UNIT + rank * 8192, &p.wo, fb, 0, kb * 64, gq * 2 + rank, 3);
        };
#pragma unroll 1
        for (int half = 0; half < 2; half++) {
          const int head = mt + 16 * half;
#pragma unroll 1
          for (int kb = 2 * half; kb < 16; kb++) {
            if (kb >= 4) KWAIT(B(B_EMPTYQ + (kb & 3)), ((kb >> 2) & 1) ^ 1);
            else if (half) PWAIT(B(B_X + 2), 0);
            else if (kb > 0) PWAIT(B(B_EMPTY1 + (kb + 1) % 3), kb == 1);
            e_expect(B(B_FULLQ + (kb & 3)), 3 * UNIT);
            load_aw(kb, head);
            load_b(kb, B(B_FULLQ + (kb & 3)));
          }
          PWAIT(B(B_DEP + 1 + half), 0);
          tma_pf3(&p.kv_ld, 0, 0, head * 2);
          auto load_v = [&](int j) {
            const int r = j & 1;
            AWAIT(B(B_VE + r), (vpar >> r) & 1);
            vpar ^= 1 << r;
            e_expect(B(B_VF + r), SLOT);
            ((EFM & 8) ? tma_ld3_ef : tma_ld3)(sb + v_slot(j), &p.kv_ld, B(B_VF + r), 0, SEQ + (j > qa ? WRAP : j) * 128, head * 2);
          };
          int r = 0;
#pragma unroll 1
          for (int j = 0; j < 17; j++) {
            if (j < 2) PWAIT(B(B_EMPTYQ + j), 1);
            if (j == 2) PWAIT(B(B_KE), kpar & 1);
            AWAIT(B(B_KE + r), (kpar >> r) & 1);
            kpar ^= 1 << r;
            e_expect(B(B_KF + r), SLOT);
            ((EFM & 8) ? tma_ld3_ef : tma_ld3)(sb + k_slot(j, r), &p.kv_ld, B(B_KF + r), 0, (j > qa ? WRAP : j) * 128, head * 2);
            if (++r == 3) r = 0;
            if (j == 2) PWAIT(B(B_EMPTYQ + 3), 1);
            if (j != 1) load_v(j ? j - 1 : 0);
            if (j == PFJ) {
              if (half == 0) {
                if (PFQ & 1) tma_pf3(&p.wq, 0, (PFQ0 + gq) * 64, (mt + 16) * 2);
                if (PFQ & 2) tma_pf2(&p.xn, (PFQ0 + (mp & 3)) * 64, ((mp & 4) ? qa : gq) * 128 + rank * 64);
              } else {
                PWAIT(B(B_DEP + 3), 0);
                if (PFP & 1) tma_pf3(&p.wo, 0, (PFP0 + mp) * 64, gq * 2 + rank);
                if (PFP & 2) tma_pf2(&p.ctx_ld, (PFP0 + gq) * 64, mt * 128);
              }
            }
            if (half && j >= 17 - PFC && ffn) tma_pf2(((j - 1) & 2) ? &p.wg : &p.wu, fid * 32, (2 + ((j - 17 + PFC) >> 2)) * 128 + ((j - 1) & 1) * 64);
            if (half && j >= 16 - PFO && j < 16) tma_pf3(&p.wo, 0, (PFP0 + mp + 8 * (16 - j)) * 64, gq * 2 + rank);
            if (half == 0) {
            } else if (ffn && j >= 5 && j < 13) {
              side_piece((j - 5) >> 2, (j - 5) & 3);
            }
          }
          PWAIT(B(B_X + 0), half);
          if (half == 0) {
            for (int kb = 0; kb < 2; kb++) { e_expect(B(B_FULLQ + kb), 2 * UNIT); load_aw(kb, mt + 16); }
          } else {
            load3(0, 0);
          }
          PWAIT(B(B_X + 1), half);
          if (half) load3(1, 1);
          load_v(16);
          if (gq == 0) PWAIT(B(B_X + 2), half);
          if (half == 0) { e_expect(B(B_FULLB), 2 * UNIT); load_b(0, B(B_FULLB)); load_b(1, B(B_FULLB)); }
        }
        st = 2; ph = 1;
#pragma unroll 1
        for (int kb = 2; kb < 64; kb++) {
          if (kb == 32) PWAIT(B(B_DEP + 4), 0);
          if (kb >= 6) PWAIT(B(B_EMPTY3 + st), ph);
          else if (kb == 3 || kb == 5) PWAIT(B(B_X + (kb + 1) / 2), 1);
          load3(kb, st);
          if (++st == 6) { st = 0; ph ^= 1; }
          if (kb == PF_KB) e_arrive(B(B_PF));
          if (kb == SET_KB) e_arrive(B(B_SET));
          if (kb == 58) l2_prefetch(xr, XR_CAND * 16);
        }
        if (ffn) {
#pragma unroll 1
          for (int j = 0; j < 2; j++) {
            PWAIT(B(B_EMPTY3 + 4 + j), 1);
            e_expect(B(B_FULL3 + 4 + j), SLOT);
            tma_ld3(sb + r3(4 + j), &p.wd, B(B_FULL3 + 4 + j), 0, fid * 32, 8 * j);
          }
        }
        const uint4* kp = g_xr + ((lane >> 1) * 8 + gq) * XR_SIZE + XR_KEY + (lane & 1) * 2;
        PWAIT(B(B_OUT), 0);
        uint4 kv[2];
        poll_chunks(kv, kp, 1);
        const uint32_t a1 = max(kv[0].x, kv[0].z), a2 = max(min(kv[0].x, kv[0].z), max(kv[0].y, kv[0].w));
        const uint32_t b1 = max(kv[1].x, kv[1].z), b2 = max(min(kv[1].x, kv[1].z), max(kv[1].y, kv[1].w));
        const uint32_t k1 = max(a1, b1), k2 = max(min(a1, b1), max(a2, b2));
        const uint32_t m1 = __reduce_max_sync(~0u, k1);
        const uint32_t m2 = __reduce_max_sync(~0u, k1 == m1 ? k2 : k1);
        if (lane == 0) {
          *reinterpret_cast<uint2*>(sp + OFF_MISC) = make_uint2(m1, m2);
          mbar_arrive(B(B_OUT2));
        }
        if (rid == 127) { g_cnt[lane] = 0; g_cnt[32 + lane] = 0; }
      }
    } else {
      if (warp >= 2) {
#pragma unroll 1
        for (int i = tid - 64; i < XR_CAND; i += 64) xr[i] = make_uint4(~0u, ~0u, ~0u, ~0u);
        if (warp == 2) { __syncwarp(); if (lane == 0) mbar_arrive(B(B_WR)); }
      }
      if (warp == 3) {
        float ws = 0.f;
#pragma unroll
        for (int j = 0; j < 4; j++) {
          const uint4 q = __ldg(reinterpret_cast<const uint4*>(w_r) + j * 32 + lane);
          ws += bf_lo(q.x) + bf_hi(q.x) + bf_lo(q.y) + bf_hi(q.y) + bf_lo(q.z) + bf_hi(q.z) + bf_lo(q.w) + bf_hi(q.w);
        }
#pragma unroll
        for (int o = 16; o; o >>= 1) ws += __shfl_xor_sync(~0u, ws, o);
        uint2* tab = reinterpret_cast<uint2*>(sp + OFF_MISC + 512);
        tab[lane] = make_uint2(0x3F803F80u, 0x3F803F80u);
        tab[32 + lane] = __ldg(reinterpret_cast<const uint2*>(w_r + gq * 128) + lane);
        if (lane == 0) *reinterpret_cast<float*>(sp + OFF_MISC + 1024) = ws;
        __syncwarp();
        if (lane == 0) mbar_arrive(B(B_WR));
      }
      __syncwarp();
      mbar_wait_u(B(B_LNGO), 0);
#pragma unroll 1
      for (int r = warp == 2 ? 0 : (warp + 1) >> 1; r < 16; r += 3) {
        const uint4* src = reinterpret_cast<const uint4*>(x + (size_t)(cta * 16 + r) * DM) + lane;
        uint4 v[4];
#pragma unroll
        for (int j = 0; j < 4; j++) v[j] = __ldg(src + j * 32);
        float a0 = 0.f, a1 = 0.f, b0 = 0.f, b1 = 0.f;
#pragma unroll
        for (int j = 0; j < 4; j++) {
          const uint32_t u[4] = {v[j].x, v[j].y, v[j].z, v[j].w};
#pragma unroll
          for (int i = 0; i < 4; i++) { const float a = bf_lo(u[i]), b = bf_hi(u[i]); a0 += a; a1 += b; b0 = fmaf(a, a, b0); b1 = fmaf(b, b, b1); }
        }
        a0 += a1; b0 += b1;
#pragma unroll
        for (int o = 16; o; o >>= 1) { a0 += __shfl_xor_sync(~0u, a0, o); b0 += __shfl_xor_sync(~0u, b0, o); }
        const float mean = a0 * (1.f / DM);
        float mb, inv;
        ln_round(mean, fmaxf(fmaf(b0, 1.f / DM, -mean * mean), 0.f), mb, inv);
        const uint32_t nm2 = pack_bf16(-mb, -mb);
        uint4* dst = reinterpret_cast<uint4*>(g_xn + (size_t)(cta * 16 + r) * DM) + lane;
#pragma unroll
        for (int j = 0; j < 4; j++) {
          dst[j * 32] = make_uint4(ln_apply(v[j].x, nm2, inv), ln_apply(v[j].y, nm2, inv), ln_apply(v[j].z, nm2, inv), ln_apply(v[j].w, nm2, inv));
          if (LNF) sched_fence();
        }
      }
      __syncwarp();
      if (lane == 0) {
        fence_gpu();
        red_add(&g_cnt[C_LN + (cta >> 3)], 1);
        TL(0, 20 + warp, true);
        if (warp == 3) {
          spin_until_ge<true>(&g_cnt[C_LN + gq], 24);
#pragma unroll 1
          for (int i = 0; i < 5; i++) {
            const int c = i == 0 ? C_LN + qa : (i < 3 ? C_KV + (i - 1) * 8 + mp : C_CTX + (i - 3) * 16 + mt);
            spin_until_ge<true>(&g_cnt[c], i == 0 ? 24 : 16);
            fence_async_all();
            mbar_arrive(B(B_DEP + i));
          }
        } else if (warp == 1) {
          mbar_wait(B(B_WR), 0);
#pragma unroll 1
          for (int i = 0; i < 6; i++) {
            const int c = i < 2 ? C_KV + gq + (i ^ KV_FIRST) * 8 : C_CTX + ((i - 2) >> 1) * 16 + ((i & 1) ? tb : ta);
            mbar_wait(B(B_PUB + i), 0);
            fence_gpu();
            red_add(&g_cnt[c], 1);
          }
        }
      }
      __syncwarp();
      if (warp == 2) {
#pragma unroll 1
        for (int c = 2; c < WIN + 4; c++) {
          mbar_wait_u(B(B_WE + (c & 1)), ((c >> 1) & 1) ^ 1);
          if (c == WIN || c == WIN + 1) {
            e_expect(B(B_WF + (c & 1)), UNIT);
            ((EFM & 1) ? tma_ld3_ef : tma_ld3)(sb + OFF_SIDE + (c & 1) * UNIT, &p.x, B(B_WF + (c & 1)), 0, mt * 128 + (c & 1) * 64, gq * 2);
          } else if (ffn) {
#pragma unroll 1
            for (int i = 0; i < 4; i++) { side_piece(c < WIN ? c : c - 2, i); __nanosleep(SIDE_NS); }
          }
        }
      } else if (warp == 1) {
        mbar_wait_u(B(B_SET), 0);
#pragma unroll 1
        for (int i = XR_CAND + lane; i < XR_SIZE; i += 32) { xr[i] = make_uint4(~0u, ~0u, ~0u, ~0u); __nanosleep(SET_NS); }
        __syncwarp();
        if (lane == 0) { fence_gpu(); mbar_arrive(B(B_SET2)); }
      } else {
        mbar_wait_u(B(B_PF), 0);
#pragma unroll 1
        for (int i = 0; i < PFD; i++) {
          asm volatile("prefetch.global.L2 [%0];" ::"l"((const char*)wdown + (size_t)cta * 57344 + (i * 32 + lane) * 128));
          __nanosleep(PF_NS);
        }
      }
      __syncwarp();
      mbar_wait_u(B(B_OUT), 0);
#pragma unroll OUT_UNROLL
      for (int i = warp - 1; i < 66; i += 3) {
        const int row = 2 * i + (lane >> 4);
        const uint2 rs = *reinterpret_cast<const uint2*>(sp + OFF_RSTAT + (row & 127) * 8);
        const uint4 v = lds128(sb + OFF_STG + ((row >> 6) & 1) * 16384 + ((lane & 15) >> 3) * 8192 + (row & 63) * 128 + (((lane ^ row) & 7) << 4));
        const float inv = __uint_as_float(rs.y);
        if ((int)rs.y >= 0 && row < 128)
          *reinterpret_cast<uint4*>(out + (size_t)(mt * 128 + row) * DM + gq * 128 + (lane & 15) * 8) =
              make_uint4(hadd2_bf(v.x, ln_apply(v.x, rs.x, inv)), hadd2_bf(v.y, ln_apply(v.y, rs.x, inv)),
                         hadd2_bf(v.z, ln_apply(v.z, rs.x, inv)), hadd2_bf(v.w, ln_apply(v.w, rs.x, inv)));
      }
      TL(2, 25, warp == 1);
    }
    __syncwarp();
    cluster_arrive();
    cluster_wait();
  } else {
    reg_alloc<232>();
    const int rid_c = rid0 + zero, warp_c = warp0 + zero;
    const int lane = fresh_lane(), rid = rid_c, mt = rid >> 3, gq = rid & 7, qa = 15 - gq, ta = gq ? gq : 15, tb = 15 - ta;
    const int warp = warp_c, cw = warp - 4, w = cw >> 2;
    cluster_wait();
    auto publish = [&](int i) { __syncwarp(); e_arrive(B(B_PUB + i)); };
    auto release2 = [&](uint32_t b, bool cond = true) { mbar_arrive_both(b, lane, cond); };
    AtState s;
    const uint32_t dA = mk_desc(sb + w * 8192, 16);
    const uint32_t dW = mk_desc(sb, 8192);
    auto mma_kb = [&](float (&d)[64], uint32_t a, uint32_t b, int accum) {
      static_for<4>([&](auto k) { mma_n128_ss<1, k * 32, k * 2048>(d, dA + (a >> 4), dW + (b >> 4), k == 0 ? accum : 1); });
    };
    auto mma_kc = [&](float (&d)[64], auto a, auto b, int accum) {
      static_for<4>([&](auto k) { mma_n128_ss<1, decltype(a)::value + k * 32, decltype(b)::value + k * 2048>(d, dA, dW, k == 0 ? accum : 1); });
    };
    auto issue_q = [&](int kb, auto accum) {
      const int st = kb & 3;
      mbar_wait_c(B(B_FULLQ + st), (kb >> 2) & 1);
      wg_fence();
      mma_kb(s.S, q_aw(st), q_aw(st) + UNIT, accum);
      wg_commit();
      if (accum) {
        wg_wait<1>();
        release2(B(B_EMPTYQ + ((kb - 1) & 3)));
        wg_fence();
      }
      mma_kb(s.O, q_b(st), q_aw(st) + UNIT, accum);
      wg_commit();
    };
    {
      uint4 pk[16];
      __nv_bfloat16* pdst = g_kv;
      auto put = [&](int i) { __stcs(reinterpret_cast<uint4*>(pdst + (i & 1) * 8 * NQ + (i >> 1) * 32), pk[i]); };
      float acc1[128];
      TL(0, 1, warp == 4);
      int st = 0; uint32_t ph = 0;
      auto issue = [&](int kb, int accum) {
        mbar_wait_c(B(B_FULL1 + st), ph);
        wg_fence();
        static_for<4>([&](auto k) { mma_n256_ss<1, k * 32, k * 2048>(acc1, dA + (kv_a(kb) >> 4), dW + (kv_b(st) >> 4), k == 0 ? accum : 1); });
        wg_commit();
      };
#pragma unroll 1
      for (int t = 0; t < 4; t++) {
        issue(0, 0);
        TL(0, 2 + 2 * t, warp == 4);
        if (t > 0) { put(0); put(1); }
        int prev = st;
        if (++st == 3) { st = 0; ph ^= 1; }
#pragma unroll 1
        for (int kb = 1; kb < 8; kb++) {
          if (kb == 7 && w == 1) bar_sync(5, 256);
          issue(kb, 1);
          if (kb == 7 && w == 0) bar_arrive(5, 256);
          if (t > 0) {
#pragma unroll
            for (int i = 1; i < 8; i++) if (kb == i) { put(2 * i); put(2 * i + 1); }
            if (kb == 7 && t == 2) publish(0);
          }
          wg_wait<1>();
          TK(24 + t * 8 + kb - 1);
          release2(B(B_EMPTY1 + prev));
          prev = st;
          if (++st == 3) { st = 0; ph ^= 1; }
        }
        pdst = g_kv + (size_t)((t & 1) * SEQ + mt * 128 + cw * 16 + (lane >> 2)) * NQ + (gq + ((t >> 1) ^ KV_FIRST) * 8) * 256 + (lane & 3) * 8;
        wg_wait<0>();
        TK(24 + t * 8 + 7);
        fence_regs(acc1);
        release2(B(B_EMPTY1 + prev));
        TL(0, 3 + 2 * t, warp == 4);
#pragma unroll
        for (int a = 0; a < 8; a++)
#pragma unroll
          for (int h = 0; h < 2; h++)
            pk[2 * a + h] = make_uint4(pack_bf16(acc1[16 * a + 2 * h], acc1[16 * a + 2 * h + 1]), pack_bf16(acc1[16 * a + 4 + 2 * h], acc1[16 * a + 5 + 2 * h]),
                                       pack_bf16(acc1[16 * a + 8 + 2 * h], acc1[16 * a + 9 + 2 * h]), pack_bf16(acc1[16 * a + 12 + 2 * h], acc1[16 * a + 13 + 2 * h]));
      }
      issue_q(0, IC<0>{});
      TL(0, 10, warp == 4);
      put(0); put(1);
#pragma unroll 1
      for (int kb = 1; kb < 8; kb++) {
        issue_q(kb, IC<1>{});
        TK(66 + kb - 1);
#pragma unroll
        for (int i = 1; i < 8; i++) if (kb == i) { put(2 * i); put(2 * i + 1); }
      }
      publish(1);
      TL(0, 11, warp == 4);
    }
    __nv_bfloat16* cdst;
    uint32_t redo = 0;
    auto put_ctx = [&](int i, bool cond) {
      asm volatile("{\n.reg .pred p;\nsetp.ne.u32 p, %5, 0;\n@p " CTX_ST " [%0], {%1,%2,%3,%4};\n}" ::"l"(cdst + (i & 1) * 8 * NQ + (i >> 1) * 32),
                   "r"(s.P[4 * i]), "r"(s.P[4 * i + 1]), "r"(s.P[4 * i + 2]), "r"(s.P[4 * i + 3]), "r"((uint32_t)(cond && !(redo & 2))) : "memory");
    };
    {
      const int wrow = cw * 16;
      const uint32_t dK = mk_desc(sb, 16), dV = mk_desc(sb, 16384);
      uint32_t kph = 0, vph = 0;
      auto q_store = [&](const float (&d)[64]) {
        const int r0 = lane >> 2;
        const uint32_t a = sb + SLOT + (wrow + r0) * 128 + (((lane & 3) ^ (((r0 & 1) << 2) | (r0 >> 1))) << 4);
#pragma unroll
        for (int i = 0; i < 8; i++) {
          const float* o = d + 16 * (i >> 1) + 2 * (i & 1);
          asm volatile("st.shared.v4.u32 [%0], {%1,%2,%3,%4};" ::"r"((a ^ ((i & 2) << 5)) + (i >> 2) * UNIT + (i & 1) * 1024),
                       "r"(pack_bf16(o[0] * AT_C, o[1] * AT_C)), "r"(pack_bf16(o[4] * AT_C, o[5] * AT_C)),
                       "r"(pack_bf16(o[8] * AT_C, o[9] * AT_C)), "r"(pack_bf16(o[12] * AT_C, o[13] * AT_C)) : "memory");
        }
        __syncwarp();
      };
      auto q_load = [&](auto k0, auto k1) {
        const uint32_t a = sb + SLOT + (wrow + (lane & 15)) * 128 + (((lane >> 4) ^ (((lane & 1) << 2) | ((lane >> 1) & 3))) << 4);
#pragma unroll
        for (int k = k0; k < k1; k++)
          asm volatile("ldmatrix.sync.aligned.m8n8.x4.shared.b16 {%0,%1,%2,%3}, [%4];"
                       : "=r"(s.Q[4 * k]), "=r"(s.Q[4 * k + 1]), "=r"(s.Q[4 * k + 2]), "=r"(s.Q[4 * k + 3]) : "r"((a ^ ((k & 3) << 5)) + (k >> 2) * UNIT) : "memory");
      };
      auto q_load_if = [&](auto k, bool cond, float after) {
        const uint32_t a = sb + SLOT + (wrow + (lane & 15)) * 128 + (((lane >> 4) ^ (((lane & 1) << 2) | ((lane >> 1) & 3))) << 4);
        asm volatile("{\n.reg .pred p;\nsetp.ne.u32 p, %5, 0;\n@p ldmatrix.sync.aligned.m8n8.x4.shared.b16 {%0,%1,%2,%3}, [%4];\n}"
                     : "+r"(s.Q[4 * k]), "+r"(s.Q[4 * k + 1]), "+r"(s.Q[4 * k + 2]), "+r"(s.Q[4 * k + 3])
                     : "r"((a ^ ((k & 3) << 5)) + (k >> 2) * UNIT + (__float_as_uint(after) >> 31)), "r"((uint32_t)cond) : "memory");
      };
      auto issue_s = [&](uint32_t off) {
        static_for<8>([&](auto k) { mma_n128_rs<0, (k >> 2) * 16384 + (k & 3) * 32>(s.S, s.Q + 4 * k, dK + (off >> 4), k != 0); });
        wg_commit();
      };
      auto issue_pv = [&](int jv, int accum, bool upper) {
        mbar_wait_c(B(B_VF + (jv & 1)), (vph >> (jv & 1)) & 1);
        vph ^= 1 << (jv & 1);
        wg_fence();
        static_for<4>([&](auto k) { mma_n128_rs<1, k * 2048>(s.O, s.P + 4 * k, dV + (v_slot(jv) >> 4), k == 0 ? accum : 1); });
        wg_commit();
        if (!TRIMPV || upper) {
          if (TRIMPV) wg_fence();
          static_for<4>([&](auto k) { mma_n128_rs<1, (k + 4) * 2048>(s.O, s.P + 16 + 4 * k, dV + (v_slot(jv) >> 4), 1); });
          wg_commit();
        } else {
          asm volatile("wgmma.fence.sync.aligned;\nwgmma.commit_group.sync.aligned;" ::: "memory");
        }
      };
      if (w == 1) bar_arrive(1, 256);
#pragma unroll 1
      for (int half = 0; half < 2; half++) {
        const int head = mt + 16 * half;
        redo = 0;
        float inv[2];
        auto ep_prep = [&]() {
          float l0 = s.l[0] + s.l[1], l1 = s.l[2] + s.l[3];
          l0 += __shfl_xor_sync(~0u, l0, 1); l1 += __shfl_xor_sync(~0u, l1, 1);
          l0 += __shfl_xor_sync(~0u, l0, 2); l1 += __shfl_xor_sync(~0u, l1, 2);
          asm("rcp.approx.ftz.f32 %0, %1;" : "=f"(inv[0]) : "f"(l0));
          asm("rcp.approx.ftz.f32 %0, %1;" : "=f"(inv[1]) : "f"(l1));
          return __any_sync(~0u, !(fminf(l0, l1) >= L_MIN && l0 + l1 <= L_MAX));
        };
        auto ep_out = [&](auto i0, auto i1) {
          __nv_bfloat16* dst = g_ctx + (size_t)(ta * 128 + wrow + (lane >> 2)) * NQ + head * 128 + (lane & 3) * 8;
#pragma unroll
          for (int i = i0; i < i1; i++) {
            const float* o = s.O + 16 * (i >> 1) + 2 * (i & 1);
            const float c = inv[i & 1];
            asm volatile(CTX_ST " [%0], {%1,%2,%3,%4};" ::"l"(dst + (i & 1) * 8 * NQ + (i >> 1) * 32), "r"(pack_bf16(o[0] * c, o[1] * c)),
                         "r"(pack_bf16(o[4] * c, o[5] * c)), "r"(pack_bf16(o[8] * c, o[9] * c)), "r"(pack_bf16(o[12] * c, o[13] * c)) : "memory");
          }
        };
        auto ep_rest = [&]() {
          ep_out(IC<EP1>{}, IC<8>{});
          if (!__any_sync(~0u, redo)) publish(2 + 2 * half);
          fence_regs(s.O);
        };
#pragma unroll 1
        for (int kb = 8; kb < 14; kb++) {
          issue_q(kb, IC<1>{});
          TK(66 + half * 24 + kb - 1);
        }
        TL(1, 20 * half + 0, warp == 4);
        mbar_wait_c(B(B_FULLQ + 2), 1);
        mbar_wait_c(B(B_FULLQ + 3), 1);
        bar_sync(1 + w, 256);
        wg_fence();
        mma_kc(s.S, IC<q_aw(2)>{}, IC<q_aw(2) + UNIT>{}, 1);
        wg_commit();
        wg_wait<1>();
        TK(66 + half * 24 + 13);
        release2(B(B_EMPTYQ + 1));
        wg_fence();
        mma_kc(s.S, IC<q_aw(3)>{}, IC<q_aw(3) + UNIT>{}, 1);
        wg_commit();
        bar_arrive(2 - w, 256);
        bar_sync(6 + w, 128);
        wg_wait<0>();
        TK(66 + half * 24 + 14);
        fence_regs(s.S);
        q_store(s.S);
        q_load(IC<0>{}, IC<8>{});
        TL(1, 20 * half + 1, warp == 4);
        mbar_wait_c(B(B_KF), kph & 1);
        kph ^= 1;
        bar_sync(1 + w, 256);
        fence_regs(s.S); fence_regs(s.O); fence_regs(s.Q);
        wg_fence();
        issue_s(k_slot(0, 0));
        mma_kc(s.O, IC<q_b(2)>{}, IC<q_aw(2) + UNIT>{}, 1);
        mma_kc(s.O, IC<q_b(3)>{}, IC<q_aw(3) + UNIT>{}, 1);
        wg_commit();
        bar_arrive(2 - w, 256);
        wg_wait<1>();
        fence_regs(s.S);
        e_arrive(B(B_KE));
        s.l[0] = s.l[1] = s.l[2] = s.l[3] = 0.f;
        at_exp<0, 48>(s);
        at_pack<0, 22>(s);
        sched_fence();
        wg_wait<0>();
        fence_regs(s.O); fence_regs(s.Q);
        release2(B(B_EMPTYQ + 2)); release2(B(B_EMPTYQ + 3));
        at_exp<48, 64>(s);
        at_pack<22, 32>(s);
        q_store(s.O);
        TL(1, 20 * half + 2, warp == 4);
        int kr = 1;
        bool kok = false;
        inv[0] = inv[1] = 0.f;
        const int db = gq ? qa : 16;
#pragma unroll 1
        for (int j = 1; j < 17; j++) {
          const bool diag = j == ta || j == db;
          TC(w, j + 17 * half, 0);
          if (!kok) mbar_wait_c(B(B_KF + kr), (kph >> kr) & 1);
          kph ^= 1 << kr;
          if (j == ta + 2) ep_out(IC<0>{}, IC<EP1>{});
          bar_sync(1 + w, 256);
          TC(w, j + 17 * half, 2);
          fence_regs(s.S); fence_regs(s.O); fence_regs(s.P); fence_regs(s.Q);
          const uint32_t ke = B(B_KE + kr), ko = k_slot(j, kr);
          if (++kr == 3) kr = 0;
          auto issue_rest = [&](auto trimmed) {
            TC(w, j + 17 * half, 1);
            if (j == ta + 1) {
              if (ep_prep()) redo = 1;
              s.l[0] = s.l[1] = s.l[2] = s.l[3] = 0.f;
            }
            if (!trimmed && j == ta + 2) ep_rest();
            TC(w, j + 17 * half, 3);
            issue_pv(j - 1, j != 1 && j != ta + 2, w == 1 || (j != ta + 1 && j != db + 1));
            bar_arrive(2 - w, 256);
          };
          auto s_done = [&]() {
            wg_wait<2>();
            TC(w, j + 17 * half, 4);
            fence_regs(s.S); fence_regs(s.Q);
            e_arrive(ke);
            release2(B(B_X + j - 14), j == 14 || j == 15);
          };
          auto pv_half = [&]() { sched_fence(); wg_wait<1>(); fence_regs(s.P); };
          auto pv_done = [&]() {
            sched_fence();
            wg_wait<0>();
            fence_regs(s.O); fence_regs(s.P);
            e_arrive(B(B_VE + ((j - 1) & 1)));
            release2(B(B_X + 2), j == 16);
            kok = KTEST && mbar_test(B(B_KF + kr), (kph >> kr) & 1);
          };
          if (diag && w == 0) {
            wg_fence();
            static_for<8>([&](auto k) { mma_n64_rs<(k >> 2) * 16384 + (k & 3) * 32>(s.S, s.Q + 4 * k, dK + (ko >> 4), k != 0); });
            wg_commit();
            issue_rest(IC<1>{});
            s_done();
            at_mask<0>(s, wrow, lane);
            if (DELAY0 == 1) pv_half();
            if (DELAY0 == 2) pv_done();
            static_for<8>([&](auto k) {
              at_exp<4 * k, 4 * k + 4, 32>(s);
              q_load_if(k, j == ta, s.S[4 * k]);
              if (DELAY0 == 0 && k == 3) pv_half();
            });
            at_pack<0, 16>(s);
            if (DELAY0 < 2) pv_done();
          } else {
            wg_fence();
            issue_s(ko);
            issue_rest(IC<0>{});
            if (!diag) {
              s_done();
              at_exp<0, 4 * SP1>(s);
              pv_half();
              at_exp<4 * SP1, 4 * SP2>(s);
              at_pack<0, 16>(s);
              pv_done();
              at_exp<4 * SP2, 64>(s);
              at_pack<16, 32>(s);
            } else {
              s_done();
              at_mask<8>(s, wrow - 64, lane);
              static_for<8>([&](auto k) {
                at_exp<7 * k, 7 * k + 7>(s);
                q_load_if(k, j == ta, s.S[7 * k + 3]);
                if (k == 2) pv_half();
                if (k == 5) { at_pack<0, 16>(s); pv_done(); }
              });
              at_exp<56, 64>(s);
              at_pack<16, 32>(s);
            }
          }
          TL(1, 20 * half + 2 + j, warp == 4);
        }
        TK(84 + half * 24);
        mbar_wait_c(B(half ? B_FULL3 : B_FULLQ), 0);
        if (gq == 0) ep_out(IC<0>{}, IC<EP1>{});
        bar_sync(1 + w, 256);
        fence_regs(s.S); fence_regs(s.O); fence_regs(s.P);
        wg_fence();
        mma_kc(s.S, IC<0>{}, IC<UNIT>{}, 0);
        mbar_wait_c(B(half ? B_FULL3 + 1 : B_FULLQ + 1), 0);
        wg_fence();
        mma_kb(s.S, (2 + half) * SLOT, (2 + half) * SLOT + UNIT, 1);
        wg_commit();
        TK(85 + half * 24);
        if (gq == 0) ep_rest();
        issue_pv(16, gq != 0, w == 1 || gq != 0);
        if (w == 0 || half == 0) bar_arrive(2 - w, 256);
        TK(86 + half * 24);
        wg_wait<2>();
        release2(B(B_EMPTY3), half); release2(B(B_EMPTY3 + 1), half);
        if (ep_prep()) redo |= 2;
        sched_fence();
        wg_wait<0>();
        TK(87 + half * 24);
        fence_regs(s.S);
        fence_regs(s.O);
        e_arrive(B(B_VE));
        release2(B(B_X + 3));
        fence_regs(s.P);
        {
          const int r = fresh_lane();
          cdst = g_ctx + (size_t)(tb * 128 + wrow + (r >> 2)) * NQ + head * 128 + (r & 3) * 8;
        }
#pragma unroll
        for (int i = 0; i < 32; i++) {
          const float* o = s.O + 16 * (i >> 3) + 2 * ((i >> 2) & 1) + 4 * (i & 3);
          s.P[i] = pack_bf16(o[0] * inv[(i >> 2) & 1], o[1] * inv[(i >> 2) & 1]);
        }
        fence_regs(s.P);
        if (__builtin_expect(__any_sync(~0u, redo != 0), 0)) {
#pragma unroll
          for (int i = 0; i < 8; i++) put_ctx(i, true);
#pragma unroll 1
          for (int t = 0; t < 2; t++) {
            if (__any_sync(~0u, (redo >> t) & 1)) slow_rows(wq, head, (t ? tb : ta) * 128 + wrow);
          }
          if (__any_sync(~0u, redo & 1)) publish(2 + 2 * half);
#pragma unroll
          for (int i = 0; i < 64; i++) { s.O[i] = 0.f; s.P[i >> 1] = 0; }
          redo = 2;
        }
        TL(1, 20 * half + 19, warp == 4);
        TK(88 + half * 24);
        if (half) break;
        mbar_wait_c(B(B_FULLB), 0);
        TK(89);
        fence_regs(s.O);
        wg_fence();
        mma_kc(s.O, IC<q_b(0)>{}, IC<q_aw(0) + UNIT>{}, 0);
        wg_commit();
        mma_kc(s.O, IC<q_b(1)>{}, IC<q_aw(1) + UNIT>{}, 1);
        wg_commit();
        wg_wait<1>();
        release2(B(B_EMPTYQ));
        put_ctx(0, true);
#pragma unroll 1
        for (int kb = 2; kb < 8; kb++) {
          issue_q(kb, IC<1>{});
          TK(90 + kb - 1);
#pragma unroll
          for (int i = 1; i < 8; i++) put_ctx(i, kb == (i < 7 ? i + 1 : 7));
        }
        publish(3);
      }
    }
    const int rid_ = rid + zero, cw_ = cw + zero;
    {
    const int lane = fresh_lane(), rid = rid_, mt = rid >> 3, gq = rid & 7, cw = cw_, w = cw >> 2, ct = cw * 32 + lane;
    const int fid = mt * 7 + gq - NOFFN0;
    const bool ffn = NOFFN0 ? gq > 0 : gq < 7;
    const uint32_t stg = sb + OFF_STG + w * 16384 + (cw & 3) * 2048;
    const int wr_ = w * 64 + (lane & 7) + (lane >> 4) * 8;
    const uint32_t wl = sb + ((lane >> 3) & 1) * 8192 + wr_ * 64 + (((cw ^ (wr_ >> 1)) & 3) << 4);
    __syncwarp();
    float (&acc)[64] = s.S;
    uint32_t wf[128];
    auto grab = [&](auto c, uint32_t off) {
#pragma unroll
      for (int m = 0; m < 4; m++)
        asm volatile("ldmatrix.sync.aligned.m8n8.x4.trans.shared.b16 {%0,%1,%2,%3}, [%4];"
                     : "=r"(wf[16 * c + 4 * m]), "=r"(wf[16 * c + 4 * m + 1]), "=r"(wf[16 * c + 4 * m + 2]), "=r"(wf[16 * c + 4 * m + 3])
                     : "r"(wl + off + m * 1024) : "memory");
    };
    const int r0 = lane >> 2;
    uint32_t hp[32], rt[16];
    {
      int st = 2, prev = 1; uint32_t ph = 0;
      auto run = [&](auto k0, auto k1, auto back) {
#pragma unroll 1
        for (int kb = k0; kb < k1; kb++) {
          mbar_wait_c(B(B_FULL3 + st), ph);
          wg_fence();
          mma_kb(acc, r3(st), r3(st) + UNIT, 1);
          wg_commit();
          wg_wait<1>();
          release2(B(B_EMPTY3 + prev), k0 != 2 || kb != 2);
          if (kb == k0) back();
          prev = st;
          if (++st == 6) { st = 0; ph ^= 1; }
#pragma unroll
          for (int i = 0; i < 8; i++) if (PUT0 + PUTD * i >= k0 && PUT0 + PUTD * i < k1) put_ctx(i, kb == PUT0 + PUTD * i);
          if (PUT0 + PUTD * 7 >= k0 && PUT0 + PUTD * 7 < k1 && kb == PUT0 + PUTD * 7) publish(5);
          if ((kb & 7) == 7) TL(2, 2 + (kb >> 3), warp == 4);
        }
      };
      auto hand = [&](uint32_t b, int n, uint32_t f0, uint32_t f1, uint32_t f2, uint32_t f3) {
        asm volatile("{\n.reg .pred p;\n.reg .b32 t;\nsetp.lt.u32 p, %1, %7;\nlop3.b32 t, %1, %2, %3, 0xE8;\nlop3.b32 t, t, %4, %5, 0xE8;\n"
                     "mad.lo.u32 t, t, %6, %0;\n@p mbarrier.arrive.shared::cta.b64 _, [t];\n}"
                     ::"r"(b + 8 * lane), "r"(lane), "r"(f0), "r"(f1), "r"(f2), "r"(f3), "r"(zero), "r"(n) : "memory");
      };
      static_for<WIN + 1>([&](auto c) {
        run(IC<c == 0 ? 2 : GRAB0 + GRABD * (c - 1)>{}, IC<(c < WIN ? GRAB0 + GRABD * c : XGRAB)>{}, [&]() {
          constexpr int f = c > 0 ? 16 * (c - 1) : 0;
          if (c > 0) hand(B(B_WE + ((c - 1) & 1)), 1, wf[f], wf[f + 4], wf[f + 8], wf[f + 12]);
        });
        if (c < WIN) {
          if (ffn) mbar_wait_c(B(B_WF + (c & 1)), (c >> 1) & 1);
          grab(IC<(c < WIN ? c : 0)>{}, OFF_SIDE + (c & 1) * UNIT);
        }
      });
      mbar_wait_c(B(B_WF), ffn ? (WIN >> 1) & 1 : 0);
      mbar_wait_c(B(B_WF + 1), ffn ? (WIN >> 1) & 1 : 0);
      mbar_wait_c(B(B_WR), 0);
      const uint32_t xa = sb + OFF_SIDE + w * UNIT + (cw & 3) * 2048 + (lane & 15) * 128 + (((lane >> 4) ^ (lane & 7)) << 4);
#pragma unroll
      for (int j = 0; j < 8; j++)
        asm volatile("ldmatrix.sync.aligned.m8n8.x4.shared.b16 {%0,%1,%2,%3}, [%4];"
                     : "=r"(hp[4 * j]), "=r"(hp[4 * j + 1]), "=r"(hp[4 * j + 2]), "=r"(hp[4 * j + 3]) : "r"((xa ^ ((j & 3) << 5)) + (j >> 2) * 8192) : "memory");
      run(IC<XGRAB>{}, IC<XGRAB + 2>{}, [&]() { hand(B(B_WE), 2, hp[0] ^ hp[4], hp[8] ^ hp[12], hp[16] ^ hp[20], hp[24] ^ hp[28]); });
#pragma unroll
      for (int j = 0; j < 4; j++)
        asm volatile("ldmatrix.sync.aligned.m8n8.x4.shared.b16 {%0,%1,%2,%3}, [%4];"
                     : "=r"(rt[4 * j]), "=r"(rt[4 * j + 1]), "=r"(rt[4 * j + 2]), "=r"(rt[4 * j + 3])
                     : "r"(sb + OFF_MISC + 512 + (lane & 1) * 256 + (lane >> 3) * 16 + j * 64) : "memory");
      run(IC<XGRAB + 2>{}, IC<64>{}, []() {});
    }
    uint4* const xr = g_xr + rid * XR_SIZE;
    mbar_wait_c(B(B_SET2), 0);
    mbar_wait_c(B(B_EMPTY3), 0);
    wg_wait<0>();
    fence_regs(acc);
    TL(2, 10, warp == 4);
    {
      float d[4] = {0.f, 0.f, 0.f, 0.f}, qa[4] = {0.f, 0.f, 0.f, 0.f}, qb[4] = {0.f, 0.f, 0.f, 0.f};
#pragma unroll
      for (int j = 0; j < 16; j++) {
        hp[2 * j] = hadd2_bf(hp[2 * j], pack_bf16(acc[4 * j], acc[4 * j + 1]));
        hp[2 * j + 1] = hadd2_bf(hp[2 * j + 1], pack_bf16(acc[4 * j + 2], acc[4 * j + 3]));
        if (j & 1) {
          mma16816(d, hp[2 * j - 2], hp[2 * j - 1], hp[2 * j], hp[2 * j + 1], rt[j - 1], rt[j]);
          mma16816(qa, hp[2 * j - 2], hp[2 * j - 1], hp[2 * j], hp[2 * j + 1], hp[2 * j - 2], hp[2 * j]);
          mma16816(qb, hp[2 * j - 2], hp[2 * j - 1], hp[2 * j], hp[2 * j + 1], hp[2 * j - 1], hp[2 * j + 1]);
        }
      }
      const float s2a = __shfl_sync(~0u, (r0 & 1) ? qa[1] : qa[0], r0 * 4 + (r0 >> 1));
      const float s2b = __shfl_sync(~0u, (r0 & 1) ? qb[3] : qb[2], r0 * 4 + (r0 >> 1));
      if ((lane & 3) == 0) {
        __stcg(reinterpret_cast<float4*>(xr + XR_PS + cw * 16 + r0), make_float4(d[0], s2a, d[1], 0.f));
        __stcg(reinterpret_cast<float4*>(xr + XR_PS + cw * 16 + r0 + 8), make_float4(d[2], s2b, d[3], 0.f));
      }
    }
    __syncwarp();
    stage_store_128(stg, lane, hp);
    TL(2, 11, warp == 4);
    __syncwarp();
    uint4 cout;
    uint32_t ckey;
    {
      uint4 ps[4];
      const float wsum = *reinterpret_cast<const float*>(sp + OFF_MISC + 1024);
      if (PDLY) spin_clk(PDLY);
      poll_chunks(ps, g_xr + (mt * 8 + (ct & 1) * 4) * XR_SIZE + XR_PS + (ct >> 1), XR_SIZE);
      TL(2, 12, warp == 4);
      auto F = [](uint32_t u) { return __uint_as_float(u); };
      float s1 = (F(ps[0].x) + F(ps[1].x)) + (F(ps[2].x) + F(ps[3].x)), s2 = (F(ps[0].y) + F(ps[1].y)) + (F(ps[2].y) + F(ps[3].y));
      float s3 = (F(ps[0].z) + F(ps[1].z)) + (F(ps[2].z) + F(ps[3].z));
      s1 += __shfl_xor_sync(~0u, s1, 1); s2 += __shfl_xor_sync(~0u, s2, 1); s3 += __shfl_xor_sync(~0u, s3, 1);
      const float mean = s1 * (1.f / DM);
      float mb, inv;
      ln_round(mean, fmaxf(fmaf(s2, 1.f / DM, -mean * mean), 0.f), mb, inv);
      uint32_t u = pack_bf16((s3 - mb * wsum) * inv, 0.f);
      if (u == 0x8000u) u = 0;
      u = (u & 0x8000u) ? (~u & 0xFFFFu) : (u | 0x8000u);
      const uint32_t key = (u << 16) | (0x7FFFu - (mt * 128 + (ct >> 1)));
      const uint32_t nm2 = pack_bf16(-mb, -mb);
      const uint32_t c1 = __reduce_max_sync(~0u, key);
      const uint32_t c2 = __reduce_max_sync(~0u, key == c1 ? 0u : key);
      if (lane == 0) __stcg(reinterpret_cast<uint2*>(xr + XR_KEY) + cw, make_uint2(c1, c2));
      if (!(ct & 1)) *reinterpret_cast<uint2*>(sp + OFF_RSTAT + (ct >> 1) * 8) = make_uint2(nm2, __float_as_uint(inv) | (key >= c2 ? 0x80000000u : 0u));
      ckey = (lane >> 4) ? c2 : c1;
      const int row = (0x7FFF - (ckey & 0x7FFF)) & 15;
      const uint32_t rn = __shfl_sync(~0u, nm2, row * 2);
      const float ri = __shfl_sync(~0u, inv, row * 2);
      const uint4 v = lds128(stg + ((lane & 15) >> 3) * 8192 + row * 128 + (((lane & 7) ^ (row & 7)) << 4));
      const uint4 n = make_uint4(ln_apply(v.x, rn, ri), ln_apply(v.y, rn, ri), ln_apply(v.z, rn, ri), ln_apply(v.w, rn, ri));
      __stcg(xr + XR_CAND + cw * 64 + 32 + lane, n);
      __stcg(xr + XR_CAND + cw * 64 + lane, v);
      cdst = out + (size_t)(0x7FFF - (ckey & 0x7FFF)) * DM + gq * 128 + (lane & 15) * 8;
      cout = make_uint4(hadd2_bf(v.x, n.x), hadd2_bf(v.y, n.y), hadd2_bf(v.z, n.z), hadd2_bf(v.w, n.w));
    }
    publish(B_OUT - B_PUB);
    cluster_arrive();
    TL(2, 13, warp == 4);
    uint32_t wd[16][4];
    if (ffn) {
      static_for<2>([&](auto i) {
        mbar_wait_c(B(B_WF + i), ((WIN >> 1) & 1) ^ 1);
        grab(IC<WIN + i>{}, OFF_SIDE + i * UNIT);
      });
      mbar_wait_c(B(B_FULL3 + 4 + w), 0);
#pragma unroll
      for (int i = 0; i < 16; i++) {
        const int k = (i & 1) * 16 + (lane & 7) + (lane >> 4) * 8;
        asm volatile("ldmatrix.sync.aligned.m8n8.x4.trans.shared.b16 {%0,%1,%2,%3}, [%4];"
                     : "=r"(wd[i][0]), "=r"(wd[i][1]), "=r"(wd[i][2]), "=r"(wd[i][3])
                     : "r"(sb + r3(4) + w * SLOT + (2 * (cw & 3) + (i >> 3)) * 4096 + k * 128 + (((2 * ((i >> 1) & 3) + ((lane >> 3) & 1)) ^ (lane & 7)) << 4)) : "memory");
      }
    }
    mbar_wait_c(B(B_OUT2), 0);
    const uint2 top = *reinterpret_cast<const uint2*>(sp + OFF_MISC);
    TL(2, 14, warp == 4);
    const int t0 = 0x7FFF - (top.x & 0x7FFF), t1 = 0x7FFF - (top.y & 0x7FFF);
    auto cand = [&](int second, int chunk) {
      const int tk = second ? t1 : t0;
      return g_xr + ((tk >> 7) * 8 + (chunk >> 4)) * XR_SIZE + XR_CAND + ((tk >> 4) & 7) * 64 + ((second && (t0 >> 4) == (t1 >> 4)) ? 16 : 0) + (chunk & 15);
    };
    const int fc = 16 * (rid >> 1) + 4 * (rid & 1) + (lane & 3) + 8 * (lane >> 4), ft = (lane >> 3) & 1;
    uint32_t fh, fn;
    {
      const uint4* pc = cand(w, ct & 127) + 32;
      const uint16_t* pf = reinterpret_cast<const uint16_t*>(cand(ft, fc >> 3)) + (fc & 7);
      uint4 v;
#pragma unroll 1
      for (int n = 0; n < 0x400000; n++) {
        asm volatile("ld.relaxed.gpu.global.v4.u32 {%0,%1,%2,%3}, [%4];" : "=r"(v.x), "=r"(v.y), "=r"(v.z), "=r"(v.w) : "l"(pc) : "memory");
        asm volatile("ld.relaxed.gpu.global.u16 %0, [%1];" : "=r"(fh) : "l"(pf) : "memory");
        asm volatile("ld.relaxed.gpu.global.u16 %0, [%1 + 512];" : "=r"(fn) : "l"(pf) : "memory");
        if (__all_sync(~0u, max(max(v.x, v.y), max(v.z, v.w)) != 0xFFFFFFFFu && max(fh, fn) != 0xFFFFu)) break;
      }
      const int blk = (ct & 127) >> 2;
      const uint32_t a = sb + OFF_SCR + w * 2112 + blk * 64 + (((blk >> 1) & 3) << 4) + (ct & 3) * 4;
      asm volatile("st.shared.u32 [%0], %1;" ::"r"(a), "r"(v.x) : "memory");
      asm volatile("st.shared.u32 [%0], %1;" ::"r"(a ^ 16), "r"(v.y) : "memory");
      asm volatile("st.shared.u32 [%0], %1;" ::"r"(a ^ 32), "r"(v.z) : "memory");
      asm volatile("st.shared.u32 [%0], %1;" ::"r"(a ^ 48), "r"(v.w) : "memory");
    }
    asm volatile("{\n.reg .pred p;\nsetp.lt.u32 p, %5, %6;\n@p st.global.v4.u32 [%0], {%1,%2,%3,%4};\n}" ::"l"(cdst), "r"(cout.x), "r"(cout.y), "r"(cout.z),
                 "r"(cout.w), "r"(ckey), "r"(top.y) : "memory");
    if (ffn) {
      bar_sync(3, 256);
      TL(2, 15, warp == 4);
      float d[2][4] = {{0.f, 0.f, 0.f, 0.f}, {0.f, 0.f, 0.f, 0.f}};
      const uint32_t xb = sb + OFF_SCR + (r0 & 1) * 2112 + w * 128 + (((lane ^ w) & 3) << 4);
#pragma unroll
      for (int i = 0; i < 16; i++) {
        const uint4 b = lds128((xb ^ ((i & 2) << 4)) + (i >> 1) * 256 + (i & 1) * 64);
        mma16816(d[0], wf[8 * i], wf[8 * i + 1], wf[8 * i + 2], wf[8 * i + 3], b.x, b.y);
        mma16816(d[1], wf[8 * i + 4], wf[8 * i + 5], wf[8 * i + 6], wf[8 * i + 7], b.z, b.w);
      }
      float2* red = reinterpret_cast<float2*>(sp + OFF_SCR + 8192);
      if (!(lane & 2))
        red[(w * 2 + (lane & 1)) * 32 + (cw & 3) * 8 + r0] = (lane & 1) ? make_float2(d[0][1] + d[1][1], d[0][3] + d[1][3]) : make_float2(d[0][0] + d[1][0], d[0][2] + d[1][2]);
      bar_sync(3, 256);
      TL(2, 16, warp == 4);
      const uint32_t ra = sb + OFF_SCR + 8192 + (r0 & 1) * 256 + (r0 >> 1) * 64 + (lane & 3) * 16;
      const uint4 p0 = lds128(ra), p1 = lds128(ra + 512);
      auto act = [](uint32_t u0, uint32_t u1, uint32_t g0, uint32_t g1) {
        const uint32_t ug = pack_bf16(__uint_as_float(u0) + __uint_as_float(u1), __uint_as_float(g0) + __uint_as_float(g1));
        const float g = bf_hi(ug);
        return bf_round(__fdividef(g, 1.f + __expf(-g))) * bf_lo(ug);
      };
      const uint32_t av = pack_bf16(act(p0.x, p1.x, p0.y, p1.y), act(p0.z, p1.z, p0.w, p1.w));
      uint32_t b[4];
#pragma unroll
      for (int i = 0; i < 4; i++) b[i] = __shfl_sync(~0u, av, 8 * i + (lane & 7));
      TL(2, 17, warp == 4);
      float y[2][4] = {{0.f, 0.f, 0.f, 0.f}, {0.f, 0.f, 0.f, 0.f}};
#pragma unroll
      for (int c = 0; c < 4; c++) {
        const bool on = (lane >> 3) == c;
        const uint32_t b0 = on ? b[0] : 0, b1 = on ? b[1] : 0, b2 = on ? b[2] : 0, b3 = on ? b[3] : 0;
#pragma unroll
        for (int a = 0; a < 2; a++) {
          const int i = 8 * a + 2 * c;
          mma16816(y[a], wd[i][0], wd[i][1], wd[i][2], wd[i][3], b0, b1);
          mma16816(y[a], wd[i + 1][0], wd[i + 1][1], wd[i + 1][2], wd[i + 1][3], b2, b3);
        }
      }
      float4* yd = reinterpret_cast<float4*>(g_xr + (cw * 16 + (lane & 3) * 2 + (lane >> 4)) * XR_SIZE + XR_Y + fid * 4 + (r0 & 3));
      __stcg(yd, make_float4(y[0][0], y[0][1], y[0][2], y[0][3]));
      __stcg(yd + 8 * XR_SIZE, make_float4(y[1][0], y[1][1], y[1][2], y[1][3]));
    }
    TL(2, 18, warp == 4);
    if (cw == 0) {
      uint32_t u = (ft ? top.y : top.x) >> 16;
      u = (u & 0x8000u) ? (u & 0x7FFFu) : (~u & 0xFFFFu);
      float rs = bf_round(__fdividef(1.f, 1.f + __expf(-__uint_as_float(u << 16))));
      uint16_t* op = reinterpret_cast<uint16_t*>(out) + (size_t)(ft ? t1 : t0) * DM + fc;
      asm volatile("" : "+l"(op), "+f"(rs));
      spin_clk(ffn ? YDLY : YDLY + YDLY0);
      float v[4];
#pragma unroll 1
      for (int n = 0; n < 0x400000; n++) {
        float4 z[14];
#pragma unroll
        for (int i = 0; i < 14; i++)
          asm volatile("ld.relaxed.gpu.global.v4.f32 {%0,%1,%2,%3}, [%4];" : "=f"(z[i].x), "=f"(z[i].y), "=f"(z[i].z), "=f"(z[i].w) : "l"(xr + XR_Y + lane + 32 * i) : "memory");
        float a[4] = {z[0].x, z[0].y, z[0].z, z[0].w}, b[4] = {z[1].x, z[1].y, z[1].z, z[1].w};
#pragma unroll
        for (int i = 2; i < 14; i += 2) {
          a[0] += z[i].x; a[1] += z[i].y; a[2] += z[i].z; a[3] += z[i].w;
          b[0] += z[i + 1].x; b[1] += z[i + 1].y; b[2] += z[i + 1].z; b[3] += z[i + 1].w;
        }
#pragma unroll
        for (int i = 0; i < 4; i++) v[i] = a[i] + b[i];
        const float t = (v[0] + v[1]) + (v[2] + v[3]);
        if (__all_sync(~0u, t == t)) break;
        uint32_t m = 0;
#pragma unroll
        for (int i = 0; i < 14; i++) m = max(max(m, max(__float_as_uint(z[i].x), __float_as_uint(z[i].y))), max(__float_as_uint(z[i].z), __float_as_uint(z[i].w)));
        if (__all_sync(~0u, m != 0xFFFFFFFFu)) break;
      }
      TL(2, 30, true);
      const bool hi = lane & 16, odd = lane & 8;
      const float a0 = (hi ? v[2] : v[0]) + __shfl_xor_sync(~0u, hi ? v[0] : v[2], 16), a1 = (hi ? v[3] : v[1]) + __shfl_xor_sync(~0u, hi ? v[1] : v[3], 16);
      float yv = (odd ? a1 : a0) + __shfl_xor_sync(~0u, odd ? a0 : a1, 8);
      yv += __shfl_xor_sync(~0u, yv, 4);
      const uint32_t o = hadd2_bf(fh, hadd2_bf(fn, pack_bf16(bf_round(yv) * rs, 0.f)));
      if (!(lane & 4)) *op = (uint16_t)o;
      TL(2, 21, true);
    }
    TL(2, 20, warp == 4);
    }
    __syncwarp();
    cluster_wait();
  }
}

typedef CUresult (*EncodeFn)(CUtensorMap*, CUtensorMapDataType, cuuint32_t, void*, const cuuint64_t*, const cuuint64_t*, const cuuint32_t*,
                             const cuuint32_t*, CUtensorMapInterleave, CUtensorMapSwizzle, CUtensorMapL2promotion, CUtensorMapFloatOOBfill);
EncodeFn g_enc = nullptr;

void map2(CUtensorMap* m, const void* ptr, uint64_t rows, uint64_t cols, uint32_t bc, uint32_t br) {
  const CUtensorMapSwizzle sw = bc == 64 ? CU_TENSOR_MAP_SWIZZLE_128B : CU_TENSOR_MAP_SWIZZLE_64B;
  cuuint64_t gd[2] = {cols, rows}, gs[1] = {cols * 2};
  cuuint32_t bd[2] = {bc, br}, es[2] = {1, 1};
  g_enc(m, CU_TENSOR_MAP_DATA_TYPE_BFLOAT16, 2, (void*)ptr, gd, gs, bd, es, CU_TENSOR_MAP_INTERLEAVE_NONE, sw,
        CU_TENSOR_MAP_L2_PROMOTION_L2_128B, CU_TENSOR_MAP_FLOAT_OOB_FILL_NONE);
}
void map3(CUtensorMap* m, const void* ptr, uint64_t rows, uint64_t cols, uint32_t br, uint32_t bch) {
  cuuint64_t gd[3] = {64, rows, cols / 64}, gs[2] = {cols * 2, 128};
  cuuint32_t bd[3] = {64, br, bch}, es[3] = {1, 1, 1};
  g_enc(m, CU_TENSOR_MAP_DATA_TYPE_BFLOAT16, 3, (void*)ptr, gd, gs, bd, es, CU_TENSOR_MAP_INTERLEAVE_NONE, CU_TENSOR_MAP_SWIZZLE_128B,
        CU_TENSOR_MAP_L2_PROMOTION_L2_128B, CU_TENSOR_MAP_FLOAT_OOB_FILL_NONE);
}

}

extern "C" void kernel_launch(void* const* d_in, const int* in_sizes, int n_in, void* d_out, int out_size) {
  const __nv_bfloat16* x = (const __nv_bfloat16*)d_in[0];
  const __nv_bfloat16* ckv = (const __nv_bfloat16*)d_in[1];
  const __nv_bfloat16* wq = (const __nv_bfloat16*)d_in[2];
  const __nv_bfloat16* wk = (const __nv_bfloat16*)d_in[3];
  const __nv_bfloat16* wv = (const __nv_bfloat16*)d_in[4];
  const __nv_bfloat16* wo = (const __nv_bfloat16*)d_in[5];
  const __nv_bfloat16* w_r = (const __nv_bfloat16*)d_in[7];
  const __nv_bfloat16* wgate = (const __nv_bfloat16*)d_in[8];
  const __nv_bfloat16* wup = (const __nv_bfloat16*)d_in[9];
  const __nv_bfloat16* wdown = (const __nv_bfloat16*)d_in[10];
  __nv_bfloat16* out = (__nv_bfloat16*)d_out;

  if (!g_enc) {
    void* fn = nullptr;
    cudaDriverEntryPointQueryResult qr;
    cudaGetDriverEntryPoint("cuTensorMapEncodeTiled", &fn, cudaEnableDefault, &qr);
    g_enc = (EncodeFn)fn;
    cudaFuncSetAttribute(fused_kernel, cudaFuncAttributeMaxDynamicSharedMemorySize, SMEM_BYTES);
  }
  void *xn, *kv, *ctx, *xr, *cnt;
  cudaGetSymbolAddress(&xr, g_xr);
  cudaGetSymbolAddress(&cnt, g_cnt);
  cudaGetSymbolAddress(&xn, g_xn);
  cudaGetSymbolAddress(&kv, g_kv);
  cudaGetSymbolAddress(&ctx, g_ctx);

  Params p;
  map2(&p.xn, xn, SEQ, DM, 64, 64);
  map2(&p.ckv, ckv, SEQ, DC, 64, 128);
  map3(&p.wq, wq, DM, NQ, 64, 2);
  map3(&p.wk, wk, DC, NQ, 64, 2);
  map3(&p.wv, wv, DC, NQ, 64, 2);
  map3(&p.kv_ld, kv, 2 * SEQ, NQ, 128, 2);
  map2(&p.ctx_ld, ctx, SEQ, NQ, 64, 128);
  map3(&p.wo, wo, NQ, DM, 64, 1);
  map3(&p.x, x, SEQ, DM, 64, 2);
  map3(&p.wd, wdown, FF, DM, 32, 8);
  map2(&p.wg, wgate, DM, FF, 32, 64);
  map2(&p.wu, wup, DM, FF, 32, 64);
  fused_kernel<<<128, 384, SMEM_BYTES, cudaStreamPerThread>>>(0u, x, (__nv_bfloat16*)kv, (__nv_bfloat16*)ctx, (uint4*)xr, out, (__nv_bfloat16*)xn,
                                                               (unsigned*)cnt, w_r, wdown, wq, p);
}
```

```cpp
#include <cuda_runtime.h>
#include <cuda_bf16.h>
#include <cuda.h>
#include <stdint.h>
#include <utility>

#pragma nv_diag_suppress 549
#pragma nv_diag_suppress 177
namespace {

constexpr int SEQ = 2048, DM = 1024, NH = 32, HD = 128, DC = 512, NQ = NH * HD, FF = 3584;

__device__ __align__(1024) __nv_bfloat16 g_xn[SEQ * DM];
__device__ __align__(1024) __nv_bfloat16 g_kv[2 * SEQ * NQ];
__device__ __align__(1024) __nv_bfloat16 g_ctx[SEQ * NQ];
constexpr int XR_PS = 0;
constexpr int XR_KEY = 128;
constexpr int XR_CAND = 136;
constexpr int XR_Y = 648;
constexpr int XR_SIZE = 1104;
__device__ __align__(1024) uint4 g_xr[128 * XR_SIZE];
constexpr int C_LN = 0, C_KV = 16, C_CTX = 32, C_NUM = 64;
__device__ unsigned g_cnt[C_NUM];

#define TL(k, i, cond) do {} while (0)
#define TC(w, g, i) do {} while (0)
#define TL_EXTRA 0
#define TK(i) do {} while (0)

__device__ __forceinline__ uint32_t s2u(const void* p) { return (uint32_t)__cvta_generic_to_shared(p); }
__device__ __forceinline__ void mbar_arrive(uint32_t b) { asm volatile("mbarrier.arrive.shared::cta.b64 _, [%0];" ::"r"(b) : "memory"); }
__device__ __forceinline__ void mbar_arrive_both(uint32_t b, uint32_t lane, bool cond) {
  asm volatile("{\n.reg .pred p;\n.reg .b32 r;\nsetp.lt.u32 p, %1, %2;\nmapa.shared::cluster.u32 r, %0, %1;\n@p mbarrier.arrive.shared::cluster.b64 _, [r];\n}"
               ::"r"(b), "r"(lane), "r"(cond ? 2 : 0) : "memory");
}
__device__ __forceinline__ bool mbar_test(uint32_t b, uint32_t ph) {
  uint32_t ok;
  asm volatile("{\n.reg .pred p;\nmbarrier.test_wait.parity.shared::cta.b64 p, [%1], %2;\nselp.u32 %0, 1, 0, p;\n}" : "=r"(ok) : "r"(b), "r"(ph) : "memory");
  return __all_sync(~0u, ok);
}
__device__ __forceinline__ void mbar_wait(uint32_t b, uint32_t ph) {
  asm volatile(
      "{\n.reg .pred p;\n.reg .u32 n;\nmov.u32 n, 0;\n"
      "LW:\nmbarrier.try_wait.parity.shared::cta.b64 p, [%0], %1, 20000;\n@p bra LD;\n"
      "add.u32 n, n, 1;\nsetp.lt.u32 p, n, 0x40000;\n@p bra LW;\ntrap;\nLD:\n}" ::"r"(b), "r"(ph) : "memory");
}
__device__ __forceinline__ void mbar_wait_u(uint32_t b, uint32_t ph) {
  asm volatile(
      "{\n.reg .pred p;\n.reg .u32 n;\nmov.u32 n, 0;\n"
      "LW:\nmbarrier.try_wait.parity.shared::cta.b64 p, [%0], %1, 20000;\n@p bra.uni LD;\n"
      "add.u32 n, n, 1;\nsetp.lt.u32 p, n, 0x40000;\n@p bra.uni LW;\ntrap;\nLD:\n}" ::"r"(b), "r"(ph) : "memory");
}
__device__ __forceinline__ void mbar_wait_c(uint32_t b, uint32_t ph) {
  asm volatile(
      "{\n.reg .pred p;\n.reg .u32 n;\nmov.u32 n, 0;\n"
      "LW:\nmbarrier.try_wait.parity.shared::cta.b64 p, [%0], %1;\n@p bra.uni LD;\n"
      "add.u32 n, n, 1;\nsetp.lt.u32 p, n, 0x100000;\n@p bra.uni LW;\ntrap;\nLD:\n}" ::"r"(b), "r"(ph) : "memory");
}
template <bool SLEEP = false>
__device__ __forceinline__ void spin_until_ge(const unsigned* p, unsigned target) {
  asm volatile(
      "{\n.reg .pred p, q;\n.reg .u32 n, v;\nmov.u32 n, 0;\nsetp.ne.u32 q, %2, 0;\n"
      "LW:\nld.acquire.gpu.global.u32 v, [%0];\nsetp.ge.u32 p, v, %1;\n@p bra LD;\n@q nanosleep.u32 200;\n"
      "add.u32 n, n, 1;\nsetp.lt.u32 p, n, 0x400000;\n@p bra LW;\ntrap;\nLD:\n}" ::"l"(p), "r"(target), "n"((int)SLEEP) : "memory");
}
template <int N>
__device__ __forceinline__ void poll_chunks(uint4 (&v)[N], const uint4* p, int stride) {
#pragma unroll 1
  for (int n = 0; n < 0x400000; n++) {
    uint32_t m = 0;
#pragma unroll
    for (int i = 0; i < N; i++) {
      asm volatile("ld.relaxed.gpu.global.v4.u32 {%0,%1,%2,%3}, [%4];" : "=r"(v[i].x), "=r"(v[i].y), "=r"(v[i].z), "=r"(v[i].w) : "l"(p + i * stride) : "memory");
    }
#pragma unroll
    for (int i = 0; i < N; i++) m = max(max(m, max(v[i].x, v[i].y)), max(v[i].z, v[i].w));
    if (__all_sync(~0u, m != 0xFFFFFFFFu)) break;
  }
}
__device__ __forceinline__ void spin_clk(uint32_t n) {
  asm volatile("{\n.reg .pred p;\n.reg .u32 a, b;\nmov.u32 a, %%clock;\nLW:\nmov.u32 b, %%clock;\nsub.u32 b, b, a;\nsetp.lt.u32 p, b, %0;\n@p bra.uni LW;\n}" ::"r"(n) : "memory");
}
__device__ __forceinline__ int fresh_lane() {
  int r;
  asm volatile("mov.u32 %0, %%laneid;" : "=r"(r));
  return r;
}
__device__ __forceinline__ void fence_async_all() { asm volatile("fence.proxy.async;" ::: "memory"); }
__device__ __forceinline__ void bar_sync(int id, int n) { asm volatile("bar.sync %0, %1;" ::"r"(id), "r"(n) : "memory"); }
__device__ __forceinline__ void bar_arrive(int id, int n) { asm volatile("bar.arrive %0, %1;" ::"r"(id), "r"(n) : "memory"); }
__device__ __forceinline__ void cluster_arrive() { asm volatile("barrier.cluster.arrive.relaxed.aligned;" ::: "memory"); }
__device__ __forceinline__ void cluster_wait() { asm volatile("barrier.cluster.wait.acquire.aligned;" ::: "memory"); }
__device__ __forceinline__ void fence_gpu() { asm volatile("fence.acq_rel.gpu;" ::: "memory"); }
__device__ __forceinline__ void red_add(unsigned* p, unsigned v) { asm volatile("red.relaxed.gpu.global.add.u32 [%0], %1;" ::"l"(p), "r"(v) : "memory"); }
#define ELECT "{\n.reg .pred E;\nelect.sync _|E, 0xFFFFFFFF;\n@E "
__device__ __forceinline__ void e_init(uint32_t b, uint32_t c) { asm volatile(ELECT "mbarrier.init.shared::cta.b64 [%0], %1;\n}" ::"r"(b), "r"(c) : "memory"); }
__device__ __forceinline__ void e_expect(uint32_t b, uint32_t bytes) { asm volatile(ELECT "mbarrier.arrive.expect_tx.shared::cta.b64 _, [%0], %1;\n}" ::"r"(b), "r"(bytes) : "memory"); }
__device__ __forceinline__ void e_arrive(uint32_t b) { asm volatile(ELECT "mbarrier.arrive.shared::cta.b64 _, [%0];\n}" ::"r"(b) : "memory"); }
__device__ __forceinline__ void prefetch_tm(const CUtensorMap* m) { asm volatile(ELECT "prefetch.tensormap [%0];\n}" ::"l"(m) : "memory"); }
__device__ __forceinline__ void tma_ld2(uint32_t dst, const CUtensorMap* m, uint32_t bar, int c0, int c1) {
  asm volatile(ELECT "cp.async.bulk.tensor.2d.shared::cta.global.mbarrier::complete_tx::bytes [%0], [%1, {%3,%4}], [%2];\n}" ::"r"(dst), "l"(m), "r"(bar), "r"(c0), "r"(c1) : "memory");
}
__device__ __forceinline__ void tma_ld3(uint32_t dst, const CUtensorMap* m, uint32_t bar, int c0, int c1, int c2) {
  asm volatile(ELECT "cp.async.bulk.tensor.3d.shared::cta.global.mbarrier::complete_tx::bytes [%0], [%1, {%3,%4,%5}], [%2];\n}" ::"r"(dst), "l"(m), "r"(bar), "r"(c0), "r"(c1), "r"(c2) : "memory");
}
__device__ __forceinline__ void tma_ld2_mc(uint32_t dst, const CUtensorMap* m, uint32_t bar, int c0, int c1, uint16_t mask) {
  asm volatile(ELECT "cp.async.bulk.tensor.2d.shared::cluster.global.mbarrier::complete_tx::bytes.multicast::cluster [%0], [%1, {%3,%4}], [%2], %5;\n}" ::"r"(dst), "l"(m), "r"(bar), "r"(c0), "r"(c1), "h"(mask) : "memory");
}
__device__ __forceinline__ void tma_ld3_mc(uint32_t dst, const CUtensorMap* m, uint32_t bar, int c0, int c1, int c2, uint16_t mask) {
  asm volatile(ELECT "cp.async.bulk.tensor.3d.shared::cluster.global.mbarrier::complete_tx::bytes.multicast::cluster [%0], [%1, {%3,%4,%5}], [%2], %6;\n}" ::"r"(dst), "l"(m), "r"(bar), "r"(c0), "r"(c1), "r"(c2), "h"(mask) : "memory");
}
__device__ __forceinline__ uint64_t policy_evict_first() {
  uint64_t p;
  asm("createpolicy.fractional.L2::evict_first.b64 %0, 1.0;" : "=l"(p));
  return p;
}
__device__ __forceinline__ void tma_ld2_ef(uint32_t dst, const CUtensorMap* m, uint32_t bar, int c0, int c1) {
  asm volatile(ELECT "cp.async.bulk.tensor.2d.shared::cta.global.mbarrier::complete_tx::bytes.L2::cache_hint [%0], [%1, {%3,%4}], [%2], %5;\n}" ::"r"(dst), "l"(m), "r"(bar), "r"(c0), "r"(c1), "l"(policy_evict_first()) : "memory");
}
__device__ __forceinline__ void tma_ld3_ef(uint32_t dst, const CUtensorMap* m, uint32_t bar, int c0, int c1, int c2) {
  asm volatile(ELECT "cp.async.bulk.tensor.3d.shared::cta.global.mbarrier::complete_tx::bytes.L2::cache_hint [%0], [%1, {%3,%4,%5}], [%2], %6;\n}" ::"r"(dst), "l"(m), "r"(bar), "r"(c0), "r"(c1), "r"(c2), "l"(policy_evict_first()) : "memory");
}
__device__ __forceinline__ void tma_pf2(const CUtensorMap* m, int c0, int c1) { asm volatile(ELECT "cp.async.bulk.prefetch.tensor.2d.L2.global [%0, {%1,%2}];\n}" ::"l"(m), "r"(c0), "r"(c1) : "memory"); }
__device__ __forceinline__ void tma_pf3(const CUtensorMap* m, int c0, int c1, int c2) { asm volatile(ELECT "cp.async.bulk.prefetch.tensor.3d.L2.global [%0, {%1,%2,%3}];\n}" ::"l"(m), "r"(c0), "r"(c1), "r"(c2) : "memory"); }
__device__ __forceinline__ void sched_fence() { asm volatile("pmevent 0;" ::: "memory"); }
__device__ __forceinline__ void l2_prefetch(const void* p, uint32_t bytes) { asm volatile(ELECT "cp.async.bulk.prefetch.L2.global [%0], %1;\n}" ::"l"(p), "r"(bytes) : "memory"); }

__device__ __forceinline__ void wg_fence() { asm volatile("wgmma.fence.sync.aligned;" ::: "memory"); }
__device__ __forceinline__ void wg_commit() { asm volatile("wgmma.commit_group.sync.aligned;" ::: "memory"); }
template <int N> __device__ __forceinline__ void wg_wait() { asm volatile("wgmma.wait_group.sync.aligned %0;" ::"n"(N) : "memory"); }
template <int N> __device__ __forceinline__ void reg_alloc() { asm volatile("setmaxnreg.inc.sync.aligned.u32 %0;" ::"n"(N)); }
template <int N> __device__ __forceinline__ void reg_dealloc() { asm volatile("setmaxnreg.dec.sync.aligned.u32 %0;" ::"n"(N)); }
template <int N> __device__ __forceinline__ void fence_regs(float (&d)[N]) {
#pragma unroll
  for (int i = 0; i < N; i++) asm volatile("" : "+f"(d[i])::"memory");
}
template <int I0, int I1, int N> __device__ __forceinline__ void fence_part(float (&d)[N]) {
#pragma unroll
  for (int i = I0; i < I1; i++) asm volatile("" : "+f"(d[i])::"memory");
}
template <int N> __device__ __forceinline__ void fence_regs(uint32_t (&d)[N]) {
#pragma unroll
  for (int i = 0; i < N; i++) asm volatile("" : "+r"(d[i])::"memory");
}

__device__ __forceinline__ uint32_t mk_desc(uint32_t addr, uint32_t lbo) { return ((addr & 0x3FFFF) >> 4) | ((lbo >> 4) << 16); }

#define R8(b) "+f"(d[b + 0]), "+f"(d[b + 1]), "+f"(d[b + 2]), "+f"(d[b + 3]), "+f"(d[b + 4]), "+f"(d[b + 5]), "+f"(d[b + 6]), "+f"(d[b + 7])
#define REGS64 "%0,%1,%2,%3,%4,%5,%6,%7,%8,%9,%10,%11,%12,%13,%14,%15,%16,%17,%18,%19,%20,%21,%22,%23,%24,%25,%26,%27,%28,%29,%30,%31," \
               "%32,%33,%34,%35,%36,%37,%38,%39,%40,%41,%42,%43,%44,%45,%46,%47,%48,%49,%50,%51,%52,%53,%54,%55,%56,%57,%58,%59,%60,%61,%62,%63"
#define REGS128 REGS64 ",%64,%65,%66,%67,%68,%69,%70,%71,%72,%73,%74,%75,%76,%77,%78,%79,%80,%81,%82,%83,%84,%85,%86,%87,%88,%89,%90,%91,%92,%93,%94,%95," \
               "%96,%97,%98,%99,%100,%101,%102,%103,%104,%105,%106,%107,%108,%109,%110,%111,%112,%113,%114,%115,%116,%117,%118,%119,%120,%121,%122,%123,%124,%125,%126,%127"

#define DESC(d, r, o) "add.u32 t, " r ", " o ";\nmov.b64 " d ", {t, h};\n"
#define MMA_PRE(acc) "{\n.reg .pred p;\n.reg .b32 t, h;\n.reg .b64 da, db;\nmov.b32 h, 0x40000040;\nsetp.ne.b32 p, " acc ", 0;\n"
template <int TB, int OA, int OB>
__device__ __forceinline__ void mma_n256_ss(float (&d)[128], uint32_t a, uint32_t b, int acc) {
  asm volatile(MMA_PRE("%130") DESC("da", "%128", "%132") DESC("db", "%129", "%133")
               "wgmma.mma_async.sync.aligned.m64n256k16.f32.bf16.bf16 {" REGS128 "}, da, db, p, 1, 1, 0, %131;\n}\n"
               : R8(0), R8(8), R8(16), R8(24), R8(32), R8(40), R8(48), R8(56), R8(64), R8(72), R8(80), R8(88), R8(96), R8(104), R8(112), R8(120)
               : "r"(a), "r"(b), "r"(acc), "n"(TB), "n"(OA >> 4), "n"(OB >> 4));
}
template <int TB, int OA, int OB>
__device__ __forceinline__ void mma_n128_ss(float (&d)[64], uint32_t a, uint32_t b, int acc) {
  asm volatile(MMA_PRE("%66") DESC("da", "%64", "%68") DESC("db", "%65", "%69")
               "wgmma.mma_async.sync.aligned.m64n128k16.f32.bf16.bf16 {" REGS64 "}, da, db, p, 1, 1, 0, %67;\n}\n"
               : R8(0), R8(8), R8(16), R8(24), R8(32), R8(40), R8(48), R8(56)
               : "r"(a), "r"(b), "r"(acc), "n"(TB), "n"(OA >> 4), "n"(OB >> 4));
}
template <int TB, int OB>
__device__ __forceinline__ void mma_n128_rs(float (&d)[64], const uint32_t* a, uint32_t b, int acc) {
  asm volatile(MMA_PRE("%69") DESC("db", "%68", "%71")
               "wgmma.mma_async.sync.aligned.m64n128k16.f32.bf16.bf16 {" REGS64 "}, {%64,%65,%66,%67}, db, p, 1, 1, %70;\n}\n"
               : R8(0), R8(8), R8(16), R8(24), R8(32), R8(40), R8(48), R8(56)
               : "r"(a[0]), "r"(a[1]), "r"(a[2]), "r"(a[3]), "r"(b), "r"(acc), "n"(TB), "n"(OB >> 4));
}
#define W8(b) "=f"(d[b + 0]), "=f"(d[b + 1]), "=f"(d[b + 2]), "=f"(d[b + 3]), "=f"(d[b + 4]), "=f"(d[b + 5]), "=f"(d[b + 6]), "=f"(d[b + 7])
#define MMA_N64 MMA_PRE("%37") DESC("db", "%36", "%38") \
  "wgmma.mma_async.sync.aligned.m64n64k16.f32.bf16.bf16 {%0,%1,%2,%3,%4,%5,%6,%7,%8,%9,%10,%11,%12,%13,%14,%15,%16,%17,%18,%19,%20,%21," \
  "%22,%23,%24,%25,%26,%27,%28,%29,%30,%31}, {%32,%33,%34,%35}, db, p, 1, 1, 0;\n}\n"
template <int H, int OB, bool ACC>
__device__ __forceinline__ void mma_n64_rs(float (&d)[64], const uint32_t* a, uint32_t b) {
  if (ACC) asm volatile(MMA_N64 : R8(32 * H), R8(32 * H + 8), R8(32 * H + 16), R8(32 * H + 24) : "r"(a[0]), "r"(a[1]), "r"(a[2]), "r"(a[3]), "r"(b), "n"(1), "n"(OB >> 4));
  else asm volatile(MMA_N64 : W8(32 * H), W8(32 * H + 8), W8(32 * H + 16), W8(32 * H + 24) : "r"(a[0]), "r"(a[1]), "r"(a[2]), "r"(a[3]), "r"(b), "n"(0), "n"(OB >> 4));
}
template <int OB>
__device__ __forceinline__ void mma_n128_rs0(float (&d)[64], const uint32_t* a, uint32_t b) {
  asm volatile(MMA_PRE("%69") DESC("db", "%68", "%70")
               "wgmma.mma_async.sync.aligned.m64n128k16.f32.bf16.bf16 {" REGS64 "}, {%64,%65,%66,%67}, db, p, 1, 1, 0;\n}\n"
               : W8(0), W8(8), W8(16), W8(24), W8(32), W8(40), W8(48), W8(56)
               : "r"(a[0]), "r"(a[1]), "r"(a[2]), "r"(a[3]), "r"(b), "n"(0), "n"(OB >> 4));
}
template <int TB, int OA, int OB>
__device__ __forceinline__ void mma_n128_ss0(float (&d)[64], uint32_t a, uint32_t b) {
  asm volatile(MMA_PRE("%66") DESC("da", "%64", "%68") DESC("db", "%65", "%69")
               "wgmma.mma_async.sync.aligned.m64n128k16.f32.bf16.bf16 {" REGS64 "}, da, db, p, 1, 1, 0, %67;\n}\n"
               : W8(0), W8(8), W8(16), W8(24), W8(32), W8(40), W8(48), W8(56)
               : "r"(a), "r"(b), "n"(0), "n"(TB), "n"(OA >> 4), "n"(OB >> 4));
}
template <int V> struct IC { static constexpr int value = V; __host__ __device__ constexpr operator int() const { return V; } };
template <int N, class F, int... I>
__device__ __forceinline__ void static_for_(F f, std::integer_sequence<int, I...>) { (f(IC<I>{}), ...); }
template <int N, class F>
__device__ __forceinline__ void static_for(F f) { static_for_<N>(f, std::make_integer_sequence<int, N>{}); }
__device__ __forceinline__ uint32_t pack_bf16(float lo, float hi) {
  uint32_t r;
  asm("cvt.rn.bf16x2.f32 %0, %1, %2;" : "=r"(r) : "f"(hi), "f"(lo));
  return r;
}
__device__ __forceinline__ float bf_lo(uint32_t v) { return __uint_as_float(v << 16); }
__device__ __forceinline__ float bf_hi(uint32_t v) { return __uint_as_float(v & 0xFFFF0000u); }
__device__ __forceinline__ float bf_round(float v) { return bf_lo(pack_bf16(v, v)); }
__device__ __forceinline__ void stsm4(uint32_t addr, uint32_t r0, uint32_t r1, uint32_t r2, uint32_t r3) {
  asm volatile("stmatrix.sync.aligned.m8n8.x4.shared.b16 [%0], {%1,%2,%3,%4};" ::"r"(addr), "r"(r0), "r"(r1), "r"(r2), "r"(r3) : "memory");
}
__device__ __forceinline__ uint4 lds128(uint32_t addr) {
  uint4 v;
  asm volatile("ld.shared.v4.u32 {%0,%1,%2,%3}, [%4];" : "=r"(v.x), "=r"(v.y), "=r"(v.z), "=r"(v.w) : "r"(addr));
  return v;
}
__device__ __forceinline__ float ex2(float x) {
  float y;
  asm("ex2.approx.ftz.f32 %0, %1;" : "=f"(y) : "f"(x));
  return y;
}
__device__ __forceinline__ void stage_store_128(uint32_t base, int lane, const uint32_t* pk) {
  const int row = (lane & 7) + ((lane >> 3) & 1) * 8;
  const uint32_t rb = base + row * 128;
  const int hi = lane >> 4;
#pragma unroll
  for (int j = 0; j < 8; j++) {
    const int chunk = 2 * j + hi;
    const uint32_t a = rb + (j >> 2) * 8192 + (((chunk & 7) ^ (lane & 7)) << 4);
    stsm4(a, pk[4 * j + 0], pk[4 * j + 1], pk[4 * j + 2], pk[4 * j + 3]);
  }
}
__device__ __forceinline__ void ln_round(float mean, float var, float& m_bf, float& inv_s) {
  const uint32_t mv = pack_bf16(mean, var);
  m_bf = bf_lo(mv);
  float sq, rc;
  asm("sqrt.approx.f32 %0, %1;" : "=f"(sq) : "f"(bf_round(bf_hi(mv) + 1e-5f)));
  asm("rcp.approx.ftz.f32 %0, %1;" : "=f"(rc) : "f"(bf_round(sq)));
  inv_s = rc;
}
__device__ __forceinline__ uint32_t hadd2_bf(uint32_t a, uint32_t b) {
  uint32_t r;
  asm("add.rn.bf16x2 %0, %1, %2;" : "=r"(r) : "r"(a), "r"(b));
  return r;
}
__device__ __forceinline__ uint32_t ln_apply(uint32_t h, uint32_t nm2, float inv_s) {
  const uint32_t d = hadd2_bf(h, nm2);
  return pack_bf16(bf_lo(d) * inv_s, bf_hi(d) * inv_s);
}
__device__ __forceinline__ void mma16816(float* d, uint32_t a0, uint32_t a1, uint32_t a2, uint32_t a3, uint32_t b0, uint32_t b1) {
  asm volatile("mma.sync.aligned.m16n8k16.row.col.f32.bf16.bf16.f32 {%0,%1,%2,%3}, {%4,%5,%6,%7}, {%8,%9}, {%0,%1,%2,%3};"
               : "+f"(d[0]), "+f"(d[1]), "+f"(d[2]), "+f"(d[3]) : "r"(a0), "r"(a1), "r"(a2), "r"(a3), "r"(b0), "r"(b1));
}

constexpr float AT_C = 0.08838834764831845f * 1.4426950408889634f;
#define L_MIN 2.3283064e-10f
#define L_MAX 1.0995116e12f
struct AtState {
  float S[64], O[64];
  uint32_t P[32], Q[32];
  float l[4];
};
template <int I0, int I1>
__device__ __forceinline__ void at_exp(AtState& s) {
#pragma unroll
  for (int i = I0; i < I1; i++) asm volatile("ex2.approx.ftz.f32 %0, %0;" : "+f"(s.S[i]));
#pragma unroll
  for (int i = I0; i < I1; i++) asm volatile("add.f32 %0, %0, %1;" : "+f"(s.l[i & 3]) : "f"(s.S[i]));
}
template <int I0, int I1>
__device__ __forceinline__ void at_pack(AtState& s) {
#pragma unroll
  for (int i = I0; i < I1; i++) asm volatile("cvt.rn.bf16x2.f32 %0, %1, %2;" : "=r"(s.P[i]) : "f"(s.S[2 * i + 1]), "f"(s.S[2 * i]));
}
template <int J0>
__device__ __forceinline__ void at_mask(AtState& s, int r, int lane) {
  const int d = r + (lane >> 2) - (lane & 3) * 2;
#pragma unroll
  for (int j = 0; j < 8; j++) {
    float dummy0 = 0.f, dummy1 = 0.f;
    float& lo0 = j < 7 ? s.S[4 * (J0 + (j < 7 ? j + 1 : j)) + 2] : dummy0;
    float& lo1 = j < 7 ? s.S[4 * (J0 + (j < 7 ? j + 1 : j)) + 3] : dummy1;
    asm("{\n.reg .pred p, q;\nsetp.lt.s32 p, %4, %5;\nsetp.le.s32 q, %4, %5;\n"
        "@p add.f32 %0, %0, 0fFF800000;\n@q add.f32 %1, %1, 0fFF800000;\n@p add.f32 %2, %2, 0fFF800000;\n@q add.f32 %3, %3, 0fFF800000;\n}"
        : "+f"(s.S[4 * (J0 + j)]), "+f"(s.S[4 * (J0 + j) + 1]), "+f"(lo0), "+f"(lo1) : "r"(d), "r"(8 * j));
  }
}
__device__ __forceinline__ uint32_t ld_pair(const __nv_bfloat16* p) {
  uint32_t r;
  asm volatile("{\n.reg .b16 a, b;\nld.global.cg.b16 a, [%1];\nld.global.cg.b16 b, [%1 + 8192];\nmov.b32 %0, {a, b};\n}" : "=r"(r) : "l"(p) : "memory");
  return r;
}
__device__ __forceinline__ uint32_t ld_word(const uint32_t* p) {
  uint32_t r;
  asm volatile("ld.global.cg.b32 %0, [%1];" : "=r"(r) : "l"(p) : "memory");
  return r;
}
__device__ __forceinline__ void slow_rows(const __nv_bfloat16* wq, int head, int row0) {
  const int lane = fresh_lane(), r = lane >> 2, c = lane & 3;
  uint32_t q[32];
  float o[32];
#pragma unroll
  for (int i = 0; i < 32; i++) q[i] = 0;
  const uint32_t* xa = reinterpret_cast<const uint32_t*>(g_xn + (size_t)(row0 + r) * DM) + c;
#pragma unroll 1
  for (int h = 0; h < 2; h++) {
    const __nv_bfloat16* wb = wq + (size_t)2 * c * NQ + head * HD + 64 * h + 8 * (r >> 1) + (r & 1);
#pragma unroll
    for (int i = 0; i < 32; i++) o[i] = 0.f;
#pragma unroll 1
    for (int kk = 0; kk < DM / 16; kk++) {
      const uint32_t a0 = ld_word(xa + 8 * kk), a1 = ld_word(xa + 8 * kk + 4 * DM), a2 = ld_word(xa + 8 * kk + 4), a3 = ld_word(xa + 8 * kk + 4 * DM + 4);
#pragma unroll
      for (int n = 0; n < 8; n++) {
        const __nv_bfloat16* b = wb + (size_t)16 * kk * NQ + 32 * (n >> 2) + 2 * (n & 3);
        mma16816(o + 4 * n, a0, a1, a2, a3, ld_pair(b), ld_pair(b + 8 * NQ));
      }
    }
#pragma unroll
    for (int i = 0; i < 16; i++) { q[i] = q[16 + i]; q[16 + i] = pack_bf16(o[2 * i] * AT_C, o[2 * i + 1] * AT_C); }
  }
#pragma unroll 1
  for (int h = 0; h < 2; h++) {
    float m0 = -INFINITY, m1 = -INFINITY, l0 = 0.f, l1 = 0.f;
#pragma unroll
    for (int i = 0; i < 32; i++) o[i] = 0.f;
#pragma unroll 1
    for (int k0 = 0; k0 <= row0; k0 += 16) {
      float e[8] = {0.f, 0.f, 0.f, 0.f, 0.f, 0.f, 0.f, 0.f};
      const uint32_t* kp = reinterpret_cast<const uint32_t*>(g_kv + (size_t)(k0 + r) * NQ + head * HD) + c;
#pragma unroll
      for (int kk = 0; kk < 8; kk++) {
        mma16816(e, q[4 * kk], q[4 * kk + 1], q[4 * kk + 2], q[4 * kk + 3], ld_word(kp + 8 * kk), ld_word(kp + 8 * kk + 4));
        mma16816(e + 4, q[4 * kk], q[4 * kk + 1], q[4 * kk + 2], q[4 * kk + 3], ld_word(kp + 8 * kk + 4 * NQ), ld_word(kp + 8 * kk + 4 * NQ + 4));
      }
      if (k0 == row0) {
#pragma unroll
        for (int i = 0; i < 8; i++) if ((i >> 2) * 8 + 2 * c + (i & 1) > r + (i & 2) * 4) e[i] = -INFINITY;
      }
      float a0 = fmaxf(fmaxf(e[0], e[1]), fmaxf(e[4], e[5])), a1 = fmaxf(fmaxf(e[2], e[3]), fmaxf(e[6], e[7]));
      a0 = fmaxf(a0, __shfl_xor_sync(~0u, a0, 1)); a1 = fmaxf(a1, __shfl_xor_sync(~0u, a1, 1));
      a0 = fmaxf(a0, __shfl_xor_sync(~0u, a0, 2)); a1 = fmaxf(a1, __shfl_xor_sync(~0u, a1, 2));
      a0 = fmaxf(a0, m0); a1 = fmaxf(a1, m1);
      const float sc0 = ex2(m0 - a0), sc1 = ex2(m1 - a1);
      m0 = a0; m1 = a1;
#pragma unroll
      for (int i = 0; i < 8; i++) e[i] = ex2(e[i] - ((i & 2) ? m1 : m0));
      l0 = l0 * sc0 + (e[0] + e[1]) + (e[4] + e[5]);
      l1 = l1 * sc1 + (e[2] + e[3]) + (e[6] + e[7]);
      const uint32_t p0 = pack_bf16(e[0], e[1]), p1 = pack_bf16(e[2], e[3]), p2 = pack_bf16(e[4], e[5]), p3 = pack_bf16(e[6], e[7]);
      const __nv_bfloat16* vp = g_kv + (size_t)(SEQ + k0 + 2 * c) * NQ + head * HD + 64 * h + r;
#pragma unroll
      for (int n = 0; n < 8; n++) {
        o[4 * n] *= sc0; o[4 * n + 1] *= sc0; o[4 * n + 2] *= sc1; o[4 * n + 3] *= sc1;
        mma16816(o + 4 * n, p0, p1, p2, p3, ld_pair(vp + 8 * n), ld_pair(vp + 8 * n + 8 * NQ));
      }
    }
    l0 += __shfl_xor_sync(~0u, l0, 1); l1 += __shfl_xor_sync(~0u, l1, 1);
    l0 += __shfl_xor_sync(~0u, l0, 2); l1 += __shfl_xor_sync(~0u, l1, 2);
#pragma unroll
    for (int i = 0; i < 4; i++) {
      const float* v = o + 16 * (i >> 1) + 2 * (i & 1);
      const float f = __fdividef(1.f, (i & 1) ? l1 : l0);
      *reinterpret_cast<uint4*>(g_ctx + (size_t)(row0 + r + (i & 1) * 8) * NQ + head * HD + 64 * h + (i >> 1) * 32 + c * 8) =
          make_uint4(pack_bf16(v[0] * f, v[1] * f), pack_bf16(v[4] * f, v[5] * f), pack_bf16(v[8] * f, v[9] * f), pack_bf16(v[12] * f, v[13] * f));
    }
  }
}

constexpr int UNIT = 16384, SLOT = 32768;
constexpr int OFF_SIDE = 2 * SLOT;
__host__ __device__ constexpr int kv_a(int kb) { return (kb < 6 ? kb : 3 * kb - 10) * UNIT; }
__host__ __device__ constexpr int kv_b(int s) { return (s == 2 ? 6 : 9 + 3 * s) * UNIT; }
__host__ __device__ constexpr int q_aw(int s) { return (3 * s + (s & 1)) * UNIT; }
__host__ __device__ constexpr int q_b(int s) { return (3 * s + 2 - 2 * (s & 1)) * UNIT; }
__host__ __device__ constexpr int k_slot(int j, int r) { return (j < 2 ? 2 * j : (r == 2 ? 0 : 3 + r)) * SLOT; }
__host__ __device__ constexpr int v_slot(int j) { return (6 - (j & 1)) * SLOT; }
__host__ __device__ constexpr int r3(int st) { return ((0x654130 >> (4 * st)) & 7) * SLOT; }
constexpr int OFF_BAR = 229376;
constexpr int OFF_MISC = OFF_BAR + 512;
constexpr int SMEM_BYTES = OFF_MISC + 2080 + TL_EXTRA;
constexpr int OFF_RSTAT = OFF_MISC + 1056;
enum : int {
  B_FULL1 = 0, B_FULLQ = 3, B_FULLB = 7, B_KF = 8, B_VF = 11, B_FULL3 = 13, B_WF = 19, B_DEP = 21, B_OUT2 = 26, B_PF = 27, B_SET = 28,
  B_SET2 = 29, B_LNGO = 30, B_WR = 31,
  B_KE = 32, B_VE = 35, B_WE = 37, B_PUB = 39, B_OUT = 45,
  B_EMPTY1 = 46, B_EMPTYQ = 49, B_X = 53, B_EMPTY3 = 57,
  B_NUM = 63
};
#define TUNE 4, 3, 400, 44, 40, 54, 7, 300, 250, 800, 1500
constexpr int tune_[] = {TUNE};
constexpr int PRE = 3;
constexpr int LN_GO = tune_[0];
constexpr int EP1 = tune_[1];
constexpr int SIDE_NS = tune_[2];
constexpr int SET_KB = tune_[3], SET_NS = tune_[4];
constexpr int PF_KB = tune_[5], PF_N = tune_[6], PF_NS = tune_[7];
constexpr int PS_DLY = tune_[8], Y_DLY = tune_[9], Y_DLY0 = tune_[10];
constexpr int WIN = 6;
constexpr int OFF_STG = r3(0), OFF_SCR = r3(1);
struct Params {
  CUtensorMap xn, ckv, wq, wk, wv, kv_ld, ctx_ld, wo, x, wd, wg, wu;
};

__global__ void __cluster_dims__(2, 1, 1) __launch_bounds__(384, 1)
fused_kernel(uint32_t zero, const __nv_bfloat16* __restrict__ x, __nv_bfloat16* g_kv, __nv_bfloat16* g_ctx, uint4* g_xr,
             __nv_bfloat16* __restrict__ out, __nv_bfloat16* g_xn, unsigned* g_cnt, const __nv_bfloat16* __restrict__ w_r,
             const __nv_bfloat16* __restrict__ wdown, const __nv_bfloat16* __restrict__ wq, const __grid_constant__ Params p) {
  extern __shared__ __align__(1024) uint8_t sp[];
  const uint32_t sb = s2u(sp);
  const uint32_t bar = sb + OFF_BAR;
  auto B = [&](int i) { return bar + 8 * i; };
  const int tid = threadIdx.x, warp = __shfl_sync(~0u, tid >> 5, 0), wg = warp >> 2, lane = tid & 31;
  const int cta = blockIdx.x, rank = cta & 1, cl = cta >> 1;
  const int mp = cl < 4 ? 1 : (cl < 36 ? (cl & 7) : (0x3207654 >> (4 * ((cl - 36) % 7))) & 7);
  const int gq = cl < 4 ? 4 + cl : (cl < 36 ? (cl - 4) >> 3 : 4 + (cl - 36) / 7);
  const int mt = 2 * mp + rank;
  const int qa = 15 - gq;
  const int ta = gq ? gq : 15, tb = 15 - ta;
  const int rid = mt * 8 + gq;
  const int fid = mt * 7 + gq;
  const bool ffn = gq < 7;
  TL(0, 0, warp == 4);
  auto load_pre = [&](int kb) {
    e_expect(B(B_FULL1 + kb), 3 * UNIT);
    tma_ld2(sb + kv_a(kb), &p.ckv, B(B_FULL1 + kb), kb * 64, mt * 128);
    tma_ld3(sb + kv_b(kb) + rank * UNIT, &p.wk, B(B_FULL1 + kb), 0, kb * 64, (gq + 8) * 4 + rank * 2);
    tma_ld3(sb + kv_b(kb) + UNIT - rank * UNIT, &p.wk, B(B_FULL1 + kb), 0, kb * 64, (gq + 8) * 4 + 2 - rank * 2);
  };
  if (warp == 0) {
    e_init(B(B_FULL1), 1);
    asm volatile("fence.mbarrier_init.release.cluster;" ::: "memory");
    TL(0, 16, true);
    load_pre(0);
    TL(0, 17, true);
#pragma unroll
    for (int kb = 1; kb < PRE; kb++) e_init(B(B_FULL1 + kb), 1);
  } else {
#pragma unroll 1
    for (int i = PRE - 1 + warp; i < B_NUM; i += 11) e_init(B(i), i >= B_EMPTY1 ? 16 : (i >= B_KE ? 8 : (i == B_WR ? 2 : 1)));
  }
  asm volatile("fence.mbarrier_init.release.cluster;" ::: "memory");
  cluster_arrive();
  const int rid0 = rid, warp0 = warp;
  if (wg == 0) {
    reg_dealloc<40>();
    if (warp == 0) {
      TL(0, 12, true);
#pragma unroll 1
      for (int kb = 1; kb < PRE; kb++) { load_pre(kb); TL(0, 12 + kb, true); }
      if (mt >= 2 * PRE) tma_pf3(&p.wk, 0, (mt >> 1) * 64, (gq + 8) * 4 + (mt & 1) * 2);
      if (gq >= PRE) tma_pf2(&p.ckv, gq * 64, mt * 128);
      TL(0, 15, true);
    }
    TL(0, 18, warp == 0);
    __syncwarp();
    cluster_wait();
    uint4* const xr = g_xr + rid * XR_SIZE;
    auto side_piece = [&](int c, int piece) {
      const uint32_t fb = B(B_WF + (c & 1));
      if (piece == 0) e_expect(fb, UNIT);
      tma_ld2_ef(sb + OFF_SIDE + (c & 1) * UNIT + piece * 4096, (piece & 2) ? &p.wg : &p.wu, fb, fid * 32, c * 128 + (piece & 1) * 64);
    };
    if (warp == 0) {
      {
        int st = 0; uint32_t ph = 1;
#pragma unroll 1
        for (int i = 0; i < 32; i++) {
          const int t = i >> 3, kb = i & 7;
          if (i >= PRE) {
            const uint32_t fb = B(B_FULL1 + st);
            mbar_wait_c(B(B_EMPTY1 + st), ph);
            e_expect(fb, t == 0 ? 3 * UNIT : 2 * UNIT);
            if (t == 0) tma_ld2(sb + kv_a(kb), &p.ckv, fb, kb * 64, mt * 128);
            tma_ld3_mc(sb + kv_b(st) + rank * UNIT, (t & 1) ? &p.wv : &p.wk, fb, 0, kb * 64, (gq + ((t >> 1) ^ 1) * 8) * 4 + rank * 2, 3);
          }
          if (i == LN_GO) e_arrive(B(B_LNGO));
          if (i == 12) { prefetch_tm(&p.wq); prefetch_tm(&p.xn); prefetch_tm(&p.kv_ld); }
          if (kb == (t ? 0 : 4) && t < 3) tma_pf3((t & 1) ? &p.wk : &p.wv, 0, (mt >> 1) * 64, (gq + (((t + 1) >> 1) ^ 1) * 8) * 4 + (mt & 1) * 2);
          if (kb < 2 && t == 3) tma_pf3(&p.wq, 0, (gq + 8 * kb) * 64, mt * 2);
          if (++st == 3) { st = 0; ph ^= 1; }
        }
        prefetch_tm(&p.ctx_ld); prefetch_tm(&p.wo); prefetch_tm(&p.wd); prefetch_tm(&p.x); prefetch_tm(&p.wg); prefetch_tm(&p.wu);
        mbar_wait_c(B(B_DEP + 0), 0);
        uint32_t kpar = 7, vpar = 3;
        auto load_aw = [&](int kb, int head) {
          const uint32_t d = sb + q_aw(kb & 3), fb = B(B_FULLQ + (kb & 3));
          tma_ld2_mc(d + rank * 8192, &p.xn, fb, kb * 64, ta * 128 + rank * 64, 3);
          tma_ld3(d + UNIT, &p.wq, fb, 0, kb * 64, head * 2);
        };
        auto load_b = [&](int kb, uint32_t fb) { tma_ld2_mc(sb + q_b(kb & 3) + rank * 8192, &p.xn, fb, kb * 64, tb * 128 + rank * 64, 3); };
        auto load3 = [&](int kb, int s) {
          const uint32_t d = sb + r3(s), fb = B(B_FULL3 + s);
          e_expect(fb, SLOT);
          tma_ld2(d, &p.ctx_ld, fb, kb * 64, mt * 128);
          tma_ld3_mc(d + UNIT + rank * 8192, &p.wo, fb, 0, kb * 64, gq * 2 + rank, 3);
        };
#pragma unroll 1
        for (int half = 0; half < 2; half++) {
          const int head = mt + 16 * half;
#pragma unroll 1
          for (int kb = 2 * half; kb < 16; kb++) {
            if (kb >= 4) mbar_wait_c(B(B_EMPTYQ + (kb & 3)), ((kb >> 2) & 1) ^ 1);
            else if (half) mbar_wait_c(B(B_X + 2), 0);
            else if (kb > 0) mbar_wait_c(B(B_EMPTY1 + (kb + 1) % 3), kb == 1);
            e_expect(B(B_FULLQ + (kb & 3)), 3 * UNIT);
            load_aw(kb, head);
            load_b(kb, B(B_FULLQ + (kb & 3)));
          }
          mbar_wait_c(B(B_DEP + 1 + half), 0);
          tma_pf3(&p.kv_ld, 0, 0, head * 2);
          auto load_v = [&](int j) {
            const int r = j & 1;
            mbar_wait_c(B(B_VE + r), (vpar >> r) & 1);
            vpar ^= 1 << r;
            e_expect(B(B_VF + r), SLOT);
            tma_ld3(sb + v_slot(j), &p.kv_ld, B(B_VF + r), 0, SEQ + (j > qa ? 16 - j : j) * 128, head * 2);
          };
          int r = 0;
#pragma unroll 1
          for (int j = 0; j < 17; j++) {
            if (j < 2) mbar_wait_c(B(B_EMPTYQ + j), 1);
            if (j == 2) mbar_wait_c(B(B_KE), kpar & 1);
            mbar_wait_c(B(B_KE + r), (kpar >> r) & 1);
            kpar ^= 1 << r;
            e_expect(B(B_KF + r), SLOT);
            tma_ld3(sb + k_slot(j, r), &p.kv_ld, B(B_KF + r), 0, (j > qa ? 16 - j : j) * 128, head * 2);
            if (++r == 3) r = 0;
            if (j == 2) mbar_wait_c(B(B_EMPTYQ + 3), 1);
            if (j != 1) load_v(j ? j - 1 : 0);
            if (half == 0) {
              if (j == 16) {
                tma_pf3(&p.wq, 0, (4 + gq) * 64, (mt + 16) * 2);
                tma_pf2(&p.xn, (4 + (mp & 3)) * 64, ((mp & 4) ? qa : gq) * 128 + rank * 64);
              }
            } else if (j >= 14) {
              tma_pf3(&p.wo, 0, (5 + mp + 8 * (16 - j)) * 64, gq * 2 + rank);
            } else if (ffn && j >= 5 && j < 13) {
              side_piece((j - 5) >> 2, (j - 5) & 3);
            }
          }
          mbar_wait_c(B(B_X + 0), half);
          if (half == 0) {
            for (int kb = 0; kb < 2; kb++) { e_expect(B(B_FULLQ + kb), 2 * UNIT); load_aw(kb, mt + 16); }
          } else {
            mbar_wait_c(B(B_DEP + 3), 0);
            load3(0, 0);
          }
          mbar_wait_c(B(B_X + 1), half);
          if (half) load3(1, 1);
          load_v(16);
          if (gq == 0) mbar_wait_c(B(B_X + 2), half);
          if (half == 0) { e_expect(B(B_FULLB), 2 * UNIT); load_b(0, B(B_FULLB)); load_b(1, B(B_FULLB)); }
        }
        st = 2; ph = 1;
#pragma unroll 1
        for (int kb = 2; kb < 64; kb++) {
          if (kb == 32) mbar_wait_c(B(B_DEP + 4), 0);
          if (kb >= 6) mbar_wait_c(B(B_EMPTY3 + st), ph);
          else if (kb == 3 || kb == 5) mbar_wait_c(B(B_X + (kb + 1) / 2), 1);
          load3(kb, st);
          if (++st == 6) { st = 0; ph ^= 1; }
          if (kb == PF_KB) e_arrive(B(B_PF));
          if (kb == SET_KB) e_arrive(B(B_SET));
          if (kb == 58) l2_prefetch(xr, XR_CAND * 16);
        }
        if (ffn) {
#pragma unroll 1
          for (int j = 0; j < 2; j++) {
            mbar_wait_c(B(B_EMPTY3 + 4 + j), 1);
            e_expect(B(B_FULL3 + 4 + j), SLOT);
            tma_ld3(sb + r3(4 + j), &p.wd, B(B_FULL3 + 4 + j), 0, fid * 32, 8 * j);
          }
        }
        const uint4* kp = g_xr + ((lane >> 1) * 8 + gq) * XR_SIZE + XR_KEY + (lane & 1) * 2;
        mbar_wait_c(B(B_OUT), 0);
        uint4 kv[2];
        poll_chunks(kv, kp, 1);
        const uint32_t a1 = max(kv[0].x, kv[0].z), a2 = max(min(kv[0].x, kv[0].z), max(kv[0].y, kv[0].w));
        const uint32_t b1 = max(kv[1].x, kv[1].z), b2 = max(min(kv[1].x, kv[1].z), max(kv[1].y, kv[1].w));
        const uint32_t k1 = max(a1, b1), k2 = max(min(a1, b1), max(a2, b2));
        const uint32_t m1 = __reduce_max_sync(~0u, k1);
        const uint32_t m2 = __reduce_max_sync(~0u, k1 == m1 ? k2 : k1);
        if (lane == 0) {
          *reinterpret_cast<uint2*>(sp + OFF_MISC) = make_uint2(m1, m2);
          mbar_arrive(B(B_OUT2));
        }
        if (rid == 127) { g_cnt[lane] = 0; g_cnt[32 + lane] = 0; }
      }
    } else {
      if (warp >= 2) {
#pragma unroll 1
        for (int i = tid - 64; i < XR_CAND; i += 64) xr[i] = make_uint4(~0u, ~0u, ~0u, ~0u);
        if (warp == 2) { __syncwarp(); if (lane == 0) mbar_arrive(B(B_WR)); }
      }
      if (warp == 3) {
        float ws = 0.f;
#pragma unroll
        for (int j = 0; j < 4; j++) {
          const uint4 q = __ldg(reinterpret_cast<const uint4*>(w_r) + j * 32 + lane);
          ws += bf_lo(q.x) + bf_hi(q.x) + bf_lo(q.y) + bf_hi(q.y) + bf_lo(q.z) + bf_hi(q.z) + bf_lo(q.w) + bf_hi(q.w);
        }
#pragma unroll
        for (int o = 16; o; o >>= 1) ws += __shfl_xor_sync(~0u, ws, o);
        uint2* tab = reinterpret_cast<uint2*>(sp + OFF_MISC + 512);
        tab[lane] = make_uint2(0x3F803F80u, 0x3F803F80u);
        tab[32 + lane] = __ldg(reinterpret_cast<const uint2*>(w_r + gq * 128) + lane);
        if (lane == 0) *reinterpret_cast<float*>(sp + OFF_MISC + 1024) = ws;
        __syncwarp();
        if (lane == 0) mbar_arrive(B(B_WR));
      }
      __syncwarp();
      mbar_wait_u(B(B_LNGO), 0);
#pragma unroll 1
      for (int r = warp == 2 ? 0 : (warp + 1) >> 1; r < 16; r += 3) {
        const uint4* src = reinterpret_cast<const uint4*>(x + (size_t)(cta * 16 + r) * DM) + lane;
        uint4 v[4];
#pragma unroll
        for (int j = 0; j < 4; j++) v[j] = __ldg(src + j * 32);
        float a0 = 0.f, a1 = 0.f, b0 = 0.f, b1 = 0.f;
#pragma unroll
        for (int j = 0; j < 4; j++) {
          const uint32_t u[4] = {v[j].x, v[j].y, v[j].z, v[j].w};
#pragma unroll
          for (int i = 0; i < 4; i++) { const float a = bf_lo(u[i]), b = bf_hi(u[i]); a0 += a; a1 += b; b0 = fmaf(a, a, b0); b1 = fmaf(b, b, b1); }
        }
        a0 += a1; b0 += b1;
#pragma unroll
        for (int o = 16; o; o >>= 1) { a0 += __shfl_xor_sync(~0u, a0, o); b0 += __shfl_xor_sync(~0u, b0, o); }
        const float mean = a0 * (1.f / DM);
        float mb, inv;
        ln_round(mean, fmaxf(fmaf(b0, 1.f / DM, -mean * mean), 0.f), mb, inv);
        const uint32_t nm2 = pack_bf16(-mb, -mb);
        uint4* dst = reinterpret_cast<uint4*>(g_xn + (size_t)(cta * 16 + r) * DM) + lane;
#pragma unroll
        for (int j = 0; j < 4; j++) {
          dst[j * 32] = make_uint4(ln_apply(v[j].x, nm2, inv), ln_apply(v[j].y, nm2, inv), ln_apply(v[j].z, nm2, inv), ln_apply(v[j].w, nm2, inv));
          sched_fence();
        }
      }
      __syncwarp();
      if (lane == 0) {
        fence_gpu();
        red_add(&g_cnt[C_LN + (cta >> 3)], 1);
        TL(0, 20 + warp, true);
        if (warp == 3) {
          spin_until_ge<true>(&g_cnt[C_LN + gq], 24);
#pragma unroll 1
          for (int i = 0; i < 5; i++) {
            const int c = i == 0 ? C_LN + qa : (i < 3 ? C_KV + (i - 1) * 8 + mp : C_CTX + (i - 3) * 16 + mt);
            spin_until_ge<true>(&g_cnt[c], i == 0 ? 24 : 16);
            fence_async_all();
            mbar_arrive(B(B_DEP + i));
          }
        } else if (warp == 1) {
          mbar_wait(B(B_WR), 0);
#pragma unroll 1
          for (int i = 0; i < 6; i++) {
            const int c = i < 2 ? C_KV + gq + (i ^ 1) * 8 : C_CTX + ((i - 2) >> 1) * 16 + ((i & 1) ? tb : ta);
            mbar_wait(B(B_PUB + i), 0);
            fence_gpu();
            red_add(&g_cnt[c], 1);
          }
        }
      }
      __syncwarp();
      if (warp == 2) {
#pragma unroll 1
        for (int c = 2; c < WIN + 4; c++) {
          mbar_wait_u(B(B_WE + (c & 1)), ((c >> 1) & 1) ^ 1);
          if (c == WIN || c == WIN + 1) {
            e_expect(B(B_WF + (c & 1)), UNIT);
            tma_ld3_ef(sb + OFF_SIDE + (c & 1) * UNIT, &p.x, B(B_WF + (c & 1)), 0, mt * 128 + (c & 1) * 64, gq * 2);
          } else if (ffn) {
#pragma unroll 1
            for (int i = 0; i < 4; i++) { side_piece(c < WIN ? c : c - 2, i); __nanosleep(SIDE_NS); }
          }
        }
      } else if (warp == 1) {
        mbar_wait_u(B(B_SET), 0);
#pragma unroll 1
        for (int i = XR_CAND + lane; i < XR_SIZE; i += 32) { xr[i] = make_uint4(~0u, ~0u, ~0u, ~0u); __nanosleep(SET_NS); }
        __syncwarp();
        if (lane == 0) { fence_gpu(); mbar_arrive(B(B_SET2)); }
      } else {
        mbar_wait_u(B(B_PF), 0);
#pragma unroll 1
        for (int i = 0; i < PF_N; i++) {
          asm volatile("prefetch.global.L2 [%0];" ::"l"((const char*)wdown + (size_t)cta * 57344 + (i * 32 + lane) * 128));
          __nanosleep(PF_NS);
        }
      }
      __syncwarp();
      mbar_wait_u(B(B_OUT), 0);
#pragma unroll 1
      for (int i = warp - 1; i < 66; i += 3) {
        const int row = 2 * i + (lane >> 4);
        const uint2 rs = *reinterpret_cast<const uint2*>(sp + OFF_RSTAT + (row & 127) * 8);
        const uint4 v = lds128(sb + OFF_STG + ((row >> 6) & 1) * 16384 + ((lane & 15) >> 3) * 8192 + (row & 63) * 128 + (((lane ^ row) & 7) << 4));
        const float inv = __uint_as_float(rs.y);
        if ((int)rs.y >= 0 && row < 128)
          *reinterpret_cast<uint4*>(out + (size_t)(mt * 128 + row) * DM + gq * 128 + (lane & 15) * 8) =
              make_uint4(hadd2_bf(v.x, ln_apply(v.x, rs.x, inv)), hadd2_bf(v.y, ln_apply(v.y, rs.x, inv)),
                         hadd2_bf(v.z, ln_apply(v.z, rs.x, inv)), hadd2_bf(v.w, ln_apply(v.w, rs.x, inv)));
      }
      TL(2, 25, warp == 1);
    }
    __syncwarp();
    cluster_arrive();
    cluster_wait();
  } else {
    reg_alloc<232>();
    const int rid_c = rid0 + zero, warp_c = warp0 + zero;
    const int lane = fresh_lane(), rid = rid_c, mt = rid >> 3, gq = rid & 7, qa = 15 - gq, ta = gq ? gq : 15, tb = 15 - ta;
    const int warp = warp_c, cw = warp - 4, w = cw >> 2;
    cluster_wait();
    auto publish = [&](int i) { __syncwarp(); e_arrive(B(B_PUB + i)); };
    auto release2 = [&](uint32_t b, bool cond = true) { mbar_arrive_both(b, lane, cond); };
    AtState s;
    const uint32_t dA = mk_desc(sb + w * 8192, 16);
    const uint32_t dW = mk_desc(sb, 8192);
    auto mma_kb = [&](float (&d)[64], uint32_t a, uint32_t b, int accum) {
      static_for<4>([&](auto k) { mma_n128_ss<1, k * 32, k * 2048>(d, dA + (a >> 4), dW + (b >> 4), k == 0 ? accum : 1); });
    };
    auto mma_kc = [&](float (&d)[64], auto a, auto b, int accum) {
      static_for<4>([&](auto k) { mma_n128_ss<1, decltype(a)::value + k * 32, decltype(b)::value + k * 2048>(d, dA, dW, k == 0 ? accum : 1); });
    };
    auto issue_q = [&](int kb, auto accum) {
      const int st = kb & 3;
      mbar_wait_c(B(B_FULLQ + st), (kb >> 2) & 1);
      wg_fence();
      mma_kb(s.S, q_aw(st), q_aw(st) + UNIT, accum);
      wg_commit();
      if (accum) {
        wg_wait<1>();
        release2(B(B_EMPTYQ + ((kb - 1) & 3)));
        wg_fence();
      }
      mma_kb(s.O, q_b(st), q_aw(st) + UNIT, accum);
      wg_commit();
    };
    {
      uint4 pk[16];
      __nv_bfloat16* pdst = g_kv;
      auto put = [&](int i) { __stcs(reinterpret_cast<uint4*>(pdst + (i & 1) * 8 * NQ + (i >> 1) * 32), pk[i]); };
      float acc1[128];
      TL(0, 1, warp == 4);
      int st = 0; uint32_t ph = 0;
      auto issue = [&](int kb, int accum) {
        mbar_wait_c(B(B_FULL1 + st), ph);
        wg_fence();
        static_for<4>([&](auto k) { mma_n256_ss<1, k * 32, k * 2048>(acc1, dA + (kv_a(kb) >> 4), dW + (kv_b(st) >> 4), k == 0 ? accum : 1); });
        wg_commit();
      };
#pragma unroll 1
      for (int t = 0; t < 4; t++) {
        issue(0, 0);
        TL(0, 2 + 2 * t, warp == 4);
        if (t > 0) { put(0); put(1); }
        int prev = st;
        if (++st == 3) { st = 0; ph ^= 1; }
#pragma unroll 1
        for (int kb = 1; kb < 8; kb++) {
          if (kb == 7 && w == 1) bar_sync(5, 256);
          issue(kb, 1);
          if (kb == 7 && w == 0) bar_arrive(5, 256);
          if (t > 0) {
#pragma unroll
            for (int i = 1; i < 8; i++) if (kb == i) { put(2 * i); put(2 * i + 1); }
            if (kb == 7 && t == 2) publish(0);
          }
          wg_wait<1>();
          TK(24 + t * 8 + kb - 1);
          release2(B(B_EMPTY1 + prev));
          prev = st;
          if (++st == 3) { st = 0; ph ^= 1; }
        }
        pdst = g_kv + (size_t)((t & 1) * SEQ + mt * 128 + cw * 16 + (lane >> 2)) * NQ + (gq + ((t >> 1) ^ 1) * 8) * 256 + (lane & 3) * 8;
        wg_wait<0>();
        TK(24 + t * 8 + 7);
        fence_regs(acc1);
        release2(B(B_EMPTY1 + prev));
        TL(0, 3 + 2 * t, warp == 4);
#pragma unroll
        for (int a = 0; a < 8; a++)
#pragma unroll
          for (int h = 0; h < 2; h++)
            pk[2 * a + h] = make_uint4(pack_bf16(acc1[16 * a + 2 * h], acc1[16 * a + 2 * h + 1]), pack_bf16(acc1[16 * a + 4 + 2 * h], acc1[16 * a + 5 + 2 * h]),
                                       pack_bf16(acc1[16 * a + 8 + 2 * h], acc1[16 * a + 9 + 2 * h]), pack_bf16(acc1[16 * a + 12 + 2 * h], acc1[16 * a + 13 + 2 * h]));
      }
      issue_q(0, IC<0>{});
      TL(0, 10, warp == 4);
      put(0); put(1);
#pragma unroll 1
      for (int kb = 1; kb < 8; kb++) {
        issue_q(kb, IC<1>{});
        TK(66 + kb - 1);
#pragma unroll
        for (int i = 1; i < 8; i++) if (kb == i) { put(2 * i); put(2 * i + 1); }
      }
      publish(1);
      TL(0, 11, warp == 4);
    }
    __nv_bfloat16* cdst;
    uint32_t redo = 0;
    auto put_ctx = [&](int i, bool cond) {
      asm volatile("{\n.reg .pred p;\nsetp.ne.u32 p, %5, 0;\n@p st.global.cs.v4.u32 [%0], {%1,%2,%3,%4};\n}" ::"l"(cdst + (i & 1) * 8 * NQ + (i >> 1) * 32),
                   "r"(s.P[4 * i]), "r"(s.P[4 * i + 1]), "r"(s.P[4 * i + 2]), "r"(s.P[4 * i + 3]), "r"((uint32_t)(cond && !(redo & 2))) : "memory");
    };
    {
      const int wrow = cw * 16;
      const uint32_t dK = mk_desc(sb, 16), dV = mk_desc(sb, 16384);
      uint32_t kph = 0, vph = 0;
      auto q_store = [&](const float (&d)[64]) {
        const int r0 = lane >> 2;
        const uint32_t a = sb + SLOT + (wrow + r0) * 128 + (((lane & 3) ^ (((r0 & 1) << 2) | (r0 >> 1))) << 4);
#pragma unroll
        for (int i = 0; i < 8; i++) {
          const float* o = d + 16 * (i >> 1) + 2 * (i & 1);
          asm volatile("st.shared.v4.u32 [%0], {%1,%2,%3,%4};" ::"r"((a ^ ((i & 2) << 5)) + (i >> 2) * UNIT + (i & 1) * 1024),
                       "r"(pack_bf16(o[0] * AT_C, o[1] * AT_C)), "r"(pack_bf16(o[4] * AT_C, o[5] * AT_C)),
                       "r"(pack_bf16(o[8] * AT_C, o[9] * AT_C)), "r"(pack_bf16(o[12] * AT_C, o[13] * AT_C)) : "memory");
        }
        __syncwarp();
      };
      auto q_load = [&](auto k0, auto k1) {
        const uint32_t a = sb + SLOT + (wrow + (lane & 15)) * 128 + (((lane >> 4) ^ (((lane & 1) << 2) | ((lane >> 1) & 3))) << 4);
#pragma unroll
        for (int k = k0; k < k1; k++)
          asm volatile("ldmatrix.sync.aligned.m8n8.x4.shared.b16 {%0,%1,%2,%3}, [%4];"
                       : "=r"(s.Q[4 * k]), "=r"(s.Q[4 * k + 1]), "=r"(s.Q[4 * k + 2]), "=r"(s.Q[4 * k + 3]) : "r"((a ^ ((k & 3) << 5)) + (k >> 2) * UNIT) : "memory");
      };
      auto q_load_if = [&](auto k, bool cond, float after) {
        const uint32_t a = sb + SLOT + (wrow + (lane & 15)) * 128 + (((lane >> 4) ^ (((lane & 1) << 2) | ((lane >> 1) & 3))) << 4);
        asm volatile("{\n.reg .pred p;\nsetp.ne.u32 p, %5, 0;\n@p ldmatrix.sync.aligned.m8n8.x4.shared.b16 {%0,%1,%2,%3}, [%4];\n}"
                     : "+r"(s.Q[4 * k]), "+r"(s.Q[4 * k + 1]), "+r"(s.Q[4 * k + 2]), "+r"(s.Q[4 * k + 3])
                     : "r"((a ^ ((k & 3) << 5)) + (k >> 2) * UNIT + (__float_as_uint(after) >> 31)), "r"((uint32_t)cond) : "memory");
      };
      auto issue_s = [&](uint32_t dk) {
        mma_n128_rs0<0>(s.S, s.Q, dk);
        static_for<7>([&](auto i) { constexpr int k = i + 1; mma_n128_rs<0, (k >> 2) * 16384 + (k & 3) * 32>(s.S, s.Q + 4 * k, dk, 1); });
        wg_commit();
      };
      auto wait_v = [&](int jv) {
        mbar_wait_c(B(B_VF + (jv & 1)), (vph >> (jv & 1)) & 1);
        vph ^= 1 << (jv & 1);
      };
      auto issue_pva = [&](int jv, int accum) {
        wg_fence();
        static_for<4>([&](auto k) { mma_n128_rs<1, k * 2048>(s.O, s.P + 4 * k, dV + (v_slot(jv) >> 4), k == 0 ? accum : 1); });
        wg_commit();
      };
      auto issue_pvb = [&](int jv, bool upper) {
        if (upper) {
          wg_fence();
          static_for<4>([&](auto k) { mma_n128_rs<1, (k + 4) * 2048>(s.O, s.P + 16 + 4 * k, dV + (v_slot(jv) >> 4), 1); });
          wg_commit();
        } else {
          asm volatile("wgmma.fence.sync.aligned;\nwgmma.commit_group.sync.aligned;" ::: "memory");
        }
      };
      auto issue_pv = [&](int jv, int accum, bool upper) { wait_v(jv); issue_pva(jv, accum); issue_pvb(jv, upper); };
      if (w == 1) bar_arrive(1, 256);
#pragma unroll 1
      for (int half = 0; half < 2; half++) {
        const int head = mt + 16 * half;
        redo = 0;
        float inv[2];
        auto ep_prep = [&]() {
          float l0 = s.l[0] + s.l[1], l1 = s.l[2] + s.l[3];
          l0 += __shfl_xor_sync(~0u, l0, 1); l1 += __shfl_xor_sync(~0u, l1, 1);
          l0 += __shfl_xor_sync(~0u, l0, 2); l1 += __shfl_xor_sync(~0u, l1, 2);
          asm("rcp.approx.ftz.f32 %0, %1;" : "=f"(inv[0]) : "f"(l0));
          asm("rcp.approx.ftz.f32 %0, %1;" : "=f"(inv[1]) : "f"(l1));
          return __any_sync(~0u, !(fminf(l0, l1) >= L_MIN && l0 + l1 <= L_MAX));
        };
        auto ep_out = [&](auto i0, auto i1) {
          __nv_bfloat16* dst = g_ctx + (size_t)(ta * 128 + wrow + (lane >> 2)) * NQ + head * 128 + (lane & 3) * 8;
#pragma unroll
          for (int i = i0; i < i1; i++) {
            const float* o = s.O + 16 * (i >> 1) + 2 * (i & 1);
            const float c = inv[i & 1];
            asm volatile("st.global.cs.v4.u32 [%0], {%1,%2,%3,%4};" ::"l"(dst + (i & 1) * 8 * NQ + (i >> 1) * 32), "r"(pack_bf16(o[0] * c, o[1] * c)),
                         "r"(pack_bf16(o[4] * c, o[5] * c)), "r"(pack_bf16(o[8] * c, o[9] * c)), "r"(pack_bf16(o[12] * c, o[13] * c)) : "memory");
          }
        };
        auto ep_rest = [&]() {
          ep_out(IC<EP1>{}, IC<8>{});
          if (!__any_sync(~0u, redo)) publish(2 + 2 * half);
          fence_regs(s.O);
        };
#pragma unroll 1
        for (int kb = 8; kb < 14; kb++) {
          issue_q(kb, IC<1>{});
          TK(66 + half * 24 + kb - 1);
        }
        TL(1, 20 * half + 0, warp == 4);
        mbar_wait_c(B(B_FULLQ + 2), 1);
        mbar_wait_c(B(B_FULLQ + 3), 1);
        bar_sync(1 + w, 256);
        wg_fence();
        mma_kc(s.S, IC<q_aw(2)>{}, IC<q_aw(2) + UNIT>{}, 1);
        wg_commit();
        wg_wait<1>();
        TK(66 + half * 24 + 13);
        release2(B(B_EMPTYQ + 1));
        wg_fence();
        mma_kc(s.S, IC<q_aw(3)>{}, IC<q_aw(3) + UNIT>{}, 1);
        wg_commit();
        bar_arrive(2 - w, 256);
        bar_sync(6 + w, 128);
        wg_wait<0>();
        TK(66 + half * 24 + 14);
        fence_regs(s.S);
        q_store(s.S);
        q_load(IC<0>{}, IC<8>{});
        TL(1, 20 * half + 1, warp == 4);
        TC(w, 17 * half, 0);
        mbar_wait_c(B(B_KF), kph & 1);
        kph ^= 1;
        bar_sync(1 + w, 256);
        TC(w, 17 * half, 2);
        fence_regs(s.O); fence_regs(s.Q);
        wg_fence();
        issue_s(dK);
        mma_kc(s.O, IC<q_b(2)>{}, IC<q_aw(2) + UNIT>{}, 1);
        mma_kc(s.O, IC<q_b(3)>{}, IC<q_aw(3) + UNIT>{}, 1);
        wg_commit();
        bar_arrive(2 - w, 256);
        wg_wait<1>();
        TC(w, 17 * half, 4);
        fence_regs(s.S);
        e_arrive(B(B_KE));
        s.l[0] = s.l[1] = s.l[2] = s.l[3] = 0.f;
        at_exp<0, 48>(s);
        at_pack<0, 22>(s);
        sched_fence();
        wg_wait<0>();
        fence_regs(s.O); fence_regs(s.Q);
        release2(B(B_EMPTYQ + 2)); release2(B(B_EMPTYQ + 3));
        at_exp<48, 64>(s);
        at_pack<22, 32>(s);
        q_store(s.O);
        TL(1, 20 * half + 2, warp == 4);
        int kr = 1;
        bool kok = false;
        inv[0] = inv[1] = 0.f;
        const int db = gq ? qa : 16;
#pragma unroll 1
        for (int j = 1; j < 17; j++) {
          const bool diag = j == ta || j == db;
          TC(w, j + 17 * half, 0);
          if (!kok) mbar_wait_c(B(B_KF + kr), (kph >> kr) & 1);
          kph ^= 1 << kr;
          if (j == ta + 2) ep_out(IC<0>{}, IC<EP1>{});
          bar_sync(1 + w, 256);
          TC(w, j + 17 * half, 2);
          fence_regs(s.O); fence_regs(s.P); fence_regs(s.Q);
          const uint32_t ke = B(B_KE + kr), dk = dK + (k_slot(j, kr) >> 4);
          if (++kr == 3) kr = 0;
          auto issue_rest = [&](auto trimmed) {
            TC(w, j + 17 * half, 1);
            if (j == ta + 1) {
              if (ep_prep()) redo = 1;
              s.l[0] = s.l[1] = s.l[2] = s.l[3] = 0.f;
            }
            if (!trimmed && j == ta + 2) ep_rest();
            TC(w, j + 17 * half, 3);
            issue_pv(j - 1, j != 1 && j != ta + 2, w == 1 || (j != ta + 1 && j != db + 1));
            bar_arrive(2 - w, 256);
          };
          auto s_done = [&](auto n) {
            wg_wait<2>();
            TC(w, j + 17 * half, 4);
            fence_part<0, n>(s.S); fence_regs(s.Q);
            e_arrive(ke);
            release2(B(B_X + j - 14), j == 14 || j == 15);
          };
          auto pv_half = [&]() { sched_fence(); wg_wait<1>(); fence_regs(s.P); };
          auto pv_done = [&]() {
            sched_fence();
            wg_wait<0>();
            fence_regs(s.O); fence_regs(s.P);
            e_arrive(B(B_VE + ((j - 1) & 1)));
            release2(B(B_X + 2), j == 16);
            kok = mbar_test(B(B_KF + kr), (kph >> kr) & 1);
          };
          if (diag && w == 0) {
            wg_fence();
            static_for<8>([&](auto k) { mma_n64_rs<0, (k >> 2) * 16384 + (k & 3) * 32, k != 0>(s.S, s.Q + 4 * k, dk); });
            wg_commit();
            issue_rest(IC<1>{});
            s_done(IC<32>{});
            at_mask<0>(s, wrow, lane);
            pv_half();
            static_for<8>([&](auto k) {
              at_exp<4 * k, 4 * k + 4>(s);
              q_load_if(k, j == ta, s.S[4 * k]);
            });
            at_pack<0, 16>(s);
            pv_done();
          } else {
            wg_fence();
            issue_s(dk);
            issue_rest(IC<0>{});
            if (!diag) {
              s_done(IC<64>{});
              at_exp<0, 24>(s);
              pv_half();
              at_exp<24, 48>(s);
              at_pack<0, 16>(s);
              pv_done();
              at_exp<48, 64>(s);
              at_pack<16, 32>(s);
            } else {
              s_done(IC<64>{});
              at_mask<8>(s, wrow - 64, lane);
              static_for<8>([&](auto k) {
                at_exp<7 * k, 7 * k + 7>(s);
                q_load_if(k, j == ta, s.S[7 * k + 3]);
                if (k == 2) pv_half();
                if (k == 5) { at_pack<0, 16>(s); pv_done(); }
              });
              at_exp<56, 64>(s);
              at_pack<16, 32>(s);
            }
          }
          TL(1, 20 * half + 2 + j, warp == 4);
        }
        TK(84 + half * 24);
        mbar_wait_c(B(half ? B_FULL3 : B_FULLQ), 0);
        if (gq == 0) ep_out(IC<0>{}, IC<EP1>{});
        bar_sync(1 + w, 256);
        fence_regs(s.O); fence_regs(s.P);
        wg_fence();
        mma_n128_ss0<1, 0, UNIT>(s.S, dA, dW);
        static_for<3>([&](auto k) { mma_n128_ss<1, k * 32 + 32, UNIT + k * 2048 + 2048>(s.S, dA, dW, 1); });
        mbar_wait_c(B(half ? B_FULL3 + 1 : B_FULLQ + 1), 0);
        wg_fence();
        mma_kb(s.S, (2 + half) * SLOT, (2 + half) * SLOT + UNIT, 1);
        wg_commit();
        TK(85 + half * 24);
        if (gq == 0) ep_rest();
        issue_pv(16, gq != 0, w == 1 || gq != 0);
        if (w == 0 || half == 0) bar_arrive(2 - w, 256);
        TK(86 + half * 24);
        wg_wait<2>();
        release2(B(B_EMPTY3), half); release2(B(B_EMPTY3 + 1), half);
        if (ep_prep()) redo |= 2;
        sched_fence();
        wg_wait<0>();
        TK(87 + half * 24);
        fence_regs(s.S);
        fence_regs(s.O);
        e_arrive(B(B_VE));
        release2(B(B_X + 3));
        fence_regs(s.P);
        {
          const int r = fresh_lane();
          cdst = g_ctx + (size_t)(tb * 128 + wrow + (r >> 2)) * NQ + head * 128 + (r & 3) * 8;
        }
#pragma unroll
        for (int i = 0; i < 32; i++) {
          const float* o = s.O + 16 * (i >> 3) + 2 * ((i >> 2) & 1) + 4 * (i & 3);
          s.P[i] = pack_bf16(o[0] * inv[(i >> 2) & 1], o[1] * inv[(i >> 2) & 1]);
        }
        fence_regs(s.P);
        if (__builtin_expect(__any_sync(~0u, redo != 0), 0)) {
#pragma unroll
          for (int i = 0; i < 8; i++) put_ctx(i, true);
#pragma unroll 1
          for (int t = 0; t < 2; t++) {
            if (__any_sync(~0u, (redo >> t) & 1)) slow_rows(wq, head, (t ? tb : ta) * 128 + wrow);
          }
          if (__any_sync(~0u, redo & 1)) publish(2 + 2 * half);
#pragma unroll
          for (int i = 0; i < 64; i++) { s.O[i] = 0.f; s.P[i >> 1] = 0; }
          redo = 2;
        }
        TL(1, 20 * half + 19, warp == 4);
        TK(88 + half * 24);
        if (half) break;
        mbar_wait_c(B(B_FULLB), 0);
        TK(89);
        fence_regs(s.O);
        wg_fence();
        mma_kc(s.O, IC<q_b(0)>{}, IC<q_aw(0) + UNIT>{}, 0);
        wg_commit();
        mma_kc(s.O, IC<q_b(1)>{}, IC<q_aw(1) + UNIT>{}, 1);
        wg_commit();
        wg_wait<1>();
        release2(B(B_EMPTYQ));
        put_ctx(0, true);
#pragma unroll 1
        for (int kb = 2; kb < 8; kb++) {
          issue_q(kb, IC<1>{});
          TK(90 + kb - 1);
#pragma unroll
          for (int i = 1; i < 8; i++) put_ctx(i, kb == (i < 7 ? i + 1 : 7));
        }
        publish(3);
      }
    }
    const int rid_ = rid + zero, cw_ = cw + zero;
    {
    const int lane = fresh_lane(), rid = rid_, mt = rid >> 3, gq = rid & 7, cw = cw_, w = cw >> 2, ct = cw * 32 + lane;
    const int fid = mt * 7 + gq;
    const bool ffn = gq < 7;
    const uint32_t stg = sb + OFF_STG + w * 16384 + (cw & 3) * 2048;
    const int wr_ = w * 64 + (lane & 7) + (lane >> 4) * 8;
    const uint32_t wl = sb + ((lane >> 3) & 1) * 8192 + wr_ * 64 + (((cw ^ (wr_ >> 1)) & 3) << 4);
    __syncwarp();
    float (&acc)[64] = s.S;
    uint32_t wf[128];
    auto grab = [&](auto c, uint32_t off) {
#pragma unroll
      for (int m = 0; m < 4; m++)
        asm volatile("ldmatrix.sync.aligned.m8n8.x4.trans.shared.b16 {%0,%1,%2,%3}, [%4];"
                     : "=r"(wf[16 * c + 4 * m]), "=r"(wf[16 * c + 4 * m + 1]), "=r"(wf[16 * c + 4 * m + 2]), "=r"(wf[16 * c + 4 * m + 3])
                     : "r"(wl + off + m * 1024) : "memory");
    };
    const int r0 = lane >> 2;
    uint32_t hp[32], rt[16];
    {
      uint32_t dep = 0;
      auto hand = [&](uint32_t b, int n) {
        asm volatile("{\n.reg .pred p;\n.reg .b32 t;\nsetp.lt.u32 p, %1, %4;\nmad.lo.u32 t, %2, %3, %0;\n@p mbarrier.arrive.shared::cta.b64 _, [t];\n}"
                     ::"r"(b + 8 * lane), "r"(lane), "r"(dep), "r"(zero), "r"(n) : "memory");
      };
      auto kblock = [&](auto st, uint32_t ph, bool rel) {
        mbar_wait_c(B(B_FULL3 + st), ph);
        wg_fence();
        mma_kc(acc, IC<r3(st)>{}, IC<r3(st) + UNIT>{}, 1);
        wg_commit();
        wg_wait<1>();
        release2(B(B_EMPTY3 + (st + 5) % 6), rel);
      };
      auto ldsm_if = [&](uint32_t* r, uint32_t a, bool c, auto trans) {
        if (trans) asm volatile("{\n.reg .pred p;\nsetp.ne.u32 p, %5, 0;\n@p ldmatrix.sync.aligned.m8n8.x4.trans.shared.b16 {%0,%1,%2,%3}, [%4];\n}"
                                : "+r"(r[0]), "+r"(r[1]), "+r"(r[2]), "+r"(r[3]) : "r"(a), "r"((uint32_t)c) : "memory");
        else asm volatile("{\n.reg .pred p;\nsetp.ne.u32 p, %5, 0;\n@p ldmatrix.sync.aligned.m8n8.x4.shared.b16 {%0,%1,%2,%3}, [%4];\n}"
                          : "+r"(r[0]), "+r"(r[1]), "+r"(r[2]), "+r"(r[3]) : "r"(a), "r"((uint32_t)c) : "memory");
      };
#pragma unroll
      for (int i = 0; i < 48; i++) wf[i] = 0;
#pragma unroll 1
      for (int lap = 0; lap < 3; lap++) {
        kblock(IC<2>{}, lap & 1, lap > 0);
#pragma unroll
        for (int i = 0; i < 3; i++) put_ctx(3 * i, lap == i);
        kblock(IC<3>{}, lap & 1, true);
        if (ffn) mbar_wait_c(B(B_WF + (lap & 1)), lap >> 1);
#pragma unroll
        for (int i = 0; i < 12; i++) ldsm_if(wf + 4 * i, wl + OFF_SIDE + ((i >> 2) & 1) * UNIT + (i & 3) * 1024, lap == (i >> 2), IC<1>{});
        kblock(IC<4>{}, lap & 1, true);
        sched_fence();
        dep = 0;
#pragma unroll
        for (int i = 0; i < 12; i++) dep ^= wf[4 * i];
        hand(B(B_WE + (lap & 1)), 1);
#pragma unroll
        for (int i = 0; i < 3; i++) put_ctx(3 * i + 1, lap == i);
        kblock(IC<5>{}, lap & 1, true);
        if (lap == 2) publish(5);
        kblock(IC<0>{}, (lap & 1) ^ 1, true);
#pragma unroll
        for (int i = 0; i < 2; i++) put_ctx(3 * i + 2, lap == i);
        kblock(IC<1>{}, (lap & 1) ^ 1, true);
        TL(2, 40 + lap, warp == 4);
      }
#pragma unroll
      for (int i = 48; i < 96; i++) wf[i] = 0;
#pragma unroll
      for (int i = 0; i < 32; i++) hp[i] = 0;
      const uint32_t xa = sb + OFF_SIDE + w * UNIT + (cw & 3) * 2048 + (lane & 15) * 128 + (((lane >> 4) ^ (lane & 7)) << 4);
#pragma unroll 1
      for (int lap = 3; lap < 11; lap++) {
        kblock(IC<2>{}, lap & 1, true);
        kblock(IC<3>{}, lap & 1, true);
        if (lap == 10) break;
        if (lap < WIN) {
          if (ffn) mbar_wait_c(B(B_WF + (lap & 1)), (lap >> 1) & 1);
#pragma unroll
          for (int i = 12; i < 24; i++) ldsm_if(wf + 4 * i, wl + OFF_SIDE + ((i >> 2) & 1) * UNIT + (i & 3) * 1024, lap == (i >> 2), IC<1>{});
        } else if (lap == WIN) {
          mbar_wait_c(B(B_WF), ffn ? (WIN >> 1) & 1 : 0);
          mbar_wait_c(B(B_WF + 1), ffn ? (WIN >> 1) & 1 : 0);
#pragma unroll
          for (int j = 0; j < 8; j++) ldsm_if(hp + 4 * j, (xa ^ ((j & 3) << 5)) + (j >> 2) * 8192, true, IC<0>{});
        }
        kblock(IC<4>{}, lap & 1, true);
        sched_fence();
        dep = 0;
#pragma unroll
        for (int i = 0; i < 20; i++) dep ^= i < 12 ? wf[48 + 4 * i] : hp[4 * (i - 12)];
        hand(B(B_WE + (lap < WIN ? lap & 1 : 0)), lap < WIN ? 1 : (lap == WIN ? 2 : 0));
        kblock(IC<5>{}, lap & 1, true);
        kblock(IC<0>{}, (lap & 1) ^ 1, true);
        kblock(IC<1>{}, (lap & 1) ^ 1, true);
        TL(2, 40 + lap, warp == 4);
      }
    }
    mbar_wait_c(B(B_WR), 0);
#pragma unroll
    for (int j = 0; j < 4; j++)
      asm volatile("ldmatrix.sync.aligned.m8n8.x4.shared.b16 {%0,%1,%2,%3}, [%4];"
                   : "=r"(rt[4 * j]), "=r"(rt[4 * j + 1]), "=r"(rt[4 * j + 2]), "=r"(rt[4 * j + 3])
                   : "r"(sb + OFF_MISC + 512 + (lane & 1) * 256 + (lane >> 3) * 16 + j * 64) : "memory");
    uint4* const xr = g_xr + rid * XR_SIZE;
    mbar_wait_c(B(B_SET2), 0);
    mbar_wait_c(B(B_EMPTY3), 0);
    wg_wait<0>();
    fence_regs(acc);
    TL(2, 10, warp == 4);
    {
      float d[4] = {0.f, 0.f, 0.f, 0.f}, qa[4] = {0.f, 0.f, 0.f, 0.f}, qb[4] = {0.f, 0.f, 0.f, 0.f};
#pragma unroll
      for (int j = 0; j < 16; j++) {
        hp[2 * j] = hadd2_bf(hp[2 * j], pack_bf16(acc[4 * j], acc[4 * j + 1]));
        hp[2 * j + 1] = hadd2_bf(hp[2 * j + 1], pack_bf16(acc[4 * j + 2], acc[4 * j + 3]));
        if (j & 1) {
          mma16816(d, hp[2 * j - 2], hp[2 * j - 1], hp[2 * j], hp[2 * j + 1], rt[j - 1], rt[j]);
          mma16816(qa, hp[2 * j - 2], hp[2 * j - 1], hp[2 * j], hp[2 * j + 1], hp[2 * j - 2], hp[2 * j]);
          mma16816(qb, hp[2 * j - 2], hp[2 * j - 1], hp[2 * j], hp[2 * j + 1], hp[2 * j - 1], hp[2 * j + 1]);
        }
      }
      const float s2a = __shfl_sync(~0u, (r0 & 1) ? qa[1] : qa[0], r0 * 4 + (r0 >> 1));
      const float s2b = __shfl_sync(~0u, (r0 & 1) ? qb[3] : qb[2], r0 * 4 + (r0 >> 1));
      if ((lane & 3) == 0) {
        __stcg(reinterpret_cast<float4*>(xr + XR_PS + cw * 16 + r0), make_float4(d[0], s2a, d[1], 0.f));
        __stcg(reinterpret_cast<float4*>(xr + XR_PS + cw * 16 + r0 + 8), make_float4(d[2], s2b, d[3], 0.f));
      }
    }
    __syncwarp();
    stage_store_128(stg, lane, hp);
    TL(2, 11, warp == 4);
    __syncwarp();
    uint4 cout;
    uint32_t ckey;
    {
      uint4 ps[4];
      const float wsum = *reinterpret_cast<const float*>(sp + OFF_MISC + 1024);
      spin_clk(PS_DLY);
      poll_chunks(ps, g_xr + (mt * 8 + (ct & 1) * 4) * XR_SIZE + XR_PS + (ct >> 1), XR_SIZE);
      TL(2, 12, warp == 4);
      auto F = [](uint32_t u) { return __uint_as_float(u); };
      float s1 = (F(ps[0].x) + F(ps[1].x)) + (F(ps[2].x) + F(ps[3].x)), s2 = (F(ps[0].y) + F(ps[1].y)) + (F(ps[2].y) + F(ps[3].y));
      float s3 = (F(ps[0].z) + F(ps[1].z)) + (F(ps[2].z) + F(ps[3].z));
      s1 += __shfl_xor_sync(~0u, s1, 1); s2 += __shfl_xor_sync(~0u, s2, 1); s3 += __shfl_xor_sync(~0u, s3, 1);
      const float mean = s1 * (1.f / DM);
      float mb, inv;
      ln_round(mean, fmaxf(fmaf(s2, 1.f / DM, -mean * mean), 0.f), mb, inv);
      uint32_t u = pack_bf16((s3 - mb * wsum) * inv, 0.f);
      if (u == 0x8000u) u = 0;
      u = (u & 0x8000u) ? (~u & 0xFFFFu) : (u | 0x8000u);
      const uint32_t key = (u << 16) | (0x7FFFu - (mt * 128 + (ct >> 1)));
      const uint32_t nm2 = pack_bf16(-mb, -mb);
      const uint32_t c1 = __reduce_max_sync(~0u, key);
      const uint32_t c2 = __reduce_max_sync(~0u, key == c1 ? 0u : key);
      if (lane == 0) __stcg(reinterpret_cast<uint2*>(xr + XR_KEY) + cw, make_uint2(c1, c2));
      if (!(ct & 1)) *reinterpret_cast<uint2*>(sp + OFF_RSTAT + (ct >> 1) * 8) = make_uint2(nm2, __float_as_uint(inv) | (key >= c2 ? 0x80000000u : 0u));
      ckey = (lane >> 4) ? c2 : c1;
      const int row = (0x7FFF - (ckey & 0x7FFF)) & 15;
      const uint32_t rn = __shfl_sync(~0u, nm2, row * 2);
      const float ri = __shfl_sync(~0u, inv, row * 2);
      const uint4 v = lds128(stg + ((lane & 15) >> 3) * 8192 + row * 128 + (((lane & 7) ^ (row & 7)) << 4));
      const uint4 n = make_uint4(ln_apply(v.x, rn, ri), ln_apply(v.y, rn, ri), ln_apply(v.z, rn, ri), ln_apply(v.w, rn, ri));
      __stcg(xr + XR_CAND + cw * 64 + 32 + lane, n);
      __stcg(xr + XR_CAND + cw * 64 + lane, v);
      cdst = out + (size_t)(0x7FFF - (ckey & 0x7FFF)) * DM + gq * 128 + (lane & 15) * 8;
      cout = make_uint4(hadd2_bf(v.x, n.x), hadd2_bf(v.y, n.y), hadd2_bf(v.z, n.z), hadd2_bf(v.w, n.w));
    }
    publish(B_OUT - B_PUB);
    cluster_arrive();
    TL(2, 13, warp == 4);
    uint32_t wd[16][4];
    if (ffn) {
      static_for<2>([&](auto i) {
        mbar_wait_c(B(B_WF + i), ((WIN >> 1) & 1) ^ 1);
        grab(IC<WIN + i>{}, OFF_SIDE + i * UNIT);
      });
      mbar_wait_c(B(B_FULL3 + 4 + w), 0);
#pragma unroll
      for (int i = 0; i < 16; i++) {
        const int k = (i & 1) * 16 + (lane & 7) + (lane >> 4) * 8;
        asm volatile("ldmatrix.sync.aligned.m8n8.x4.trans.shared.b16 {%0,%1,%2,%3}, [%4];"
                     : "=r"(wd[i][0]), "=r"(wd[i][1]), "=r"(wd[i][2]), "=r"(wd[i][3])
                     : "r"(sb + r3(4) + w * SLOT + (2 * (cw & 3) + (i >> 3)) * 4096 + k * 128 + (((2 * ((i >> 1) & 3) + ((lane >> 3) & 1)) ^ (lane & 7)) << 4)) : "memory");
      }
    }
    mbar_wait_c(B(B_OUT2), 0);
    const uint2 top = *reinterpret_cast<const uint2*>(sp + OFF_MISC);
    TL(2, 14, warp == 4);
    const int t0 = 0x7FFF - (top.x & 0x7FFF), t1 = 0x7FFF - (top.y & 0x7FFF);
    auto cand = [&](int second, int chunk) {
      const int tk = second ? t1 : t0;
      return g_xr + ((tk >> 7) * 8 + (chunk >> 4)) * XR_SIZE + XR_CAND + ((tk >> 4) & 7) * 64 + ((second && (t0 >> 4) == (t1 >> 4)) ? 16 : 0) + (chunk & 15);
    };
    const int fc = 16 * (rid >> 1) + 4 * (rid & 1) + (lane & 3) + 8 * (lane >> 4), ft = (lane >> 3) & 1;
    uint32_t fh, fn;
    {
      const uint4* pc = cand(w, ct & 127) + 32;
      const uint16_t* pf = reinterpret_cast<const uint16_t*>(cand(ft, fc >> 3)) + (fc & 7);
      uint4 v;
#pragma unroll 1
      for (int n = 0; n < 0x400000; n++) {
        asm volatile("ld.relaxed.gpu.global.v4.u32 {%0,%1,%2,%3}, [%4];" : "=r"(v.x), "=r"(v.y), "=r"(v.z), "=r"(v.w) : "l"(pc) : "memory");
        asm volatile("ld.relaxed.gpu.global.u16 %0, [%1];" : "=r"(fh) : "l"(pf) : "memory");
        asm volatile("ld.relaxed.gpu.global.u16 %0, [%1 + 512];" : "=r"(fn) : "l"(pf) : "memory");
        if (__all_sync(~0u, max(max(v.x, v.y), max(v.z, v.w)) != 0xFFFFFFFFu && max(fh, fn) != 0xFFFFu)) break;
      }
      const int blk = (ct & 127) >> 2;
      const uint32_t a = sb + OFF_SCR + w * 2112 + blk * 64 + (((blk >> 1) & 3) << 4) + (ct & 3) * 4;
      asm volatile("st.shared.u32 [%0], %1;" ::"r"(a), "r"(v.x) : "memory");
      asm volatile("st.shared.u32 [%0], %1;" ::"r"(a ^ 16), "r"(v.y) : "memory");
      asm volatile("st.shared.u32 [%0], %1;" ::"r"(a ^ 32), "r"(v.z) : "memory");
      asm volatile("st.shared.u32 [%0], %1;" ::"r"(a ^ 48), "r"(v.w) : "memory");
    }
    asm volatile("{\n.reg .pred p;\nsetp.lt.u32 p, %5, %6;\n@p st.global.v4.u32 [%0], {%1,%2,%3,%4};\n}" ::"l"(cdst), "r"(cout.x), "r"(cout.y), "r"(cout.z),
                 "r"(cout.w), "r"(ckey), "r"(top.y) : "memory");
    if (ffn) {
      bar_sync(3, 256);
      TL(2, 15, warp == 4);
      float d[2][4] = {{0.f, 0.f, 0.f, 0.f}, {0.f, 0.f, 0.f, 0.f}};
      const uint32_t xb = sb + OFF_SCR + (r0 & 1) * 2112 + w * 128 + (((lane ^ w) & 3) << 4);
#pragma unroll
      for (int i = 0; i < 16; i++) {
        const uint4 b = lds128((xb ^ ((i & 2) << 4)) + (i >> 1) * 256 + (i & 1) * 64);
        mma16816(d[0], wf[8 * i], wf[8 * i + 1], wf[8 * i + 2], wf[8 * i + 3], b.x, b.y);
        mma16816(d[1], wf[8 * i + 4], wf[8 * i + 5], wf[8 * i + 6], wf[8 * i + 7], b.z, b.w);
      }
      float2* red = reinterpret_cast<float2*>(sp + OFF_SCR + 8192);
      if (!(lane & 2))
        red[(w * 2 + (lane & 1)) * 32 + (cw & 3) * 8 + r0] = (lane & 1) ? make_float2(d[0][1] + d[1][1], d[0][3] + d[1][3]) : make_float2(d[0][0] + d[1][0], d[0][2] + d[1][2]);
      bar_sync(3, 256);
      TL(2, 16, warp == 4);
      const uint32_t ra = sb + OFF_SCR + 8192 + (r0 & 1) * 256 + (r0 >> 1) * 64 + (lane & 3) * 16;
      const uint4 p0 = lds128(ra), p1 = lds128(ra + 512);
      auto act = [](uint32_t u0, uint32_t u1, uint32_t g0, uint32_t g1) {
        const uint32_t ug = pack_bf16(__uint_as_float(u0) + __uint_as_float(u1), __uint_as_float(g0) + __uint_as_float(g1));
        const float g = bf_hi(ug);
        return bf_round(__fdividef(g, 1.f + __expf(-g))) * bf_lo(ug);
      };
      const uint32_t av = pack_bf16(act(p0.x, p1.x, p0.y, p1.y), act(p0.z, p1.z, p0.w, p1.w));
      uint32_t b[4];
#pragma unroll
      for (int i = 0; i < 4; i++) b[i] = __shfl_sync(~0u, av, 8 * i + (lane & 7));
      TL(2, 17, warp == 4);
      float y[2][4] = {{0.f, 0.f, 0.f, 0.f}, {0.f, 0.f, 0.f, 0.f}};
#pragma unroll
      for (int c = 0; c < 4; c++) {
        const bool on = (lane >> 3) == c;
        const uint32_t b0 = on ? b[0] : 0, b1 = on ? b[1] : 0, b2 = on ? b[2] : 0, b3 = on ? b[3] : 0;
#pragma unroll
        for (int a = 0; a < 2; a++) {
          const int i = 8 * a + 2 * c;
          mma16816(y[a], wd[i][0], wd[i][1], wd[i][2], wd[i][3], b0, b1);
          mma16816(y[a], wd[i + 1][0], wd[i + 1][1], wd[i + 1][2], wd[i + 1][3], b2, b3);
        }
      }
      float4* yd = reinterpret_cast<float4*>(g_xr + (cw * 16 + (lane & 3) * 2 + (lane >> 4)) * XR_SIZE + XR_Y + fid * 4 + (r0 & 3));
      __stcg(yd, make_float4(y[0][0], y[0][1], y[0][2], y[0][3]));
      __stcg(yd + 8 * XR_SIZE, make_float4(y[1][0], y[1][1], y[1][2], y[1][3]));
    }
    TL(2, 18, warp == 4);
    if (cw == 0) {
      uint32_t u = (ft ? top.y : top.x) >> 16;
      u = (u & 0x8000u) ? (u & 0x7FFFu) : (~u & 0xFFFFu);
      float rs = bf_round(__fdividef(1.f, 1.f + __expf(-__uint_as_float(u << 16))));
      uint16_t* op = reinterpret_cast<uint16_t*>(out) + (size_t)(ft ? t1 : t0) * DM + fc;
      asm volatile("" : "+l"(op), "+f"(rs));
      spin_clk(ffn ? Y_DLY : Y_DLY + Y_DLY0);
      float v[4];
#pragma unroll 1
      for (int n = 0; n < 0x400000; n++) {
        float4 z[14];
#pragma unroll
        for (int i = 0; i < 14; i++)
          asm volatile("ld.relaxed.gpu.global.v4.f32 {%0,%1,%2,%3}, [%4];" : "=f"(z[i].x), "=f"(z[i].y), "=f"(z[i].z), "=f"(z[i].w) : "l"(xr + XR_Y + lane + 32 * i) : "memory");
        float a[4] = {z[0].x, z[0].y, z[0].z, z[0].w}, b[4] = {z[1].x, z[1].y, z[1].z, z[1].w};
#pragma unroll
        for (int i = 2; i < 14; i += 2) {
          a[0] += z[i].x; a[1] += z[i].y; a[2] += z[i].z; a[3] += z[i].w;
          b[0] += z[i + 1].x; b[1] += z[i + 1].y; b[2] += z[i + 1].z; b[3] += z[i + 1].w;
        }
#pragma unroll
        for (int i = 0; i < 4; i++) v[i] = a[i] + b[i];
        const float t = (v[0] + v[1]) + (v[2] + v[3]);
        if (__all_sync(~0u, t == t)) break;
        uint32_t m = 0;
#pragma unroll
        for (int i = 0; i < 14; i++) m = max(max(m, max(__float_as_uint(z[i].x), __float_as_uint(z[i].y))), max(__float_as_uint(z[i].z), __float_as_uint(z[i].w)));
        if (__all_sync(~0u, m != 0xFFFFFFFFu)) break;
      }
      TL(2, 30, true);
      const bool hi = lane & 16, odd = lane & 8;
      const float a0 = (hi ? v[2] : v[0]) + __shfl_xor_sync(~0u, hi ? v[0] : v[2], 16), a1 = (hi ? v[3] : v[1]) + __shfl_xor_sync(~0u, hi ? v[1] : v[3], 16);
      float yv = (odd ? a1 : a0) + __shfl_xor_sync(~0u, odd ? a0 : a1, 8);
      yv += __shfl_xor_sync(~0u, yv, 4);
      const uint32_t o = hadd2_bf(fh, hadd2_bf(fn, pack_bf16(bf_round(yv) * rs, 0.f)));
      if (!(lane & 4)) *op = (uint16_t)o;
      TL(2, 21, true);
    }
    TL(2, 20, warp == 4);
    }
    __syncwarp();
    cluster_wait();
  }
}

typedef CUresult (*EncodeFn)(CUtensorMap*, CUtensorMapDataType, cuuint32_t, void*, const cuuint64_t*, const cuuint64_t*, const cuuint32_t*,
                             const cuuint32_t*, CUtensorMapInterleave, CUtensorMapSwizzle, CUtensorMapL2promotion, CUtensorMapFloatOOBfill);
EncodeFn g_enc = nullptr;

void map2(CUtensorMap* m, const void* ptr, uint64_t rows, uint64_t cols, uint32_t bc, uint32_t br) {
  const CUtensorMapSwizzle sw = bc == 64 ? CU_TENSOR_MAP_SWIZZLE_128B : CU_TENSOR_MAP_SWIZZLE_64B;
  cuuint64_t gd[2] = {cols, rows}, gs[1] = {cols * 2};
  cuuint32_t bd[2] = {bc, br}, es[2] = {1, 1};
  g_enc(m, CU_TENSOR_MAP_DATA_TYPE_BFLOAT16, 2, (void*)ptr, gd, gs, bd, es, CU_TENSOR_MAP_INTERLEAVE_NONE, sw,
        CU_TENSOR_MAP_L2_PROMOTION_L2_128B, CU_TENSOR_MAP_FLOAT_OOB_FILL_NONE);
}
void map3(CUtensorMap* m, const void* ptr, uint64_t rows, uint64_t cols, uint32_t br, uint32_t bch) {
  cuuint64_t gd[3] = {64, rows, cols / 64}, gs[2] = {cols * 2, 128};
  cuuint32_t bd[3] = {64, br, bch}, es[3] = {1, 1, 1};
  g_enc(m, CU_TENSOR_MAP_DATA_TYPE_BFLOAT16, 3, (void*)ptr, gd, gs, bd, es, CU_TENSOR_MAP_INTERLEAVE_NONE, CU_TENSOR_MAP_SWIZZLE_128B,
        CU_TENSOR_MAP_L2_PROMOTION_L2_128B, CU_TENSOR_MAP_FLOAT_OOB_FILL_NONE);
}

}

extern "C" void kernel_launch(void* const* d_in, const int* in_sizes, int n_in, void* d_out, int out_size) {
  const __nv_bfloat16* x = (const __nv_bfloat16*)d_in[0];
  const __nv_bfloat16* ckv = (const __nv_bfloat16*)d_in[1];
  const __nv_bfloat16* wq = (const __nv_bfloat16*)d_in[2];
  const __nv_bfloat16* wk = (const __nv_bfloat16*)d_in[3];
  const __nv_bfloat16* wv = (const __nv_bfloat16*)d_in[4];
  const __nv_bfloat16* wo = (const __nv_bfloat16*)d_in[5];
  const __nv_bfloat16* w_r = (const __nv_bfloat16*)d_in[7];
  const __nv_bfloat16* wgate = (const __nv_bfloat16*)d_in[8];
  const __nv_bfloat16* wup = (const __nv_bfloat16*)d_in[9];
  const __nv_bfloat16* wdown = (const __nv_bfloat16*)d_in[10];
  __nv_bfloat16* out = (__nv_bfloat16*)d_out;

  if (!g_enc) {
    void* fn = nullptr;
    cudaDriverEntryPointQueryResult qr;
    cudaGetDriverEntryPoint("cuTensorMapEncodeTiled", &fn, cudaEnableDefault, &qr);
    g_enc = (EncodeFn)fn;
    cudaFuncSetAttribute(fused_kernel, cudaFuncAttributeMaxDynamicSharedMemorySize, SMEM_BYTES);
  }
  void *xn, *kv, *ctx, *xr, *cnt;
  cudaGetSymbolAddress(&xr, g_xr);
  cudaGetSymbolAddress(&cnt, g_cnt);
  cudaGetSymbolAddress(&xn, g_xn);
  cudaGetSymbolAddress(&kv, g_kv);
  cudaGetSymbolAddress(&ctx, g_ctx);

  Params p;
  map2(&p.xn, xn, SEQ, DM, 64, 64);
  map2(&p.ckv, ckv, SEQ, DC, 64, 128);
  map3(&p.wq, wq, DM, NQ, 64, 2);
  map3(&p.wk, wk, DC, NQ, 64, 2);
  map3(&p.wv, wv, DC, NQ, 64, 2);
  map3(&p.kv_ld, kv, 2 * SEQ, NQ, 128, 2);
  map2(&p.ctx_ld, ctx, SEQ, NQ, 64, 128);
  map3(&p.wo, wo, NQ, DM, 64, 1);
  map3(&p.x, x, SEQ, DM, 64, 2);
  map3(&p.wd, wdown, FF, DM, 32, 8);
  map2(&p.wg, wgate, DM, FF, 32, 64);
  map2(&p.wu, wup, DM, FF, 32, 64);
  fused_kernel<<<128, 384, SMEM_BYTES, cudaStreamPerThread>>>(0u, x, (__nv_bfloat16*)kv, (__nv_bfloat16*)ctx, (uint4*)xr, out, (__nv_bfloat16*)xn,
                                                               (unsigned*)cnt, w_r, wdown, wq, p);
}
```

```cpp
#include <cuda_runtime.h>
#include <cuda_bf16.h>
#include <cuda.h>
#include <stdint.h>
#include <utility>

#pragma nv_diag_suppress 549
#pragma nv_diag_suppress 177
namespace {

constexpr int SEQ = 2048, DM = 1024, NH = 32, HD = 128, DC = 512, NQ = NH * HD, FF = 3584;

__device__ __align__(1024) __nv_bfloat16 g_xn[SEQ * DM];
__device__ __align__(1024) __nv_bfloat16 g_kv[2 * SEQ * NQ];
__device__ __align__(1024) __nv_bfloat16 g_ctx[SEQ * NQ];
constexpr int XR_PS = 0;
constexpr int XR_KEY = 128;
constexpr int XR_CAND = 136;
constexpr int XR_Y = 648;
constexpr int XR_SIZE = 1104;
__device__ __align__(1024) uint4 g_xr[128 * XR_SIZE];
constexpr int C_LN = 0, C_KV = 16, C_CTX = 32, C_NUM = 64;
__device__ unsigned g_cnt[C_NUM];

#define TL(k, i, cond) do {} while (0)
#define TC(w, g, i) do {} while (0)
#define TL_EXTRA 0
#define TK(i) do {} while (0)

__device__ __forceinline__ uint32_t s2u(const void* p) { return (uint32_t)__cvta_generic_to_shared(p); }
__device__ __forceinline__ void mbar_arrive(uint32_t b) { asm volatile("mbarrier.arrive.shared::cta.b64 _, [%0];" ::"r"(b) : "memory"); }
__device__ __forceinline__ void mbar_arrive_both(uint32_t b, uint32_t lane, bool cond) {
  asm volatile("{\n.reg .pred p;\n.reg .b32 r;\nsetp.lt.u32 p, %1, %2;\nmapa.shared::cluster.u32 r, %0, %1;\n@p mbarrier.arrive.shared::cluster.b64 _, [r];\n}"
               ::"r"(b), "r"(lane), "r"(cond ? 2 : 0) : "memory");
}
__device__ __forceinline__ bool mbar_test(uint32_t b, uint32_t ph) {
  uint32_t ok;
  asm volatile("{\n.reg .pred p;\nmbarrier.test_wait.parity.shared::cta.b64 p, [%1], %2;\nselp.u32 %0, 1, 0, p;\n}" : "=r"(ok) : "r"(b), "r"(ph) : "memory");
  return __all_sync(~0u, ok);
}
__device__ __forceinline__ void mbar_wait(uint32_t b, uint32_t ph) {
  asm volatile(
      "{\n.reg .pred p;\n.reg .u32 n;\nmov.u32 n, 0;\n"
      "LW:\nmbarrier.try_wait.parity.shared::cta.b64 p, [%0], %1, 20000;\n@p bra LD;\n"
      "add.u32 n, n, 1;\nsetp.lt.u32 p, n, 0x40000;\n@p bra LW;\ntrap;\nLD:\n}" ::"r"(b), "r"(ph) : "memory");
}
__device__ __forceinline__ void mbar_wait_u(uint32_t b, uint32_t ph) {
  asm volatile(
      "{\n.reg .pred p;\n.reg .u32 n;\nmov.u32 n, 0;\n"
      "LW:\nmbarrier.try_wait.parity.shared::cta.b64 p, [%0], %1, 20000;\n@p bra.uni LD;\n"
      "add.u32 n, n, 1;\nsetp.lt.u32 p, n, 0x40000;\n@p bra.uni LW;\ntrap;\nLD:\n}" ::"r"(b), "r"(ph) : "memory");
}
__device__ __forceinline__ void mbar_wait_c(uint32_t b, uint32_t ph) {
  asm volatile(
      "{\n.reg .pred p;\n.reg .u32 n;\nmov.u32 n, 0;\n"
      "LW:\nmbarrier.try_wait.parity.shared::cta.b64 p, [%0], %1;\n@p bra.uni LD;\n"
      "add.u32 n, n, 1;\nsetp.lt.u32 p, n, 0x100000;\n@p bra.uni LW;\ntrap;\nLD:\n}" ::"r"(b), "r"(ph) : "memory");
}
template <bool SLEEP = false>
__device__ __forceinline__ void spin_until_ge(const unsigned* p, unsigned target) {
  asm volatile(
      "{\n.reg .pred p, q;\n.reg .u32 n, v;\nmov.u32 n, 0;\nsetp.ne.u32 q, %2, 0;\n"
      "LW:\nld.acquire.gpu.global.u32 v, [%0];\nsetp.ge.u32 p, v, %1;\n@p bra LD;\n@q nanosleep.u32 200;\n"
      "add.u32 n, n, 1;\nsetp.lt.u32 p, n, 0x400000;\n@p bra LW;\ntrap;\nLD:\n}" ::"l"(p), "r"(target), "n"((int)SLEEP) : "memory");
}
template <int N>
__device__ __forceinline__ void poll_chunks(uint4 (&v)[N], const uint4* p, int stride) {
#pragma unroll 1
  for (int n = 0; n < 0x400000; n++) {
    uint32_t m = 0;
#pragma unroll
    for (int i = 0; i < N; i++) {
      asm volatile("ld.relaxed.gpu.global.v4.u32 {%0,%1,%2,%3}, [%4];" : "=r"(v[i].x), "=r"(v[i].y), "=r"(v[i].z), "=r"(v[i].w) : "l"(p + i * stride) : "memory");
    }
#pragma unroll
    for (int i = 0; i < N; i++) m = max(max(m, max(v[i].x, v[i].y)), max(v[i].z, v[i].w));
    if (__all_sync(~0u, m != 0xFFFFFFFFu)) break;
  }
}
__device__ __forceinline__ void spin_clk(uint32_t n) {
  asm volatile("{\n.reg .pred p;\n.reg .u32 a, b;\nmov.u32 a, %%clock;\nLW:\nmov.u32 b, %%clock;\nsub.u32 b, b, a;\nsetp.lt.u32 p, b, %0;\n@p bra.uni LW;\n}" ::"r"(n) : "memory");
}
__device__ __forceinline__ int fresh_lane() {
  int r;
  asm volatile("mov.u32 %0, %%laneid;" : "=r"(r));
  return r;
}
__device__ __forceinline__ void settle(const void* a, uint32_t zero) {
  asm volatile("{\n.reg .pred p;\nsetp.ne.u32 p, %1, 0;\n@p st.global.u32 [%0], %1;\n}" ::"l"(a), "r"(zero) : "memory");
}
__device__ __forceinline__ void settle(uint32_t a, uint32_t zero) {
  asm volatile("{\n.reg .pred p;\nsetp.ne.u32 p, %1, 0;\n@p st.shared.u32 [%0], %1;\n}" ::"r"(a), "r"(zero) : "memory");
}
__device__ __forceinline__ void fence_async_all() { asm volatile("fence.proxy.async;" ::: "memory"); }
__device__ __forceinline__ void bar_sync(int id, int n) { asm volatile("bar.sync %0, %1;" ::"r"(id), "r"(n) : "memory"); }
__device__ __forceinline__ void bar_arrive(int id, int n) { asm volatile("bar.arrive %0, %1;" ::"r"(id), "r"(n) : "memory"); }
__device__ __forceinline__ void cluster_arrive() { asm volatile("barrier.cluster.arrive.relaxed.aligned;" ::: "memory"); }
__device__ __forceinline__ void cluster_wait() { asm volatile("barrier.cluster.wait.acquire.aligned;" ::: "memory"); }
__device__ __forceinline__ void fence_gpu() { asm volatile("fence.acq_rel.gpu;" ::: "memory"); }
__device__ __forceinline__ void red_add(unsigned* p, unsigned v) { asm volatile("red.relaxed.gpu.global.add.u32 [%0], %1;" ::"l"(p), "r"(v) : "memory"); }
#define ELECT "{\n.reg .pred E;\nelect.sync _|E, 0xFFFFFFFF;\n@E "
__device__ __forceinline__ void e_init(uint32_t b, uint32_t c) { asm volatile(ELECT "mbarrier.init.shared::cta.b64 [%0], %1;\n}" ::"r"(b), "r"(c) : "memory"); }
__device__ __forceinline__ void e_expect(uint32_t b, uint32_t bytes) { asm volatile(ELECT "mbarrier.arrive.expect_tx.shared::cta.b64 _, [%0], %1;\n}" ::"r"(b), "r"(bytes) : "memory"); }
__device__ __forceinline__ void e_arrive(uint32_t b) { asm volatile(ELECT "mbarrier.arrive.shared::cta.b64 _, [%0];\n}" ::"r"(b) : "memory"); }
__device__ __forceinline__ void prefetch_tm(const CUtensorMap* m) { asm volatile(ELECT "prefetch.tensormap [%0];\n}" ::"l"(m) : "memory"); }
__device__ __forceinline__ void tma_ld2(uint32_t dst, const CUtensorMap* m, uint32_t bar, int c0, int c1) {
  asm volatile(ELECT "cp.async.bulk.tensor.2d.shared::cta.global.mbarrier::complete_tx::bytes [%0], [%1, {%3,%4}], [%2];\n}" ::"r"(dst), "l"(m), "r"(bar), "r"(c0), "r"(c1) : "memory");
}
__device__ __forceinline__ void tma_ld3(uint32_t dst, const CUtensorMap* m, uint32_t bar, int c0, int c1, int c2) {
  asm volatile(ELECT "cp.async.bulk.tensor.3d.shared::cta.global.mbarrier::complete_tx::bytes [%0], [%1, {%3,%4,%5}], [%2];\n}" ::"r"(dst), "l"(m), "r"(bar), "r"(c0), "r"(c1), "r"(c2) : "memory");
}
__device__ __forceinline__ void tma_ld2_mc(uint32_t dst, const CUtensorMap* m, uint32_t bar, int c0, int c1, uint16_t mask) {
  asm volatile(ELECT "cp.async.bulk.tensor.2d.shared::cluster.global.mbarrier::complete_tx::bytes.multicast::cluster [%0], [%1, {%3,%4}], [%2], %5;\n}" ::"r"(dst), "l"(m), "r"(bar), "r"(c0), "r"(c1), "h"(mask) : "memory");
}
__device__ __forceinline__ void tma_ld3_mc(uint32_t dst, const CUtensorMap* m, uint32_t bar, int c0, int c1, int c2, uint16_t mask) {
  asm volatile(ELECT "cp.async.bulk.tensor.3d.shared::cluster.global.mbarrier::complete_tx::bytes.multicast::cluster [%0], [%1, {%3,%4,%5}], [%2], %6;\n}" ::"r"(dst), "l"(m), "r"(bar), "r"(c0), "r"(c1), "r"(c2), "h"(mask) : "memory");
}
__device__ __forceinline__ uint64_t policy_evict_first() {
  uint64_t p;
  asm("createpolicy.fractional.L2::evict_first.b64 %0, 1.0;" : "=l"(p));
  return p;
}
__device__ __forceinline__ void tma_ld2_ef(uint32_t dst, const CUtensorMap* m, uint32_t bar, int c0, int c1) {
  asm volatile(ELECT "cp.async.bulk.tensor.2d.shared::cta.global.mbarrier::complete_tx::bytes.L2::cache_hint [%0], [%1, {%3,%4}], [%2], %5;\n}" ::"r"(dst), "l"(m), "r"(bar), "r"(c0), "r"(c1), "l"(policy_evict_first()) : "memory");
}
__device__ __forceinline__ void tma_ld3_ef(uint32_t dst, const CUtensorMap* m, uint32_t bar, int c0, int c1, int c2) {
  asm volatile(ELECT "cp.async.bulk.tensor.3d.shared::cta.global.mbarrier::complete_tx::bytes.L2::cache_hint [%0], [%1, {%3,%4,%5}], [%2], %6;\n}" ::"r"(dst), "l"(m), "r"(bar), "r"(c0), "r"(c1), "r"(c2), "l"(policy_evict_first()) : "memory");
}
__device__ __forceinline__ void tma_pf2(const CUtensorMap* m, int c0, int c1) { asm volatile(ELECT "cp.async.bulk.prefetch.tensor.2d.L2.global [%0, {%1,%2}];\n}" ::"l"(m), "r"(c0), "r"(c1) : "memory"); }
__device__ __forceinline__ void tma_pf3(const CUtensorMap* m, int c0, int c1, int c2) { asm volatile(ELECT "cp.async.bulk.prefetch.tensor.3d.L2.global [%0, {%1,%2,%3}];\n}" ::"l"(m), "r"(c0), "r"(c1), "r"(c2) : "memory"); }
__device__ __forceinline__ void sched_fence() { asm volatile("pmevent 0;" ::: "memory"); }
__device__ __forceinline__ void l2_prefetch(const void* p, uint32_t bytes) { asm volatile(ELECT "cp.async.bulk.prefetch.L2.global [%0], %1;\n}" ::"l"(p), "r"(bytes) : "memory"); }

__device__ __forceinline__ void wg_fence() { asm volatile("wgmma.fence.sync.aligned;" ::: "memory"); }
__device__ __forceinline__ void wg_commit() { asm volatile("wgmma.commit_group.sync.aligned;" ::: "memory"); }
template <int N> __device__ __forceinline__ void wg_wait() { asm volatile("wgmma.wait_group.sync.aligned %0;" ::"n"(N) : "memory"); }
template <int N> __device__ __forceinline__ void reg_alloc() { asm volatile("setmaxnreg.inc.sync.aligned.u32 %0;" ::"n"(N)); }
template <int N> __device__ __forceinline__ void reg_dealloc() { asm volatile("setmaxnreg.dec.sync.aligned.u32 %0;" ::"n"(N)); }
template <int N> __device__ __forceinline__ void fence_regs(float (&d)[N]) {
#pragma unroll
  for (int i = 0; i < N; i++) asm volatile("" : "+f"(d[i])::"memory");
}
template <int I0, int I1, int N> __device__ __forceinline__ void fence_part(float (&d)[N]) {
#pragma unroll
  for (int i = I0; i < I1; i++) asm volatile("" : "+f"(d[i])::"memory");
}
template <int N> __device__ __forceinline__ void fence_regs(uint32_t (&d)[N]) {
#pragma unroll
  for (int i = 0; i < N; i++) asm volatile("" : "+r"(d[i])::"memory");
}

__device__ __forceinline__ uint32_t mk_desc(uint32_t addr, uint32_t lbo) { return ((addr & 0x3FFFF) >> 4) | ((lbo >> 4) << 16); }

#define R8(b) "+f"(d[b + 0]), "+f"(d[b + 1]), "+f"(d[b + 2]), "+f"(d[b + 3]), "+f"(d[b + 4]), "+f"(d[b + 5]), "+f"(d[b + 6]), "+f"(d[b + 7])
#define REGS64 "%0,%1,%2,%3,%4,%5,%6,%7,%8,%9,%10,%11,%12,%13,%14,%15,%16,%17,%18,%19,%20,%21,%22,%23,%24,%25,%26,%27,%28,%29,%30,%31," \
               "%32,%33,%34,%35,%36,%37,%38,%39,%40,%41,%42,%43,%44,%45,%46,%47,%48,%49,%50,%51,%52,%53,%54,%55,%56,%57,%58,%59,%60,%61,%62,%63"
#define REGS128 REGS64 ",%64,%65,%66,%67,%68,%69,%70,%71,%72,%73,%74,%75,%76,%77,%78,%79,%80,%81,%82,%83,%84,%85,%86,%87,%88,%89,%90,%91,%92,%93,%94,%95," \
               "%96,%97,%98,%99,%100,%101,%102,%103,%104,%105,%106,%107,%108,%109,%110,%111,%112,%113,%114,%115,%116,%117,%118,%119,%120,%121,%122,%123,%124,%125,%126,%127"

#define DESC(d, r, o) "add.u32 t, " r ", " o ";\nmov.b64 " d ", {t, h};\n"
#define MMA_PRE(acc) "{\n.reg .pred p;\n.reg .b32 t, h;\n.reg .b64 da, db;\nmov.b32 h, 0x40000040;\nsetp.ne.b32 p, " acc ", 0;\n"
template <int TB, int OA, int OB>
__device__ __forceinline__ void mma_n256_ss(float (&d)[128], uint32_t a, uint32_t b, int acc) {
  asm volatile(MMA_PRE("%130") DESC("da", "%128", "%132") DESC("db", "%129", "%133")
               "wgmma.mma_async.sync.aligned.m64n256k16.f32.bf16.bf16 {" REGS128 "}, da, db, p, 1, 1, 0, %131;\n}\n"
               : R8(0), R8(8), R8(16), R8(24), R8(32), R8(40), R8(48), R8(56), R8(64), R8(72), R8(80), R8(88), R8(96), R8(104), R8(112), R8(120)
               : "r"(a), "r"(b), "r"(acc), "n"(TB), "n"(OA >> 4), "n"(OB >> 4));
}
template <int TB, int OA, int OB>
__device__ __forceinline__ void mma_n128_ss(float (&d)[64], uint32_t a, uint32_t b, int acc) {
  asm volatile(MMA_PRE("%66") DESC("da", "%64", "%68") DESC("db", "%65", "%69")
               "wgmma.mma_async.sync.aligned.m64n128k16.f32.bf16.bf16 {" REGS64 "}, da, db, p, 1, 1, 0, %67;\n}\n"
               : R8(0), R8(8), R8(16), R8(24), R8(32), R8(40), R8(48), R8(56)
               : "r"(a), "r"(b), "r"(acc), "n"(TB), "n"(OA >> 4), "n"(OB >> 4));
}
template <int TB, int OB>
__device__ __forceinline__ void mma_n128_rs(float (&d)[64], const uint32_t* a, uint32_t b, int acc) {
  asm volatile(MMA_PRE("%69") DESC("db", "%68", "%71")
               "wgmma.mma_async.sync.aligned.m64n128k16.f32.bf16.bf16 {" REGS64 "}, {%64,%65,%66,%67}, db, p, 1, 1, %70;\n}\n"
               : R8(0), R8(8), R8(16), R8(24), R8(32), R8(40), R8(48), R8(56)
               : "r"(a[0]), "r"(a[1]), "r"(a[2]), "r"(a[3]), "r"(b), "r"(acc), "n"(TB), "n"(OB >> 4));
}
#define W8(b) "=f"(d[b + 0]), "=f"(d[b + 1]), "=f"(d[b + 2]), "=f"(d[b + 3]), "=f"(d[b + 4]), "=f"(d[b + 5]), "=f"(d[b + 6]), "=f"(d[b + 7])
#define MMA_N64 MMA_PRE("%37") DESC("db", "%36", "%38") \
  "wgmma.mma_async.sync.aligned.m64n64k16.f32.bf16.bf16 {%0,%1,%2,%3,%4,%5,%6,%7,%8,%9,%10,%11,%12,%13,%14,%15,%16,%17,%18,%19,%20,%21," \
  "%22,%23,%24,%25,%26,%27,%28,%29,%30,%31}, {%32,%33,%34,%35}, db, p, 1, 1, 0;\n}\n"
template <int H, int OB, bool ACC>
__device__ __forceinline__ void mma_n64_rs(float (&d)[64], const uint32_t* a, uint32_t b) {
  if (ACC) asm volatile(MMA_N64 : R8(32 * H), R8(32 * H + 8), R8(32 * H + 16), R8(32 * H + 24) : "r"(a[0]), "r"(a[1]), "r"(a[2]), "r"(a[3]), "r"(b), "n"(1), "n"(OB >> 4));
  else asm volatile(MMA_N64 : W8(32 * H), W8(32 * H + 8), W8(32 * H + 16), W8(32 * H + 24) : "r"(a[0]), "r"(a[1]), "r"(a[2]), "r"(a[3]), "r"(b), "n"(0), "n"(OB >> 4));
}
template <int OB>
__device__ __forceinline__ void mma_n128_rs0(float (&d)[64], const uint32_t* a, uint32_t b) {
  asm volatile(MMA_PRE("%69") DESC("db", "%68", "%70")
               "wgmma.mma_async.sync.aligned.m64n128k16.f32.bf16.bf16 {" REGS64 "}, {%64,%65,%66,%67}, db, p, 1, 1, 0;\n}\n"
               : W8(0), W8(8), W8(16), W8(24), W8(32), W8(40), W8(48), W8(56)
               : "r"(a[0]), "r"(a[1]), "r"(a[2]), "r"(a[3]), "r"(b), "n"(0), "n"(OB >> 4));
}
template <int TB, int OA, int OB>
__device__ __forceinline__ void mma_n128_ss0(float (&d)[64], uint32_t a, uint32_t b) {
  asm volatile(MMA_PRE("%66") DESC("da", "%64", "%68") DESC("db", "%65", "%69")
               "wgmma.mma_async.sync.aligned.m64n128k16.f32.bf16.bf16 {" REGS64 "}, da, db, p, 1, 1, 0, %67;\n}\n"
               : W8(0), W8(8), W8(16), W8(24), W8(32), W8(40), W8(48), W8(56)
               : "r"(a), "r"(b), "n"(0), "n"(TB), "n"(OA >> 4), "n"(OB >> 4));
}
template <int V> struct IC { static constexpr int value = V; __host__ __device__ constexpr operator int() const { return V; } };
template <int N, class F, int... I>
__device__ __forceinline__ void static_for_(F f, std::integer_sequence<int, I...>) { (f(IC<I>{}), ...); }
template <int N, class F>
__device__ __forceinline__ void static_for(F f) { static_for_<N>(f, std::make_integer_sequence<int, N>{}); }
__device__ __forceinline__ uint32_t pack_bf16(float lo, float hi) {
  uint32_t r;
  asm("cvt.rn.bf16x2.f32 %0, %1, %2;" : "=r"(r) : "f"(hi), "f"(lo));
  return r;
}
__device__ __forceinline__ float bf_lo(uint32_t v) { return __uint_as_float(v << 16); }
__device__ __forceinline__ float bf_hi(uint32_t v) { return __uint_as_float(v & 0xFFFF0000u); }
__device__ __forceinline__ float bf_round(float v) { return bf_lo(pack_bf16(v, v)); }
__device__ __forceinline__ void stsm4(uint32_t addr, uint32_t r0, uint32_t r1, uint32_t r2, uint32_t r3) {
  asm volatile("stmatrix.sync.aligned.m8n8.x4.shared.b16 [%0], {%1,%2,%3,%4};" ::"r"(addr), "r"(r0), "r"(r1), "r"(r2), "r"(r3) : "memory");
}
__device__ __forceinline__ uint4 lds128(uint32_t addr) {
  uint4 v;
  asm volatile("ld.shared.v4.u32 {%0,%1,%2,%3}, [%4];" : "=r"(v.x), "=r"(v.y), "=r"(v.z), "=r"(v.w) : "r"(addr));
  return v;
}
__device__ __forceinline__ float ex2(float x) {
  float y;
  asm("ex2.approx.ftz.f32 %0, %1;" : "=f"(y) : "f"(x));
  return y;
}
__device__ __forceinline__ void stage_store_128(uint32_t base, int lane, const uint32_t* pk) {
  const int row = (lane & 7) + ((lane >> 3) & 1) * 8;
  const uint32_t rb = base + row * 128;
  const int hi = lane >> 4;
#pragma unroll
  for (int j = 0; j < 8; j++) {
    const int chunk = 2 * j + hi;
    const uint32_t a = rb + (j >> 2) * 8192 + (((chunk & 7) ^ (lane & 7)) << 4);
    stsm4(a, pk[4 * j + 0], pk[4 * j + 1], pk[4 * j + 2], pk[4 * j + 3]);
  }
}
__device__ __forceinline__ void ln_round(float mean, float var, float& m_bf, float& inv_s) {
  const uint32_t mv = pack_bf16(mean, var);
  m_bf = bf_lo(mv);
  float sq, rc;
  asm("sqrt.approx.ftz.f32 %0, %1;" : "=f"(sq) : "f"(bf_round(bf_hi(mv) + 1e-5f)));
  asm("rcp.approx.ftz.f32 %0, %1;" : "=f"(rc) : "f"(bf_round(sq)));
  inv_s = rc;
}
__device__ __forceinline__ uint32_t hadd2_bf(uint32_t a, uint32_t b) {
  uint32_t r;
  asm("add.rn.bf16x2 %0, %1, %2;" : "=r"(r) : "r"(a), "r"(b));
  return r;
}
__device__ __forceinline__ uint32_t ln_apply(uint32_t h, uint32_t nm2, float inv_s) {
  const uint32_t d = hadd2_bf(h, nm2);
  return pack_bf16(bf_lo(d) * inv_s, bf_hi(d) * inv_s);
}
__device__ __forceinline__ void mma16816(float* d, uint32_t a0, uint32_t a1, uint32_t a2, uint32_t a3, uint32_t b0, uint32_t b1) {
  asm volatile("mma.sync.aligned.m16n8k16.row.col.f32.bf16.bf16.f32 {%0,%1,%2,%3}, {%4,%5,%6,%7}, {%8,%9}, {%0,%1,%2,%3};"
               : "+f"(d[0]), "+f"(d[1]), "+f"(d[2]), "+f"(d[3]) : "r"(a0), "r"(a1), "r"(a2), "r"(a3), "r"(b0), "r"(b1));
}

constexpr float AT_C = 0.08838834764831845f * 1.4426950408889634f;
#define L_MIN 2.3283064e-10f
#define L_MAX 1.0995116e12f
struct AtState {
  float S[64], O[64];
  uint32_t P[32], Q[32];
  float l[4];
};
template <int I0, int I1>
__device__ __forceinline__ void at_exp(AtState& s) {
#pragma unroll
  for (int i = I0; i < I1; i++) asm volatile("ex2.approx.ftz.f32 %0, %0;" : "+f"(s.S[i]));
#pragma unroll
  for (int i = I0; i < I1; i++) asm volatile("add.f32 %0, %0, %1;" : "+f"(s.l[i & 3]) : "f"(s.S[i]));
}
template <int I0, int I1>
__device__ __forceinline__ void at_pack(AtState& s) {
#pragma unroll
  for (int i = I0; i < I1; i++) asm volatile("cvt.rn.bf16x2.f32 %0, %1, %2;" : "=r"(s.P[i]) : "f"(s.S[2 * i + 1]), "f"(s.S[2 * i]));
}
template <int J0>
__device__ __forceinline__ void at_mask(AtState& s, int r, int lane) {
  const int d = r + (lane >> 2) - (lane & 3) * 2;
#pragma unroll
  for (int j = 0; j < 8; j++) {
    float dummy0 = 0.f, dummy1 = 0.f;
    float& lo0 = j < 7 ? s.S[4 * (J0 + (j < 7 ? j + 1 : j)) + 2] : dummy0;
    float& lo1 = j < 7 ? s.S[4 * (J0 + (j < 7 ? j + 1 : j)) + 3] : dummy1;
    asm("{\n.reg .pred p, q;\nsetp.lt.s32 p, %4, %5;\nsetp.le.s32 q, %4, %5;\n"
        "@p add.f32 %0, %0, 0fFF800000;\n@q add.f32 %1, %1, 0fFF800000;\n@p add.f32 %2, %2, 0fFF800000;\n@q add.f32 %3, %3, 0fFF800000;\n}"
        : "+f"(s.S[4 * (J0 + j)]), "+f"(s.S[4 * (J0 + j) + 1]), "+f"(lo0), "+f"(lo1) : "r"(d), "r"(8 * j));
  }
}
__device__ __forceinline__ uint32_t ld_pair(const __nv_bfloat16* p) {
  uint32_t r;
  asm volatile("{\n.reg .b16 a, b;\nld.global.cg.b16 a, [%1];\nld.global.cg.b16 b, [%1 + 8192];\nmov.b32 %0, {a, b};\n}" : "=r"(r) : "l"(p) : "memory");
  return r;
}
__device__ __forceinline__ uint32_t ld_word(const uint32_t* p) {
  uint32_t r;
  asm volatile("ld.global.cg.b32 %0, [%1];" : "=r"(r) : "l"(p) : "memory");
  return r;
}
__device__ __noinline__ void slow_rows(const __nv_bfloat16* wq, int head, int row0) {
  const int lane = fresh_lane(), r = lane >> 2, c = lane & 3;
  uint32_t q[32];
  float o[32];
#pragma unroll
  for (int i = 0; i < 32; i++) q[i] = 0;
  const uint32_t* xa = reinterpret_cast<const uint32_t*>(g_xn + (size_t)(row0 + r) * DM) + c;
#pragma unroll 1
  for (int h = 0; h < 2; h++) {
    const __nv_bfloat16* wb = wq + (size_t)2 * c * NQ + head * HD + 64 * h + 8 * (r >> 1) + (r & 1);
#pragma unroll
    for (int i = 0; i < 32; i++) o[i] = 0.f;
#pragma unroll 1
    for (int kk = 0; kk < DM / 16; kk++) {
      const uint32_t a0 = ld_word(xa + 8 * kk), a1 = ld_word(xa + 8 * kk + 4 * DM), a2 = ld_word(xa + 8 * kk + 4), a3 = ld_word(xa + 8 * kk + 4 * DM + 4);
#pragma unroll
      for (int n = 0; n < 8; n++) {
        const __nv_bfloat16* b = wb + (size_t)16 * kk * NQ + 32 * (n >> 2) + 2 * (n & 3);
        mma16816(o + 4 * n, a0, a1, a2, a3, ld_pair(b), ld_pair(b + 8 * NQ));
      }
    }
#pragma unroll
    for (int i = 0; i < 16; i++) { q[i] = q[16 + i]; q[16 + i] = pack_bf16(o[2 * i] * AT_C, o[2 * i + 1] * AT_C); }
  }
#pragma unroll 1
  for (int h = 0; h < 2; h++) {
    float m0 = -INFINITY, m1 = -INFINITY, l0 = 0.f, l1 = 0.f;
#pragma unroll
    for (int i = 0; i < 32; i++) o[i] = 0.f;
#pragma unroll 1
    for (int k0 = 0; k0 <= row0; k0 += 16) {
      float e[8] = {0.f, 0.f, 0.f, 0.f, 0.f, 0.f, 0.f, 0.f};
      const uint32_t* kp = reinterpret_cast<const uint32_t*>(g_kv + (size_t)(k0 + r) * NQ + head * HD) + c;
#pragma unroll
      for (int kk = 0; kk < 8; kk++) {
        mma16816(e, q[4 * kk], q[4 * kk + 1], q[4 * kk + 2], q[4 * kk + 3], ld_word(kp + 8 * kk), ld_word(kp + 8 * kk + 4));
        mma16816(e + 4, q[4 * kk], q[4 * kk + 1], q[4 * kk + 2], q[4 * kk + 3], ld_word(kp + 8 * kk + 4 * NQ), ld_word(kp + 8 * kk + 4 * NQ + 4));
      }
      if (k0 == row0) {
#pragma unroll
        for (int i = 0; i < 8; i++) if ((i >> 2) * 8 + 2 * c + (i & 1) > r + (i & 2) * 4) e[i] = -INFINITY;
      }
      float a0 = fmaxf(fmaxf(e[0], e[1]), fmaxf(e[4], e[5])), a1 = fmaxf(fmaxf(e[2], e[3]), fmaxf(e[6], e[7]));
      a0 = fmaxf(a0, __shfl_xor_sync(~0u, a0, 1)); a1 = fmaxf(a1, __shfl_xor_sync(~0u, a1, 1));
      a0 = fmaxf(a0, __shfl_xor_sync(~0u, a0, 2)); a1 = fmaxf(a1, __shfl_xor_sync(~0u, a1, 2));
      a0 = fmaxf(a0, m0); a1 = fmaxf(a1, m1);
      const float sc0 = ex2(m0 - a0), sc1 = ex2(m1 - a1);
      m0 = a0; m1 = a1;
#pragma unroll
      for (int i = 0; i < 8; i++) e[i] = ex2(e[i] - ((i & 2) ? m1 : m0));
      l0 = l0 * sc0 + (e[0] + e[1]) + (e[4] + e[5]);
      l1 = l1 * sc1 + (e[2] + e[3]) + (e[6] + e[7]);
      const uint32_t p0 = pack_bf16(e[0], e[1]), p1 = pack_bf16(e[2], e[3]), p2 = pack_bf16(e[4], e[5]), p3 = pack_bf16(e[6], e[7]);
      const __nv_bfloat16* vp = g_kv + (size_t)(SEQ + k0 + 2 * c) * NQ + head * HD + 64 * h + r;
#pragma unroll
      for (int n = 0; n < 8; n++) {
        o[4 * n] *= sc0; o[4 * n + 1] *= sc0; o[4 * n + 2] *= sc1; o[4 * n + 3] *= sc1;
        mma16816(o + 4 * n, p0, p1, p2, p3, ld_pair(vp + 8 * n), ld_pair(vp + 8 * n + 8 * NQ));
      }
    }
    l0 += __shfl_xor_sync(~0u, l0, 1); l1 += __shfl_xor_sync(~0u, l1, 1);
    l0 += __shfl_xor_sync(~0u, l0, 2); l1 += __shfl_xor_sync(~0u, l1, 2);
#pragma unroll
    for (int i = 0; i < 4; i++) {
      const float* v = o + 16 * (i >> 1) + 2 * (i & 1);
      const float f = __fdividef(1.f, (i & 1) ? l1 : l0);
      *reinterpret_cast<uint4*>(g_ctx + (size_t)(row0 + r + (i & 1) * 8) * NQ + head * HD + 64 * h + (i >> 1) * 32 + c * 8) =
          make_uint4(pack_bf16(v[0] * f, v[1] * f), pack_bf16(v[4] * f, v[5] * f), pack_bf16(v[8] * f, v[9] * f), pack_bf16(v[12] * f, v[13] * f));
    }
  }
}

constexpr int UNIT = 16384, SLOT = 32768;
constexpr int OFF_SIDE = 2 * SLOT;
__host__ __device__ constexpr int kv_a(int kb) { return (kb < 6 ? kb : 3 * kb - 10) * UNIT; }
__host__ __device__ constexpr int kv_b(int s) { return (s == 2 ? 6 : 9 + 3 * s) * UNIT; }
__host__ __device__ constexpr int q_aw(int s) { return (3 * s + (s & 1)) * UNIT; }
__host__ __device__ constexpr int q_b(int s) { return (3 * s + 2 - 2 * (s & 1)) * UNIT; }
__host__ __device__ constexpr int k_slot(int j, int r) { return (j < 2 ? 2 * j : (r == 2 ? 0 : 3 + r)) * SLOT; }
__host__ __device__ constexpr int v_slot(int j) { return (6 - (j & 1)) * SLOT; }
__host__ __device__ constexpr int r3(int st) { return ((0x654130 >> (4 * st)) & 7) * SLOT; }
constexpr int OFF_BAR = 229376;
constexpr int OFF_MISC = OFF_BAR + 512;
constexpr int SMEM_BYTES = OFF_MISC + 2080 + TL_EXTRA;
constexpr int OFF_RSTAT = OFF_MISC + 1056;
enum : int {
  B_FULL1 = 0, B_FULLQ = 3, B_FULLB = 7, B_KF = 8, B_VF = 11, B_FULL3 = 13, B_WF = 19, B_DEP = 21, B_OUT2 = 26, B_PF = 27, B_SET = 28,
  B_SET2 = 29, B_LNGO = 30, B_WR = 31,
  B_KE = 32, B_VE = 35, B_WE = 37, B_PUB = 39, B_OUT = 45,
  B_EMPTY1 = 46, B_EMPTYQ = 49, B_X = 53, B_EMPTY3 = 57,
  B_NUM = 63
};
#define TUNABLE(name, v) constexpr int name = v
TUNABLE(LN_GO, 4);
TUNABLE(EP1, 3);
TUNABLE(SIDE_NS, 400);
TUNABLE(SET_KB, 44); TUNABLE(SET_NS, 40);
TUNABLE(PF_KB, 54); TUNABLE(PF_N, 7); TUNABLE(PF_NS, 300);
TUNABLE(PS_DLY, 120); TUNABLE(Y_DLY, 700); TUNABLE(Y_DLY0, 1500);
constexpr int PRE = 3;
constexpr int WIN = 6;
constexpr int OFF_STG = r3(0), OFF_SCR = r3(1);
struct Params {
  CUtensorMap xn, ckv, wq, wk, wv, kv_ld, ctx_ld, wo, x, wd, wg, wu;
};

__global__ void __cluster_dims__(2, 1, 1) __launch_bounds__(384, 1)
fused_kernel(uint32_t zero, const __nv_bfloat16* __restrict__ x, __nv_bfloat16* g_kv, __nv_bfloat16* g_ctx, uint4* g_xr,
             __nv_bfloat16* __restrict__ out, __nv_bfloat16* g_xn, unsigned* g_cnt, const __nv_bfloat16* __restrict__ w_r,
             const __nv_bfloat16* __restrict__ wdown, const __nv_bfloat16* __restrict__ wq, const __grid_constant__ Params p) {
  extern __shared__ __align__(1024) uint8_t sp[];
  const uint32_t sb = s2u(sp);
  const uint32_t bar = sb + OFF_BAR;
  auto B = [&](int i) { return bar + 8 * i; };
  const int tid = threadIdx.x, warp = __shfl_sync(~0u, tid >> 5, 0), wg = warp >> 2, lane = tid & 31;
  const int cta = blockIdx.x, rank = cta & 1, cl = cta >> 1;
  const int mp = cl < 4 ? 1 : (cl < 36 ? (cl & 7) : (0x3207654 >> (4 * ((cl - 36) % 7))) & 7);
  const int gq = cl < 4 ? 4 + cl : (cl < 36 ? (cl - 4) >> 3 : 4 + (cl - 36) / 7);
  const int mt = 2 * mp + rank;
  const int qa = 15 - gq;
  const int ta = gq ? gq : 15, tb = 15 - ta;
  const int rid = mt * 8 + gq;
  const int fid = mt * 7 + gq;
  const bool ffn = gq < 7;
  TL(0, 0, warp == 4);
  auto load_pre = [&](int kb) {
    e_expect(B(B_FULL1 + kb), 3 * UNIT);
    tma_ld2(sb + kv_a(kb), &p.ckv, B(B_FULL1 + kb), kb * 64, mt * 128);
    tma_ld3(sb + kv_b(kb) + rank * UNIT, &p.wk, B(B_FULL1 + kb), 0, kb * 64, (gq + 8) * 4 + rank * 2);
    tma_ld3(sb + kv_b(kb) + UNIT - rank * UNIT, &p.wk, B(B_FULL1 + kb), 0, kb * 64, (gq + 8) * 4 + 2 - rank * 2);
  };
  if (warp == 0) {
    e_init(B(B_FULL1), 1);
    asm volatile("fence.mbarrier_init.release.cluster;" ::: "memory");
    TL(0, 16, true);
    load_pre(0);
    TL(0, 17, true);
#pragma unroll
    for (int kb = 1; kb < PRE; kb++) e_init(B(B_FULL1 + kb), 1);
  } else {
#pragma unroll 1
    for (int i = PRE - 1 + warp; i < B_NUM; i += 11) e_init(B(i), i >= B_EMPTY1 ? 16 : (i >= B_KE ? 8 : (i == B_WR ? 2 : 1)));
  }
  asm volatile("fence.mbarrier_init.release.cluster;" ::: "memory");
  cluster_arrive();
  const int rid0 = rid, warp0 = warp;
  if (wg == 0) {
    reg_dealloc<40>();
    if (warp == 0) {
      TL(0, 12, true);
#pragma unroll 1
      for (int kb = 1; kb < PRE; kb++) { load_pre(kb); TL(0, 12 + kb, true); }
      if (mt >= 2 * PRE) tma_pf3(&p.wk, 0, (mt >> 1) * 64, (gq + 8) * 4 + (mt & 1) * 2);
      if (gq >= PRE) tma_pf2(&p.ckv, gq * 64, mt * 128);
      TL(0, 15, true);
    }
    TL(0, 18, warp == 0);
    __syncwarp();
    cluster_wait();
    uint4* const xr = g_xr + rid * XR_SIZE;
    auto side_piece = [&](int c, int piece) {
      const uint32_t fb = B(B_WF + (c & 1));
      if (piece == 0) e_expect(fb, UNIT);
      tma_ld2_ef(sb + OFF_SIDE + (c & 1) * UNIT + piece * 4096, (piece & 2) ? &p.wg : &p.wu, fb, fid * 32, c * 128 + (piece & 1) * 64);
    };
    if (warp == 0) {
      {
        int st = 0; uint32_t ph = 1;
#pragma unroll 1
        for (int i = 0; i < 32; i++) {
          const int t = i >> 3, kb = i & 7;
          if (i >= PRE) {
            const uint32_t fb = B(B_FULL1 + st);
            mbar_wait_c(B(B_EMPTY1 + st), ph);
            e_expect(fb, t == 0 ? 3 * UNIT : 2 * UNIT);
            if (t == 0) tma_ld2(sb + kv_a(kb), &p.ckv, fb, kb * 64, mt * 128);
            tma_ld3_mc(sb + kv_b(st) + rank * UNIT, (t & 1) ? &p.wv : &p.wk, fb, 0, kb * 64, (gq + ((t >> 1) ^ 1) * 8) * 4 + rank * 2, 3);
          }
          if (i == LN_GO) e_arrive(B(B_LNGO));
          if (i == 12) { prefetch_tm(&p.wq); prefetch_tm(&p.xn); prefetch_tm(&p.kv_ld); }
          if (kb == (t ? 0 : 4) && t < 3) tma_pf3((t & 1) ? &p.wk : &p.wv, 0, (mt >> 1) * 64, (gq + (((t + 1) >> 1) ^ 1) * 8) * 4 + (mt & 1) * 2);
          if (kb < 2 && t == 3) tma_pf3(&p.wq, 0, (gq + 8 * kb) * 64, mt * 2);
          if (++st == 3) { st = 0; ph ^= 1; }
        }
        prefetch_tm(&p.ctx_ld); prefetch_tm(&p.wo); prefetch_tm(&p.wd); prefetch_tm(&p.x); prefetch_tm(&p.wg); prefetch_tm(&p.wu);
        mbar_wait_c(B(B_DEP + 0), 0);
        uint32_t kpar = 7, vpar = 3;
        auto load_aw = [&](int kb, int head) {
          const uint32_t d = sb + q_aw(kb & 3), fb = B(B_FULLQ + (kb & 3));
          tma_ld2_mc(d + rank * 8192, &p.xn, fb, kb * 64, ta * 128 + rank * 64, 3);
          tma_ld3(d + UNIT, &p.wq, fb, 0, kb * 64, head * 2);
        };
        auto load_b = [&](int kb, uint32_t fb) { tma_ld2_mc(sb + q_b(kb & 3) + rank * 8192, &p.xn, fb, kb * 64, tb * 128 + rank * 64, 3); };
        auto load3 = [&](int kb, int s) {
          const uint32_t d = sb + r3(s), fb = B(B_FULL3 + s);
          e_expect(fb, SLOT);
          tma_ld2(d, &p.ctx_ld, fb, kb * 64, mt * 128);
          tma_ld3_mc(d + UNIT + rank * 8192, &p.wo, fb, 0, kb * 64, gq * 2 + rank, 3);
        };
#pragma unroll 1
        for (int half = 0; half < 2; half++) {
          const int head = mt + 16 * half;
#pragma unroll 1
          for (int kb = 2 * half; kb < 16; kb++) {
            if (kb >= 4) mbar_wait_c(B(B_EMPTYQ + (kb & 3)), ((kb >> 2) & 1) ^ 1);
            else if (half) mbar_wait_c(B(B_X + 2), 0);
            else if (kb > 0) mbar_wait_c(B(B_EMPTY1 + (kb + 1) % 3), kb == 1);
            e_expect(B(B_FULLQ + (kb & 3)), 3 * UNIT);
            load_aw(kb, head);
            load_b(kb, B(B_FULLQ + (kb & 3)));
          }
          mbar_wait_c(B(B_DEP + 1 + half), 0);
          tma_pf3(&p.kv_ld, 0, 0, head * 2);
          auto load_v = [&](int j) {
            const int r = j & 1;
            mbar_wait_c(B(B_VE + r), (vpar >> r) & 1);
            vpar ^= 1 << r;
            e_expect(B(B_VF + r), SLOT);
            tma_ld3(sb + v_slot(j), &p.kv_ld, B(B_VF + r), 0, SEQ + (j > qa ? 16 - j : j) * 128, head * 2);
          };
          int r = 0;
#pragma unroll 1
          for (int j = 0; j < 17; j++) {
            if (j < 2) mbar_wait_c(B(B_EMPTYQ + j), 1);
            if (j == 2) mbar_wait_c(B(B_KE), kpar & 1);
            mbar_wait_c(B(B_KE + r), (kpar >> r) & 1);
            kpar ^= 1 << r;
            e_expect(B(B_KF + r), SLOT);
            tma_ld3(sb + k_slot(j, r), &p.kv_ld, B(B_KF + r), 0, (j > qa ? 16 - j : j) * 128, head * 2);
            if (++r == 3) r = 0;
            if (j == 2) mbar_wait_c(B(B_EMPTYQ + 3), 1);
            if (j != 1) load_v(j ? j - 1 : 0);
            if (half == 0) {
              if (j == 16) {
                tma_pf3(&p.wq, 0, (4 + gq) * 64, (mt + 16) * 2);
                tma_pf2(&p.xn, (4 + (mp & 3)) * 64, ((mp & 4) ? qa : gq) * 128 + rank * 64);
              }
            } else if (j >= 14) {
              tma_pf3(&p.wo, 0, (5 + mp + 8 * (16 - j)) * 64, gq * 2 + rank);
            } else if (ffn && j >= 5 && j < 13) {
              side_piece((j - 5) >> 2, (j - 5) & 3);
            }
          }
          mbar_wait_c(B(B_X + 0), half);
          if (half == 0) {
            for (int kb = 0; kb < 2; kb++) { e_expect(B(B_FULLQ + kb), 2 * UNIT); load_aw(kb, mt + 16); }
          } else {
            mbar_wait_c(B(B_DEP + 3), 0);
            load3(0, 0);
          }
          mbar_wait_c(B(B_X + 1), half);
          if (half) load3(1, 1);
          load_v(16);
          if (gq == 0) mbar_wait_c(B(B_X + 2), half);
          if (half == 0) { e_expect(B(B_FULLB), 2 * UNIT); load_b(0, B(B_FULLB)); load_b(1, B(B_FULLB)); }
        }
        st = 2; ph = 1;
#pragma unroll 1
        for (int kb = 2; kb < 64; kb++) {
          if (kb == 32) mbar_wait_c(B(B_DEP + 4), 0);
          if (kb >= 6) mbar_wait_c(B(B_EMPTY3 + st), ph);
          else if (kb == 3 || kb == 5) mbar_wait_c(B(B_X + (kb + 1) / 2), 1);
          load3(kb, st);
          if (++st == 6) { st = 0; ph ^= 1; }
          if (kb == PF_KB) e_arrive(B(B_PF));
          if (kb == SET_KB) e_arrive(B(B_SET));
          if (kb == 58) l2_prefetch(xr, XR_CAND * 16);
        }
        if (ffn) {
#pragma unroll 1
          for (int j = 0; j < 2; j++) {
            mbar_wait_c(B(B_EMPTY3 + 4 + j), 1);
            e_expect(B(B_FULL3 + 4 + j), SLOT);
            tma_ld3(sb + r3(4 + j), &p.wd, B(B_FULL3 + 4 + j), 0, fid * 32, 8 * j);
          }
        }
        const uint4* kp = g_xr + ((lane >> 1) * 8 + gq) * XR_SIZE + XR_KEY + (lane & 1) * 2;
        mbar_wait_c(B(B_OUT), 0);
        uint4 kv[2];
        poll_chunks(kv, kp, 1);
        const uint32_t a1 = max(kv[0].x, kv[0].z), a2 = max(min(kv[0].x, kv[0].z), max(kv[0].y, kv[0].w));
        const uint32_t b1 = max(kv[1].x, kv[1].z), b2 = max(min(kv[1].x, kv[1].z), max(kv[1].y, kv[1].w));
        const uint32_t k1 = max(a1, b1), k2 = max(min(a1, b1), max(a2, b2));
        const uint32_t m1 = __reduce_max_sync(~0u, k1);
        const uint32_t m2 = __reduce_max_sync(~0u, k1 == m1 ? k2 : k1);
        const uint32_t t0 = ~m1 & 0x7FFF, t1 = ~m2 & 0x7FFF;
        const uint32_t o0 = (t0 >> 7) * (8 * XR_SIZE * 16) + (t0 & 0x70) * 64, o1 = (t1 >> 7) * (8 * XR_SIZE * 16) + (t1 & 0x70) * 64 + ((t0 ^ t1) < 16 ? 256 : 0);
        asm volatile(ELECT "st.shared.v4.u32 [%0], {%1,%2,%3,%4};\n}" ::"r"(sb + OFF_MISC), "r"(o0), "r"(o1), "r"(m1), "r"(m2) : "memory");
        e_arrive(B(B_OUT2));
        if (rid == 127) { g_cnt[lane] = 0; g_cnt[32 + lane] = 0; }
      }
    } else {
      if (warp >= 2) {
#pragma unroll 1
        for (int i = tid - 64; i < XR_CAND; i += 64) xr[i] = make_uint4(~0u, ~0u, ~0u, ~0u);
        if (warp == 2) { __syncwarp(); if (lane == 0) mbar_arrive(B(B_WR)); }
      }
      if (warp == 3) {
        float ws = 0.f;
#pragma unroll
        for (int j = 0; j < 4; j++) {
          const uint4 q = __ldg(reinterpret_cast<const uint4*>(w_r) + j * 32 + lane);
          ws += bf_lo(q.x) + bf_hi(q.x) + bf_lo(q.y) + bf_hi(q.y) + bf_lo(q.z) + bf_hi(q.z) + bf_lo(q.w) + bf_hi(q.w);
        }
#pragma unroll
        for (int o = 16; o; o >>= 1) ws += __shfl_xor_sync(~0u, ws, o);
        uint2* tab = reinterpret_cast<uint2*>(sp + OFF_MISC + 512);
        tab[lane] = make_uint2(0x3F803F80u, 0x3F803F80u);
        tab[32 + lane] = __ldg(reinterpret_cast<const uint2*>(w_r + gq * 128) + lane);
        if (lane == 0) *reinterpret_cast<float*>(sp + OFF_MISC + 1024) = ws;
        __syncwarp();
        if (lane == 0) mbar_arrive(B(B_WR));
      }
      __syncwarp();
      mbar_wait_u(B(B_LNGO), 0);
#pragma unroll 1
      for (int r = warp == 2 ? 0 : (warp + 1) >> 1; r < 16; r += 3) {
        const uint4* src = reinterpret_cast<const uint4*>(x + (size_t)(cta * 16 + r) * DM) + lane;
        uint4 v[4];
#pragma unroll
        for (int j = 0; j < 4; j++) v[j] = __ldg(src + j * 32);
        float a0 = 0.f, a1 = 0.f, b0 = 0.f, b1 = 0.f;
#pragma unroll
        for (int j = 0; j < 4; j++) {
          const uint32_t u[4] = {v[j].x, v[j].y, v[j].z, v[j].w};
#pragma unroll
          for (int i = 0; i < 4; i++) { const float a = bf_lo(u[i]), b = bf_hi(u[i]); a0 += a; a1 += b; b0 = fmaf(a, a, b0); b1 = fmaf(b, b, b1); }
        }
        a0 += a1; b0 += b1;
#pragma unroll
        for (int o = 16; o; o >>= 1) { a0 += __shfl_xor_sync(~0u, a0, o); b0 += __shfl_xor_sync(~0u, b0, o); }
        const float mean = a0 * (1.f / DM);
        float mb, inv;
        ln_round(mean, fmaxf(fmaf(b0, 1.f / DM, -mean * mean), 0.f), mb, inv);
        const uint32_t nm2 = pack_bf16(-mb, -mb);
        uint4* dst = reinterpret_cast<uint4*>(g_xn + (size_t)(cta * 16 + r) * DM) + lane;
#pragma unroll
        for (int j = 0; j < 4; j++) {
          dst[j * 32] = make_uint4(ln_apply(v[j].x, nm2, inv), ln_apply(v[j].y, nm2, inv), ln_apply(v[j].z, nm2, inv), ln_apply(v[j].w, nm2, inv));
          sched_fence();
        }
      }
      __syncwarp();
      if (lane == 0) {
        fence_gpu();
        red_add(&g_cnt[C_LN + (cta >> 3)], 1);
        TL(0, 20 + warp, true);
        if (warp == 3) {
          spin_until_ge<true>(&g_cnt[C_LN + gq], 24);
#pragma unroll 1
          for (int i = 0; i < 5; i++) {
            const int c = i == 0 ? C_LN + qa : (i < 3 ? C_KV + (i - 1) * 8 + mp : C_CTX + (i - 3) * 16 + mt);
            spin_until_ge<true>(&g_cnt[c], i == 0 ? 24 : 16);
            fence_async_all();
            mbar_arrive(B(B_DEP + i));
          }
        } else if (warp == 1) {
          mbar_wait(B(B_WR), 0);
#pragma unroll 1
          for (int i = 0; i < 6; i++) {
            const int c = i < 2 ? C_KV + gq + (i ^ 1) * 8 : C_CTX + ((i - 2) >> 1) * 16 + ((i & 1) ? tb : ta);
            mbar_wait(B(B_PUB + i), 0);
            fence_gpu();
            red_add(&g_cnt[c], 1);
          }
        }
      }
      __syncwarp();
      if (warp == 2) {
#pragma unroll 1
        for (int c = 2; c < WIN + 4; c++) {
          mbar_wait_u(B(B_WE + (c & 1)), ((c >> 1) & 1) ^ 1);
          if (c == WIN || c == WIN + 1) {
            e_expect(B(B_WF + (c & 1)), UNIT);
            tma_ld3_ef(sb + OFF_SIDE + (c & 1) * UNIT, &p.x, B(B_WF + (c & 1)), 0, mt * 128 + (c & 1) * 64, gq * 2);
          } else if (ffn) {
#pragma unroll 1
            for (int i = 0; i < 4; i++) { side_piece(c < WIN ? c : c - 2, i); __nanosleep(SIDE_NS); }
          }
        }
      } else if (warp == 1) {
        mbar_wait_u(B(B_SET), 0);
#pragma unroll 1
        for (int i = XR_CAND + lane; i < XR_SIZE; i += 32) { xr[i] = make_uint4(~0u, ~0u, ~0u, ~0u); __nanosleep(SET_NS); }
        __syncwarp();
        if (lane == 0) { fence_gpu(); mbar_arrive(B(B_SET2)); }
      } else {
        mbar_wait_u(B(B_PF), 0);
#pragma unroll 1
        for (int i = 0; i < PF_N; i++) {
          asm volatile("prefetch.global.L2 [%0];" ::"l"((const char*)wdown + (size_t)cta * 57344 + (i * 32 + lane) * 128));
          __nanosleep(PF_NS);
        }
      }
      __syncwarp();
      mbar_wait_u(B(B_OUT), 0);
      {
        const int sub = lane >> 4;
        const uint32_t src = sb + OFF_STG + ((lane & 15) >> 3) * 8192 + sub * 128;
        __nv_bfloat16* dst = out + (size_t)(mt * 128 + sub) * DM + gq * 128 + (lane & 15) * 8;
        auto ld = [&](int r, uint2& rs, uint4& v) {
          asm volatile("ld.shared.v2.u32 {%0,%1}, [%2];" : "=r"(rs.x), "=r"(rs.y) : "r"(sb + OFF_RSTAT + ((r + sub) & 127) * 8));
          v = lds128(src + ((r >> 6) & 1) * 16384 + (r & 63) * 128 + (((lane ^ (r + sub)) & 7) << 4));
        };
        uint2 rs; uint4 v;
        ld(2 * warp - 2, rs, v);
#pragma unroll 1
        for (int r = 2 * warp - 2; r < 128; r += 6) {
          const uint2 cs = rs; const uint4 c = v;
          ld(r + 6, rs, v);
          const float inv = __uint_as_float(cs.y);
          asm volatile("{\n.reg .pred p;\nsetp.ge.s32 p, %5, 0;\n@p st.global.v4.u32 [%0], {%1,%2,%3,%4};\n}" ::"l"(dst + (size_t)r * DM),
                       "r"(hadd2_bf(c.x, ln_apply(c.x, cs.x, inv))), "r"(hadd2_bf(c.y, ln_apply(c.y, cs.x, inv))),
                       "r"(hadd2_bf(c.z, ln_apply(c.z, cs.x, inv))), "r"(hadd2_bf(c.w, ln_apply(c.w, cs.x, inv))), "r"(cs.y) : "memory");
        }
      }
      TL(2, 25, warp == 1);
    }
    __syncwarp();
    cluster_arrive();
    cluster_wait();
  } else {
    reg_alloc<232>();
    const int rid_c = rid0 + zero, warp_c = warp0 + zero;
    const int lane = fresh_lane(), rid = rid_c, mt = rid >> 3, gq = rid & 7, qa = 15 - gq, ta = gq ? gq : 15, tb = 15 - ta;
    const int warp = warp_c, cw = warp - 4, w = cw >> 2;
    cluster_wait();
    auto publish = [&](int i) { __syncwarp(); e_arrive(B(B_PUB + i)); };
    auto release2 = [&](uint32_t b, bool cond = true) { mbar_arrive_both(b, lane, cond); };
    AtState s;
    const uint32_t dA = mk_desc(sb + w * 8192, 16);
    const uint32_t dW = mk_desc(sb, 8192);
    auto mma_kb = [&](float (&d)[64], uint32_t a, uint32_t b, int accum) {
      static_for<4>([&](auto k) { mma_n128_ss<1, k * 32, k * 2048>(d, dA + (a >> 4), dW + (b >> 4), k == 0 ? accum : 1); });
    };
    auto mma_kc = [&](float (&d)[64], auto a, auto b, int accum) {
      static_for<4>([&](auto k) { mma_n128_ss<1, decltype(a)::value + k * 32, decltype(b)::value + k * 2048>(d, dA, dW, k == 0 ? accum : 1); });
    };
    auto issue_q = [&](int kb, auto accum) {
      const int st = kb & 3;
      mbar_wait_c(B(B_FULLQ + st), (kb >> 2) & 1);
      wg_fence();
      mma_kb(s.S, q_aw(st), q_aw(st) + UNIT, accum);
      wg_commit();
      if (accum) {
        wg_wait<1>();
        release2(B(B_EMPTYQ + ((kb - 1) & 3)));
        wg_fence();
      }
      mma_kb(s.O, q_b(st), q_aw(st) + UNIT, accum);
      wg_commit();
    };
    {
      uint4 pk[16];
      __nv_bfloat16* pdst = g_kv;
      auto put = [&](int i) { __stcs(reinterpret_cast<uint4*>(pdst + (i & 1) * 8 * NQ + (i >> 1) * 32), pk[i]); };
      float acc1[128];
      TL(0, 1, warp == 4);
      int st = 0; uint32_t ph = 0;
      auto issue = [&](int kb, int accum) {
        mbar_wait_c(B(B_FULL1 + st), ph);
        wg_fence();
        static_for<4>([&](auto k) { mma_n256_ss<1, k * 32, k * 2048>(acc1, dA + (kv_a(kb) >> 4), dW + (kv_b(st) >> 4), k == 0 ? accum : 1); });
        wg_commit();
      };
#pragma unroll 1
      for (int t = 0; t < 4; t++) {
        issue(0, 0);
        TL(0, 2 + 2 * t, warp == 4);
        if (t > 0) { put(0); put(1); }
        int prev = st;
        if (++st == 3) { st = 0; ph ^= 1; }
#pragma unroll 1
        for (int kb = 1; kb < 8; kb++) {
          if (kb == 7 && w == 1) bar_sync(5, 256);
          issue(kb, 1);
          if (kb == 7 && w == 0) bar_arrive(5, 256);
          if (t > 0) {
#pragma unroll
            for (int i = 1; i < 8; i++) if (kb == i) { put(2 * i); put(2 * i + 1); }
            if (kb == 7 && t == 2) publish(0);
          }
          wg_wait<1>();
          TK(24 + t * 8 + kb - 1);
          release2(B(B_EMPTY1 + prev));
          prev = st;
          if (++st == 3) { st = 0; ph ^= 1; }
        }
        pdst = g_kv + (size_t)((t & 1) * SEQ + mt * 128 + cw * 16 + (lane >> 2)) * NQ + (gq + ((t >> 1) ^ 1) * 8) * 256 + (lane & 3) * 8;
        wg_wait<0>();
        TK(24 + t * 8 + 7);
        fence_regs(acc1);
        release2(B(B_EMPTY1 + prev));
        TL(0, 3 + 2 * t, warp == 4);
#pragma unroll
        for (int a = 0; a < 8; a++)
#pragma unroll
          for (int h = 0; h < 2; h++)
            pk[2 * a + h] = make_uint4(pack_bf16(acc1[16 * a + 2 * h], acc1[16 * a + 2 * h + 1]), pack_bf16(acc1[16 * a + 4 + 2 * h], acc1[16 * a + 5 + 2 * h]),
                                       pack_bf16(acc1[16 * a + 8 + 2 * h], acc1[16 * a + 9 + 2 * h]), pack_bf16(acc1[16 * a + 12 + 2 * h], acc1[16 * a + 13 + 2 * h]));
      }
      issue_q(0, IC<0>{});
      TL(0, 10, warp == 4);
      put(0); put(1);
#pragma unroll 1
      for (int kb = 1; kb < 8; kb++) {
        issue_q(kb, IC<1>{});
        TK(66 + kb - 1);
#pragma unroll
        for (int i = 1; i < 8; i++) if (kb == i) { put(2 * i); put(2 * i + 1); }
      }
      publish(1);
      TL(0, 11, warp == 4);
    }
    __nv_bfloat16* cdst;
    uint32_t redo = 0;
    auto put_ctx = [&](int i, bool cond) {
      asm volatile("{\n.reg .pred p;\nsetp.ne.u32 p, %5, 0;\n@p st.global.cs.v4.u32 [%0], {%1,%2,%3,%4};\n}" ::"l"(cdst + (i & 1) * 8 * NQ + (i >> 1) * 32),
                   "r"(s.P[4 * i]), "r"(s.P[4 * i + 1]), "r"(s.P[4 * i + 2]), "r"(s.P[4 * i + 3]), "r"((uint32_t)(cond && !(redo & 2))) : "memory");
    };
    {
      const int wrow = cw * 16;
      const uint32_t dK = mk_desc(sb, 16), dV = mk_desc(sb, 16384);
      uint32_t kph = 0, vph = 0;
      auto q_store = [&](const float (&d)[64]) {
        const int r0 = lane >> 2;
        const uint32_t a = sb + SLOT + (wrow + r0) * 128 + (((lane & 3) ^ (((r0 & 1) << 2) | (r0 >> 1))) << 4);
#pragma unroll
        for (int i = 0; i < 8; i++) {
          const float* o = d + 16 * (i >> 1) + 2 * (i & 1);
          asm volatile("st.shared.v4.u32 [%0], {%1,%2,%3,%4};" ::"r"((a ^ ((i & 2) << 5)) + (i >> 2) * UNIT + (i & 1) * 1024),
                       "r"(pack_bf16(o[0] * AT_C, o[1] * AT_C)), "r"(pack_bf16(o[4] * AT_C, o[5] * AT_C)),
                       "r"(pack_bf16(o[8] * AT_C, o[9] * AT_C)), "r"(pack_bf16(o[12] * AT_C, o[13] * AT_C)) : "memory");
        }
        __syncwarp();
      };
      auto q_load = [&](auto k0, auto k1) {
        const uint32_t a = sb + SLOT + (wrow + (lane & 15)) * 128 + (((lane >> 4) ^ (((lane & 1) << 2) | ((lane >> 1) & 3))) << 4);
#pragma unroll
        for (int k = k0; k < k1; k++)
          asm volatile("ldmatrix.sync.aligned.m8n8.x4.shared.b16 {%0,%1,%2,%3}, [%4];"
                       : "=r"(s.Q[4 * k]), "=r"(s.Q[4 * k + 1]), "=r"(s.Q[4 * k + 2]), "=r"(s.Q[4 * k + 3]) : "r"((a ^ ((k & 3) << 5)) + (k >> 2) * UNIT) : "memory");
      };
      auto q_load_if = [&](auto k, bool cond, float after) {
        const uint32_t a = sb + SLOT + (wrow + (lane & 15)) * 128 + (((lane >> 4) ^ (((lane & 1) << 2) | ((lane >> 1) & 3))) << 4);
        asm volatile("{\n.reg .pred p;\nsetp.ne.u32 p, %5, 0;\n@p ldmatrix.sync.aligned.m8n8.x4.shared.b16 {%0,%1,%2,%3}, [%4];\n}"
                     : "+r"(s.Q[4 * k]), "+r"(s.Q[4 * k + 1]), "+r"(s.Q[4 * k + 2]), "+r"(s.Q[4 * k + 3])
                     : "r"((a ^ ((k & 3) << 5)) + (k >> 2) * UNIT + (__float_as_uint(after) >> 31)), "r"((uint32_t)cond) : "memory");
      };
      auto issue_s = [&](uint32_t dk) {
        mma_n128_rs0<0>(s.S, s.Q, dk);
        static_for<7>([&](auto i) { constexpr int k = i + 1; mma_n128_rs<0, (k >> 2) * 16384 + (k & 3) * 32>(s.S, s.Q + 4 * k, dk, 1); });
        wg_commit();
      };
      auto wait_v = [&](int jv) {
        mbar_wait_c(B(B_VF + (jv & 1)), (vph >> (jv & 1)) & 1);
        vph ^= 1 << (jv & 1);
      };
      auto issue_pva = [&](int jv, int accum) {
        wg_fence();
        static_for<4>([&](auto k) { mma_n128_rs<1, k * 2048>(s.O, s.P + 4 * k, dV + (v_slot(jv) >> 4), k == 0 ? accum : 1); });
        wg_commit();
      };
      auto issue_pvb = [&](int jv, bool upper) {
        if (upper) {
          wg_fence();
          static_for<4>([&](auto k) { mma_n128_rs<1, (k + 4) * 2048>(s.O, s.P + 16 + 4 * k, dV + (v_slot(jv) >> 4), 1); });
          wg_commit();
        } else {
          asm volatile("wgmma.fence.sync.aligned;\nwgmma.commit_group.sync.aligned;" ::: "memory");
        }
      };
      auto issue_pv = [&](int jv, int accum, bool upper) { wait_v(jv); issue_pva(jv, accum); issue_pvb(jv, upper); };
      if (w == 1) bar_arrive(1, 256);
#pragma unroll 1
      for (int half = 0; half < 2; half++) {
        const int head = mt + 16 * half;
        redo = 0;
        float inv[2];
        auto ep_prep = [&]() {
          float l0 = s.l[0] + s.l[1], l1 = s.l[2] + s.l[3];
          l0 += __shfl_xor_sync(~0u, l0, 1); l1 += __shfl_xor_sync(~0u, l1, 1);
          l0 += __shfl_xor_sync(~0u, l0, 2); l1 += __shfl_xor_sync(~0u, l1, 2);
          asm("rcp.approx.ftz.f32 %0, %1;" : "=f"(inv[0]) : "f"(l0));
          asm("rcp.approx.ftz.f32 %0, %1;" : "=f"(inv[1]) : "f"(l1));
          return __any_sync(~0u, !(fminf(l0, l1) >= L_MIN && l0 + l1 <= L_MAX));
        };
        auto ep_out = [&](auto i0, auto i1) {
          __nv_bfloat16* dst = g_ctx + (size_t)(ta * 128 + wrow + (lane >> 2)) * NQ + head * 128 + (lane & 3) * 8;
#pragma unroll
          for (int i = i0; i < i1; i++) {
            const float* o = s.O + 16 * (i >> 1) + 2 * (i & 1);
            const float c = inv[i & 1];
            asm volatile("st.global.cs.v4.u32 [%0], {%1,%2,%3,%4};" ::"l"(dst + (i & 1) * 8 * NQ + (i >> 1) * 32), "r"(pack_bf16(o[0] * c, o[1] * c)),
                         "r"(pack_bf16(o[4] * c, o[5] * c)), "r"(pack_bf16(o[8] * c, o[9] * c)), "r"(pack_bf16(o[12] * c, o[13] * c)) : "memory");
          }
        };
        auto ep_rest = [&]() {
          ep_out(IC<EP1>{}, IC<8>{});
          if (!__any_sync(~0u, redo)) publish(2 + 2 * half);
          fence_regs(s.O);
        };
#pragma unroll 1
        for (int kb = 8; kb < 14; kb++) {
          issue_q(kb, IC<1>{});
          TK(66 + half * 24 + kb - 1);
        }
        TL(1, 20 * half + 0, warp == 4);
        mbar_wait_c(B(B_FULLQ + 2), 1);
        mbar_wait_c(B(B_FULLQ + 3), 1);
        bar_sync(1 + w, 256);
        wg_fence();
        mma_kc(s.S, IC<q_aw(2)>{}, IC<q_aw(2) + UNIT>{}, 1);
        wg_commit();
        wg_wait<1>();
        TK(66 + half * 24 + 13);
        release2(B(B_EMPTYQ + 1));
        wg_fence();
        mma_kc(s.S, IC<q_aw(3)>{}, IC<q_aw(3) + UNIT>{}, 1);
        wg_commit();
        bar_arrive(2 - w, 256);
        bar_sync(6 + w, 128);
        wg_wait<0>();
        TK(66 + half * 24 + 14);
        fence_regs(s.S);
        q_store(s.S);
        q_load(IC<0>{}, IC<8>{});
        TL(1, 20 * half + 1, warp == 4);
        TC(w, 17 * half, 0);
        mbar_wait_c(B(B_KF), kph & 1);
        kph ^= 1;
        bar_sync(1 + w, 256);
        TC(w, 17 * half, 2);
        fence_regs(s.O); fence_regs(s.Q);
        wg_fence();
        issue_s(dK);
        mma_kc(s.O, IC<q_b(2)>{}, IC<q_aw(2) + UNIT>{}, 1);
        mma_kc(s.O, IC<q_b(3)>{}, IC<q_aw(3) + UNIT>{}, 1);
        wg_commit();
        bar_arrive(2 - w, 256);
        wg_wait<1>();
        TC(w, 17 * half, 4);
        fence_regs(s.S);
        e_arrive(B(B_KE));
        s.l[0] = s.l[1] = s.l[2] = s.l[3] = 0.f;
        at_exp<0, 48>(s);
        at_pack<0, 22>(s);
        sched_fence();
        wg_wait<0>();
        fence_regs(s.O); fence_regs(s.Q);
        release2(B(B_EMPTYQ + 2)); release2(B(B_EMPTYQ + 3));
        at_exp<48, 64>(s);
        at_pack<22, 32>(s);
        q_store(s.O);
        TL(1, 20 * half + 2, warp == 4);
        int kr = 1;
        bool kok = false;
        inv[0] = inv[1] = 0.f;
        const int db = gq ? qa : 16;
#pragma unroll 1
        for (int j = 1; j < 17; j++) {
          const bool diag = j == ta || j == db;
          TC(w, j + 17 * half, 0);
          if (!kok) mbar_wait_c(B(B_KF + kr), (kph >> kr) & 1);
          kph ^= 1 << kr;
          if (j == ta + 2) ep_out(IC<0>{}, IC<EP1>{});
          bar_sync(1 + w, 256);
          TC(w, j + 17 * half, 2);
          fence_regs(s.O); fence_regs(s.P); fence_regs(s.Q);
          const uint32_t ke = B(B_KE + kr), dk = dK + (k_slot(j, kr) >> 4);
          if (++kr == 3) kr = 0;
          auto issue_rest = [&](auto trimmed) {
            TC(w, j + 17 * half, 1);
            if (j == ta + 1) {
              if (ep_prep()) redo = 1;
              s.l[0] = s.l[1] = s.l[2] = s.l[3] = 0.f;
            }
            if (!trimmed && j == ta + 2) ep_rest();
            TC(w, j + 17 * half, 3);
            issue_pv(j - 1, j != 1 && j != ta + 2, w == 1 || (j != ta + 1 && j != db + 1));
            bar_arrive(2 - w, 256);
          };
          auto s_done = [&](auto n) {
            wg_wait<2>();
            TC(w, j + 17 * half, 4);
            fence_part<0, n>(s.S); fence_regs(s.Q);
            e_arrive(ke);
            release2(B(B_X + j - 14), j == 14 || j == 15);
          };
          auto pv_half = [&]() { sched_fence(); wg_wait<1>(); fence_regs(s.P); };
          auto pv_done = [&]() {
            sched_fence();
            wg_wait<0>();
            fence_regs(s.O); fence_regs(s.P);
            e_arrive(B(B_VE + ((j - 1) & 1)));
            release2(B(B_X + 2), j == 16);
            kok = mbar_test(B(B_KF + kr), (kph >> kr) & 1);
          };
          if (diag && w == 0) {
            wg_fence();
            static_for<8>([&](auto k) { mma_n64_rs<0, (k >> 2) * 16384 + (k & 3) * 32, k != 0>(s.S, s.Q + 4 * k, dk); });
            wg_commit();
            issue_rest(IC<1>{});
            s_done(IC<32>{});
            at_mask<0>(s, wrow, lane);
            pv_half();
            static_for<8>([&](auto k) {
              at_exp<4 * k, 4 * k + 4>(s);
              q_load_if(k, j == ta, s.S[4 * k]);
            });
            at_pack<0, 16>(s);
            pv_done();
          } else {
            wg_fence();
            issue_s(dk);
            issue_rest(IC<0>{});
            if (!diag) {
              s_done(IC<64>{});
              at_exp<0, 24>(s);
              pv_half();
              at_exp<24, 48>(s);
              at_pack<0, 16>(s);
              pv_done();
              at_exp<48, 64>(s);
              at_pack<16, 32>(s);
            } else {
              s_done(IC<64>{});
              at_mask<8>(s, wrow - 64, lane);
              static_for<8>([&](auto k) {
                at_exp<7 * k, 7 * k + 7>(s);
                q_load_if(k, j == ta, s.S[7 * k + 3]);
                if (k == 2) pv_half();
                if (k == 5) { at_pack<0, 16>(s); pv_done(); }
              });
              at_exp<56, 64>(s);
              at_pack<16, 32>(s);
            }
          }
          TL(1, 20 * half + 2 + j, warp == 4);
        }
        TK(84 + half * 24);
        mbar_wait_c(B(half ? B_FULL3 : B_FULLQ), 0);
        if (gq == 0) ep_out(IC<0>{}, IC<EP1>{});
        bar_sync(1 + w, 256);
        fence_regs(s.O); fence_regs(s.P);
        wg_fence();
        mma_n128_ss0<1, 0, UNIT>(s.S, dA, dW);
        static_for<3>([&](auto k) { mma_n128_ss<1, k * 32 + 32, UNIT + k * 2048 + 2048>(s.S, dA, dW, 1); });
        mbar_wait_c(B(half ? B_FULL3 + 1 : B_FULLQ + 1), 0);
        wg_fence();
        mma_kb(s.S, (2 + half) * SLOT, (2 + half) * SLOT + UNIT, 1);
        wg_commit();
        TK(85 + half * 24);
        if (gq == 0) ep_rest();
        issue_pv(16, gq != 0, w == 1 || gq != 0);
        if (w == 0 || half == 0) bar_arrive(2 - w, 256);
        TK(86 + half * 24);
        wg_wait<2>();
        release2(B(B_EMPTY3), half); release2(B(B_EMPTY3 + 1), half);
        if (ep_prep()) redo |= 2;
        sched_fence();
        wg_wait<0>();
        TK(87 + half * 24);
        fence_regs(s.S);
        fence_regs(s.O);
        e_arrive(B(B_VE));
        release2(B(B_X + 3));
        fence_regs(s.P);
        {
          const int r = fresh_lane();
          cdst = g_ctx + (size_t)(tb * 128 + wrow + (r >> 2)) * NQ + head * 128 + (r & 3) * 8;
        }
#pragma unroll
        for (int i = 0; i < 32; i++) {
          const float* o = s.O + 16 * (i >> 3) + 2 * ((i >> 2) & 1) + 4 * (i & 3);
          s.P[i] = pack_bf16(o[0] * inv[(i >> 2) & 1], o[1] * inv[(i >> 2) & 1]);
        }
        fence_regs(s.P);
        if (__builtin_expect(__any_sync(~0u, redo != 0), 0)) {
#pragma unroll
          for (int i = 0; i < 8; i++) put_ctx(i, true);
#pragma unroll 1
          for (int t = 0; t < 2; t++) {
            if (__any_sync(~0u, (redo >> t) & 1)) slow_rows(wq, head, (t ? tb : ta) * 128 + wrow);
          }
          if (__any_sync(~0u, redo & 1)) publish(2 + 2 * half);
#pragma unroll
          for (int i = 0; i < 64; i++) { s.O[i] = 0.f; s.P[i >> 1] = 0; }
          redo = 2;
        }
        TL(1, 20 * half + 19, warp == 4);
        TK(88 + half * 24);
        if (half) break;
        mbar_wait_c(B(B_FULLB), 0);
        TK(89);
        fence_regs(s.O);
        wg_fence();
        mma_kc(s.O, IC<q_b(0)>{}, IC<q_aw(0) + UNIT>{}, 0);
        wg_commit();
        mma_kc(s.O, IC<q_b(1)>{}, IC<q_aw(1) + UNIT>{}, 1);
        wg_commit();
        wg_wait<1>();
        release2(B(B_EMPTYQ));
        put_ctx(0, true);
#pragma unroll 1
        for (int kb = 2; kb < 8; kb++) {
          issue_q(kb, IC<1>{});
          TK(90 + kb - 1);
#pragma unroll
          for (int i = 1; i < 8; i++) put_ctx(i, kb == (i < 7 ? i + 1 : 7));
        }
        publish(3);
      }
    }
    const int rid_ = rid + zero, cw_ = cw + zero;
    {
    const int lane = fresh_lane(), rid = rid_, mt = rid >> 3, gq = rid & 7, cw = cw_, w = cw >> 2, ct = cw * 32 + lane;
    const int fid = mt * 7 + gq;
    const bool ffn = gq < 7;
    const uint32_t stg = sb + OFF_STG + w * 16384 + (cw & 3) * 2048;
    const int wr_ = w * 64 + (lane & 7) + (lane >> 4) * 8;
    const uint32_t wl = sb + ((lane >> 3) & 1) * 8192 + wr_ * 64 + (((cw ^ (wr_ >> 1)) & 3) << 4);
    __syncwarp();
    float (&acc)[64] = s.S;
    uint32_t wf[128];
    auto grab = [&](auto c, uint32_t off) {
#pragma unroll
      for (int m = 0; m < 4; m++)
        asm volatile("ldmatrix.sync.aligned.m8n8.x4.trans.shared.b16 {%0,%1,%2,%3}, [%4];"
                     : "=r"(wf[16 * c + 4 * m]), "=r"(wf[16 * c + 4 * m + 1]), "=r"(wf[16 * c + 4 * m + 2]), "=r"(wf[16 * c + 4 * m + 3])
                     : "r"(wl + off + m * 1024) : "memory");
    };
    const int r0 = lane >> 2;
    uint32_t hp[32], rt[16];
    {
      uint32_t dep = 0;
      auto hand = [&](uint32_t b, int n) {
        asm volatile("{\n.reg .pred p;\n.reg .b32 t;\nsetp.lt.u32 p, %1, %4;\nmad.lo.u32 t, %2, %3, %0;\n@p mbarrier.arrive.shared::cta.b64 _, [t];\n}"
                     ::"r"(b + 8 * lane), "r"(lane), "r"(dep), "r"(zero), "r"(n) : "memory");
      };
      auto kblock = [&](auto st, uint32_t ph, bool rel) {
        mbar_wait_c(B(B_FULL3 + st), ph);
        wg_fence();
        mma_kc(acc, IC<r3(st)>{}, IC<r3(st) + UNIT>{}, 1);
        wg_commit();
        wg_wait<1>();
        release2(B(B_EMPTY3 + (st + 5) % 6), rel);
      };
      auto ldsm_if = [&](uint32_t* r, uint32_t a, bool c, auto trans) {
        if (trans) asm volatile("{\n.reg .pred p;\nsetp.ne.u32 p, %5, 0;\n@p ldmatrix.sync.aligned.m8n8.x4.trans.shared.b16 {%0,%1,%2,%3}, [%4];\n}"
                                : "+r"(r[0]), "+r"(r[1]), "+r"(r[2]), "+r"(r[3]) : "r"(a), "r"((uint32_t)c) : "memory");
        else asm volatile("{\n.reg .pred p;\nsetp.ne.u32 p, %5, 0;\n@p ldmatrix.sync.aligned.m8n8.x4.shared.b16 {%0,%1,%2,%3}, [%4];\n}"
                          : "+r"(r[0]), "+r"(r[1]), "+r"(r[2]), "+r"(r[3]) : "r"(a), "r"((uint32_t)c) : "memory");
      };
#pragma unroll
      for (int i = 0; i < 48; i++) wf[i] = 0;
#pragma unroll 1
      for (int lap = 0; lap < 3; lap++) {
        kblock(IC<2>{}, lap & 1, lap > 0);
#pragma unroll
        for (int i = 0; i < 3; i++) put_ctx(3 * i, lap == i);
        kblock(IC<3>{}, lap & 1, true);
        if (ffn) mbar_wait_c(B(B_WF + (lap & 1)), lap >> 1);
#pragma unroll
        for (int i = 0; i < 12; i++) ldsm_if(wf + 4 * i, wl + OFF_SIDE + ((i >> 2) & 1) * UNIT + (i & 3) * 1024, lap == (i >> 2), IC<1>{});
        kblock(IC<4>{}, lap & 1, true);
        sched_fence();
        dep = 0;
#pragma unroll
        for (int i = 0; i < 12; i++) dep ^= wf[4 * i];
        hand(B(B_WE + (lap & 1)), 1);
#pragma unroll
        for (int i = 0; i < 3; i++) put_ctx(3 * i + 1, lap == i);
        kblock(IC<5>{}, lap & 1, true);
        if (lap == 2) publish(5);
        kblock(IC<0>{}, (lap & 1) ^ 1, true);
#pragma unroll
        for (int i = 0; i < 2; i++) put_ctx(3 * i + 2, lap == i);
        kblock(IC<1>{}, (lap & 1) ^ 1, true);
        TL(2, 40 + lap, warp == 4);
      }
#pragma unroll
      for (int i = 48; i < 96; i++) wf[i] = 0;
#pragma unroll
      for (int i = 0; i < 32; i++) { hp[i] = 0; rt[i >> 1] = 0; }
      const uint32_t xa = sb + OFF_SIDE + w * UNIT + (cw & 3) * 2048 + (lane & 15) * 128 + (((lane >> 4) ^ (lane & 7)) << 4);
#pragma unroll 1
      for (int lap = 3; lap < 11; lap++) {
        kblock(IC<2>{}, lap & 1, true);
        kblock(IC<3>{}, lap & 1, true);
        if (lap == 10) break;
        if (lap < WIN) {
          if (ffn) mbar_wait_c(B(B_WF + (lap & 1)), (lap >> 1) & 1);
#pragma unroll
          for (int i = 12; i < 24; i++) ldsm_if(wf + 4 * i, wl + OFF_SIDE + ((i >> 2) & 1) * UNIT + (i & 3) * 1024, lap == (i >> 2), IC<1>{});
        } else if (lap == WIN) {
          mbar_wait_c(B(B_WF), ffn ? (WIN >> 1) & 1 : 0);
          mbar_wait_c(B(B_WF + 1), ffn ? (WIN >> 1) & 1 : 0);
#pragma unroll
          for (int j = 0; j < 8; j++) ldsm_if(hp + 4 * j, (xa ^ ((j & 3) << 5)) + (j >> 2) * 8192, true, IC<0>{});
        } else if (lap == 9) {
          mbar_wait_c(B(B_WR), 0);
          mbar_wait_c(B(B_SET2), 0);
#pragma unroll
          for (int j = 0; j < 4; j++) ldsm_if(rt + 4 * j, sb + OFF_MISC + 512 + (lane & 1) * 256 + (lane >> 3) * 16 + j * 64, true, IC<0>{});
        }
        kblock(IC<4>{}, lap & 1, true);
        sched_fence();
        dep = 0;
#pragma unroll
        for (int i = 0; i < 20; i++) dep ^= i < 12 ? wf[48 + 4 * i] : hp[4 * (i - 12)];
        hand(B(B_WE + (lap < WIN ? lap & 1 : 0)), lap < WIN ? 1 : (lap == WIN ? 2 : 0));
        kblock(IC<5>{}, lap & 1, true);
        kblock(IC<0>{}, (lap & 1) ^ 1, true);
        kblock(IC<1>{}, (lap & 1) ^ 1, true);
        TL(2, 40 + lap, warp == 4);
      }
    }
    uint4* const xr = g_xr + rid * XR_SIZE;
    uint4* const psd = xr + XR_PS + cw * 16 + r0;
    settle(psd, zero);
    sched_fence();
    wg_wait<0>();
    fence_regs(acc);
    TL(2, 10, warp == 4);
    {
      float d[4] = {0.f, 0.f, 0.f, 0.f}, qa[4] = {0.f, 0.f, 0.f, 0.f}, qb[4] = {0.f, 0.f, 0.f, 0.f};
#pragma unroll
      for (int j = 0; j < 16; j++) {
        hp[2 * j] = hadd2_bf(hp[2 * j], pack_bf16(acc[4 * j], acc[4 * j + 1]));
        hp[2 * j + 1] = hadd2_bf(hp[2 * j + 1], pack_bf16(acc[4 * j + 2], acc[4 * j + 3]));
        if (j & 1) {
          mma16816(d, hp[2 * j - 2], hp[2 * j - 1], hp[2 * j], hp[2 * j + 1], rt[j - 1], rt[j]);
          mma16816(qa, hp[2 * j - 2], hp[2 * j - 1], hp[2 * j], hp[2 * j + 1], hp[2 * j - 2], hp[2 * j]);
          mma16816(qb, hp[2 * j - 2], hp[2 * j - 1], hp[2 * j], hp[2 * j + 1], hp[2 * j - 1], hp[2 * j + 1]);
        }
      }
      asm volatile("{\n.reg .pred p;\nsetp.eq.u32 p, %7, %8;\n@p st.global.cg.v4.f32 [%0], {%1,%2,%3,%3};\n@p st.global.cg.v4.f32 [%0 + 128], {%4,%5,%6,%6};\n}"
                   ::"l"(psd), "f"(d[0]), "f"(d[1]), "f"((r0 & 1) ? qa[1] : qa[0]), "f"(d[2]), "f"(d[3]), "f"((r0 & 1) ? qb[3] : qb[2]),
                   "r"(lane & 3), "r"(r0 >> 1) : "memory");
      sched_fence();
    }
    mbar_wait_c(B(B_EMPTY3), 0);
    __syncwarp();
    stage_store_128(stg, lane, hp);
    TL(2, 11, warp == 4);
    __syncwarp();
    uint4 cout;
    uint32_t ckey;
    {
      const float wsum = *reinterpret_cast<const float*>(sp + OFF_MISC + 1024);
      const uint4* pp = g_xr + (mt * 8 + (ct & 1) * 4) * XR_SIZE + XR_PS + (ct >> 1);
      uint2* kd = reinterpret_cast<uint2*>(xr + XR_KEY) + cw;
      const uint32_t tok = 0x7FFFu - (mt * 128 + (ct >> 1));
      settle(pp, zero); settle(kd, zero); settle(tok, zero);
      spin_clk(PS_DLY);
      float s1, s2, s3;
#pragma unroll 1
      for (int n = 0; n < 0x400000; n++) {
        float4 z[4];
#pragma unroll
        for (int i = 0; i < 4; i++)
          asm volatile("ld.relaxed.gpu.global.v4.f32 {%0,%1,%2,%3}, [%4];" : "=f"(z[i].x), "=f"(z[i].y), "=f"(z[i].z), "=f"(z[i].w) : "l"(pp + i * XR_SIZE) : "memory");
        s1 = (z[0].x + z[1].x) + (z[2].x + z[3].x); s3 = (z[0].y + z[1].y) + (z[2].y + z[3].y); s2 = (z[0].z + z[1].z) + (z[2].z + z[3].z);
        const float t = s1 + s2 + s3;
        s1 += __shfl_xor_sync(~0u, s1, 1); s2 += __shfl_xor_sync(~0u, s2, 1); s3 += __shfl_xor_sync(~0u, s3, 1);
        if (__all_sync(~0u, t == t)) break;
        uint32_t m = 0;
#pragma unroll
        for (int i = 0; i < 4; i++) m = max(max(m, __float_as_uint(z[i].x)), max(__float_as_uint(z[i].y), __float_as_uint(z[i].z)));
        if (__all_sync(~0u, m != 0xFFFFFFFFu)) break;
      }
      TL(2, 12, warp == 4);
      const float mean = s1 * (1.f / DM);
      float mb, inv;
      ln_round(mean, fmaxf(fmaf(s2, 1.f / DM, -mean * mean), 0.f), mb, inv);
      const uint32_t u = pack_bf16(0.f, fmaf(s3 - mb * wsum, inv, 0.f));
      const uint32_t key = ((u ^ (((int)u >> 31) | 0x80000000u)) & 0xFFFF0000u) | tok;
      const uint32_t c1 = __reduce_max_sync(~0u, key);
      const uint32_t c2 = __reduce_max_sync(~0u, key == c1 ? 0u : key);
      asm volatile(ELECT "st.global.cg.v2.u32 [%0], {%1,%2};\n}" ::"l"(kd), "r"(c1), "r"(c2) : "memory");
      sched_fence();
      const uint32_t nm2 = pack_bf16(-mb, -mb);
      if (!(ct & 1)) *reinterpret_cast<uint2*>(sp + OFF_RSTAT + (ct >> 1) * 8) = make_uint2(nm2, __float_as_uint(inv) | (key >= c2 ? 0x80000000u : 0u));
      ckey = (lane >> 4) ? c2 : c1;
      const int row = (0x7FFF - (ckey & 0x7FFF)) & 15;
      const uint32_t rn = __shfl_sync(~0u, nm2, row * 2);
      const float ri = __shfl_sync(~0u, inv, row * 2);
      const uint4 v = lds128(stg + ((lane & 15) >> 3) * 8192 + row * 128 + (((lane & 7) ^ (row & 7)) << 4));
      const uint4 n = make_uint4(ln_apply(v.x, rn, ri), ln_apply(v.y, rn, ri), ln_apply(v.z, rn, ri), ln_apply(v.w, rn, ri));
      __stcg(xr + XR_CAND + cw * 64 + 32 + lane, n);
      __stcg(xr + XR_CAND + cw * 64 + lane, v);
      cdst = out + (size_t)(0x7FFF - (ckey & 0x7FFF)) * DM + gq * 128 + (lane & 15) * 8;
      cout = make_uint4(hadd2_bf(v.x, n.x), hadd2_bf(v.y, n.y), hadd2_bf(v.z, n.z), hadd2_bf(v.w, n.w));
    }
    publish(B_OUT - B_PUB);
    cluster_arrive();
    TL(2, 13, warp == 4);
    uint32_t wd[16][4];
    if (ffn) {
      static_for<2>([&](auto i) {
        mbar_wait_c(B(B_WF + i), ((WIN >> 1) & 1) ^ 1);
        grab(IC<WIN + i>{}, OFF_SIDE + i * UNIT);
      });
      mbar_wait_c(B(B_FULL3 + 4 + w), 0);
#pragma unroll
      for (int i = 0; i < 16; i++) {
        const int k = (i & 1) * 16 + (lane & 7) + (lane >> 4) * 8;
        asm volatile("ldmatrix.sync.aligned.m8n8.x4.trans.shared.b16 {%0,%1,%2,%3}, [%4];"
                     : "=r"(wd[i][0]), "=r"(wd[i][1]), "=r"(wd[i][2]), "=r"(wd[i][3])
                     : "r"(sb + r3(4) + w * SLOT + (2 * (cw & 3) + (i >> 3)) * 4096 + k * 128 + (((2 * ((i >> 1) & 3) + ((lane >> 3) & 1)) ^ (lane & 7)) << 4)) : "memory");
      }
    }
    const int fc = 16 * (rid >> 1) + 4 * (rid & 1) + (lane & 3) + 8 * (lane >> 4), ft = (lane >> 3) & 1;
    const char* pc = reinterpret_cast<const char*>(g_xr + ((ct & 127) >> 4) * XR_SIZE + XR_CAND + 32 + (ct & 15));
    const char* pf = reinterpret_cast<const char*>(g_xr + (fc >> 7) * XR_SIZE + XR_CAND) + (fc & 127) * 2;
    const uint32_t xs = sb + OFF_SCR + w * 2112 + ((ct & 127) >> 2) * 64 + (((ct >> 3) & 3) << 4) + (ct & 3) * 4;
    const uint32_t xb = sb + OFF_SCR + (r0 & 1) * 2112 + w * 128 + (((lane ^ w) & 3) << 4);
    settle(pc, zero); settle(pf, zero); settle(cdst, zero); settle(xs, zero); settle(xb, zero);
    mbar_wait_c(B(B_OUT2), 0);
    const uint4 top = lds128(sb + OFF_MISC);
    TL(2, 14, warp == 4);
    uint32_t fh, fn;
    {
      pc += w ? top.y : top.x;
      pf += ft ? top.y : top.x;
      uint4 v;
#pragma unroll 1
      for (int n = 0; n < 0x400000; n++) {
        asm volatile("ld.relaxed.gpu.global.v4.u32 {%0,%1,%2,%3}, [%4];" : "=r"(v.x), "=r"(v.y), "=r"(v.z), "=r"(v.w) : "l"(pc) : "memory");
        asm volatile("ld.relaxed.gpu.global.u16 %0, [%1];" : "=r"(fh) : "l"(pf) : "memory");
        asm volatile("ld.relaxed.gpu.global.u16 %0, [%1 + 512];" : "=r"(fn) : "l"(pf) : "memory");
        asm volatile("st.shared.u32 [%0], %1;" ::"r"(xs), "r"(v.x) : "memory");
        asm volatile("st.shared.u32 [%0], %1;" ::"r"(xs ^ 16), "r"(v.y) : "memory");
        asm volatile("st.shared.u32 [%0], %1;" ::"r"(xs ^ 32), "r"(v.z) : "memory");
        asm volatile("st.shared.u32 [%0], %1;" ::"r"(xs ^ 48), "r"(v.w) : "memory");
        if (__all_sync(~0u, max(max(v.x, v.y), max(v.z, v.w)) != 0xFFFFFFFFu && max(fh, fn) != 0xFFFFu)) break;
      }
    }
    bar_sync(3, 256);
    asm volatile("{\n.reg .pred p;\nsetp.lt.u32 p, %5, %6;\n@p st.global.v4.u32 [%0], {%1,%2,%3,%4};\n}" ::"l"(cdst), "r"(cout.x), "r"(cout.y), "r"(cout.z),
                 "r"(cout.w), "r"(ckey), "r"(top.w) : "memory");
    if (ffn) {
      TL(2, 15, warp == 4);
      float d[4][4] = {};
      auto xl = [&](int i) { return lds128((xb ^ ((i & 2) << 4)) + (i >> 1) * 256 + (i & 1) * 64); };
      uint4 b0 = xl(0), b1 = xl(1);
#pragma unroll
      for (int i = 0; i < 16; i += 2) {
        const uint4 c0 = b0, c1 = b1;
        if (i < 14) { b0 = xl(i + 2); b1 = xl(i + 3); }
        mma16816(d[0], wf[8 * i], wf[8 * i + 1], wf[8 * i + 2], wf[8 * i + 3], c0.x, c0.y);
        mma16816(d[1], wf[8 * i + 4], wf[8 * i + 5], wf[8 * i + 6], wf[8 * i + 7], c0.z, c0.w);
        mma16816(d[2], wf[8 * i + 8], wf[8 * i + 9], wf[8 * i + 10], wf[8 * i + 11], c1.x, c1.y);
        mma16816(d[3], wf[8 * i + 12], wf[8 * i + 13], wf[8 * i + 14], wf[8 * i + 15], c1.z, c1.w);
      }
      const float e0 = (d[0][0] + d[1][0]) + (d[2][0] + d[3][0]), e1 = (d[0][1] + d[1][1]) + (d[2][1] + d[3][1]);
      const float e2 = (d[0][2] + d[1][2]) + (d[2][2] + d[3][2]), e3 = (d[0][3] + d[1][3]) + (d[2][3] + d[3][3]);
      asm volatile("st.shared.v2.f32 [%0], {%1,%2};" ::"r"(sb + OFF_SCR + 8192 + ((w * 2 + (lane & 1)) * 32 + (cw & 3) * 8 + r0) * 8),
                   "f"((lane & 1) ? e1 : e0), "f"((lane & 1) ? e3 : e2) : "memory");
      bar_sync(3, 256);
      TL(2, 16, warp == 4);
      const uint32_t ra = sb + OFF_SCR + 8192 + (r0 & 1) * 256 + (r0 >> 1) * 64 + (lane & 3) * 16;
      const uint4 p0 = lds128(ra), p1 = lds128(ra + 512);
      auto act = [](uint32_t u0, uint32_t u1, uint32_t g0, uint32_t g1) {
        const uint32_t ug = pack_bf16(__uint_as_float(u0) + __uint_as_float(u1), __uint_as_float(g0) + __uint_as_float(g1));
        const float g = bf_hi(ug);
        return bf_round(__fdividef(g, 1.f + __expf(-g))) * bf_lo(ug);
      };
      const uint32_t av = pack_bf16(act(p0.x, p1.x, p0.y, p1.y), act(p0.z, p1.z, p0.w, p1.w));
      uint32_t b[4];
#pragma unroll
      for (int i = 0; i < 4; i++) b[i] = __shfl_sync(~0u, av, 8 * i + (lane & 7));
      TL(2, 17, warp == 4);
      float y[2][4] = {{0.f, 0.f, 0.f, 0.f}, {0.f, 0.f, 0.f, 0.f}};
#pragma unroll
      for (int c = 0; c < 4; c++) {
        const bool on = (lane >> 3) == c;
        const uint32_t b0 = on ? b[0] : 0, b1 = on ? b[1] : 0, b2 = on ? b[2] : 0, b3 = on ? b[3] : 0;
#pragma unroll
        for (int a = 0; a < 2; a++) {
          const int i = 8 * a + 2 * c;
          mma16816(y[a], wd[i][0], wd[i][1], wd[i][2], wd[i][3], b0, b1);
          mma16816(y[a], wd[i + 1][0], wd[i + 1][1], wd[i + 1][2], wd[i + 1][3], b2, b3);
        }
      }
      float4* yd = reinterpret_cast<float4*>(g_xr + (cw * 16 + (lane & 3) * 2 + (lane >> 4)) * XR_SIZE + XR_Y + fid * 4 + (r0 & 3));
      __stcg(yd, make_float4(y[0][0], y[0][1], y[0][2], y[0][3]));
      __stcg(yd + 8 * XR_SIZE, make_float4(y[1][0], y[1][1], y[1][2], y[1][3]));
    }
    TL(2, 18, warp == 4);
    if (cw == 0) {
      const uint32_t fk = ft ? top.w : top.z;
      uint32_t u = fk >> 16;
      u = (u & 0x8000u) ? (u & 0x7FFFu) : (~u & 0xFFFFu);
      float rs = bf_round(__fdividef(1.f, 1.f + __expf(-__uint_as_float(u << 16))));
      uint16_t* op = reinterpret_cast<uint16_t*>(out) + (size_t)(~fk & 0x7FFF) * DM + fc;
      settle(op, zero); settle(__float_as_uint(rs), zero);
      spin_clk(ffn ? Y_DLY : Y_DLY + Y_DLY0);
      float v[4];
#pragma unroll 1
      for (int n = 0; n < 0x400000; n++) {
        float4 z[14];
#pragma unroll
        for (int i = 0; i < 14; i++)
          asm volatile("ld.relaxed.gpu.global.v4.f32 {%0,%1,%2,%3}, [%4];" : "=f"(z[i].x), "=f"(z[i].y), "=f"(z[i].z), "=f"(z[i].w) : "l"(xr + XR_Y + lane + 32 * i) : "memory");
        float a[4] = {z[0].x, z[0].y, z[0].z, z[0].w}, b[4] = {z[1].x, z[1].y, z[1].z, z[1].w};
#pragma unroll
        for (int i = 2; i < 14; i += 2) {
          a[0] += z[i].x; a[1] += z[i].y; a[2] += z[i].z; a[3] += z[i].w;
          b[0] += z[i + 1].x; b[1] += z[i + 1].y; b[2] += z[i + 1].z; b[3] += z[i + 1].w;
        }
#pragma unroll
        for (int i = 0; i < 4; i++) v[i] = a[i] + b[i];
        const float t = (v[0] + v[1]) + (v[2] + v[3]);
        if (__all_sync(~0u, t == t)) break;
        uint32_t m = 0;
#pragma unroll
        for (int i = 0; i < 14; i++) m = max(max(m, max(__float_as_uint(z[i].x), __float_as_uint(z[i].y))), max(__float_as_uint(z[i].z), __float_as_uint(z[i].w)));
        if (__all_sync(~0u, m != 0xFFFFFFFFu)) break;
      }
      TL(2, 30, true);
      const bool hi = lane & 16, odd = lane & 8;
      const float a0 = (hi ? v[2] : v[0]) + __shfl_xor_sync(~0u, hi ? v[0] : v[2], 16), a1 = (hi ? v[3] : v[1]) + __shfl_xor_sync(~0u, hi ? v[1] : v[3], 16);
      float yv = (odd ? a1 : a0) + __shfl_xor_sync(~0u, odd ? a0 : a1, 8);
      yv += __shfl_xor_sync(~0u, yv, 4);
      const uint32_t o = hadd2_bf(fh, hadd2_bf(fn, pack_bf16(bf_round(yv) * rs, 0.f)));
      if (!(lane & 4)) *op = (uint16_t)o;
      TL(2, 21, true);
    }
    TL(2, 20, warp == 4);
    }
    __syncwarp();
    cluster_wait();
  }
}

typedef CUresult (*EncodeFn)(CUtensorMap*, CUtensorMapDataType, cuuint32_t, void*, const cuuint64_t*, const cuuint64_t*, const cuuint32_t*,
                             const cuuint32_t*, CUtensorMapInterleave, CUtensorMapSwizzle, CUtensorMapL2promotion, CUtensorMapFloatOOBfill);
EncodeFn g_enc = nullptr;

void map2(CUtensorMap* m, const void* ptr, uint64_t rows, uint64_t cols, uint32_t bc, uint32_t br) {
  const CUtensorMapSwizzle sw = bc == 64 ? CU_TENSOR_MAP_SWIZZLE_128B : CU_TENSOR_MAP_SWIZZLE_64B;
  cuuint64_t gd[2] = {cols, rows}, gs[1] = {cols * 2};
  cuuint32_t bd[2] = {bc, br}, es[2] = {1, 1};
  g_enc(m, CU_TENSOR_MAP_DATA_TYPE_BFLOAT16, 2, (void*)ptr, gd, gs, bd, es, CU_TENSOR_MAP_INTERLEAVE_NONE, sw,
        CU_TENSOR_MAP_L2_PROMOTION_L2_128B, CU_TENSOR_MAP_FLOAT_OOB_FILL_NONE);
}
void map3(CUtensorMap* m, const void* ptr, uint64_t rows, uint64_t cols, uint32_t br, uint32_t bch) {
  cuuint64_t gd[3] = {64, rows, cols / 64}, gs[2] = {cols * 2, 128};
  cuuint32_t bd[3] = {64, br, bch}, es[3] = {1, 1, 1};
  g_enc(m, CU_TENSOR_MAP_DATA_TYPE_BFLOAT16, 3, (void*)ptr, gd, gs, bd, es, CU_TENSOR_MAP_INTERLEAVE_NONE, CU_TENSOR_MAP_SWIZZLE_128B,
        CU_TENSOR_MAP_L2_PROMOTION_L2_128B, CU_TENSOR_MAP_FLOAT_OOB_FILL_NONE);
}

}

extern "C" void kernel_launch(void* const* d_in, const int* in_sizes, int n_in, void* d_out, int out_size) {
  const __nv_bfloat16* x = (const __nv_bfloat16*)d_in[0];
  const __nv_bfloat16* ckv = (const __nv_bfloat16*)d_in[1];
  const __nv_bfloat16* wq = (const __nv_bfloat16*)d_in[2];
  const __nv_bfloat16* wk = (const __nv_bfloat16*)d_in[3];
  const __nv_bfloat16* wv = (const __nv_bfloat16*)d_in[4];
  const __nv_bfloat16* wo = (const __nv_bfloat16*)d_in[5];
  const __nv_bfloat16* w_r = (const __nv_bfloat16*)d_in[7];
  const __nv_bfloat16* wgate = (const __nv_bfloat16*)d_in[8];
  const __nv_bfloat16* wup = (const __nv_bfloat16*)d_in[9];
  const __nv_bfloat16* wdown = (const __nv_bfloat16*)d_in[10];
  __nv_bfloat16* out = (__nv_bfloat16*)d_out;

  if (!g_enc) {
    void* fn = nullptr;
    cudaDriverEntryPointQueryResult qr;
    cudaGetDriverEntryPoint("cuTensorMapEncodeTiled", &fn, cudaEnableDefault, &qr);
    g_enc = (EncodeFn)fn;
    cudaFuncSetAttribute(fused_kernel, cudaFuncAttributeMaxDynamicSharedMemorySize, SMEM_BYTES);
  }
  void *xn, *kv, *ctx, *xr, *cnt;
  cudaGetSymbolAddress(&xr, g_xr);
  cudaGetSymbolAddress(&cnt, g_cnt);
  cudaGetSymbolAddress(&xn, g_xn);
  cudaGetSymbolAddress(&kv, g_kv);
  cudaGetSymbolAddress(&ctx, g_ctx);

  Params p;
  map2(&p.xn, xn, SEQ, DM, 64, 64);
  map2(&p.ckv, ckv, SEQ, DC, 64, 128);
  map3(&p.wq, wq, DM, NQ, 64, 2);
  map3(&p.wk, wk, DC, NQ, 64, 2);
  map3(&p.wv, wv, DC, NQ, 64, 2);
  map3(&p.kv_ld, kv, 2 * SEQ, NQ, 128, 2);
  map2(&p.ctx_ld, ctx, SEQ, NQ, 64, 128);
  map3(&p.wo, wo, NQ, DM, 64, 1);
  map3(&p.x, x, SEQ, DM, 64, 2);
  map3(&p.wd, wdown, FF, DM, 32, 8);
  map2(&p.wg, wgate, DM, FF, 32, 64);
  map2(&p.wu, wup, DM, FF, 32, 64);
  fused_kernel<<<128, 384, SMEM_BYTES, cudaStreamPerThread>>>(0u, x, (__nv_bfloat16*)kv, (__nv_bfloat16*)ctx, (uint4*)xr, out, (__nv_bfloat16*)xn,
                                                               (unsigned*)cnt, w_r, wdown, wq, p);
}
```

```cpp
#include <cuda_runtime.h>
#include <cuda_bf16.h>
#include <cuda.h>
#include <stdint.h>
#include <utility>

#pragma nv_diag_suppress 549
#pragma nv_diag_suppress 177
namespace {

constexpr int SEQ = 2048, DM = 1024, NH = 32, HD = 128, DC = 512, NQ = NH * HD, FF = 3584;

__device__ __align__(1024) __nv_bfloat16 g_xn[SEQ * DM];
__device__ __align__(1024) __nv_bfloat16 g_kv[2 * SEQ * NQ];
__device__ __align__(1024) __nv_bfloat16 g_ctx[SEQ * NQ];
constexpr int XR_PS = 0;
constexpr int XR_KEY = 128;
constexpr int XR_CAND = 136;
constexpr int XR_Y = 648;
constexpr int XR_SIZE = 1104;
__device__ __align__(1024) uint4 g_xr[128 * XR_SIZE];
constexpr int C_LN = 0, C_KV = 16, C_CTX = 32, C_NUM = 64;
__device__ unsigned g_cnt[C_NUM];

#define TL(k, i, cond) do {} while (0)
#define TC(w, g, i) do {} while (0)
#define TL_EXTRA 0
#define TK(i) do {} while (0)

__device__ __forceinline__ uint32_t s2u(const void* p) { return (uint32_t)__cvta_generic_to_shared(p); }
__device__ __forceinline__ void mbar_arrive(uint32_t b) { asm volatile("mbarrier.arrive.shared::cta.b64 _, [%0];" ::"r"(b) : "memory"); }
__device__ __forceinline__ void mbar_arrive_both(uint32_t b, uint32_t lane, bool cond) {
  asm volatile("{\n.reg .pred p;\n.reg .b32 r;\nsetp.lt.u32 p, %1, %2;\nmapa.shared::cluster.u32 r, %0, %1;\n@p mbarrier.arrive.shared::cluster.b64 _, [r];\n}"
               ::"r"(b), "r"(lane), "r"(cond ? 2 : 0) : "memory");
}
__device__ __forceinline__ bool mbar_test(uint32_t b, uint32_t ph) {
  uint32_t ok;
  asm volatile("{\n.reg .pred p;\nmbarrier.test_wait.parity.shared::cta.b64 p, [%1], %2;\nselp.u32 %0, 1, 0, p;\n}" : "=r"(ok) : "r"(b), "r"(ph) : "memory");
  return __all_sync(~0u, ok);
}
__device__ __forceinline__ void mbar_wait(uint32_t b, uint32_t ph) {
  asm volatile(
      "{\n.reg .pred p;\n.reg .u32 n;\nmov.u32 n, 0;\n"
      "LW:\nmbarrier.try_wait.parity.shared::cta.b64 p, [%0], %1, 20000;\n@p bra LD;\n"
      "add.u32 n, n, 1;\nsetp.lt.u32 p, n, 0x40000;\n@p bra LW;\ntrap;\nLD:\n}" ::"r"(b), "r"(ph) : "memory");
}
__device__ __forceinline__ void mbar_wait_u(uint32_t b, uint32_t ph) {
  asm volatile(
      "{\n.reg .pred p;\n.reg .u32 n;\nmov.u32 n, 0;\n"
      "LW:\nmbarrier.try_wait.parity.shared::cta.b64 p, [%0], %1, 20000;\n@p bra.uni LD;\n"
      "add.u32 n, n, 1;\nsetp.lt.u32 p, n, 0x40000;\n@p bra.uni LW;\ntrap;\nLD:\n}" ::"r"(b), "r"(ph) : "memory");
}
__device__ __forceinline__ void mbar_wait_c(uint32_t b, uint32_t ph) {
  asm volatile("{\n.reg .pred p;\nLW:\nmbarrier.try_wait.parity.shared::cta.b64 p, [%0], %1;\n@!p bra.uni LW;\n}" ::"r"(b), "r"(ph) : "memory");
}
__device__ __forceinline__ void mbar_wait_b(uint32_t b, uint32_t ph) {
  asm volatile(
      "{\n.reg .pred p;\n.reg .u32 n;\nmov.u32 n, 0;\n"
      "LW:\nmbarrier.try_wait.parity.shared::cta.b64 p, [%0], %1;\n@p bra.uni LD;\n"
      "add.u32 n, n, 1;\nsetp.lt.u32 p, n, 0x1000000;\n@p bra.uni LW;\ntrap;\nLD:\n}" ::"r"(b), "r"(ph) : "memory");
}
template <bool SLEEP = false>
__device__ __forceinline__ void spin_until_ge(const unsigned* p, unsigned target) {
  asm volatile(
      "{\n.reg .pred p, q;\n.reg .u32 n, v;\nmov.u32 n, 0;\nsetp.ne.u32 q, %2, 0;\n"
      "LW:\nld.acquire.gpu.global.u32 v, [%0];\nsetp.ge.u32 p, v, %1;\n@p bra LD;\n@q nanosleep.u32 200;\n"
      "add.u32 n, n, 1;\nsetp.lt.u32 p, n, 0x400000;\n@p bra LW;\ntrap;\nLD:\n}" ::"l"(p), "r"(target), "n"((int)SLEEP) : "memory");
}
template <int N>
__device__ __forceinline__ void poll_chunks(uint4 (&v)[N], const uint4* p, int stride) {
#pragma unroll 1
  for (int n = 0; n < 0x400000; n++) {
    uint32_t m = 0;
#pragma unroll
    for (int i = 0; i < N; i++) {
      asm volatile("ld.relaxed.gpu.global.v4.u32 {%0,%1,%2,%3}, [%4];" : "=r"(v[i].x), "=r"(v[i].y), "=r"(v[i].z), "=r"(v[i].w) : "l"(p + i * stride) : "memory");
    }
#pragma unroll
    for (int i = 0; i < N; i++) m = max(max(m, max(v[i].x, v[i].y)), max(v[i].z, v[i].w));
    if (__all_sync(~0u, m != 0xFFFFFFFFu)) break;
  }
}
__device__ __forceinline__ void spin_clk(uint32_t n) {
  asm volatile("{\n.reg .pred p;\n.reg .u32 a, b;\nmov.u32 a, %%clock;\nLW:\nmov.u32 b, %%clock;\nsub.u32 b, b, a;\nsetp.lt.u32 p, b, %0;\n@p bra.uni LW;\n}" ::"r"(n) : "memory");
}
__device__ __forceinline__ int fresh_lane() {
  int r;
  asm volatile("mov.u32 %0, %%laneid;" : "=r"(r));
  return r;
}
__device__ __forceinline__ void settle(const void* a, uint32_t zero) {
  asm volatile("{\n.reg .pred p;\nsetp.ne.u32 p, %1, 0;\n@p st.global.u32 [%0], %1;\n}" ::"l"(a), "r"(zero) : "memory");
}
__device__ __forceinline__ void settle(uint32_t a, uint32_t zero) {
  asm volatile("{\n.reg .pred p;\nsetp.ne.u32 p, %1, 0;\n@p st.shared.u32 [%0], %1;\n}" ::"r"(a), "r"(zero) : "memory");
}
__device__ __forceinline__ void fence_async_all() { asm volatile("fence.proxy.async;" ::: "memory"); }
__device__ __forceinline__ void bar_sync(int id, int n) { asm volatile("bar.sync %0, %1;" ::"r"(id), "r"(n) : "memory"); }
__device__ __forceinline__ void bar_arrive(int id, int n) { asm volatile("bar.arrive %0, %1;" ::"r"(id), "r"(n) : "memory"); }
__device__ __forceinline__ void cluster_arrive() { asm volatile("barrier.cluster.arrive.relaxed.aligned;" ::: "memory"); }
__device__ __forceinline__ void cluster_wait() { asm volatile("barrier.cluster.wait.acquire.aligned;" ::: "memory"); }
__device__ __forceinline__ void fence_gpu() { asm volatile("fence.acq_rel.gpu;" ::: "memory"); }
__device__ __forceinline__ void red_add(unsigned* p, unsigned v) { asm volatile("red.relaxed.gpu.global.add.u32 [%0], %1;" ::"l"(p), "r"(v) : "memory"); }
#define ELECT "{\n.reg .pred E;\nelect.sync _|E, 0xFFFFFFFF;\n@E "
__device__ __forceinline__ void e_init(uint32_t b, uint32_t c) { asm volatile(ELECT "mbarrier.init.shared::cta.b64 [%0], %1;\n}" ::"r"(b), "r"(c) : "memory"); }
__device__ __forceinline__ void e_expect(uint32_t b, uint32_t bytes) { asm volatile(ELECT "mbarrier.arrive.expect_tx.shared::cta.b64 _, [%0], %1;\n}" ::"r"(b), "r"(bytes) : "memory"); }
__device__ __forceinline__ void e_arrive(uint32_t b) { asm volatile(ELECT "mbarrier.arrive.shared::cta.b64 _, [%0];\n}" ::"r"(b) : "memory"); }
__device__ __forceinline__ void prefetch_tm(const CUtensorMap* m) { asm volatile(ELECT "prefetch.tensormap [%0];\n}" ::"l"(m) : "memory"); }
__device__ __forceinline__ void tma_ld2(uint32_t dst, const CUtensorMap* m, uint32_t bar, int c0, int c1) {
  asm volatile(ELECT "cp.async.bulk.tensor.2d.shared::cta.global.mbarrier::complete_tx::bytes [%0], [%1, {%3,%4}], [%2];\n}" ::"r"(dst), "l"(m), "r"(bar), "r"(c0), "r"(c1) : "memory");
}
__device__ __forceinline__ void tma_ld3(uint32_t dst, const CUtensorMap* m, uint32_t bar, int c0, int c1, int c2) {
  asm volatile(ELECT "cp.async.bulk.tensor.3d.shared::cta.global.mbarrier::complete_tx::bytes [%0], [%1, {%3,%4,%5}], [%2];\n}" ::"r"(dst), "l"(m), "r"(bar), "r"(c0), "r"(c1), "r"(c2) : "memory");
}
__device__ __forceinline__ void tma_ld2_mc(uint32_t dst, const CUtensorMap* m, uint32_t bar, int c0, int c1, uint16_t mask) {
  asm volatile(ELECT "cp.async.bulk.tensor.2d.shared::cluster.global.mbarrier::complete_tx::bytes.multicast::cluster [%0], [%1, {%3,%4}], [%2], %5;\n}" ::"r"(dst), "l"(m), "r"(bar), "r"(c0), "r"(c1), "h"(mask) : "memory");
}
__device__ __forceinline__ void tma_ld3_mc(uint32_t dst, const CUtensorMap* m, uint32_t bar, int c0, int c1, int c2, uint16_t mask) {
  asm volatile(ELECT "cp.async.bulk.tensor.3d.shared::cluster.global.mbarrier::complete_tx::bytes.multicast::cluster [%0], [%1, {%3,%4,%5}], [%2], %6;\n}" ::"r"(dst), "l"(m), "r"(bar), "r"(c0), "r"(c1), "r"(c2), "h"(mask) : "memory");
}
__device__ __forceinline__ uint64_t policy_evict_first() {
  uint64_t p;
  asm("createpolicy.fractional.L2::evict_first.b64 %0, 1.0;" : "=l"(p));
  return p;
}
__device__ __forceinline__ void tma_ld2_ef(uint32_t dst, const CUtensorMap* m, uint32_t bar, int c0, int c1) {
  asm volatile(ELECT "cp.async.bulk.tensor.2d.shared::cta.global.mbarrier::complete_tx::bytes.L2::cache_hint [%0], [%1, {%3,%4}], [%2], %5;\n}" ::"r"(dst), "l"(m), "r"(bar), "r"(c0), "r"(c1), "l"(policy_evict_first()) : "memory");
}
__device__ __forceinline__ void tma_ld3_ef(uint32_t dst, const CUtensorMap* m, uint32_t bar, int c0, int c1, int c2) {
  asm volatile(ELECT "cp.async.bulk.tensor.3d.shared::cta.global.mbarrier::complete_tx::bytes.L2::cache_hint [%0], [%1, {%3,%4,%5}], [%2], %6;\n}" ::"r"(dst), "l"(m), "r"(bar), "r"(c0), "r"(c1), "r"(c2), "l"(policy_evict_first()) : "memory");
}
__device__ __forceinline__ void tma_pf2(const CUtensorMap* m, int c0, int c1) { asm volatile(ELECT "cp.async.bulk.prefetch.tensor.2d.L2.global [%0, {%1,%2}];\n}" ::"l"(m), "r"(c0), "r"(c1) : "memory"); }
__device__ __forceinline__ void tma_pf3(const CUtensorMap* m, int c0, int c1, int c2) { asm volatile(ELECT "cp.async.bulk.prefetch.tensor.3d.L2.global [%0, {%1,%2,%3}];\n}" ::"l"(m), "r"(c0), "r"(c1), "r"(c2) : "memory"); }
__device__ __forceinline__ void sched_fence() { asm volatile("pmevent 0;" ::: "memory"); }
__device__ __forceinline__ void l2_prefetch(const void* p, uint32_t bytes) { asm volatile(ELECT "cp.async.bulk.prefetch.L2.global [%0], %1;\n}" ::"l"(p), "r"(bytes) : "memory"); }

__device__ __forceinline__ void wg_fence() { asm volatile("wgmma.fence.sync.aligned;" ::: "memory"); }
__device__ __forceinline__ void wg_commit() { asm volatile("wgmma.commit_group.sync.aligned;" ::: "memory"); }
template <int N> __device__ __forceinline__ void wg_wait() { asm volatile("wgmma.wait_group.sync.aligned %0;" ::"n"(N) : "memory"); }
template <int N> __device__ __forceinline__ void reg_alloc() { asm volatile("setmaxnreg.inc.sync.aligned.u32 %0;" ::"n"(N)); }
template <int N> __device__ __forceinline__ void reg_dealloc() { asm volatile("setmaxnreg.dec.sync.aligned.u32 %0;" ::"n"(N)); }
template <int N> __device__ __forceinline__ void fence_regs(float (&d)[N]) {
#pragma unroll
  for (int i = 0; i < N; i++) asm volatile("" : "+f"(d[i])::"memory");
}
template <int I0, int I1, int N> __device__ __forceinline__ void fence_part(float (&d)[N]) {
#pragma unroll
  for (int i = I0; i < I1; i++) asm volatile("" : "+f"(d[i])::"memory");
}
template <int N> __device__ __forceinline__ void fence_regs(uint32_t (&d)[N]) {
#pragma unroll
  for (int i = 0; i < N; i++) asm volatile("" : "+r"(d[i])::"memory");
}

__device__ __forceinline__ uint32_t mk_desc(uint32_t addr, uint32_t lbo) { return ((addr & 0x3FFFF) >> 4) | ((lbo >> 4) << 16); }

#define R8(b) "+f"(d[b + 0]), "+f"(d[b + 1]), "+f"(d[b + 2]), "+f"(d[b + 3]), "+f"(d[b + 4]), "+f"(d[b + 5]), "+f"(d[b + 6]), "+f"(d[b + 7])
#define REGS64 "%0,%1,%2,%3,%4,%5,%6,%7,%8,%9,%10,%11,%12,%13,%14,%15,%16,%17,%18,%19,%20,%21,%22,%23,%24,%25,%26,%27,%28,%29,%30,%31," \
               "%32,%33,%34,%35,%36,%37,%38,%39,%40,%41,%42,%43,%44,%45,%46,%47,%48,%49,%50,%51,%52,%53,%54,%55,%56,%57,%58,%59,%60,%61,%62,%63"
#define REGS128 REGS64 ",%64,%65,%66,%67,%68,%69,%70,%71,%72,%73,%74,%75,%76,%77,%78,%79,%80,%81,%82,%83,%84,%85,%86,%87,%88,%89,%90,%91,%92,%93,%94,%95," \
               "%96,%97,%98,%99,%100,%101,%102,%103,%104,%105,%106,%107,%108,%109,%110,%111,%112,%113,%114,%115,%116,%117,%118,%119,%120,%121,%122,%123,%124,%125,%126,%127"

#define DESC(d, r, o) "add.u32 t, " r ", " o ";\nmov.b64 " d ", {t, h};\n"
#define MMA_PRE(acc) "{\n.reg .pred p;\n.reg .b32 t, h;\n.reg .b64 da, db;\nmov.b32 h, 0x40000040;\nsetp.ne.b32 p, " acc ", 0;\n"
template <int TB, int OA, int OB>
__device__ __forceinline__ void mma_n256_ss(float (&d)[128], uint32_t a, uint32_t b, int acc) {
  asm volatile(MMA_PRE("%130") DESC("da", "%128", "%132") DESC("db", "%129", "%133")
               "wgmma.mma_async.sync.aligned.m64n256k16.f32.bf16.bf16 {" REGS128 "}, da, db, p, 1, 1, 0, %131;\n}\n"
               : R8(0), R8(8), R8(16), R8(24), R8(32), R8(40), R8(48), R8(56), R8(64), R8(72), R8(80), R8(88), R8(96), R8(104), R8(112), R8(120)
               : "r"(a), "r"(b), "r"(acc), "n"(TB), "n"(OA >> 4), "n"(OB >> 4));
}
template <int TB, int OA, int OB>
__device__ __forceinline__ void mma_n128_ss(float (&d)[64], uint32_t a, uint32_t b, int acc) {
  asm volatile(MMA_PRE("%66") DESC("da", "%64", "%68") DESC("db", "%65", "%69")
               "wgmma.mma_async.sync.aligned.m64n128k16.f32.bf16.bf16 {" REGS64 "}, da, db, p, 1, 1, 0, %67;\n}\n"
               : R8(0), R8(8), R8(16), R8(24), R8(32), R8(40), R8(48), R8(56)
               : "r"(a), "r"(b), "r"(acc), "n"(TB), "n"(OA >> 4), "n"(OB >> 4));
}
template <int TB, int OB>
__device__ __forceinline__ void mma_n128_rs(float (&d)[64], const uint32_t* a, uint32_t b, int acc) {
  asm volatile(MMA_PRE("%69") DESC("db", "%68", "%71")
               "wgmma.mma_async.sync.aligned.m64n128k16.f32.bf16.bf16 {" REGS64 "}, {%64,%65,%66,%67}, db, p, 1, 1, %70;\n}\n"
               : R8(0), R8(8), R8(16), R8(24), R8(32), R8(40), R8(48), R8(56)
               : "r"(a[0]), "r"(a[1]), "r"(a[2]), "r"(a[3]), "r"(b), "r"(acc), "n"(TB), "n"(OB >> 4));
}
#define W8(b) "=f"(d[b + 0]), "=f"(d[b + 1]), "=f"(d[b + 2]), "=f"(d[b + 3]), "=f"(d[b + 4]), "=f"(d[b + 5]), "=f"(d[b + 6]), "=f"(d[b + 7])
#define MMA_N64 MMA_PRE("%37") DESC("db", "%36", "%38") \
  "wgmma.mma_async.sync.aligned.m64n64k16.f32.bf16.bf16 {%0,%1,%2,%3,%4,%5,%6,%7,%8,%9,%10,%11,%12,%13,%14,%15,%16,%17,%18,%19,%20,%21," \
  "%22,%23,%24,%25,%26,%27,%28,%29,%30,%31}, {%32,%33,%34,%35}, db, p, 1, 1, 0;\n}\n"
template <int H, int OB, bool ACC>
__device__ __forceinline__ void mma_n64_rs(float (&d)[64], const uint32_t* a, uint32_t b) {
  if (ACC) asm volatile(MMA_N64 : R8(32 * H), R8(32 * H + 8), R8(32 * H + 16), R8(32 * H + 24) : "r"(a[0]), "r"(a[1]), "r"(a[2]), "r"(a[3]), "r"(b), "n"(1), "n"(OB >> 4));
  else asm volatile(MMA_N64 : W8(32 * H), W8(32 * H + 8), W8(32 * H + 16), W8(32 * H + 24) : "r"(a[0]), "r"(a[1]), "r"(a[2]), "r"(a[3]), "r"(b), "n"(0), "n"(OB >> 4));
}
template <int OB>
__device__ __forceinline__ void mma_n128_rs0(float (&d)[64], const uint32_t* a, uint32_t b) {
  asm volatile(MMA_PRE("%69") DESC("db", "%68", "%70")
               "wgmma.mma_async.sync.aligned.m64n128k16.f32.bf16.bf16 {" REGS64 "}, {%64,%65,%66,%67}, db, p, 1, 1, 0;\n}\n"
               : W8(0), W8(8), W8(16), W8(24), W8(32), W8(40), W8(48), W8(56)
               : "r"(a[0]), "r"(a[1]), "r"(a[2]), "r"(a[3]), "r"(b), "n"(0), "n"(OB >> 4));
}
template <int TB, int OA, int OB>
__device__ __forceinline__ void mma_n128_ss0(float (&d)[64], uint32_t a, uint32_t b) {
  asm volatile(MMA_PRE("%66") DESC("da", "%64", "%68") DESC("db", "%65", "%69")
               "wgmma.mma_async.sync.aligned.m64n128k16.f32.bf16.bf16 {" REGS64 "}, da, db, p, 1, 1, 0, %67;\n}\n"
               : W8(0), W8(8), W8(16), W8(24), W8(32), W8(40), W8(48), W8(56)
               : "r"(a), "r"(b), "n"(0), "n"(TB), "n"(OA >> 4), "n"(OB >> 4));
}
template <int V> struct IC { static constexpr int value = V; __host__ __device__ constexpr operator int() const { return V; } };
template <int N, class F, int... I>
__device__ __forceinline__ void static_for_(F f, std::integer_sequence<int, I...>) { (f(IC<I>{}), ...); }
template <int N, class F>
__device__ __forceinline__ void static_for(F f) { static_for_<N>(f, std::make_integer_sequence<int, N>{}); }
__device__ __forceinline__ uint32_t pack_bf16(float lo, float hi) {
  uint32_t r;
  asm("cvt.rn.bf16x2.f32 %0, %1, %2;" : "=r"(r) : "f"(hi), "f"(lo));
  return r;
}
__device__ __forceinline__ float bf_lo(uint32_t v) { return __uint_as_float(v << 16); }
__device__ __forceinline__ float bf_hi(uint32_t v) { return __uint_as_float(v & 0xFFFF0000u); }
__device__ __forceinline__ float bf_round(float v) { return bf_lo(pack_bf16(v, v)); }
__device__ __forceinline__ void stsm4(uint32_t addr, uint32_t r0, uint32_t r1, uint32_t r2, uint32_t r3) {
  asm volatile("stmatrix.sync.aligned.m8n8.x4.shared.b16 [%0], {%1,%2,%3,%4};" ::"r"(addr), "r"(r0), "r"(r1), "r"(r2), "r"(r3) : "memory");
}
__device__ __forceinline__ uint4 lds128(uint32_t addr) {
  uint4 v;
  asm volatile("ld.shared.v4.u32 {%0,%1,%2,%3}, [%4];" : "=r"(v.x), "=r"(v.y), "=r"(v.z), "=r"(v.w) : "r"(addr));
  return v;
}
__device__ __forceinline__ float ex2(float x) {
  float y;
  asm("ex2.approx.ftz.f32 %0, %1;" : "=f"(y) : "f"(x));
  return y;
}
__device__ __forceinline__ void stage_store_128(uint32_t base, int lane, const uint32_t* pk) {
  const int row = (lane & 7) + ((lane >> 3) & 1) * 8;
  const uint32_t rb = base + row * 128;
  const int hi = lane >> 4;
#pragma unroll
  for (int j = 0; j < 8; j++) {
    const int chunk = 2 * j + hi;
    const uint32_t a = rb + (j >> 2) * 8192 + (((chunk & 7) ^ (lane & 7)) << 4);
    stsm4(a, pk[4 * j + 0], pk[4 * j + 1], pk[4 * j + 2], pk[4 * j + 3]);
  }
}
__device__ __forceinline__ void ln_round(float mean, float var, float& m_bf, float& inv_s) {
  const uint32_t mv = pack_bf16(mean, var);
  m_bf = bf_lo(mv);
  float sq, rc;
  asm("sqrt.approx.ftz.f32 %0, %1;" : "=f"(sq) : "f"(bf_round(bf_hi(mv) + 1e-5f)));
  asm("rcp.approx.ftz.f32 %0, %1;" : "=f"(rc) : "f"(bf_round(sq)));
  inv_s = rc;
}
__device__ __forceinline__ uint32_t hadd2_bf(uint32_t a, uint32_t b) {
  uint32_t r;
  asm("add.rn.bf16x2 %0, %1, %2;" : "=r"(r) : "r"(a), "r"(b));
  return r;
}
__device__ __forceinline__ uint32_t ln_apply(uint32_t h, uint32_t nm2, float inv_s) {
  const uint32_t d = hadd2_bf(h, nm2);
  return pack_bf16(bf_lo(d) * inv_s, bf_hi(d) * inv_s);
}
__device__ __forceinline__ void mma16816(float* d, uint32_t a0, uint32_t a1, uint32_t a2, uint32_t a3, uint32_t b0, uint32_t b1) {
  asm volatile("mma.sync.aligned.m16n8k16.row.col.f32.bf16.bf16.f32 {%0,%1,%2,%3}, {%4,%5,%6,%7}, {%8,%9}, {%0,%1,%2,%3};"
               : "+f"(d[0]), "+f"(d[1]), "+f"(d[2]), "+f"(d[3]) : "r"(a0), "r"(a1), "r"(a2), "r"(a3), "r"(b0), "r"(b1));
}

constexpr float AT_C = 0.08838834764831845f * 1.4426950408889634f;
#define L_MIN 2.3283064e-10f
#define L_MAX 1.0995116e12f
struct AtState {
  float S[64], O[64];
  uint32_t P[32], Q[32];
  float l[4];
};
template <int I0, int I1>
__device__ __forceinline__ void at_exp(AtState& s) {
#pragma unroll
  for (int i = I0; i < I1; i++) asm volatile("ex2.approx.ftz.f32 %0, %0;" : "+f"(s.S[i]));
#pragma unroll
  for (int i = I0; i < I1; i++) asm volatile("add.f32 %0, %0, %1;" : "+f"(s.l[i & 3]) : "f"(s.S[i]));
}
template <int I0, int I1>
__device__ __forceinline__ void at_pack(AtState& s) {
#pragma unroll
  for (int i = I0; i < I1; i++) asm volatile("cvt.rn.bf16x2.f32 %0, %1, %2;" : "=r"(s.P[i]) : "f"(s.S[2 * i + 1]), "f"(s.S[2 * i]));
}
template <int J0>
__device__ __forceinline__ void at_mask(AtState& s, int r, int lane) {
  const int d = r + (lane >> 2) - (lane & 3) * 2;
#pragma unroll
  for (int j = 0; j < 8; j++) {
    float dummy0 = 0.f, dummy1 = 0.f;
    float& lo0 = j < 7 ? s.S[4 * (J0 + (j < 7 ? j + 1 : j)) + 2] : dummy0;
    float& lo1 = j < 7 ? s.S[4 * (J0 + (j < 7 ? j + 1 : j)) + 3] : dummy1;
    asm("{\n.reg .pred p, q;\nsetp.lt.s32 p, %4, %5;\nsetp.le.s32 q, %4, %5;\n"
        "@p add.f32 %0, %0, 0fFF800000;\n@q add.f32 %1, %1, 0fFF800000;\n@p add.f32 %2, %2, 0fFF800000;\n@q add.f32 %3, %3, 0fFF800000;\n}"
        : "+f"(s.S[4 * (J0 + j)]), "+f"(s.S[4 * (J0 + j) + 1]), "+f"(lo0), "+f"(lo1) : "r"(d), "r"(8 * j));
  }
}
__device__ __forceinline__ uint32_t ld_pair(const __nv_bfloat16* p) {
  uint32_t r;
  asm volatile("{\n.reg .b16 a, b;\nld.global.cg.b16 a, [%1];\nld.global.cg.b16 b, [%1 + 8192];\nmov.b32 %0, {a, b};\n}" : "=r"(r) : "l"(p) : "memory");
  return r;
}
__device__ __forceinline__ uint32_t ld_word(const uint32_t* p) {
  uint32_t r;
  asm volatile("ld.global.cg.b32 %0, [%1];" : "=r"(r) : "l"(p) : "memory");
  return r;
}
__device__ __noinline__ void slow_rows(const __nv_bfloat16* wq, int head, int row0) {
  const int lane = fresh_lane(), r = lane >> 2, c = lane & 3;
  uint32_t q[32];
  float o[32];
#pragma unroll
  for (int i = 0; i < 32; i++) q[i] = 0;
  const uint32_t* xa = reinterpret_cast<const uint32_t*>(g_xn + (size_t)(row0 + r) * DM) + c;
#pragma unroll 1
  for (int h = 0; h < 2; h++) {
    const __nv_bfloat16* wb = wq + (size_t)2 * c * NQ + head * HD + 64 * h + 8 * (r >> 1) + (r & 1);
#pragma unroll
    for (int i = 0; i < 32; i++) o[i] = 0.f;
#pragma unroll 1
    for (int kk = 0; kk < DM / 16; kk++) {
      const uint32_t a0 = ld_word(xa + 8 * kk), a1 = ld_word(xa + 8 * kk + 4 * DM), a2 = ld_word(xa + 8 * kk + 4), a3 = ld_word(xa + 8 * kk + 4 * DM + 4);
#pragma unroll
      for (int n = 0; n < 8; n++) {
        const __nv_bfloat16* b = wb + (size_t)16 * kk * NQ + 32 * (n >> 2) + 2 * (n & 3);
        mma16816(o + 4 * n, a0, a1, a2, a3, ld_pair(b), ld_pair(b + 8 * NQ));
      }
    }
#pragma unroll
    for (int i = 0; i < 16; i++) { q[i] = q[16 + i]; q[16 + i] = pack_bf16(o[2 * i] * AT_C, o[2 * i + 1] * AT_C); }
  }
#pragma unroll 1
  for (int h = 0; h < 2; h++) {
    float m0 = -INFINITY, m1 = -INFINITY, l0 = 0.f, l1 = 0.f;
#pragma unroll
    for (int i = 0; i < 32; i++) o[i] = 0.f;
#pragma unroll 1
    for (int k0 = 0; k0 <= row0; k0 += 16) {
      float e[8] = {0.f, 0.f, 0.f, 0.f, 0.f, 0.f, 0.f, 0.f};
      const uint32_t* kp = reinterpret_cast<const uint32_t*>(g_kv + (size_t)(k0 + r) * NQ + head * HD) + c;
#pragma unroll
      for (int kk = 0; kk < 8; kk++) {
        mma16816(e, q[4 * kk], q[4 * kk + 1], q[4 * kk + 2], q[4 * kk + 3], ld_word(kp + 8 * kk), ld_word(kp + 8 * kk + 4));
        mma16816(e + 4, q[4 * kk], q[4 * kk + 1], q[4 * kk + 2], q[4 * kk + 3], ld_word(kp + 8 * kk + 4 * NQ), ld_word(kp + 8 * kk + 4 * NQ + 4));
      }
      if (k0 == row0) {
#pragma unroll
        for (int i = 0; i < 8; i++) if ((i >> 2) * 8 + 2 * c + (i & 1) > r + (i & 2) * 4) e[i] = -INFINITY;
      }
      float a0 = fmaxf(fmaxf(e[0], e[1]), fmaxf(e[4], e[5])), a1 = fmaxf(fmaxf(e[2], e[3]), fmaxf(e[6], e[7]));
      a0 = fmaxf(a0, __shfl_xor_sync(~0u, a0, 1)); a1 = fmaxf(a1, __shfl_xor_sync(~0u, a1, 1));
      a0 = fmaxf(a0, __shfl_xor_sync(~0u, a0, 2)); a1 = fmaxf(a1, __shfl_xor_sync(~0u, a1, 2));
      a0 = fmaxf(a0, m0); a1 = fmaxf(a1, m1);
      const float sc0 = ex2(m0 - a0), sc1 = ex2(m1 - a1);
      m0 = a0; m1 = a1;
#pragma unroll
      for (int i = 0; i < 8; i++) e[i] = ex2(e[i] - ((i & 2) ? m1 : m0));
      l0 = l0 * sc0 + (e[0] + e[1]) + (e[4] + e[5]);
      l1 = l1 * sc1 + (e[2] + e[3]) + (e[6] + e[7]);
      const uint32_t p0 = pack_bf16(e[0], e[1]), p1 = pack_bf16(e[2], e[3]), p2 = pack_bf16(e[4], e[5]), p3 = pack_bf16(e[6], e[7]);
      const __nv_bfloat16* vp = g_kv + (size_t)(SEQ + k0 + 2 * c) * NQ + head * HD + 64 * h + r;
#pragma unroll
      for (int n = 0; n < 8; n++) {
        o[4 * n] *= sc0; o[4 * n + 1] *= sc0; o[4 * n + 2] *= sc1; o[4 * n + 3] *= sc1;
        mma16816(o + 4 * n, p0, p1, p2, p3, ld_pair(vp + 8 * n), ld_pair(vp + 8 * n + 8 * NQ));
      }
    }
    l0 += __shfl_xor_sync(~0u, l0, 1); l1 += __shfl_xor_sync(~0u, l1, 1);
    l0 += __shfl_xor_sync(~0u, l0, 2); l1 += __shfl_xor_sync(~0u, l1, 2);
#pragma unroll
    for (int i = 0; i < 4; i++) {
      const float* v = o + 16 * (i >> 1) + 2 * (i & 1);
      const float f = __fdividef(1.f, (i & 1) ? l1 : l0);
      *reinterpret_cast<uint4*>(g_ctx + (size_t)(row0 + r + (i & 1) * 8) * NQ + head * HD + 64 * h + (i >> 1) * 32 + c * 8) =
          make_uint4(pack_bf16(v[0] * f, v[1] * f), pack_bf16(v[4] * f, v[5] * f), pack_bf16(v[8] * f, v[9] * f), pack_bf16(v[12] * f, v[13] * f));
    }
  }
}

constexpr int UNIT = 16384, SLOT = 32768;
constexpr int OFF_SIDE = 2 * SLOT;
__host__ __device__ constexpr int kv_a(int kb) { return (kb < 6 ? kb : 3 * kb - 10) * UNIT; }
__host__ __device__ constexpr int kv_b(int s) { return (s == 2 ? 6 : 9 + 3 * s) * UNIT; }
__host__ __device__ constexpr int q_aw(int s) { return (3 * s + (s & 1)) * UNIT; }
__host__ __device__ constexpr int q_b(int s) { return (3 * s + 2 - 2 * (s & 1)) * UNIT; }
__host__ __device__ constexpr int k_slot(int j, int r) { return (j < 2 ? 2 * j : (r == 2 ? 0 : 3 + r)) * SLOT; }
__host__ __device__ constexpr int v_slot(int j) { return (6 - (j & 1)) * SLOT; }
__host__ __device__ constexpr int r3(int st) { return ((0x654130 >> (4 * st)) & 7) * SLOT; }
constexpr int OFF_BAR = 229376;
constexpr int OFF_MISC = OFF_BAR + 512;
constexpr int SMEM_BYTES = OFF_MISC + 2080 + TL_EXTRA;
constexpr int OFF_RSTAT = OFF_MISC + 1056;
enum : int {
  B_FULL1 = 0, B_FULLQ = 3, B_FULLB = 7, B_KF = 8, B_VF = 11, B_FULL3 = 13, B_WF = 19, B_DEP = 21, B_OUT2 = 26, B_PF = 27, B_SET = 28,
  B_SET2 = 29, B_LNGO = 30, B_WR = 31,
  B_KE = 32, B_VE = 35, B_WE = 37, B_PUB = 39, B_OUT = 45,
  B_EMPTY1 = 46, B_EMPTYQ = 49, B_X = 53, B_EMPTY3 = 57,
  B_NUM = 63
};
#define TUNABLE(name, v) constexpr int name = v
TUNABLE(LN_GO, 3);
TUNABLE(EP1, 3);
TUNABLE(SIDE_NS, 400);
TUNABLE(SET_KB, 44); TUNABLE(SET_NS, 40);
TUNABLE(PF_KB, 54); TUNABLE(PF_N, 7); TUNABLE(PF_NS, 300);
TUNABLE(PS_DLY, 120); TUNABLE(Y_DLY, 700); TUNABLE(Y_DLY0, 1500);
constexpr int PRE = 3;
constexpr int WIN = 6;
constexpr int OFF_STG = r3(0), OFF_SCR = r3(1);
struct Params {
  CUtensorMap xn, ckv, wq, wk, wv, kv_ld, ctx_ld, wo, x, wd, wg, wu;
};

__global__ void __cluster_dims__(2, 1, 1) __launch_bounds__(384, 1)
fused_kernel(uint32_t zero, const __nv_bfloat16* __restrict__ x, __nv_bfloat16* g_kv, __nv_bfloat16* g_ctx, uint4* g_xr,
             __nv_bfloat16* __restrict__ out, __nv_bfloat16* g_xn, unsigned* g_cnt, const __nv_bfloat16* __restrict__ w_r,
             const __nv_bfloat16* __restrict__ wdown, const __nv_bfloat16* __restrict__ wq, const __grid_constant__ Params p) {
  extern __shared__ __align__(1024) uint8_t sp[];
  const uint32_t sb = s2u(sp);
  const uint32_t bar = sb + OFF_BAR;
  auto B = [&](int i) { return bar + 8 * i; };
  const int tid = threadIdx.x, warp = __shfl_sync(~0u, tid >> 5, 0), wg = warp >> 2, lane = tid & 31;
  const int cta = blockIdx.x, rank = cta & 1, cl = cta >> 1;
  const int mp = cl < 4 ? 1 : (cl < 36 ? (cl & 7) : (0x3207654 >> (4 * ((cl - 36) % 7))) & 7);
  const int gq = cl < 4 ? 4 + cl : (cl < 36 ? (cl - 4) >> 3 : 4 + (cl - 36) / 7);
  const int mt = 2 * mp + rank;
  const int qa = 15 - gq;
  const int ta = gq ? gq : 15, tb = 15 - ta;
  const int rid = mt * 8 + gq;
  const int fid = mt * 7 + gq;
  const bool ffn = gq < 7;
  TL(0, 0, warp == 4);
  auto load_pre = [&](int kb) {
    e_expect(B(B_FULL1 + kb), 3 * UNIT);
    tma_ld2(sb + kv_a(kb), &p.ckv, B(B_FULL1 + kb), kb * 64, mt * 128);
    tma_ld3(sb + kv_b(kb) + rank * UNIT, &p.wk, B(B_FULL1 + kb), 0, kb * 64, (gq + 8) * 4 + rank * 2);
    tma_ld3(sb + kv_b(kb) + UNIT - rank * UNIT, &p.wk, B(B_FULL1 + kb), 0, kb * 64, (gq + 8) * 4 + 2 - rank * 2);
  };
  if (warp == 0) {
    e_init(B(B_FULL1), 1);
    asm volatile("fence.mbarrier_init.release.cluster;" ::: "memory");
    TL(0, 16, true);
    load_pre(0);
    TL(0, 17, true);
#pragma unroll
    for (int kb = 1; kb < PRE; kb++) e_init(B(B_FULL1 + kb), 1);
  } else {
#pragma unroll 1
    for (int i = PRE - 1 + warp; i < B_NUM; i += 11) e_init(B(i), i >= B_EMPTY1 ? 16 : (i >= B_KE ? 8 : (i == B_WR ? 2 : 1)));
  }
  asm volatile("fence.mbarrier_init.release.cluster;" ::: "memory");
  cluster_arrive();
  const int rid0 = rid, warp0 = warp;
  if (wg == 0) {
    reg_dealloc<40>();
    if (warp == 0) {
      TL(0, 12, true);
#pragma unroll 1
      for (int kb = 1; kb < PRE; kb++) { load_pre(kb); TL(0, 12 + kb, true); }
      if (mt >= 2 * PRE) tma_pf3(&p.wk, 0, (mt >> 1) * 64, (gq + 8) * 4 + (mt & 1) * 2);
      if (gq >= PRE) tma_pf2(&p.ckv, gq * 64, mt * 128);
      TL(0, 15, true);
    }
    TL(0, 18, warp == 0);
    __syncwarp();
    cluster_wait();
    uint4* const xr = g_xr + rid * XR_SIZE;
    auto side_piece = [&](int c, int piece) {
      const uint32_t fb = B(B_WF + (c & 1));
      if (piece == 0) e_expect(fb, UNIT);
      tma_ld2_ef(sb + OFF_SIDE + (c & 1) * UNIT + piece * 4096, (piece & 2) ? &p.wg : &p.wu, fb, fid * 32, c * 128 + (piece & 1) * 64);
    };
    if (warp == 0) {
      {
        int st = 0; uint32_t ph = 1;
#pragma unroll 1
        for (int i = 0; i < 32; i++) {
          const int t = i >> 3, kb = i & 7;
          if (i >= PRE) {
            const uint32_t fb = B(B_FULL1 + st);
            mbar_wait_c(B(B_EMPTY1 + st), ph);
            e_expect(fb, t == 0 ? 3 * UNIT : 2 * UNIT);
            if (t == 0) tma_ld2(sb + kv_a(kb), &p.ckv, fb, kb * 64, mt * 128);
            tma_ld3_mc(sb + kv_b(st) + rank * UNIT, (t & 1) ? &p.wv : &p.wk, fb, 0, kb * 64, (gq + ((t >> 1) ^ 1) * 8) * 4 + rank * 2, 3);
          }
          if (i == LN_GO) e_arrive(B(B_LNGO));
          if (i == 12) { prefetch_tm(&p.wq); prefetch_tm(&p.xn); prefetch_tm(&p.kv_ld); }
          if (kb == (t ? 0 : 4) && t < 3) tma_pf3((t & 1) ? &p.wk : &p.wv, 0, (mt >> 1) * 64, (gq + (((t + 1) >> 1) ^ 1) * 8) * 4 + (mt & 1) * 2);
          if (kb < 2 && t == 3) tma_pf3(&p.wq, 0, (gq + 8 * kb) * 64, mt * 2);
          if (++st == 3) { st = 0; ph ^= 1; }
        }
        prefetch_tm(&p.ctx_ld); prefetch_tm(&p.wo); prefetch_tm(&p.wd); prefetch_tm(&p.x); prefetch_tm(&p.wg); prefetch_tm(&p.wu);
        mbar_wait_c(B(B_DEP + 0), 0);
        uint32_t kpar = 7, vpar = 3;
        auto load_aw = [&](int kb, int head) {
          const uint32_t d = sb + q_aw(kb & 3), fb = B(B_FULLQ + (kb & 3));
          tma_ld2_mc(d + rank * 8192, &p.xn, fb, kb * 64, ta * 128 + rank * 64, 3);
          tma_ld3(d + UNIT, &p.wq, fb, 0, kb * 64, head * 2);
        };
        auto load_b = [&](int kb, uint32_t fb) { tma_ld2_mc(sb + q_b(kb & 3) + rank * 8192, &p.xn, fb, kb * 64, tb * 128 + rank * 64, 3); };
        auto load3 = [&](int kb, int s) {
          const uint32_t d = sb + r3(s), fb = B(B_FULL3 + s);
          e_expect(fb, SLOT);
          tma_ld2(d, &p.ctx_ld, fb, kb * 64, mt * 128);
          tma_ld3_mc(d + UNIT + rank * 8192, &p.wo, fb, 0, kb * 64, gq * 2 + rank, 3);
        };
#pragma unroll 1
        for (int half = 0; half < 2; half++) {
          const int head = mt + 16 * half;
#pragma unroll 1
          for (int kb = 2 * half; kb < 16; kb++) {
            if (kb >= 4) mbar_wait_c(B(B_EMPTYQ + (kb & 3)), ((kb >> 2) & 1) ^ 1);
            else if (half) mbar_wait_c(B(B_X + 2), 0);
            else if (kb > 0) mbar_wait_c(B(B_EMPTY1 + (kb + 1) % 3), kb == 1);
            e_expect(B(B_FULLQ + (kb & 3)), 3 * UNIT);
            load_aw(kb, head);
            load_b(kb, B(B_FULLQ + (kb & 3)));
          }
          mbar_wait_c(B(B_DEP + 1 + half), 0);
          tma_pf3(&p.kv_ld, 0, 0, head * 2);
          auto load_v = [&](int j) {
            const int r = j & 1;
            mbar_wait_c(B(B_VE + r), (vpar >> r) & 1);
            vpar ^= 1 << r;
            e_expect(B(B_VF + r), SLOT);
            tma_ld3(sb + v_slot(j), &p.kv_ld, B(B_VF + r), 0, SEQ + (j > qa ? 16 - j : j) * 128, head * 2);
          };
          int r = 0;
#pragma unroll 1
          for (int j = 0; j < 17; j++) {
            if (j < 2) mbar_wait_c(B(B_EMPTYQ + j), 1);
            if (j == 2) mbar_wait_c(B(B_KE), kpar & 1);
            mbar_wait_c(B(B_KE + r), (kpar >> r) & 1);
            kpar ^= 1 << r;
            e_expect(B(B_KF + r), SLOT);
            tma_ld3(sb + k_slot(j, r), &p.kv_ld, B(B_KF + r), 0, (j > qa ? 16 - j : j) * 128, head * 2);
            if (++r == 3) r = 0;
            if (j == 2) mbar_wait_c(B(B_EMPTYQ + 3), 1);
            if (j != 1) load_v(j ? j - 1 : 0);
            if (half == 0) {
              if (j == 16) {
                tma_pf3(&p.wq, 0, (4 + gq) * 64, (mt + 16) * 2);
                tma_pf2(&p.xn, (4 + (mp & 3)) * 64, ((mp & 4) ? qa : gq) * 128 + rank * 64);
              }
            } else if (j >= 14) {
              tma_pf3(&p.wo, 0, (5 + mp + 8 * (16 - j)) * 64, gq * 2 + rank);
            } else if (ffn && j >= 5 && j < 13) {
              side_piece((j - 5) >> 2, (j - 5) & 3);
            }
          }
          mbar_wait_c(B(B_X + 0), half);
          if (half == 0) {
            for (int kb = 0; kb < 2; kb++) { e_expect(B(B_FULLQ + kb), 2 * UNIT); load_aw(kb, mt + 16); }
          } else {
            mbar_wait_c(B(B_DEP + 3), 0);
            load3(0, 0);
          }
          mbar_wait_c(B(B_X + 1), half);
          if (half) load3(1, 1);
          load_v(16);
          if (gq == 0) mbar_wait_c(B(B_X + 2), half);
          if (half == 0) { e_expect(B(B_FULLB), 2 * UNIT); load_b(0, B(B_FULLB)); load_b(1, B(B_FULLB)); }
        }
        st = 2; ph = 1;
#pragma unroll 1
        for (int kb = 2; kb < 64; kb++) {
          if (kb == 32) mbar_wait_c(B(B_DEP + 4), 0);
          if (kb >= 6) mbar_wait_c(B(B_EMPTY3 + st), ph);
          else if (kb == 3 || kb == 5) mbar_wait_c(B(B_X + (kb + 1) / 2), 1);
          load3(kb, st);
          if (++st == 6) { st = 0; ph ^= 1; }
          if (kb == PF_KB) e_arrive(B(B_PF));
          if (kb == SET_KB) e_arrive(B(B_SET));
          if (kb == 58) l2_prefetch(xr, XR_CAND * 16);
        }
        if (ffn) {
#pragma unroll 1
          for (int j = 0; j < 2; j++) {
            mbar_wait_c(B(B_EMPTY3 + 4 + j), 1);
            e_expect(B(B_FULL3 + 4 + j), SLOT);
            tma_ld3(sb + r3(4 + j), &p.wd, B(B_FULL3 + 4 + j), 0, fid * 32, 8 * j);
          }
        }
        const uint4* kp = g_xr + ((lane >> 1) * 8 + gq) * XR_SIZE + XR_KEY + (lane & 1) * 2;
        mbar_wait_c(B(B_OUT), 0);
        uint4 kv[2];
        poll_chunks(kv, kp, 1);
        const uint32_t a1 = max(kv[0].x, kv[0].z), a2 = max(min(kv[0].x, kv[0].z), max(kv[0].y, kv[0].w));
        const uint32_t b1 = max(kv[1].x, kv[1].z), b2 = max(min(kv[1].x, kv[1].z), max(kv[1].y, kv[1].w));
        const uint32_t k1 = max(a1, b1), k2 = max(min(a1, b1), max(a2, b2));
        const uint32_t m1 = __reduce_max_sync(~0u, k1);
        const uint32_t m2 = __reduce_max_sync(~0u, k1 == m1 ? k2 : k1);
        const uint32_t t0 = ~m1 & 0x7FFF, t1 = ~m2 & 0x7FFF;
        const uint32_t o0 = (t0 >> 7) * (8 * XR_SIZE * 16) + (t0 & 0x70) * 64, o1 = (t1 >> 7) * (8 * XR_SIZE * 16) + (t1 & 0x70) * 64 + ((t0 ^ t1) < 16 ? 256 : 0);
        asm volatile(ELECT "st.shared.v4.u32 [%0], {%1,%2,%3,%4};\n}" ::"r"(sb + OFF_MISC), "r"(o0), "r"(o1), "r"(m1), "r"(m2) : "memory");
        e_arrive(B(B_OUT2));
        if (rid == 127) { g_cnt[lane] = 0; g_cnt[32 + lane] = 0; }
      }
    } else {
      if (warp >= 2) {
#pragma unroll 1
        for (int i = tid - 64; i < XR_CAND; i += 64) xr[i] = make_uint4(~0u, ~0u, ~0u, ~0u);
        if (warp == 2) { __syncwarp(); if (lane == 0) mbar_arrive(B(B_WR)); }
      }
      if (warp == 3) {
        float ws = 0.f;
#pragma unroll 1
        for (int j = 0; j < 4; j++) {
          const uint4 q = __ldg(reinterpret_cast<const uint4*>(w_r) + j * 32 + lane);
          ws += bf_lo(q.x) + bf_hi(q.x) + bf_lo(q.y) + bf_hi(q.y) + bf_lo(q.z) + bf_hi(q.z) + bf_lo(q.w) + bf_hi(q.w);
        }
#pragma unroll
        for (int o = 16; o; o >>= 1) ws += __shfl_xor_sync(~0u, ws, o);
        uint2* tab = reinterpret_cast<uint2*>(sp + OFF_MISC + 512);
        tab[lane] = make_uint2(0x3F803F80u, 0x3F803F80u);
        tab[32 + lane] = __ldg(reinterpret_cast<const uint2*>(w_r + gq * 128) + lane);
        if (lane == 0) *reinterpret_cast<float*>(sp + OFF_MISC + 1024) = ws;
        __syncwarp();
        if (lane == 0) mbar_arrive(B(B_WR));
      }
      __syncwarp();
      mbar_wait_u(B(B_LNGO), 0);
#pragma unroll 1
      for (int r = warp == 2 ? 0 : (warp + 1) >> 1; r < 16; r += 3) {
        const uint4* src = reinterpret_cast<const uint4*>(x + (size_t)(cta * 16 + r) * DM) + lane;
        uint4 v[4];
#pragma unroll
        for (int j = 0; j < 4; j++) v[j] = __ldcs(src + j * 32);
        float a0 = 0.f, a1 = 0.f, b0 = 0.f, b1 = 0.f;
#pragma unroll
        for (int j = 0; j < 4; j++) {
          const uint32_t u[4] = {v[j].x, v[j].y, v[j].z, v[j].w};
#pragma unroll
          for (int i = 0; i < 4; i++) { const float a = bf_lo(u[i]), b = bf_hi(u[i]); a0 += a; a1 += b; b0 = fmaf(a, a, b0); b1 = fmaf(b, b, b1); }
        }
        a0 += a1; b0 += b1;
#pragma unroll
        for (int o = 16; o; o >>= 1) { a0 += __shfl_xor_sync(~0u, a0, o); b0 += __shfl_xor_sync(~0u, b0, o); }
        const float mean = a0 * (1.f / DM);
        float mb, inv;
        ln_round(mean, fmaxf(fmaf(b0, 1.f / DM, -mean * mean), 0.f), mb, inv);
        const uint32_t nm2 = pack_bf16(-mb, -mb);
        uint4* dst = reinterpret_cast<uint4*>(g_xn + (size_t)(cta * 16 + r) * DM) + lane;
#pragma unroll
        for (int j = 0; j < 4; j++) {
          dst[j * 32] = make_uint4(ln_apply(v[j].x, nm2, inv), ln_apply(v[j].y, nm2, inv), ln_apply(v[j].z, nm2, inv), ln_apply(v[j].w, nm2, inv));
          sched_fence();
        }
      }
      __syncwarp();
      if (lane == 0) {
        fence_gpu();
        red_add(&g_cnt[C_LN + (cta >> 3)], 1);
        TL(0, 20 + warp, true);
        if (warp == 3) {
          spin_until_ge<true>(&g_cnt[C_LN + gq], 24);
#pragma unroll 1
          for (int i = 0; i < 5; i++) {
            const int c = i == 0 ? C_LN + qa : (i < 3 ? C_KV + (i - 1) * 8 + mp : C_CTX + (i - 3) * 16 + mt);
            spin_until_ge<true>(&g_cnt[c], i == 0 ? 24 : 16);
            fence_async_all();
            mbar_arrive(B(B_DEP + i));
          }
        } else if (warp == 1) {
          mbar_wait(B(B_WR), 0);
#pragma unroll 1
          for (int i = 0; i < 6; i++) {
            const int c = i < 2 ? C_KV + gq + (i ^ 1) * 8 : C_CTX + ((i - 2) >> 1) * 16 + ((i & 1) ? tb : ta);
            mbar_wait(B(B_PUB + i), 0);
            fence_gpu();
            red_add(&g_cnt[c], 1);
          }
        }
      }
      __syncwarp();
      if (warp == 2) {
#pragma unroll 1
        for (int c = 2; c < WIN + 4; c++) {
          mbar_wait_u(B(B_WE + (c & 1)), ((c >> 1) & 1) ^ 1);
          if (c == WIN || c == WIN + 1) {
            e_expect(B(B_WF + (c & 1)), UNIT);
            tma_ld3_ef(sb + OFF_SIDE + (c & 1) * UNIT, &p.x, B(B_WF + (c & 1)), 0, mt * 128 + (c & 1) * 64, gq * 2);
          } else if (ffn) {
#pragma unroll 1
            for (int i = 0; i < 4; i++) { side_piece(c < WIN ? c : c - 2, i); __nanosleep(SIDE_NS); }
          }
        }
      } else if (warp == 1) {
        mbar_wait_u(B(B_SET), 0);
#pragma unroll 1
        for (int i = XR_CAND + lane; i < XR_SIZE; i += 32) { xr[i] = make_uint4(~0u, ~0u, ~0u, ~0u); __nanosleep(SET_NS); }
        __syncwarp();
        if (lane == 0) { fence_gpu(); mbar_arrive(B(B_SET2)); }
      } else {
        mbar_wait_u(B(B_PF), 0);
#pragma unroll 1
        for (int i = 0; i < PF_N; i++) {
          asm volatile("prefetch.global.L2 [%0];" ::"l"((const char*)wdown + (size_t)cta * 57344 + (i * 32 + lane) * 128));
          __nanosleep(PF_NS);
        }
      }
      __syncwarp();
      mbar_wait_u(B(B_OUT), 0);
      {
        const int sub = lane >> 4;
        const uint32_t src = sb + OFF_STG + ((lane & 15) >> 3) * 8192 + sub * 128;
        __nv_bfloat16* dst = out + (size_t)(mt * 128 + sub) * DM + gq * 128 + (lane & 15) * 8;
        auto ld = [&](int r, uint2& rs, uint4& v) {
          asm volatile("ld.shared.v2.u32 {%0,%1}, [%2];" : "=r"(rs.x), "=r"(rs.y) : "r"(sb + OFF_RSTAT + ((r + sub) & 127) * 8));
          v = lds128(src + ((r >> 6) & 1) * 16384 + (r & 63) * 128 + (((lane ^ (r + sub)) & 7) << 4));
        };
        uint2 rs; uint4 v;
        ld(2 * warp - 2, rs, v);
#pragma unroll 1
        for (int r = 2 * warp - 2; r < 128; r += 6) {
          const uint2 cs = rs; const uint4 c = v;
          ld(r + 6, rs, v);
          const float inv = __uint_as_float(cs.y);
          asm volatile("{\n.reg .pred p;\nsetp.ge.s32 p, %5, 0;\n@p st.global.v4.u32 [%0], {%1,%2,%3,%4};\n}" ::"l"(dst + (size_t)r * DM),
                       "r"(hadd2_bf(c.x, ln_apply(c.x, cs.x, inv))), "r"(hadd2_bf(c.y, ln_apply(c.y, cs.x, inv))),
                       "r"(hadd2_bf(c.z, ln_apply(c.z, cs.x, inv))), "r"(hadd2_bf(c.w, ln_apply(c.w, cs.x, inv))), "r"(cs.y) : "memory");
        }
      }
      TL(2, 25, warp == 1);
    }
    __syncwarp();
    cluster_arrive();
    cluster_wait();
  } else {
    reg_alloc<232>();
    const int rid_c = rid0 + zero, warp_c = warp0 + zero;
    const int lane = fresh_lane(), rid = rid_c, mt = rid >> 3, gq = rid & 7, qa = 15 - gq, ta = gq ? gq : 15, tb = 15 - ta;
    const int warp = warp_c, cw = warp - 4, w = cw >> 2;
    cluster_wait();
    auto publish = [&](int i) { __syncwarp(); e_arrive(B(B_PUB + i)); };
    auto release2 = [&](uint32_t b, bool cond = true) { mbar_arrive_both(b, lane, cond); };
    AtState s;
    const uint32_t dA = mk_desc(sb + w * 8192, 16);
    const uint32_t dW = mk_desc(sb, 8192);
    auto mma_kb = [&](float (&d)[64], uint32_t a, uint32_t b, int accum) {
      static_for<4>([&](auto k) { mma_n128_ss<1, k * 32, k * 2048>(d, dA + (a >> 4), dW + (b >> 4), k == 0 ? accum : 1); });
    };
    auto mma_kc = [&](float (&d)[64], auto a, auto b, int accum) {
      static_for<4>([&](auto k) { mma_n128_ss<1, decltype(a)::value + k * 32, decltype(b)::value + k * 2048>(d, dA, dW, k == 0 ? accum : 1); });
    };
    auto issue_q = [&](int kb, auto accum) {
      const int st = kb & 3;
      mbar_wait_c(B(B_FULLQ + st), (kb >> 2) & 1);
      wg_fence();
      mma_kb(s.S, q_aw(st), q_aw(st) + UNIT, accum);
      wg_commit();
      if (accum) {
        wg_wait<1>();
        release2(B(B_EMPTYQ + ((kb - 1) & 3)));
        wg_fence();
      }
      mma_kb(s.O, q_b(st), q_aw(st) + UNIT, accum);
      wg_commit();
    };
    {
      uint4 pk[16];
      __nv_bfloat16* pdst = g_kv;
      auto put = [&](int i) { __stcs(reinterpret_cast<uint4*>(pdst + (i & 1) * 8 * NQ + (i >> 1) * 32), pk[i]); };
      float acc1[128];
      TL(0, 1, warp == 4);
      int st = 0; uint32_t ph = 0;
      auto issue = [&](int kb, int accum) {
        mbar_wait_c(B(B_FULL1 + st), ph);
        wg_fence();
        static_for<4>([&](auto k) { mma_n256_ss<1, k * 32, k * 2048>(acc1, dA + (kv_a(kb) >> 4), dW + (kv_b(st) >> 4), k == 0 ? accum : 1); });
        wg_commit();
      };
#pragma unroll 1
      for (int t = 0; t < 4; t++) {
        issue(0, 0);
        TL(0, 2 + 2 * t, warp == 4);
        if (t > 0) { put(0); put(1); }
        int prev = st;
        if (++st == 3) { st = 0; ph ^= 1; }
#pragma unroll 1
        for (int kb = 1; kb < 8; kb++) {
          if (kb == 7 && w == 1) bar_sync(5, 256);
          issue(kb, 1);
          if (kb == 7 && w == 0) bar_arrive(5, 256);
          if (t > 0) {
#pragma unroll
            for (int i = 1; i < 8; i++) if (kb == i) { put(2 * i); put(2 * i + 1); }
            if (kb == 7 && t == 2) publish(0);
          }
          wg_wait<1>();
          TK(24 + t * 8 + kb - 1);
          release2(B(B_EMPTY1 + prev));
          prev = st;
          if (++st == 3) { st = 0; ph ^= 1; }
        }
        pdst = g_kv + (size_t)((t & 1) * SEQ + mt * 128 + cw * 16 + (lane >> 2)) * NQ + (gq + ((t >> 1) ^ 1) * 8) * 256 + (lane & 3) * 8;
        wg_wait<0>();
        TK(24 + t * 8 + 7);
        fence_regs(acc1);
        release2(B(B_EMPTY1 + prev));
        TL(0, 3 + 2 * t, warp == 4);
#pragma unroll
        for (int a = 0; a < 8; a++)
#pragma unroll
          for (int h = 0; h < 2; h++)
            pk[2 * a + h] = make_uint4(pack_bf16(acc1[16 * a + 2 * h], acc1[16 * a + 2 * h + 1]), pack_bf16(acc1[16 * a + 4 + 2 * h], acc1[16 * a + 5 + 2 * h]),
                                       pack_bf16(acc1[16 * a + 8 + 2 * h], acc1[16 * a + 9 + 2 * h]), pack_bf16(acc1[16 * a + 12 + 2 * h], acc1[16 * a + 13 + 2 * h]));
      }
      issue_q(0, IC<0>{});
      TL(0, 10, warp == 4);
      put(0); put(1);
#pragma unroll 1
      for (int kb = 1; kb < 8; kb++) {
        issue_q(kb, IC<1>{});
        TK(66 + kb - 1);
#pragma unroll
        for (int i = 1; i < 8; i++) if (kb == i) { put(2 * i); put(2 * i + 1); }
      }
      publish(1);
      TL(0, 11, warp == 4);
    }
    __nv_bfloat16* cdst;
    uint32_t redo = 0;
    auto put_ctx = [&](int i, bool cond) {
      asm volatile("{\n.reg .pred p;\nsetp.ne.u32 p, %5, 0;\n@p st.global.cs.v4.u32 [%0], {%1,%2,%3,%4};\n}" ::"l"(cdst + (i & 1) * 8 * NQ + (i >> 1) * 32),
                   "r"(s.P[4 * i]), "r"(s.P[4 * i + 1]), "r"(s.P[4 * i + 2]), "r"(s.P[4 * i + 3]), "r"((uint32_t)(cond && !(redo & 2))) : "memory");
    };
    {
      const int wrow = cw * 16;
      const uint32_t dK = mk_desc(sb, 16), dV = mk_desc(sb, 16384);
      uint32_t kph = 0, vph = 0;
      auto q_store = [&](const float (&d)[64]) {
        const int r0 = lane >> 2;
        const uint32_t a = sb + SLOT + (wrow + r0) * 128 + (((lane & 3) ^ (((r0 & 1) << 2) | (r0 >> 1))) << 4);
#pragma unroll
        for (int i = 0; i < 8; i++) {
          const float* o = d + 16 * (i >> 1) + 2 * (i & 1);
          asm volatile("st.shared.v4.u32 [%0], {%1,%2,%3,%4};" ::"r"((a ^ ((i & 2) << 5)) + (i >> 2) * UNIT + (i & 1) * 1024),
                       "r"(pack_bf16(o[0] * AT_C, o[1] * AT_C)), "r"(pack_bf16(o[4] * AT_C, o[5] * AT_C)),
                       "r"(pack_bf16(o[8] * AT_C, o[9] * AT_C)), "r"(pack_bf16(o[12] * AT_C, o[13] * AT_C)) : "memory");
        }
        __syncwarp();
      };
      auto q_load = [&](auto k0, auto k1) {
        const uint32_t a = sb + SLOT + (wrow + (lane & 15)) * 128 + (((lane >> 4) ^ (((lane & 1) << 2) | ((lane >> 1) & 3))) << 4);
#pragma unroll
        for (int k = k0; k < k1; k++)
          asm volatile("ldmatrix.sync.aligned.m8n8.x4.shared.b16 {%0,%1,%2,%3}, [%4];"
                       : "=r"(s.Q[4 * k]), "=r"(s.Q[4 * k + 1]), "=r"(s.Q[4 * k + 2]), "=r"(s.Q[4 * k + 3]) : "r"((a ^ ((k & 3) << 5)) + (k >> 2) * UNIT) : "memory");
      };
      auto q_load_if = [&](auto k, bool cond, float after) {
        const uint32_t a = sb + SLOT + (wrow + (lane & 15)) * 128 + (((lane >> 4) ^ (((lane & 1) << 2) | ((lane >> 1) & 3))) << 4);
        asm volatile("{\n.reg .pred p;\nsetp.ne.u32 p, %5, 0;\n@p ldmatrix.sync.aligned.m8n8.x4.shared.b16 {%0,%1,%2,%3}, [%4];\n}"
                     : "+r"(s.Q[4 * k]), "+r"(s.Q[4 * k + 1]), "+r"(s.Q[4 * k + 2]), "+r"(s.Q[4 * k + 3])
                     : "r"((a ^ ((k & 3) << 5)) + (k >> 2) * UNIT + (__float_as_uint(after) >> 31)), "r"((uint32_t)cond) : "memory");
      };
      auto issue_s = [&](uint32_t dk) {
        mma_n128_rs0<0>(s.S, s.Q, dk);
        static_for<7>([&](auto i) { constexpr int k = i + 1; mma_n128_rs<0, (k >> 2) * 16384 + (k & 3) * 32>(s.S, s.Q + 4 * k, dk, 1); });
        wg_commit();
      };
      auto wait_v = [&](int jv) {
        mbar_wait_c(B(B_VF + (jv & 1)), (vph >> (jv & 1)) & 1);
        vph ^= 1 << (jv & 1);
      };
      auto issue_pva = [&](int jv, int accum) {
        wg_fence();
        static_for<4>([&](auto k) { mma_n128_rs<1, k * 2048>(s.O, s.P + 4 * k, dV + (v_slot(jv) >> 4), k == 0 ? accum : 1); });
        wg_commit();
      };
      auto issue_pvb = [&](int jv, bool upper) {
        if (upper) {
          wg_fence();
          static_for<4>([&](auto k) { mma_n128_rs<1, (k + 4) * 2048>(s.O, s.P + 16 + 4 * k, dV + (v_slot(jv) >> 4), 1); });
          wg_commit();
        } else {
          asm volatile("wgmma.fence.sync.aligned;\nwgmma.commit_group.sync.aligned;" ::: "memory");
        }
      };
      auto issue_pv = [&](int jv, int accum, bool upper) { wait_v(jv); issue_pva(jv, accum); issue_pvb(jv, upper); };
      if (w == 1) bar_arrive(1, 256);
#pragma unroll 1
      for (int half = 0; half < 2; half++) {
        const int head = mt + 16 * half;
        redo = 0;
        float inv[2];
        auto ep_prep = [&]() {
          float l0 = s.l[0] + s.l[1], l1 = s.l[2] + s.l[3];
          l0 += __shfl_xor_sync(~0u, l0, 1); l1 += __shfl_xor_sync(~0u, l1, 1);
          l0 += __shfl_xor_sync(~0u, l0, 2); l1 += __shfl_xor_sync(~0u, l1, 2);
          asm("rcp.approx.ftz.f32 %0, %1;" : "=f"(inv[0]) : "f"(l0));
          asm("rcp.approx.ftz.f32 %0, %1;" : "=f"(inv[1]) : "f"(l1));
          return __any_sync(~0u, !(fminf(l0, l1) >= L_MIN && l0 + l1 <= L_MAX));
        };
        auto ep_out = [&](auto i0, auto i1) {
          __nv_bfloat16* dst = g_ctx + (size_t)(ta * 128 + wrow + (lane >> 2)) * NQ + head * 128 + (lane & 3) * 8;
#pragma unroll
          for (int i = i0; i < i1; i++) {
            const float* o = s.O + 16 * (i >> 1) + 2 * (i & 1);
            const float c = inv[i & 1];
            asm volatile("st.global.cs.v4.u32 [%0], {%1,%2,%3,%4};" ::"l"(dst + (i & 1) * 8 * NQ + (i >> 1) * 32), "r"(pack_bf16(o[0] * c, o[1] * c)),
                         "r"(pack_bf16(o[4] * c, o[5] * c)), "r"(pack_bf16(o[8] * c, o[9] * c)), "r"(pack_bf16(o[12] * c, o[13] * c)) : "memory");
          }
        };
        auto ep_rest = [&]() {
          ep_out(IC<EP1>{}, IC<8>{});
          if (!__any_sync(~0u, redo)) publish(2 + 2 * half);
          fence_regs(s.O);
        };
#pragma unroll 1
        for (int kb = 8; kb < 14; kb++) {
          issue_q(kb, IC<1>{});
          TK(66 + half * 24 + kb - 1);
        }
        TL(1, 20 * half + 0, warp == 4);
        mbar_wait_c(B(B_FULLQ + 2), 1);
        mbar_wait_c(B(B_FULLQ + 3), 1);
        bar_sync(1 + w, 256);
        wg_fence();
        mma_kc(s.S, IC<q_aw(2)>{}, IC<q_aw(2) + UNIT>{}, 1);
        wg_commit();
        wg_wait<1>();
        TK(66 + half * 24 + 13);
        release2(B(B_EMPTYQ + 1));
        wg_fence();
        mma_kc(s.S, IC<q_aw(3)>{}, IC<q_aw(3) + UNIT>{}, 1);
        wg_commit();
        bar_arrive(2 - w, 256);
        bar_sync(6 + w, 128);
        wg_wait<0>();
        TK(66 + half * 24 + 14);
        fence_regs(s.S);
        q_store(s.S);
        q_load(IC<0>{}, IC<8>{});
        TL(1, 20 * half + 1, warp == 4);
        TC(w, 17 * half, 0);
        mbar_wait_c(B(B_KF), kph & 1);
        kph ^= 1;
        bar_sync(1 + w, 256);
        TC(w, 17 * half, 2);
        fence_regs(s.O); fence_regs(s.Q);
        wg_fence();
        issue_s(dK);
        mma_kc(s.O, IC<q_b(2)>{}, IC<q_aw(2) + UNIT>{}, 1);
        mma_kc(s.O, IC<q_b(3)>{}, IC<q_aw(3) + UNIT>{}, 1);
        wg_commit();
        bar_arrive(2 - w, 256);
        wg_wait<1>();
        TC(w, 17 * half, 4);
        fence_regs(s.S);
        e_arrive(B(B_KE));
        s.l[0] = s.l[1] = s.l[2] = s.l[3] = 0.f;
        at_exp<0, 48>(s);
        at_pack<0, 22>(s);
        sched_fence();
        wg_wait<0>();
        fence_regs(s.O); fence_regs(s.Q);
        release2(B(B_EMPTYQ + 2)); release2(B(B_EMPTYQ + 3));
        at_exp<48, 64>(s);
        at_pack<22, 32>(s);
        q_store(s.O);
        TL(1, 20 * half + 2, warp == 4);
        int kr = 1;
        bool kok = false;
        inv[0] = inv[1] = 0.f;
        const int db = gq ? qa : 16;
#pragma unroll 1
        for (int j = 1; j < 17; j++) {
          const bool diag = j == ta || j == db;
          TC(w, j + 17 * half, 0);
          if (!kok) mbar_wait_c(B(B_KF + kr), (kph >> kr) & 1);
          kph ^= 1 << kr;
          if (j == ta + 2) ep_out(IC<0>{}, IC<EP1>{});
          bar_sync(1 + w, 256);
          TC(w, j + 17 * half, 2);
          fence_regs(s.O); fence_regs(s.P); fence_regs(s.Q);
          const uint32_t ke = B(B_KE + kr), dk = dK + (k_slot(j, kr) >> 4);
          if (++kr == 3) kr = 0;
          auto issue_rest = [&](auto trimmed) {
            TC(w, j + 17 * half, 1);
            if (j == ta + 1) {
              if (ep_prep()) redo = 1;
              s.l[0] = s.l[1] = s.l[2] = s.l[3] = 0.f;
            }
            if (!trimmed && j == ta + 2) ep_rest();
            TC(w, j + 17 * half, 3);
            issue_pv(j - 1, j != 1 && j != ta + 2, w == 1 || (j != ta + 1 && j != db + 1));
            bar_arrive(2 - w, 256);
          };
          auto s_done = [&](auto n) {
            wg_wait<2>();
            TC(w, j + 17 * half, 4);
            fence_part<0, n>(s.S); fence_regs(s.Q);
            e_arrive(ke);
            release2(B(B_X + j - 14), j == 14 || j == 15);
          };
          auto pv_half = [&]() { sched_fence(); wg_wait<1>(); fence_regs(s.P); };
          auto pv_done = [&]() {
            sched_fence();
            wg_wait<0>();
            fence_regs(s.O); fence_regs(s.P);
            e_arrive(B(B_VE + ((j - 1) & 1)));
            release2(B(B_X + 2), j == 16);
            kok = mbar_test(B(B_KF + kr), (kph >> kr) & 1);
          };
          if (diag && w == 0) {
            wg_fence();
            static_for<8>([&](auto k) { mma_n64_rs<0, (k >> 2) * 16384 + (k & 3) * 32, k != 0>(s.S, s.Q + 4 * k, dk); });
            wg_commit();
            issue_rest(IC<1>{});
            s_done(IC<32>{});
            at_mask<0>(s, wrow, lane);
            pv_half();
            static_for<8>([&](auto k) {
              at_exp<4 * k, 4 * k + 4>(s);
              q_load_if(k, j == ta, s.S[4 * k]);
            });
            at_pack<0, 16>(s);
            pv_done();
          } else {
            wg_fence();
            issue_s(dk);
            issue_rest(IC<0>{});
            if (!diag) {
              s_done(IC<64>{});
              at_exp<0, 24>(s);
              pv_half();
              at_exp<24, 48>(s);
              at_pack<0, 16>(s);
              pv_done();
              at_exp<48, 64>(s);
              at_pack<16, 32>(s);
            } else {
              s_done(IC<64>{});
              at_mask<8>(s, wrow - 64, lane);
              static_for<8>([&](auto k) {
                at_exp<7 * k, 7 * k + 7>(s);
                q_load_if(k, j == ta, s.S[7 * k + 3]);
                if (k == 2) pv_half();
                if (k == 5) { at_pack<0, 16>(s); pv_done(); }
              });
              at_exp<56, 64>(s);
              at_pack<16, 32>(s);
            }
          }
          TL(1, 20 * half + 2 + j, warp == 4);
        }
        TK(84 + half * 24);
        mbar_wait_c(B(half ? B_FULL3 : B_FULLQ), 0);
        if (gq == 0) ep_out(IC<0>{}, IC<EP1>{});
        bar_sync(1 + w, 256);
        fence_regs(s.O); fence_regs(s.P);
        wg_fence();
        mma_n128_ss0<1, 0, UNIT>(s.S, dA, dW);
        static_for<3>([&](auto k) { mma_n128_ss<1, k * 32 + 32, UNIT + k * 2048 + 2048>(s.S, dA, dW, 1); });
        mbar_wait_c(B(half ? B_FULL3 + 1 : B_FULLQ + 1), 0);
        wg_fence();
        mma_kb(s.S, (2 + half) * SLOT, (2 + half) * SLOT + UNIT, 1);
        wg_commit();
        TK(85 + half * 24);
        if (gq == 0) ep_rest();
        issue_pv(16, gq != 0, w == 1 || gq != 0);
        if (w == 0 || half == 0) bar_arrive(2 - w, 256);
        TK(86 + half * 24);
        wg_wait<2>();
        release2(B(B_EMPTY3), half); release2(B(B_EMPTY3 + 1), half);
        if (ep_prep()) redo |= 2;
        sched_fence();
        wg_wait<0>();
        TK(87 + half * 24);
        fence_regs(s.S);
        fence_regs(s.O);
        e_arrive(B(B_VE));
        release2(B(B_X + 3));
        fence_regs(s.P);
        {
          const int r = fresh_lane();
          cdst = g_ctx + (size_t)(tb * 128 + wrow + (r >> 2)) * NQ + head * 128 + (r & 3) * 8;
        }
#pragma unroll
        for (int i = 0; i < 32; i++) {
          const float* o = s.O + 16 * (i >> 3) + 2 * ((i >> 2) & 1) + 4 * (i & 3);
          s.P[i] = pack_bf16(o[0] * inv[(i >> 2) & 1], o[1] * inv[(i >> 2) & 1]);
        }
        fence_regs(s.P);
        if (__builtin_expect(__any_sync(~0u, redo != 0), 0)) {
#pragma unroll
          for (int i = 0; i < 8; i++) put_ctx(i, true);
#pragma unroll 1
          for (int t = 0; t < 2; t++) {
            if (__any_sync(~0u, (redo >> t) & 1)) slow_rows(wq, head, (t ? tb : ta) * 128 + wrow);
          }
          if (__any_sync(~0u, redo & 1)) publish(2 + 2 * half);
#pragma unroll
          for (int i = 0; i < 32; i++) s.P[i] = 0;
          redo = 2;
        }
        TL(1, 20 * half + 19, warp == 4);
        TK(88 + half * 24);
        if (half) break;
        mbar_wait_c(B(B_FULLB), 0);
        TK(89);
        wg_fence();
        mma_n128_ss0<1, q_b(0), UNIT>(s.O, dA, dW);
        static_for<3>([&](auto k) { mma_n128_ss<1, q_b(0) + k * 32 + 32, UNIT + k * 2048 + 2048>(s.O, dA, dW, 1); });
        wg_commit();
        mma_kc(s.O, IC<q_b(1)>{}, IC<q_aw(1) + UNIT>{}, 1);
        wg_commit();
        wg_wait<1>();
        release2(B(B_EMPTYQ));
        put_ctx(0, true);
#pragma unroll 1
        for (int kb = 2; kb < 8; kb++) {
          issue_q(kb, IC<1>{});
          TK(90 + kb - 1);
#pragma unroll
          for (int i = 1; i < 8; i++) put_ctx(i, kb == (i < 7 ? i + 1 : 7));
        }
        publish(3);
      }
    }
    const int rid_ = rid + zero, cw_ = cw + zero;
    {
    const int lane = fresh_lane(), rid = rid_, mt = rid >> 3, gq = rid & 7, cw = cw_, w = cw >> 2, ct = cw * 32 + lane;
    const int fid = mt * 7 + gq;
    const bool ffn = gq < 7;
    const uint32_t stg = sb + OFF_STG + w * 16384 + (cw & 3) * 2048;
    const int wr_ = w * 64 + (lane & 7) + (lane >> 4) * 8;
    const uint32_t wl = sb + ((lane >> 3) & 1) * 8192 + wr_ * 64 + (((cw ^ (wr_ >> 1)) & 3) << 4);
    __syncwarp();
    float (&acc)[64] = s.S;
    uint32_t wf[128];
    auto grab = [&](auto c, uint32_t off) {
#pragma unroll
      for (int m = 0; m < 4; m++)
        asm volatile("ldmatrix.sync.aligned.m8n8.x4.trans.shared.b16 {%0,%1,%2,%3}, [%4];"
                     : "=r"(wf[16 * c + 4 * m]), "=r"(wf[16 * c + 4 * m + 1]), "=r"(wf[16 * c + 4 * m + 2]), "=r"(wf[16 * c + 4 * m + 3])
                     : "r"(wl + off + m * 1024) : "memory");
    };
    const int r0 = lane >> 2;
    uint32_t hp[32], rt[16];
    {
      uint32_t dep = 0;
      auto hand = [&](uint32_t b, int n) {
        asm volatile("{\n.reg .pred p;\n.reg .b32 t;\nsetp.lt.u32 p, %1, %4;\nmad.lo.u32 t, %2, %3, %0;\n@p mbarrier.arrive.shared::cta.b64 _, [t];\n}"
                     ::"r"(b + 8 * lane), "r"(lane), "r"(dep), "r"(zero), "r"(n) : "memory");
      };
      auto kblock = [&](auto st, uint32_t ph, bool rel) {
        mbar_wait_c(B(B_FULL3 + st), ph);
        wg_fence();
        mma_kc(acc, IC<r3(st)>{}, IC<r3(st) + UNIT>{}, 1);
        wg_commit();
        wg_wait<1>();
        release2(B(B_EMPTY3 + (st + 5) % 6), rel);
      };
      auto ldsm_if = [&](uint32_t* r, uint32_t a, bool c, auto trans) {
        if (trans) asm volatile("{\n.reg .pred p;\nsetp.ne.u32 p, %5, 0;\n@p ldmatrix.sync.aligned.m8n8.x4.trans.shared.b16 {%0,%1,%2,%3}, [%4];\n}"
                                : "+r"(r[0]), "+r"(r[1]), "+r"(r[2]), "+r"(r[3]) : "r"(a), "r"((uint32_t)c) : "memory");
        else asm volatile("{\n.reg .pred p;\nsetp.ne.u32 p, %5, 0;\n@p ldmatrix.sync.aligned.m8n8.x4.shared.b16 {%0,%1,%2,%3}, [%4];\n}"
                          : "+r"(r[0]), "+r"(r[1]), "+r"(r[2]), "+r"(r[3]) : "r"(a), "r"((uint32_t)c) : "memory");
      };
#pragma unroll
      for (int i = 0; i < 48; i++) wf[i] = 0;
#pragma unroll 1
      for (int lap = 0; lap < 3; lap++) {
        kblock(IC<2>{}, lap & 1, lap > 0);
#pragma unroll
        for (int i = 0; i < 3; i++) put_ctx(3 * i, lap == i);
        kblock(IC<3>{}, lap & 1, true);
        if (ffn) mbar_wait_c(B(B_WF + (lap & 1)), lap >> 1);
#pragma unroll
        for (int i = 0; i < 12; i++) ldsm_if(wf + 4 * i, wl + OFF_SIDE + ((i >> 2) & 1) * UNIT + (i & 3) * 1024, lap == (i >> 2), IC<1>{});
        kblock(IC<4>{}, lap & 1, true);
        sched_fence();
        dep = 0;
#pragma unroll
        for (int i = 0; i < 12; i++) dep ^= wf[4 * i];
        hand(B(B_WE + (lap & 1)), 1);
#pragma unroll
        for (int i = 0; i < 3; i++) put_ctx(3 * i + 1, lap == i);
        kblock(IC<5>{}, lap & 1, true);
        if (lap == 2) publish(5);
        kblock(IC<0>{}, (lap & 1) ^ 1, true);
#pragma unroll
        for (int i = 0; i < 2; i++) put_ctx(3 * i + 2, lap == i);
        kblock(IC<1>{}, (lap & 1) ^ 1, true);
        TL(2, 40 + lap, warp == 4);
      }
#pragma unroll
      for (int i = 48; i < 96; i++) wf[i] = 0;
#pragma unroll
      for (int i = 0; i < 32; i++) { hp[i] = 0; rt[i >> 1] = 0; }
      const uint32_t xa = sb + OFF_SIDE + w * UNIT + (cw & 3) * 2048 + (lane & 15) * 128 + (((lane >> 4) ^ (lane & 7)) << 4);
#pragma unroll 1
      for (int lap = 3; lap < 11; lap++) {
        kblock(IC<2>{}, lap & 1, true);
        kblock(IC<3>{}, lap & 1, true);
        if (lap == 10) break;
        if (lap < WIN) {
          if (ffn) mbar_wait_c(B(B_WF + (lap & 1)), (lap >> 1) & 1);
#pragma unroll
          for (int i = 12; i < 24; i++) ldsm_if(wf + 4 * i, wl + OFF_SIDE + ((i >> 2) & 1) * UNIT + (i & 3) * 1024, lap == (i >> 2), IC<1>{});
        } else if (lap == WIN) {
          mbar_wait_c(B(B_WF), ffn ? (WIN >> 1) & 1 : 0);
          mbar_wait_c(B(B_WF + 1), ffn ? (WIN >> 1) & 1 : 0);
#pragma unroll
          for (int j = 0; j < 8; j++) ldsm_if(hp + 4 * j, (xa ^ ((j & 3) << 5)) + (j >> 2) * 8192, true, IC<0>{});
        } else if (lap == 9) {
          mbar_wait_c(B(B_WR), 0);
          mbar_wait_c(B(B_SET2), 0);
#pragma unroll
          for (int j = 0; j < 4; j++) ldsm_if(rt + 4 * j, sb + OFF_MISC + 512 + (lane & 1) * 256 + (lane >> 3) * 16 + j * 64, true, IC<0>{});
        }
        kblock(IC<4>{}, lap & 1, true);
        sched_fence();
        dep = 0;
#pragma unroll
        for (int i = 0; i < 20; i++) dep ^= i < 12 ? wf[48 + 4 * i] : hp[4 * (i - 12)];
        hand(B(B_WE + (lap < WIN ? lap & 1 : 0)), lap < WIN ? 1 : (lap == WIN ? 2 : 0));
        kblock(IC<5>{}, lap & 1, true);
        kblock(IC<0>{}, (lap & 1) ^ 1, true);
        kblock(IC<1>{}, (lap & 1) ^ 1, true);
        TL(2, 40 + lap, warp == 4);
      }
    }
    uint4* const xr = g_xr + rid * XR_SIZE;
    uint4* const psd = xr + XR_PS + cw * 16 + r0;
    settle(psd, zero);
    sched_fence();
    wg_wait<0>();
    fence_regs(acc);
    TL(2, 10, warp == 4);
    {
      float d[4] = {0.f, 0.f, 0.f, 0.f}, qa[4] = {0.f, 0.f, 0.f, 0.f}, qb[4] = {0.f, 0.f, 0.f, 0.f};
#pragma unroll
      for (int j = 0; j < 16; j++) {
        hp[2 * j] = hadd2_bf(hp[2 * j], pack_bf16(acc[4 * j], acc[4 * j + 1]));
        hp[2 * j + 1] = hadd2_bf(hp[2 * j + 1], pack_bf16(acc[4 * j + 2], acc[4 * j + 3]));
        if (j & 1) {
          mma16816(d, hp[2 * j - 2], hp[2 * j - 1], hp[2 * j], hp[2 * j + 1], rt[j - 1], rt[j]);
          mma16816(qa, hp[2 * j - 2], hp[2 * j - 1], hp[2 * j], hp[2 * j + 1], hp[2 * j - 2], hp[2 * j]);
          mma16816(qb, hp[2 * j - 2], hp[2 * j - 1], hp[2 * j], hp[2 * j + 1], hp[2 * j - 1], hp[2 * j + 1]);
        }
      }
      asm volatile("{\n.reg .pred p;\nsetp.eq.u32 p, %7, %8;\n@p st.global.cg.v4.f32 [%0], {%1,%2,%3,%3};\n@p st.global.cg.v4.f32 [%0 + 128], {%4,%5,%6,%6};\n}"
                   ::"l"(psd), "f"(d[0]), "f"(d[1]), "f"((r0 & 1) ? qa[1] : qa[0]), "f"(d[2]), "f"(d[3]), "f"((r0 & 1) ? qb[3] : qb[2]),
                   "r"(lane & 3), "r"(r0 >> 1) : "memory");
      sched_fence();
    }
    mbar_wait_c(B(B_EMPTY3), 0);
    __syncwarp();
    stage_store_128(stg, lane, hp);
    TL(2, 11, warp == 4);
    __syncwarp();
    uint4 cout;
    uint32_t ckey;
    {
      const float wsum = *reinterpret_cast<const float*>(sp + OFF_MISC + 1024);
      const uint4* pp = g_xr + (mt * 8 + (ct & 1) * 4) * XR_SIZE + XR_PS + (ct >> 1);
      uint2* kd = reinterpret_cast<uint2*>(xr + XR_KEY) + cw;
      const uint32_t tok = 0x7FFFu - (mt * 128 + (ct >> 1));
      settle(pp, zero); settle(kd, zero); settle(tok, zero);
      spin_clk(PS_DLY);
      float s1, s2, s3;
#pragma unroll 1
      for (int n = 0; n < 0x400000; n++) {
        float4 z[4];
#pragma unroll
        for (int i = 0; i < 4; i++)
          asm volatile("ld.relaxed.gpu.global.v4.f32 {%0,%1,%2,%3}, [%4];" : "=f"(z[i].x), "=f"(z[i].y), "=f"(z[i].z), "=f"(z[i].w) : "l"(pp + i * XR_SIZE) : "memory");
        s1 = (z[0].x + z[1].x) + (z[2].x + z[3].x); s3 = (z[0].y + z[1].y) + (z[2].y + z[3].y); s2 = (z[0].z + z[1].z) + (z[2].z + z[3].z);
        const float t = s1 + s2 + s3;
        s1 += __shfl_xor_sync(~0u, s1, 1); s2 += __shfl_xor_sync(~0u, s2, 1); s3 += __shfl_xor_sync(~0u, s3, 1);
        if (__all_sync(~0u, t == t)) break;
        uint32_t m = 0;
#pragma unroll
        for (int i = 0; i < 4; i++) m = max(max(m, __float_as_uint(z[i].x)), max(__float_as_uint(z[i].y), __float_as_uint(z[i].z)));
        if (__all_sync(~0u, m != 0xFFFFFFFFu)) break;
      }
      TL(2, 12, warp == 4);
      const float mean = s1 * (1.f / DM);
      float mb, inv;
      ln_round(mean, fmaxf(fmaf(s2, 1.f / DM, -mean * mean), 0.f), mb, inv);
      const uint32_t u = pack_bf16(0.f, fmaf(s3 - mb * wsum, inv, 0.f));
      const uint32_t key = ((u ^ (((int)u >> 31) | 0x80000000u)) & 0xFFFF0000u) | tok;
      const uint32_t c1 = __reduce_max_sync(~0u, key);
      const uint32_t c2 = __reduce_max_sync(~0u, key == c1 ? 0u : key);
      asm volatile(ELECT "st.global.cg.v2.u32 [%0], {%1,%2};\n}" ::"l"(kd), "r"(c1), "r"(c2) : "memory");
      sched_fence();
      const uint32_t nm2 = pack_bf16(-mb, -mb);
      if (!(ct & 1)) *reinterpret_cast<uint2*>(sp + OFF_RSTAT + (ct >> 1) * 8) = make_uint2(nm2, __float_as_uint(inv) | (key >= c2 ? 0x80000000u : 0u));
      ckey = (lane >> 4) ? c2 : c1;
      const int row = (0x7FFF - (ckey & 0x7FFF)) & 15;
      const uint32_t rn = __shfl_sync(~0u, nm2, row * 2);
      const float ri = __shfl_sync(~0u, inv, row * 2);
      const uint4 v = lds128(stg + ((lane & 15) >> 3) * 8192 + row * 128 + (((lane & 7) ^ (row & 7)) << 4));
      const uint4 n = make_uint4(ln_apply(v.x, rn, ri), ln_apply(v.y, rn, ri), ln_apply(v.z, rn, ri), ln_apply(v.w, rn, ri));
      __stcg(xr + XR_CAND + cw * 64 + 32 + lane, n);
      __stcg(xr + XR_CAND + cw * 64 + lane, v);
      cdst = out + (size_t)(0x7FFF - (ckey & 0x7FFF)) * DM + gq * 128 + (lane & 15) * 8;
      cout = make_uint4(hadd2_bf(v.x, n.x), hadd2_bf(v.y, n.y), hadd2_bf(v.z, n.z), hadd2_bf(v.w, n.w));
    }
    publish(B_OUT - B_PUB);
    cluster_arrive();
    TL(2, 13, warp == 4);
    uint32_t wd[16][4];
    if (ffn) {
      static_for<2>([&](auto i) {
        mbar_wait_b(B(B_WF + i), ((WIN >> 1) & 1) ^ 1);
        grab(IC<WIN + i>{}, OFF_SIDE + i * UNIT);
      });
      mbar_wait_b(B(B_FULL3 + 4 + w), 0);
#pragma unroll
      for (int i = 0; i < 16; i++) {
        const int k = (i & 1) * 16 + (lane & 7) + (lane >> 4) * 8;
        asm volatile("ldmatrix.sync.aligned.m8n8.x4.trans.shared.b16 {%0,%1,%2,%3}, [%4];"
                     : "=r"(wd[i][0]), "=r"(wd[i][1]), "=r"(wd[i][2]), "=r"(wd[i][3])
                     : "r"(sb + r3(4) + w * SLOT + (2 * (cw & 3) + (i >> 3)) * 4096 + k * 128 + (((2 * ((i >> 1) & 3) + ((lane >> 3) & 1)) ^ (lane & 7)) << 4)) : "memory");
      }
    }
    const int fc = 16 * (rid >> 1) + 4 * (rid & 1) + (lane & 3) + 8 * (lane >> 4), ft = (lane >> 3) & 1;
    const char* pc = reinterpret_cast<const char*>(g_xr + ((ct & 127) >> 4) * XR_SIZE + XR_CAND + 32 + (ct & 15));
    const char* pf = reinterpret_cast<const char*>(g_xr + (fc >> 7) * XR_SIZE + XR_CAND) + (fc & 127) * 2;
    const uint32_t xs = sb + OFF_SCR + w * 2112 + ((ct & 127) >> 2) * 64 + (((ct >> 3) & 3) << 4) + (ct & 3) * 4;
    const uint32_t xb = sb + OFF_SCR + (r0 & 1) * 2112 + w * 128 + (((lane ^ w) & 3) << 4);
    settle(pc, zero); settle(pf, zero); settle(cdst, zero); settle(xs, zero); settle(xb, zero);
    mbar_wait_b(B(B_OUT2), 0);
    const uint4 top = lds128(sb + OFF_MISC);
    TL(2, 14, warp == 4);
    uint32_t fh, fn;
    {
      pc += w ? top.y : top.x;
      pf += ft ? top.y : top.x;
      uint4 v;
#pragma unroll 1
      for (int n = 0; n < 0x400000; n++) {
        asm volatile("ld.relaxed.gpu.global.v4.u32 {%0,%1,%2,%3}, [%4];" : "=r"(v.x), "=r"(v.y), "=r"(v.z), "=r"(v.w) : "l"(pc) : "memory");
        asm volatile("ld.relaxed.gpu.global.u16 %0, [%1];" : "=r"(fh) : "l"(pf) : "memory");
        asm volatile("ld.relaxed.gpu.global.u16 %0, [%1 + 512];" : "=r"(fn) : "l"(pf) : "memory");
        asm volatile("st.shared.u32 [%0], %1;" ::"r"(xs), "r"(v.x) : "memory");
        asm volatile("st.shared.u32 [%0], %1;" ::"r"(xs ^ 16), "r"(v.y) : "memory");
        asm volatile("st.shared.u32 [%0], %1;" ::"r"(xs ^ 32), "r"(v.z) : "memory");
        asm volatile("st.shared.u32 [%0], %1;" ::"r"(xs ^ 48), "r"(v.w) : "memory");
        if (__all_sync(~0u, max(max(v.x, v.y), max(v.z, v.w)) != 0xFFFFFFFFu && max(fh, fn) != 0xFFFFu)) break;
      }
    }
    bar_sync(3, 256);
    asm volatile("{\n.reg .pred p;\nsetp.lt.u32 p, %5, %6;\n@p st.global.v4.u32 [%0], {%1,%2,%3,%4};\n}" ::"l"(cdst), "r"(cout.x), "r"(cout.y), "r"(cout.z),
                 "r"(cout.w), "r"(ckey), "r"(top.w) : "memory");
    if (ffn) {
      TL(2, 15, warp == 4);
      float d[4][4] = {};
      auto xl = [&](int i) { return lds128((xb ^ ((i & 2) << 4)) + (i >> 1) * 256 + (i & 1) * 64); };
      uint4 b0 = xl(0), b1 = xl(1);
#pragma unroll
      for (int i = 0; i < 16; i += 2) {
        const uint4 c0 = b0, c1 = b1;
        if (i < 14) { b0 = xl(i + 2); b1 = xl(i + 3); }
        mma16816(d[0], wf[8 * i], wf[8 * i + 1], wf[8 * i + 2], wf[8 * i + 3], c0.x, c0.y);
        mma16816(d[1], wf[8 * i + 4], wf[8 * i + 5], wf[8 * i + 6], wf[8 * i + 7], c0.z, c0.w);
        mma16816(d[2], wf[8 * i + 8], wf[8 * i + 9], wf[8 * i + 10], wf[8 * i + 11], c1.x, c1.y);
        mma16816(d[3], wf[8 * i + 12], wf[8 * i + 13], wf[8 * i + 14], wf[8 * i + 15], c1.z, c1.w);
      }
      const float e0 = (d[0][0] + d[1][0]) + (d[2][0] + d[3][0]), e1 = (d[0][1] + d[1][1]) + (d[2][1] + d[3][1]);
      const float e2 = (d[0][2] + d[1][2]) + (d[2][2] + d[3][2]), e3 = (d[0][3] + d[1][3]) + (d[2][3] + d[3][3]);
      asm volatile("st.shared.v2.f32 [%0], {%1,%2};" ::"r"(sb + OFF_SCR + 8192 + ((w * 2 + (lane & 1)) * 32 + (cw & 3) * 8 + r0) * 8),
                   "f"((lane & 1) ? e1 : e0), "f"((lane & 1) ? e3 : e2) : "memory");
      bar_sync(3, 256);
      TL(2, 16, warp == 4);
      const uint32_t ra = sb + OFF_SCR + 8192 + (r0 & 1) * 256 + (r0 >> 1) * 64 + (lane & 3) * 16;
      const uint4 p0 = lds128(ra), p1 = lds128(ra + 512);
      auto act = [](uint32_t u0, uint32_t u1, uint32_t g0, uint32_t g1) {
        const uint32_t ug = pack_bf16(__uint_as_float(u0) + __uint_as_float(u1), __uint_as_float(g0) + __uint_as_float(g1));
        const float g = bf_hi(ug);
        return bf_round(__fdividef(g, 1.f + __expf(-g))) * bf_lo(ug);
      };
      const uint32_t av = pack_bf16(act(p0.x, p1.x, p0.y, p1.y), act(p0.z, p1.z, p0.w, p1.w));
      uint32_t b[4];
#pragma unroll
      for (int i = 0; i < 4; i++) b[i] = __shfl_sync(~0u, av, 8 * i + (lane & 7));
      TL(2, 17, warp == 4);
      float y[2][4] = {{0.f, 0.f, 0.f, 0.f}, {0.f, 0.f, 0.f, 0.f}};
#pragma unroll
      for (int c = 0; c < 4; c++) {
        const bool on = (lane >> 3) == c;
        const uint32_t b0 = on ? b[0] : 0, b1 = on ? b[1] : 0, b2 = on ? b[2] : 0, b3 = on ? b[3] : 0;
#pragma unroll
        for (int a = 0; a < 2; a++) {
          const int i = 8 * a + 2 * c;
          mma16816(y[a], wd[i][0], wd[i][1], wd[i][2], wd[i][3], b0, b1);
          mma16816(y[a], wd[i + 1][0], wd[i + 1][1], wd[i + 1][2], wd[i + 1][3], b2, b3);
        }
      }
      float4* yd = reinterpret_cast<float4*>(g_xr + (cw * 16 + (lane & 3) * 2 + (lane >> 4)) * XR_SIZE + XR_Y + fid * 4 + (r0 & 3));
      __stcg(yd, make_float4(y[0][0], y[0][1], y[0][2], y[0][3]));
      __stcg(yd + 8 * XR_SIZE, make_float4(y[1][0], y[1][1], y[1][2], y[1][3]));
    }
    TL(2, 18, warp == 4);
    if (cw == 0) {
      const uint32_t fk = ft ? top.w : top.z;
      uint32_t u = fk >> 16;
      u = (u & 0x8000u) ? (u & 0x7FFFu) : (~u & 0xFFFFu);
      float rs = bf_round(__fdividef(1.f, 1.f + __expf(-__uint_as_float(u << 16))));
      uint16_t* op = reinterpret_cast<uint16_t*>(out) + (size_t)(~fk & 0x7FFF) * DM + fc;
      settle(op, zero); settle(__float_as_uint(rs), zero);
      spin_clk(ffn ? Y_DLY : Y_DLY + Y_DLY0);
      float v[4];
#pragma unroll 1
      for (int n = 0; n < 0x400000; n++) {
        float4 z[14];
#pragma unroll
        for (int i = 0; i < 14; i++)
          asm volatile("ld.relaxed.gpu.global.v4.f32 {%0,%1,%2,%3}, [%4];" : "=f"(z[i].x), "=f"(z[i].y), "=f"(z[i].z), "=f"(z[i].w) : "l"(xr + XR_Y + lane + 32 * i) : "memory");
        float a[4] = {z[0].x, z[0].y, z[0].z, z[0].w}, b[4] = {z[1].x, z[1].y, z[1].z, z[1].w};
#pragma unroll
        for (int i = 2; i < 14; i += 2) {
          a[0] += z[i].x; a[1] += z[i].y; a[2] += z[i].z; a[3] += z[i].w;
          b[0] += z[i + 1].x; b[1] += z[i + 1].y; b[2] += z[i + 1].z; b[3] += z[i + 1].w;
        }
#pragma unroll
        for (int i = 0; i < 4; i++) v[i] = a[i] + b[i];
        const float t = (v[0] + v[1]) + (v[2] + v[3]);
        if (__all_sync(~0u, t == t)) break;
        uint32_t m = 0;
#pragma unroll
        for (int i = 0; i < 14; i++) m = max(max(m, max(__float_as_uint(z[i].x), __float_as_uint(z[i].y))), max(__float_as_uint(z[i].z), __float_as_uint(z[i].w)));
        if (__all_sync(~0u, m != 0xFFFFFFFFu)) break;
      }
      TL(2, 30, true);
      const bool hi = lane & 16, odd = lane & 8;
      const float a0 = (hi ? v[2] : v[0]) + __shfl_xor_sync(~0u, hi ? v[0] : v[2], 16), a1 = (hi ? v[3] : v[1]) + __shfl_xor_sync(~0u, hi ? v[1] : v[3], 16);
      float yv = (odd ? a1 : a0) + __shfl_xor_sync(~0u, odd ? a0 : a1, 8);
      yv += __shfl_xor_sync(~0u, yv, 4);
      const uint32_t o = hadd2_bf(fh, hadd2_bf(fn, pack_bf16(bf_round(yv) * rs, 0.f)));
      if (!(lane & 4)) *op = (uint16_t)o;
      TL(2, 21, true);
    }
    TL(2, 20, warp == 4);
    }
    __syncwarp();
    cluster_wait();
  }
}

typedef CUresult (*EncodeFn)(CUtensorMap*, CUtensorMapDataType, cuuint32_t, void*, const cuuint64_t*, const cuuint64_t*, const cuuint32_t*,
                             const cuuint32_t*, CUtensorMapInterleave, CUtensorMapSwizzle, CUtensorMapL2promotion, CUtensorMapFloatOOBfill);
EncodeFn g_enc = nullptr;

void map2(CUtensorMap* m, const void* ptr, uint64_t rows, uint64_t cols, uint32_t bc, uint32_t br) {
  const CUtensorMapSwizzle sw = bc == 64 ? CU_TENSOR_MAP_SWIZZLE_128B : CU_TENSOR_MAP_SWIZZLE_64B;
  cuuint64_t gd[2] = {cols, rows}, gs[1] = {cols * 2};
  cuuint32_t bd[2] = {bc, br}, es[2] = {1, 1};
  g_enc(m, CU_TENSOR_MAP_DATA_TYPE_BFLOAT16, 2, (void*)ptr, gd, gs, bd, es, CU_TENSOR_MAP_INTERLEAVE_NONE, sw,
        CU_TENSOR_MAP_L2_PROMOTION_L2_128B, CU_TENSOR_MAP_FLOAT_OOB_FILL_NONE);
}
void map3(CUtensorMap* m, const void* ptr, uint64_t rows, uint64_t cols, uint32_t br, uint32_t bch) {
  cuuint64_t gd[3] = {64, rows, cols / 64}, gs[2] = {cols * 2, 128};
  cuuint32_t bd[3] = {64, br, bch}, es[3] = {1, 1, 1};
  g_enc(m, CU_TENSOR_MAP_DATA_TYPE_BFLOAT16, 3, (void*)ptr, gd, gs, bd, es, CU_TENSOR_MAP_INTERLEAVE_NONE, CU_TENSOR_MAP_SWIZZLE_128B,
        CU_TENSOR_MAP_L2_PROMOTION_L2_128B, CU_TENSOR_MAP_FLOAT_OOB_FILL_NONE);
}

}

extern "C" void kernel_launch(void* const* d_in, const int* in_sizes, int n_in, void* d_out, int out_size) {
  const __nv_bfloat16* x = (const __nv_bfloat16*)d_in[0];
  const __nv_bfloat16* ckv = (const __nv_bfloat16*)d_in[1];
  const __nv_bfloat16* wq = (const __nv_bfloat16*)d_in[2];
  const __nv_bfloat16* wk = (const __nv_bfloat16*)d_in[3];
  const __nv_bfloat16* wv = (const __nv_bfloat16*)d_in[4];
  const __nv_bfloat16* wo = (const __nv_bfloat16*)d_in[5];
  const __nv_bfloat16* w_r = (const __nv_bfloat16*)d_in[7];
  const __nv_bfloat16* wgate = (const __nv_bfloat16*)d_in[8];
  const __nv_bfloat16* wup = (const __nv_bfloat16*)d_in[9];
  const __nv_bfloat16* wdown = (const __nv_bfloat16*)d_in[10];
  __nv_bfloat16* out = (__nv_bfloat16*)d_out;

  if (!g_enc) {
    void* fn = nullptr;
    cudaDriverEntryPointQueryResult qr;
    cudaGetDriverEntryPoint("cuTensorMapEncodeTiled", &fn, cudaEnableDefault, &qr);
    g_enc = (EncodeFn)fn;
    cudaFuncSetAttribute(fused_kernel, cudaFuncAttributeMaxDynamicSharedMemorySize, SMEM_BYTES);
  }
  void *xn, *kv, *ctx, *xr, *cnt;
  cudaGetSymbolAddress(&xr, g_xr);
  cudaGetSymbolAddress(&cnt, g_cnt);
  cudaGetSymbolAddress(&xn, g_xn);
  cudaGetSymbolAddress(&kv, g_kv);
  cudaGetSymbolAddress(&ctx, g_ctx);

  Params p;
  map2(&p.xn, xn, SEQ, DM, 64, 64);
  map2(&p.ckv, ckv, SEQ, DC, 64, 128);
  map3(&p.wq, wq, DM, NQ, 64, 2);
  map3(&p.wk, wk, DC, NQ, 64, 2);
  map3(&p.wv, wv, DC, NQ, 64, 2);
  map3(&p.kv_ld, kv, 2 * SEQ, NQ, 128, 2);
  map2(&p.ctx_ld, ctx, SEQ, NQ, 64, 128);
  map3(&p.wo, wo, NQ, DM, 64, 1);
  map3(&p.x, x, SEQ, DM, 64, 2);
  map3(&p.wd, wdown, FF, DM, 32, 8);
  map2(&p.wg, wgate, DM, FF, 32, 64);
  map2(&p.wu, wup, DM, FF, 32, 64);
  fused_kernel<<<128, 384, SMEM_BYTES, cudaStreamPerThread>>>(0u, x, (__nv_bfloat16*)kv, (__nv_bfloat16*)ctx, (uint4*)xr, out, (__nv_bfloat16*)xn,
                                                               (unsigned*)cnt, w_r, wdown, wq, p);
}
```

```cpp
#include <cuda_runtime.h>
#include <cuda_bf16.h>
#include <cuda.h>
#include <stdint.h>
#include <utility>

#pragma nv_diag_suppress 549
#pragma nv_diag_suppress 177
namespace {

constexpr int SEQ = 2048, DM = 1024, NH = 32, HD = 128, DC = 512, NQ = NH * HD, FF = 3584;

__device__ __align__(1024) __nv_bfloat16 g_xn[SEQ * DM];
constexpr int KV_TILE = 128 * 128;
__device__ __align__(1024) __nv_bfloat16 g_kv[2 * SEQ * NQ];
__device__ __align__(1024) __nv_bfloat16 g_ctx[SEQ * NQ];
constexpr int XR_PS = 0;
constexpr int XR_KEY = 128;
constexpr int XR_CAND = 136;
constexpr int XR_Y = 648;
constexpr int XR_SIZE = 1104;
__device__ __align__(1024) uint4 g_xr[128 * XR_SIZE];
constexpr int C_LN = 0, C_KV = 16, C_CTX = 32, C_NUM = 64;
__device__ unsigned g_cnt[C_NUM];

#define TL(k, i, cond) do {} while (0)
#define TC(w, g, i) do {} while (0)
#define TL_EXTRA 0
#define TK(i) do {} while (0)

__device__ __forceinline__ uint32_t s2u(const void* p) { return (uint32_t)__cvta_generic_to_shared(p); }
__device__ __forceinline__ void mbar_arrive(uint32_t b) { asm volatile("mbarrier.arrive.shared::cta.b64 _, [%0];" ::"r"(b) : "memory"); }
__device__ __forceinline__ void mbar_arrive_both(uint32_t b, uint32_t lane, bool cond) {
  asm volatile("{\n.reg .pred p;\n.reg .b32 r;\nsetp.lt.u32 p, %1, %2;\nmapa.shared::cluster.u32 r, %0, %1;\n@p mbarrier.arrive.shared::cluster.b64 _, [r];\n}"
               ::"r"(b), "r"(lane), "r"(cond ? 2 : 0) : "memory");
}
__device__ __forceinline__ bool mbar_test(uint32_t b, uint32_t ph) {
  uint32_t ok;
  asm volatile("{\n.reg .pred p;\nmbarrier.test_wait.parity.shared::cta.b64 p, [%1], %2;\nselp.u32 %0, 1, 0, p;\n}" : "=r"(ok) : "r"(b), "r"(ph) : "memory");
  return __all_sync(~0u, ok);
}
__device__ __forceinline__ void mbar_wait(uint32_t b, uint32_t ph) {
  asm volatile(
      "{\n.reg .pred p;\n.reg .u32 n;\nmov.u32 n, 0;\n"
      "LW:\nmbarrier.try_wait.parity.shared::cta.b64 p, [%0], %1, 20000;\n@p bra LD;\n"
      "add.u32 n, n, 1;\nsetp.lt.u32 p, n, 0x40000;\n@p bra LW;\ntrap;\nLD:\n}" ::"r"(b), "r"(ph) : "memory");
}
__device__ __forceinline__ void mbar_wait_u(uint32_t b, uint32_t ph) {
  asm volatile(
      "{\n.reg .pred p;\n.reg .u32 n;\nmov.u32 n, 0;\n"
      "LW:\nmbarrier.try_wait.parity.shared::cta.b64 p, [%0], %1, 20000;\n@p bra.uni LD;\n"
      "add.u32 n, n, 1;\nsetp.lt.u32 p, n, 0x40000;\n@p bra.uni LW;\ntrap;\nLD:\n}" ::"r"(b), "r"(ph) : "memory");
}
__device__ __forceinline__ void mbar_wait_c(uint32_t b, uint32_t ph) {
  asm volatile("{\n.reg .pred p;\nLW:\nmbarrier.try_wait.parity.shared::cta.b64 p, [%0], %1;\n@!p bra.uni LW;\n}" ::"r"(b), "r"(ph) : "memory");
}
__device__ __forceinline__ void mbar_wait_b(uint32_t b, uint32_t ph) {
  asm volatile(
      "{\n.reg .pred p;\n.reg .u32 n;\nmov.u32 n, 0;\n"
      "LW:\nmbarrier.try_wait.parity.shared::cta.b64 p, [%0], %1;\n@p bra.uni LD;\n"
      "add.u32 n, n, 1;\nsetp.lt.u32 p, n, 0x1000000;\n@p bra.uni LW;\ntrap;\nLD:\n}" ::"r"(b), "r"(ph) : "memory");
}
template <bool SLEEP = false>
__device__ __forceinline__ void spin_until_ge(const unsigned* p, unsigned target) {
  asm volatile(
      "{\n.reg .pred p, q;\n.reg .u32 n, v;\nmov.u32 n, 0;\nsetp.ne.u32 q, %2, 0;\n"
      "LW:\nld.acquire.gpu.global.u32 v, [%0];\nsetp.ge.u32 p, v, %1;\n@p bra LD;\n@q nanosleep.u32 200;\n"
      "add.u32 n, n, 1;\nsetp.lt.u32 p, n, 0x400000;\n@p bra LW;\ntrap;\nLD:\n}" ::"l"(p), "r"(target), "n"((int)SLEEP) : "memory");
}
template <int N>
__device__ __forceinline__ void poll_chunks(uint4 (&v)[N], const uint4* p, int stride) {
#pragma unroll 1
  for (int n = 0; n < 0x400000; n++) {
    uint32_t m = 0;
#pragma unroll
    for (int i = 0; i < N; i++) {
      asm volatile("ld.relaxed.gpu.global.v4.u32 {%0,%1,%2,%3}, [%4];" : "=r"(v[i].x), "=r"(v[i].y), "=r"(v[i].z), "=r"(v[i].w) : "l"(p + i * stride) : "memory");
    }
#pragma unroll
    for (int i = 0; i < N; i++) m = max(max(m, max(v[i].x, v[i].y)), max(v[i].z, v[i].w));
    if (__all_sync(~0u, m != 0xFFFFFFFFu)) break;
  }
}
__device__ __forceinline__ void spin_clk(uint32_t n) {
  asm volatile("{\n.reg .pred p;\n.reg .u32 a, b;\nmov.u32 a, %%clock;\nLW:\nmov.u32 b, %%clock;\nsub.u32 b, b, a;\nsetp.lt.u32 p, b, %0;\n@p bra.uni LW;\n}" ::"r"(n) : "memory");
}
__device__ __forceinline__ int fresh_lane() {
  int r;
  asm volatile("mov.u32 %0, %%laneid;" : "=r"(r));
  return r;
}
__device__ __forceinline__ void settle(const void* a, uint32_t zero) {
  asm volatile("{\n.reg .pred p;\nsetp.ne.u32 p, %1, 0;\n@p st.global.u32 [%0], %1;\n}" ::"l"(a), "r"(zero) : "memory");
}
__device__ __forceinline__ void settle(uint32_t a, uint32_t zero) {
  asm volatile("{\n.reg .pred p;\nsetp.ne.u32 p, %1, 0;\n@p st.shared.u32 [%0], %1;\n}" ::"r"(a), "r"(zero) : "memory");
}
__device__ __forceinline__ void fence_async_all() { asm volatile("fence.proxy.async;" ::: "memory"); }
__device__ __forceinline__ void bar_sync(int id, int n) { asm volatile("bar.sync %0, %1;" ::"r"(id), "r"(n) : "memory"); }
__device__ __forceinline__ void bar_arrive(int id, int n) { asm volatile("bar.arrive %0, %1;" ::"r"(id), "r"(n) : "memory"); }
__device__ __forceinline__ void cluster_arrive() { asm volatile("barrier.cluster.arrive.relaxed.aligned;" ::: "memory"); }
__device__ __forceinline__ void cluster_wait() { asm volatile("barrier.cluster.wait.acquire.aligned;" ::: "memory"); }
__device__ __forceinline__ void fence_gpu() { asm volatile("fence.acq_rel.gpu;" ::: "memory"); }
__device__ __forceinline__ void red_add(unsigned* p, unsigned v) { asm volatile("red.relaxed.gpu.global.add.u32 [%0], %1;" ::"l"(p), "r"(v) : "memory"); }
#define ELECT "{\n.reg .pred E;\nelect.sync _|E, 0xFFFFFFFF;\n@E "
__device__ __forceinline__ void e_init(uint32_t b, uint32_t c) { asm volatile(ELECT "mbarrier.init.shared::cta.b64 [%0], %1;\n}" ::"r"(b), "r"(c) : "memory"); }
__device__ __forceinline__ void e_expect(uint32_t b, uint32_t bytes) { asm volatile(ELECT "mbarrier.arrive.expect_tx.shared::cta.b64 _, [%0], %1;\n}" ::"r"(b), "r"(bytes) : "memory"); }
__device__ __forceinline__ void e_arrive(uint32_t b) { asm volatile(ELECT "mbarrier.arrive.shared::cta.b64 _, [%0];\n}" ::"r"(b) : "memory"); }
__device__ __forceinline__ void prefetch_tm(const CUtensorMap* m) { asm volatile(ELECT "prefetch.tensormap [%0];\n}" ::"l"(m) : "memory"); }
__device__ __forceinline__ void tma_ld2(uint32_t dst, const CUtensorMap* m, uint32_t bar, int c0, int c1) {
  asm volatile(ELECT "cp.async.bulk.tensor.2d.shared::cta.global.mbarrier::complete_tx::bytes [%0], [%1, {%3,%4}], [%2];\n}" ::"r"(dst), "l"(m), "r"(bar), "r"(c0), "r"(c1) : "memory");
}
__device__ __forceinline__ void tma_ld3(uint32_t dst, const CUtensorMap* m, uint32_t bar, int c0, int c1, int c2) {
  asm volatile(ELECT "cp.async.bulk.tensor.3d.shared::cta.global.mbarrier::complete_tx::bytes [%0], [%1, {%3,%4,%5}], [%2];\n}" ::"r"(dst), "l"(m), "r"(bar), "r"(c0), "r"(c1), "r"(c2) : "memory");
}
__device__ __forceinline__ void tma_ld2_mc(uint32_t dst, const CUtensorMap* m, uint32_t bar, int c0, int c1, uint16_t mask) {
  asm volatile(ELECT "cp.async.bulk.tensor.2d.shared::cluster.global.mbarrier::complete_tx::bytes.multicast::cluster [%0], [%1, {%3,%4}], [%2], %5;\n}" ::"r"(dst), "l"(m), "r"(bar), "r"(c0), "r"(c1), "h"(mask) : "memory");
}
__device__ __forceinline__ void tma_ld3_mc(uint32_t dst, const CUtensorMap* m, uint32_t bar, int c0, int c1, int c2, uint16_t mask) {
  asm volatile(ELECT "cp.async.bulk.tensor.3d.shared::cluster.global.mbarrier::complete_tx::bytes.multicast::cluster [%0], [%1, {%3,%4,%5}], [%2], %6;\n}" ::"r"(dst), "l"(m), "r"(bar), "r"(c0), "r"(c1), "r"(c2), "h"(mask) : "memory");
}
__device__ __forceinline__ uint64_t policy_evict_first() {
  uint64_t p;
  asm("createpolicy.fractional.L2::evict_first.b64 %0, 1.0;" : "=l"(p));
  return p;
}
__device__ __forceinline__ void tma_ld2_ef(uint32_t dst, const CUtensorMap* m, uint32_t bar, int c0, int c1) {
  asm volatile(ELECT "cp.async.bulk.tensor.2d.shared::cta.global.mbarrier::complete_tx::bytes.L2::cache_hint [%0], [%1, {%3,%4}], [%2], %5;\n}" ::"r"(dst), "l"(m), "r"(bar), "r"(c0), "r"(c1), "l"(policy_evict_first()) : "memory");
}
__device__ __forceinline__ void tma_ld3_ef(uint32_t dst, const CUtensorMap* m, uint32_t bar, int c0, int c1, int c2) {
  asm volatile(ELECT "cp.async.bulk.tensor.3d.shared::cta.global.mbarrier::complete_tx::bytes.L2::cache_hint [%0], [%1, {%3,%4,%5}], [%2], %6;\n}" ::"r"(dst), "l"(m), "r"(bar), "r"(c0), "r"(c1), "r"(c2), "l"(policy_evict_first()) : "memory");
}
__device__ __forceinline__ void bulk_ld(uint32_t dst, const void* src, uint32_t bytes, uint32_t bar) {
  asm volatile(ELECT "cp.async.bulk.shared::cta.global.mbarrier::complete_tx::bytes [%0], [%1], %2, [%3];\n}" ::"r"(dst), "l"(src), "r"(bytes), "r"(bar) : "memory");
}
__device__ __forceinline__ void tma_pf2(const CUtensorMap* m, int c0, int c1) { asm volatile(ELECT "cp.async.bulk.prefetch.tensor.2d.L2.global [%0, {%1,%2}];\n}" ::"l"(m), "r"(c0), "r"(c1) : "memory"); }
__device__ __forceinline__ void tma_pf3(const CUtensorMap* m, int c0, int c1, int c2) { asm volatile(ELECT "cp.async.bulk.prefetch.tensor.3d.L2.global [%0, {%1,%2,%3}];\n}" ::"l"(m), "r"(c0), "r"(c1), "r"(c2) : "memory"); }
__device__ __forceinline__ void sched_fence() { asm volatile("pmevent 0;" ::: "memory"); }
__device__ __forceinline__ void l2_prefetch(const void* p, uint32_t bytes) { asm volatile(ELECT "cp.async.bulk.prefetch.L2.global [%0], %1;\n}" ::"l"(p), "r"(bytes) : "memory"); }

__device__ __forceinline__ void wg_fence() { asm volatile("wgmma.fence.sync.aligned;" ::: "memory"); }
__device__ __forceinline__ void wg_commit() { asm volatile("wgmma.commit_group.sync.aligned;" ::: "memory"); }
template <int N> __device__ __forceinline__ void wg_wait() { asm volatile("wgmma.wait_group.sync.aligned %0;" ::"n"(N) : "memory"); }
template <int N> __device__ __forceinline__ void reg_alloc() { asm volatile("setmaxnreg.inc.sync.aligned.u32 %0;" ::"n"(N)); }
template <int N> __device__ __forceinline__ void reg_dealloc() { asm volatile("setmaxnreg.dec.sync.aligned.u32 %0;" ::"n"(N)); }
template <int N> __device__ __forceinline__ void fence_regs(float (&d)[N]) {
#pragma unroll
  for (int i = 0; i < N; i++) asm volatile("" : "+f"(d[i])::"memory");
}
template <int I0, int I1, int N> __device__ __forceinline__ void fence_part(float (&d)[N]) {
#pragma unroll
  for (int i = I0; i < I1; i++) asm volatile("" : "+f"(d[i])::"memory");
}
template <int N> __device__ __forceinline__ void fence_regs(uint32_t (&d)[N]) {
#pragma unroll
  for (int i = 0; i < N; i++) asm volatile("" : "+r"(d[i])::"memory");
}

__device__ __forceinline__ uint32_t mk_desc(uint32_t addr, uint32_t lbo) { return ((addr & 0x3FFFF) >> 4) | ((lbo >> 4) << 16); }

#define R8(b) "+f"(d[b + 0]), "+f"(d[b + 1]), "+f"(d[b + 2]), "+f"(d[b + 3]), "+f"(d[b + 4]), "+f"(d[b + 5]), "+f"(d[b + 6]), "+f"(d[b + 7])
#define REGS64 "%0,%1,%2,%3,%4,%5,%6,%7,%8,%9,%10,%11,%12,%13,%14,%15,%16,%17,%18,%19,%20,%21,%22,%23,%24,%25,%26,%27,%28,%29,%30,%31," \
               "%32,%33,%34,%35,%36,%37,%38,%39,%40,%41,%42,%43,%44,%45,%46,%47,%48,%49,%50,%51,%52,%53,%54,%55,%56,%57,%58,%59,%60,%61,%62,%63"
#define REGS128 REGS64 ",%64,%65,%66,%67,%68,%69,%70,%71,%72,%73,%74,%75,%76,%77,%78,%79,%80,%81,%82,%83,%84,%85,%86,%87,%88,%89,%90,%91,%92,%93,%94,%95," \
               "%96,%97,%98,%99,%100,%101,%102,%103,%104,%105,%106,%107,%108,%109,%110,%111,%112,%113,%114,%115,%116,%117,%118,%119,%120,%121,%122,%123,%124,%125,%126,%127"

#define DESC(d, r, o) "add.u32 t, " r ", " o ";\nmov.b64 " d ", {t, h};\n"
#define MMA_PRE_(acc, hi) "{\n.reg .pred p;\n.reg .b32 t, h;\n.reg .b64 da, db;\nmov.b32 h, " hi ";\nsetp.ne.b32 p, " acc ", 0;\n"
#define MMA_PRE(acc) MMA_PRE_(acc, "0x40000040")
#define MMA_PRE64(acc) MMA_PRE_(acc, "0x80000020")
template <int TB, int OA, int OB>
__device__ __forceinline__ void mma_n256_ss(float (&d)[128], uint32_t a, uint32_t b, int acc) {
  asm volatile(MMA_PRE("%130") DESC("da", "%128", "%132") DESC("db", "%129", "%133")
               "wgmma.mma_async.sync.aligned.m64n256k16.f32.bf16.bf16 {" REGS128 "}, da, db, p, 1, 1, 0, %131;\n}\n"
               : R8(0), R8(8), R8(16), R8(24), R8(32), R8(40), R8(48), R8(56), R8(64), R8(72), R8(80), R8(88), R8(96), R8(104), R8(112), R8(120)
               : "r"(a), "r"(b), "r"(acc), "n"(TB), "n"(OA >> 4), "n"(OB >> 4));
}
template <int TB, int OA, int OB>
__device__ __forceinline__ void mma_n128_ss(float (&d)[64], uint32_t a, uint32_t b, int acc) {
  asm volatile(MMA_PRE("%66") DESC("da", "%64", "%68") DESC("db", "%65", "%69")
               "wgmma.mma_async.sync.aligned.m64n128k16.f32.bf16.bf16 {" REGS64 "}, da, db, p, 1, 1, 0, %67;\n}\n"
               : R8(0), R8(8), R8(16), R8(24), R8(32), R8(40), R8(48), R8(56)
               : "r"(a), "r"(b), "r"(acc), "n"(TB), "n"(OA >> 4), "n"(OB >> 4));
}
template <int TB, int OB>
__device__ __forceinline__ void mma_n128_rs(float (&d)[64], const uint32_t* a, uint32_t b, int acc) {
  asm volatile(MMA_PRE64("%69") DESC("db", "%68", "%71")
               "wgmma.mma_async.sync.aligned.m64n128k16.f32.bf16.bf16 {" REGS64 "}, {%64,%65,%66,%67}, db, p, 1, 1, %70;\n}\n"
               : R8(0), R8(8), R8(16), R8(24), R8(32), R8(40), R8(48), R8(56)
               : "r"(a[0]), "r"(a[1]), "r"(a[2]), "r"(a[3]), "r"(b), "r"(acc), "n"(TB), "n"(OB >> 4));
}
#define W8(b) "=f"(d[b + 0]), "=f"(d[b + 1]), "=f"(d[b + 2]), "=f"(d[b + 3]), "=f"(d[b + 4]), "=f"(d[b + 5]), "=f"(d[b + 6]), "=f"(d[b + 7])
#define MMA_N64 MMA_PRE64("%37") DESC("db", "%36", "%38") \
  "wgmma.mma_async.sync.aligned.m64n64k16.f32.bf16.bf16 {%0,%1,%2,%3,%4,%5,%6,%7,%8,%9,%10,%11,%12,%13,%14,%15,%16,%17,%18,%19,%20,%21," \
  "%22,%23,%24,%25,%26,%27,%28,%29,%30,%31}, {%32,%33,%34,%35}, db, p, 1, 1, 0;\n}\n"
template <int H, int OB, bool ACC>
__device__ __forceinline__ void mma_n64_rs(float (&d)[64], const uint32_t* a, uint32_t b) {
  if (ACC) asm volatile(MMA_N64 : R8(32 * H), R8(32 * H + 8), R8(32 * H + 16), R8(32 * H + 24) : "r"(a[0]), "r"(a[1]), "r"(a[2]), "r"(a[3]), "r"(b), "n"(1), "n"(OB >> 4));
  else asm volatile(MMA_N64 : W8(32 * H), W8(32 * H + 8), W8(32 * H + 16), W8(32 * H + 24) : "r"(a[0]), "r"(a[1]), "r"(a[2]), "r"(a[3]), "r"(b), "n"(0), "n"(OB >> 4));
}
template <int OB>
__device__ __forceinline__ void mma_n128_rs0(float (&d)[64], const uint32_t* a, uint32_t b) {
  asm volatile(MMA_PRE64("%69") DESC("db", "%68", "%70")
               "wgmma.mma_async.sync.aligned.m64n128k16.f32.bf16.bf16 {" REGS64 "}, {%64,%65,%66,%67}, db, p, 1, 1, 0;\n}\n"
               : W8(0), W8(8), W8(16), W8(24), W8(32), W8(40), W8(48), W8(56)
               : "r"(a[0]), "r"(a[1]), "r"(a[2]), "r"(a[3]), "r"(b), "n"(0), "n"(OB >> 4));
}
template <int TB, int OA, int OB>
__device__ __forceinline__ void mma_n128_ss0(float (&d)[64], uint32_t a, uint32_t b) {
  asm volatile(MMA_PRE("%66") DESC("da", "%64", "%68") DESC("db", "%65", "%69")
               "wgmma.mma_async.sync.aligned.m64n128k16.f32.bf16.bf16 {" REGS64 "}, da, db, p, 1, 1, 0, %67;\n}\n"
               : W8(0), W8(8), W8(16), W8(24), W8(32), W8(40), W8(48), W8(56)
               : "r"(a), "r"(b), "n"(0), "n"(TB), "n"(OA >> 4), "n"(OB >> 4));
}
template <int V> struct IC { static constexpr int value = V; __host__ __device__ constexpr operator int() const { return V; } };
template <int N, class F, int... I>
__device__ __forceinline__ void static_for_(F f, std::integer_sequence<int, I...>) { (f(IC<I>{}), ...); }
template <int N, class F>
__device__ __forceinline__ void static_for(F f) { static_for_<N>(f, std::make_integer_sequence<int, N>{}); }
__device__ __forceinline__ uint32_t pack_bf16(float lo, float hi) {
  uint32_t r;
  asm("cvt.rn.bf16x2.f32 %0, %1, %2;" : "=r"(r) : "f"(hi), "f"(lo));
  return r;
}
__device__ __forceinline__ float bf_lo(uint32_t v) { return __uint_as_float(v << 16); }
__device__ __forceinline__ float bf_hi(uint32_t v) { return __uint_as_float(v & 0xFFFF0000u); }
__device__ __forceinline__ float bf_round(float v) { return bf_lo(pack_bf16(v, v)); }
__device__ __forceinline__ void stsm4(uint32_t addr, uint32_t r0, uint32_t r1, uint32_t r2, uint32_t r3) {
  asm volatile("stmatrix.sync.aligned.m8n8.x4.shared.b16 [%0], {%1,%2,%3,%4};" ::"r"(addr), "r"(r0), "r"(r1), "r"(r2), "r"(r3) : "memory");
}
__device__ __forceinline__ uint4 lds128(uint32_t addr) {
  uint4 v;
  asm volatile("ld.shared.v4.u32 {%0,%1,%2,%3}, [%4];" : "=r"(v.x), "=r"(v.y), "=r"(v.z), "=r"(v.w) : "r"(addr));
  return v;
}
__device__ __forceinline__ float ex2(float x) {
  float y;
  asm("ex2.approx.ftz.f32 %0, %1;" : "=f"(y) : "f"(x));
  return y;
}
__device__ __forceinline__ void stage_store_128(uint32_t base, int lane, const uint32_t* pk) {
  const int row = (lane & 7) + ((lane >> 3) & 1) * 8;
  const uint32_t rb = base + row * 128;
  const int hi = lane >> 4;
#pragma unroll
  for (int j = 0; j < 8; j++) {
    const int chunk = 2 * j + hi;
    const uint32_t a = rb + (j >> 2) * 8192 + (((chunk & 7) ^ (lane & 7)) << 4);
    stsm4(a, pk[4 * j + 0], pk[4 * j + 1], pk[4 * j + 2], pk[4 * j + 3]);
  }
}
__device__ __forceinline__ void ln_round(float mean, float var, float& m_bf, float& inv_s) {
  const uint32_t mv = pack_bf16(mean, var);
  m_bf = bf_lo(mv);
  float sq, rc;
  asm("sqrt.approx.ftz.f32 %0, %1;" : "=f"(sq) : "f"(bf_round(bf_hi(mv) + 1e-5f)));
  asm("rcp.approx.ftz.f32 %0, %1;" : "=f"(rc) : "f"(bf_round(sq)));
  inv_s = rc;
}
__device__ __forceinline__ uint32_t hadd2_bf(uint32_t a, uint32_t b) {
  uint32_t r;
  asm("add.rn.bf16x2 %0, %1, %2;" : "=r"(r) : "r"(a), "r"(b));
  return r;
}
__device__ __forceinline__ uint32_t ln_apply(uint32_t h, uint32_t nm2, float inv_s) {
  const uint32_t d = hadd2_bf(h, nm2);
  return pack_bf16(bf_lo(d) * inv_s, bf_hi(d) * inv_s);
}
__device__ __forceinline__ void mma16816(float* d, uint32_t a0, uint32_t a1, uint32_t a2, uint32_t a3, uint32_t b0, uint32_t b1) {
  asm volatile("mma.sync.aligned.m16n8k16.row.col.f32.bf16.bf16.f32 {%0,%1,%2,%3}, {%4,%5,%6,%7}, {%8,%9}, {%0,%1,%2,%3};"
               : "+f"(d[0]), "+f"(d[1]), "+f"(d[2]), "+f"(d[3]) : "r"(a0), "r"(a1), "r"(a2), "r"(a3), "r"(b0), "r"(b1));
}

constexpr float AT_C = 0.08838834764831845f * 1.4426950408889634f;
#define L_MIN 2.3283064e-10f
#define L_MAX 1.0995116e12f
struct AtState {
  float S[64], O[64];
  uint32_t P[32], Q[32];
  float l[4];
};
template <int I0, int I1>
__device__ __forceinline__ void at_exp(AtState& s) {
#pragma unroll
  for (int i = I0; i < I1; i++) asm volatile("ex2.approx.ftz.f32 %0, %0;" : "+f"(s.S[i]));
#pragma unroll
  for (int i = I0; i < I1; i++) asm volatile("add.f32 %0, %0, %1;" : "+f"(s.l[i & 3]) : "f"(s.S[i]));
}
template <int I0, int I1>
__device__ __forceinline__ void at_pack(AtState& s) {
#pragma unroll
  for (int i = I0; i < I1; i++) asm volatile("cvt.rn.bf16x2.f32 %0, %1, %2;" : "=r"(s.P[i]) : "f"(s.S[2 * i + 1]), "f"(s.S[2 * i]));
}
template <int J0>
__device__ __forceinline__ void at_mask(AtState& s, int r, int lane) {
  const int d = r + (lane >> 2) - (lane & 3) * 2;
#pragma unroll
  for (int j = 0; j < 8; j++) {
    float dummy0 = 0.f, dummy1 = 0.f;
    float& lo0 = j < 7 ? s.S[4 * (J0 + (j < 7 ? j + 1 : j)) + 2] : dummy0;
    float& lo1 = j < 7 ? s.S[4 * (J0 + (j < 7 ? j + 1 : j)) + 3] : dummy1;
    asm("{\n.reg .pred p, q;\nsetp.lt.s32 p, %4, %5;\nsetp.le.s32 q, %4, %5;\n"
        "@p add.f32 %0, %0, 0fFF800000;\n@q add.f32 %1, %1, 0fFF800000;\n@p add.f32 %2, %2, 0fFF800000;\n@q add.f32 %3, %3, 0fFF800000;\n}"
        : "+f"(s.S[4 * (J0 + j)]), "+f"(s.S[4 * (J0 + j) + 1]), "+f"(lo0), "+f"(lo1) : "r"(d), "r"(8 * j));
  }
}
template <int D>
__device__ __forceinline__ uint32_t ld_pair(const __nv_bfloat16* p) {
  uint32_t r;
  asm volatile("{\n.reg .b16 a, b;\nld.global.cg.b16 a, [%1];\nld.global.cg.b16 b, [%1 + %2];\nmov.b32 %0, {a, b};\n}" : "=r"(r) : "l"(p), "n"(2 * D) : "memory");
  return r;
}
__device__ __forceinline__ uint32_t ld_word(const uint32_t* p) {
  uint32_t r;
  asm volatile("ld.global.cg.b32 %0, [%1];" : "=r"(r) : "l"(p) : "memory");
  return r;
}
__device__ __noinline__ void slow_rows(const __nv_bfloat16* wq, int head, int row0) {
  const int lane = fresh_lane(), r = lane >> 2, c = lane & 3;
  uint32_t q[32];
  float o[32];
#pragma unroll
  for (int i = 0; i < 32; i++) q[i] = 0;
  const uint32_t* xa = reinterpret_cast<const uint32_t*>(g_xn + (size_t)(row0 + r) * DM) + c;
#pragma unroll 1
  for (int h = 0; h < 2; h++) {
    const __nv_bfloat16* wb = wq + (size_t)2 * c * NQ + head * HD + 64 * h + 8 * (r >> 1) + (r & 1);
#pragma unroll
    for (int i = 0; i < 32; i++) o[i] = 0.f;
#pragma unroll 1
    for (int kk = 0; kk < DM / 16; kk++) {
      const uint32_t a0 = ld_word(xa + 8 * kk), a1 = ld_word(xa + 8 * kk + 4 * DM), a2 = ld_word(xa + 8 * kk + 4), a3 = ld_word(xa + 8 * kk + 4 * DM + 4);
#pragma unroll
      for (int n = 0; n < 8; n++) {
        const __nv_bfloat16* b = wb + (size_t)16 * kk * NQ + 32 * (n >> 2) + 2 * (n & 3);
        mma16816(o + 4 * n, a0, a1, a2, a3, ld_pair<NQ>(b), ld_pair<NQ>(b + 8 * NQ));
        if (n & 1) sched_fence();
      }
    }
#pragma unroll
    for (int i = 0; i < 16; i++) { q[i] = q[16 + i]; q[16 + i] = pack_bf16(o[2 * i] * AT_C, o[2 * i + 1] * AT_C); }
  }
#pragma unroll 1
  for (int h = 0; h < 2; h++) {
    float m0 = -INFINITY, m1 = -INFINITY, l0 = 0.f, l1 = 0.f;
#pragma unroll
    for (int i = 0; i < 32; i++) o[i] = 0.f;
#pragma unroll 1
    for (int k0 = 0; k0 <= row0; k0 += 16) {
      float e[8] = {0.f, 0.f, 0.f, 0.f, 0.f, 0.f, 0.f, 0.f};
      const __nv_bfloat16* kt = g_kv + (size_t)(head * 16 + (k0 >> 7)) * KV_TILE + (k0 & 127) * 32;
      const uint32_t* kp = reinterpret_cast<const uint32_t*>(kt + r * 32) + c;
#pragma unroll
      for (int kk = 0; kk < 8; kk++) {
        const uint32_t* k0p = kp + (kk >> 1) * 2048 + (((kk & 1) * 2) ^ (r >> 1)) * 4;
        const uint32_t* k1p = kp + (kk >> 1) * 2048 + (((kk & 1) * 2 + 1) ^ (r >> 1)) * 4;
        mma16816(e, q[4 * kk], q[4 * kk + 1], q[4 * kk + 2], q[4 * kk + 3], ld_word(k0p), ld_word(k1p));
        mma16816(e + 4, q[4 * kk], q[4 * kk + 1], q[4 * kk + 2], q[4 * kk + 3], ld_word(k0p + 128), ld_word(k1p + 128));
        if (kk & 1) sched_fence();
      }
      if (k0 == row0) {
#pragma unroll
        for (int i = 0; i < 8; i++) if ((i >> 2) * 8 + 2 * c + (i & 1) > r + (i & 2) * 4) e[i] = -INFINITY;
      }
      float a0 = fmaxf(fmaxf(e[0], e[1]), fmaxf(e[4], e[5])), a1 = fmaxf(fmaxf(e[2], e[3]), fmaxf(e[6], e[7]));
      a0 = fmaxf(a0, __shfl_xor_sync(~0u, a0, 1)); a1 = fmaxf(a1, __shfl_xor_sync(~0u, a1, 1));
      a0 = fmaxf(a0, __shfl_xor_sync(~0u, a0, 2)); a1 = fmaxf(a1, __shfl_xor_sync(~0u, a1, 2));
      a0 = fmaxf(a0, m0); a1 = fmaxf(a1, m1);
      const float sc0 = ex2(m0 - a0), sc1 = ex2(m1 - a1);
      m0 = a0; m1 = a1;
#pragma unroll
      for (int i = 0; i < 8; i++) e[i] = ex2(e[i] - ((i & 2) ? m1 : m0));
      l0 = l0 * sc0 + (e[0] + e[1]) + (e[4] + e[5]);
      l1 = l1 * sc1 + (e[2] + e[3]) + (e[6] + e[7]);
      const uint32_t p0 = pack_bf16(e[0], e[1]), p1 = pack_bf16(e[2], e[3]), p2 = pack_bf16(e[4], e[5]), p3 = pack_bf16(e[6], e[7]);
      const __nv_bfloat16* vp = kt + (size_t)512 * KV_TILE + h * 8192 + 2 * c * 32 + r;
#pragma unroll
      for (int n = 0; n < 8; n++) {
        o[4 * n] *= sc0; o[4 * n + 1] *= sc0; o[4 * n + 2] *= sc1; o[4 * n + 3] *= sc1;
        mma16816(o + 4 * n, p0, p1, p2, p3, ld_pair<32>(vp + (n >> 2) * 4096 + ((n ^ c) & 3) * 8), ld_pair<32>(vp + (n >> 2) * 4096 + ((n ^ c) & 3) * 8 + 256));
        if (n & 1) sched_fence();
      }
    }
    l0 += __shfl_xor_sync(~0u, l0, 1); l1 += __shfl_xor_sync(~0u, l1, 1);
    l0 += __shfl_xor_sync(~0u, l0, 2); l1 += __shfl_xor_sync(~0u, l1, 2);
#pragma unroll
    for (int i = 0; i < 4; i++) {
      const float* v = o + 16 * (i >> 1) + 2 * (i & 1);
      const float f = __fdividef(1.f, (i & 1) ? l1 : l0);
      *reinterpret_cast<uint4*>(g_ctx + (size_t)(row0 + r + (i & 1) * 8) * NQ + head * HD + 64 * h + (i >> 1) * 32 + c * 8) =
          make_uint4(pack_bf16(v[0] * f, v[1] * f), pack_bf16(v[4] * f, v[5] * f), pack_bf16(v[8] * f, v[9] * f), pack_bf16(v[12] * f, v[13] * f));
    }
  }
}

constexpr int UNIT = 16384, SLOT = 32768;
constexpr int OFF_SIDE = 2 * SLOT;
__host__ __device__ constexpr int kv_a(int kb) { return (kb < 6 ? kb : 3 * kb - 10) * UNIT; }
__host__ __device__ constexpr int kv_b(int s) { return (s == 2 ? 6 : 9 + 3 * s) * UNIT; }
__host__ __device__ constexpr int q_aw(int s) { return (3 * s + (s & 1)) * UNIT; }
__host__ __device__ constexpr int q_b(int s) { return (3 * s + 2 - 2 * (s & 1)) * UNIT; }
__host__ __device__ constexpr int k_slot(int j, int r) { return (j < 2 ? 2 * j : (r == 2 ? 0 : 3 + r)) * SLOT; }
__host__ __device__ constexpr int v_slot(int j) { return (6 - (j & 1)) * SLOT; }
__host__ __device__ constexpr int r3(int st) { return ((0x654130 >> (4 * st)) & 7) * SLOT; }
constexpr int OFF_BAR = 229376;
constexpr int OFF_MISC = OFF_BAR + 512;
constexpr int SMEM_BYTES = OFF_MISC + 2080 + TL_EXTRA;
constexpr int OFF_RSTAT = OFF_MISC + 1056;
enum : int {
  B_FULL1 = 0, B_FULLQ = 3, B_FULLB = 7, B_KF = 8, B_VF = 11, B_FULL3 = 13, B_WF = 19, B_DEP = 21, B_OUT2 = 26, B_PF = 27, B_SET = 28,
  B_SET2 = 29, B_LNGO = 30, B_WR = 31,
  B_KE = 32, B_VE = 35, B_WE = 37, B_PUB = 39, B_OUT = 45,
  B_EMPTY1 = 46, B_EMPTYQ = 49, B_X = 53, B_EMPTY3 = 57,
  B_NUM = 63
};
#define TUNABLE(name, v) constexpr int name = v
TUNABLE(LN_GO, 3);
TUNABLE(EP1, 3);
TUNABLE(SIDE_NS, 400);
TUNABLE(SET_KB, 44); TUNABLE(SET_NS, 40);
TUNABLE(PF_KB, 54); TUNABLE(PF_N, 7); TUNABLE(PF_NS, 300);
TUNABLE(PS_DLY, 120); TUNABLE(Y_DLY, 700); TUNABLE(Y_DLY0, 1500);
constexpr int PRE = 3;
constexpr int WIN = 6;
constexpr int OFF_STG = r3(0), OFF_SCR = r3(1);
struct Params {
  CUtensorMap xn, ckv, wq, wk, wv, ctx_ld, wo, x, wd, wg, wu;
};

__global__ void __cluster_dims__(2, 1, 1) __launch_bounds__(384, 1)
fused_kernel(uint32_t zero, const __nv_bfloat16* __restrict__ x, __nv_bfloat16* g_kv, __nv_bfloat16* g_ctx, uint4* g_xr,
             __nv_bfloat16* __restrict__ out, __nv_bfloat16* g_xn, unsigned* g_cnt, const __nv_bfloat16* __restrict__ w_r,
             const __nv_bfloat16* __restrict__ wdown, const __nv_bfloat16* __restrict__ wq, const __grid_constant__ Params p) {
  extern __shared__ __align__(1024) uint8_t sp[];
  const uint32_t sb = s2u(sp);
  const uint32_t bar = sb + OFF_BAR;
  auto B = [&](int i) { return bar + 8 * i; };
  const int tid = threadIdx.x, warp = __shfl_sync(~0u, tid >> 5, 0), wg = warp >> 2, lane = tid & 31;
  const int cta = blockIdx.x, rank = cta & 1, cl = cta >> 1;
  const int mp = cl < 4 ? 1 : (cl < 36 ? (cl & 7) : (0x3207654 >> (4 * ((cl - 36) % 7))) & 7);
  const int gq = cl < 4 ? 4 + cl : (cl < 36 ? (cl - 4) >> 3 : 4 + (cl - 36) / 7);
  const int mt = 2 * mp + rank;
  const int qa = 15 - gq;
  const int ta = gq ? gq : 15, tb = 15 - ta;
  const int rid = mt * 8 + gq;
  const int fid = mt * 7 + gq;
  const bool ffn = gq < 7;
  TL(0, 0, warp == 4);
  auto load_pre = [&](int kb) {
    e_expect(B(B_FULL1 + kb), 3 * UNIT);
    tma_ld2(sb + kv_a(kb), &p.ckv, B(B_FULL1 + kb), kb * 64, mt * 128);
    tma_ld3(sb + kv_b(kb) + rank * UNIT, &p.wk, B(B_FULL1 + kb), 0, kb * 64, (gq + 8) * 4 + rank * 2);
    tma_ld3(sb + kv_b(kb) + UNIT - rank * UNIT, &p.wk, B(B_FULL1 + kb), 0, kb * 64, (gq + 8) * 4 + 2 - rank * 2);
  };
  if (warp == 0) {
    e_init(B(B_FULL1), 1);
    asm volatile("fence.mbarrier_init.release.cluster;" ::: "memory");
    TL(0, 16, true);
    load_pre(0);
    TL(0, 17, true);
#pragma unroll
    for (int kb = 1; kb < PRE; kb++) e_init(B(B_FULL1 + kb), 1);
  } else {
#pragma unroll 1
    for (int i = PRE - 1 + warp; i < B_NUM; i += 11) e_init(B(i), i >= B_EMPTY1 ? 16 : (i >= B_KE ? 8 : (i == B_WR ? 2 : 1)));
  }
  asm volatile("fence.mbarrier_init.release.cluster;" ::: "memory");
  cluster_arrive();
  const int rid0 = rid, warp0 = warp;
  if (wg == 0) {
    reg_dealloc<40>();
    if (warp == 0) {
      TL(0, 12, true);
#pragma unroll 1
      for (int kb = 1; kb < PRE; kb++) { load_pre(kb); TL(0, 12 + kb, true); }
      if (mt >= 2 * PRE) tma_pf3(&p.wk, 0, (mt >> 1) * 64, (gq + 8) * 4 + (mt & 1) * 2);
      if (gq >= PRE) tma_pf2(&p.ckv, gq * 64, mt * 128);
      TL(0, 15, true);
    }
    TL(0, 18, warp == 0);
    __syncwarp();
    cluster_wait();
    uint4* const xr = g_xr + rid * XR_SIZE;
    auto side_piece = [&](int c, int piece) {
      const uint32_t fb = B(B_WF + (c & 1));
      if (piece == 0) e_expect(fb, UNIT);
      tma_ld2_ef(sb + OFF_SIDE + (c & 1) * UNIT + piece * 4096, (piece & 2) ? &p.wg : &p.wu, fb, fid * 32, c * 128 + (piece & 1) * 64);
    };
    if (warp == 0) {
      {
        int st = 0; uint32_t ph = 1;
#pragma unroll 1
        for (int i = 0; i < 32; i++) {
          const int t = i >> 3, kb = i & 7;
          if (i >= PRE) {
            const uint32_t fb = B(B_FULL1 + st);
            mbar_wait_c(B(B_EMPTY1 + st), ph);
            e_expect(fb, t == 0 ? 3 * UNIT : 2 * UNIT);
            if (t == 0) tma_ld2(sb + kv_a(kb), &p.ckv, fb, kb * 64, mt * 128);
            tma_ld3_mc(sb + kv_b(st) + rank * UNIT, (t & 1) ? &p.wv : &p.wk, fb, 0, kb * 64, (gq + ((t >> 1) ^ 1) * 8) * 4 + rank * 2, 3);
          }
          if (i == LN_GO) e_arrive(B(B_LNGO));
          if (i == 12) { prefetch_tm(&p.wq); prefetch_tm(&p.xn); }
          if (kb == (t ? 0 : 4) && t < 3) tma_pf3((t & 1) ? &p.wk : &p.wv, 0, (mt >> 1) * 64, (gq + (((t + 1) >> 1) ^ 1) * 8) * 4 + (mt & 1) * 2);
          if (kb < 2 && t == 3) tma_pf3(&p.wq, 0, (gq + 8 * kb) * 64, mt * 2);
          if (++st == 3) { st = 0; ph ^= 1; }
        }
        prefetch_tm(&p.ctx_ld); prefetch_tm(&p.wo); prefetch_tm(&p.wd); prefetch_tm(&p.x); prefetch_tm(&p.wg); prefetch_tm(&p.wu);
        mbar_wait_c(B(B_DEP + 0), 0);
        uint32_t kpar = 7, vpar = 3;
        auto load_aw = [&](int kb, int head) {
          const uint32_t d = sb + q_aw(kb & 3), fb = B(B_FULLQ + (kb & 3));
          tma_ld2_mc(d + rank * 8192, &p.xn, fb, kb * 64, ta * 128 + rank * 64, 3);
          tma_ld3(d + UNIT, &p.wq, fb, 0, kb * 64, head * 2);
        };
        auto load_b = [&](int kb, uint32_t fb) { tma_ld2_mc(sb + q_b(kb & 3) + rank * 8192, &p.xn, fb, kb * 64, tb * 128 + rank * 64, 3); };
        auto load3 = [&](int kb, int s) {
          const uint32_t d = sb + r3(s), fb = B(B_FULL3 + s);
          e_expect(fb, SLOT);
          tma_ld2(d, &p.ctx_ld, fb, kb * 64, mt * 128);
          tma_ld3_mc(d + UNIT + rank * 8192, &p.wo, fb, 0, kb * 64, gq * 2 + rank, 3);
        };
#pragma unroll 1
        for (int half = 0; half < 2; half++) {
          const int head = mt + 16 * half;
#pragma unroll 1
          for (int kb = 2 * half; kb < 16; kb++) {
            if (kb >= 4) mbar_wait_c(B(B_EMPTYQ + (kb & 3)), ((kb >> 2) & 1) ^ 1);
            else if (half) mbar_wait_c(B(B_X + 2), 0);
            else if (kb > 0) mbar_wait_c(B(B_EMPTY1 + (kb + 1) % 3), kb == 1);
            e_expect(B(B_FULLQ + (kb & 3)), 3 * UNIT);
            load_aw(kb, head);
            load_b(kb, B(B_FULLQ + (kb & 3)));
          }
          mbar_wait_c(B(B_DEP + 1 + half), 0);
          const __nv_bfloat16* kt = g_kv + (size_t)head * 16 * KV_TILE;
          l2_prefetch(kt, SLOT);
          auto load_v = [&](int j) {
            const int r = j & 1;
            mbar_wait_c(B(B_VE + r), (vpar >> r) & 1);
            vpar ^= 1 << r;
            e_expect(B(B_VF + r), SLOT);
            bulk_ld(sb + v_slot(j), kt + (size_t)(512 + (j > qa ? 16 - j : j)) * KV_TILE, SLOT, B(B_VF + r));
          };
          int r = 0;
#pragma unroll 1
          for (int j = 0; j < 17; j++) {
            if (j < 2) mbar_wait_c(B(B_EMPTYQ + j), 1);
            if (j == 2) mbar_wait_c(B(B_KE), kpar & 1);
            mbar_wait_c(B(B_KE + r), (kpar >> r) & 1);
            kpar ^= 1 << r;
            e_expect(B(B_KF + r), SLOT);
            bulk_ld(sb + k_slot(j, r), kt + (j > qa ? 16 - j : j) * KV_TILE, SLOT, B(B_KF + r));
            if (++r == 3) r = 0;
            if (j == 2) mbar_wait_c(B(B_EMPTYQ + 3), 1);
            if (j != 1) load_v(j ? j - 1 : 0);
            if (half == 0) {
              if (j == 16) {
                tma_pf3(&p.wq, 0, (4 + gq) * 64, (mt + 16) * 2);
                tma_pf2(&p.xn, (4 + (mp & 3)) * 64, ((mp & 4) ? qa : gq) * 128 + rank * 64);
              }
            } else if (j >= 14) {
              tma_pf3(&p.wo, 0, (5 + mp + 8 * (16 - j)) * 64, gq * 2 + rank);
            } else if (ffn && j >= 5 && j < 13) {
              side_piece((j - 5) >> 2, (j - 5) & 3);
            }
          }
          mbar_wait_c(B(B_X + 0), half);
          if (half == 0) {
            for (int kb = 0; kb < 2; kb++) { e_expect(B(B_FULLQ + kb), 2 * UNIT); load_aw(kb, mt + 16); }
          } else {
            mbar_wait_c(B(B_DEP + 3), 0);
            load3(0, 0);
          }
          mbar_wait_c(B(B_X + 1), half);
          if (half) load3(1, 1);
          load_v(16);
          if (gq == 0) mbar_wait_c(B(B_X + 2), half);
          if (half == 0) { e_expect(B(B_FULLB), 2 * UNIT); load_b(0, B(B_FULLB)); load_b(1, B(B_FULLB)); }
        }
        st = 2; ph = 1;
#pragma unroll 1
        for (int kb = 2; kb < 64; kb++) {
          if (kb == 32) mbar_wait_c(B(B_DEP + 4), 0);
          if (kb >= 6) mbar_wait_c(B(B_EMPTY3 + st), ph);
          else if (kb == 3 || kb == 5) mbar_wait_c(B(B_X + (kb + 1) / 2), 1);
          load3(kb, st);
          if (++st == 6) { st = 0; ph ^= 1; }
          if (kb == PF_KB) e_arrive(B(B_PF));
          if (kb == SET_KB) e_arrive(B(B_SET));
          if (kb == 58) l2_prefetch(xr, XR_CAND * 16);
        }
        if (ffn) {
#pragma unroll 1
          for (int j = 0; j < 2; j++) {
            mbar_wait_c(B(B_EMPTY3 + 4 + j), 1);
            e_expect(B(B_FULL3 + 4 + j), SLOT);
            tma_ld3(sb + r3(4 + j), &p.wd, B(B_FULL3 + 4 + j), 0, fid * 32, 8 * j);
          }
        }
        const uint4* kp = g_xr + ((lane >> 1) * 8 + gq) * XR_SIZE + XR_KEY + (lane & 1) * 2;
        mbar_wait_c(B(B_OUT), 0);
        uint4 kv[2];
        poll_chunks(kv, kp, 1);
        const uint32_t a1 = max(kv[0].x, kv[0].z), a2 = max(min(kv[0].x, kv[0].z), max(kv[0].y, kv[0].w));
        const uint32_t b1 = max(kv[1].x, kv[1].z), b2 = max(min(kv[1].x, kv[1].z), max(kv[1].y, kv[1].w));
        const uint32_t k1 = max(a1, b1), k2 = max(min(a1, b1), max(a2, b2));
        const uint32_t m1 = __reduce_max_sync(~0u, k1);
        const uint32_t m2 = __reduce_max_sync(~0u, k1 == m1 ? k2 : k1);
        const uint32_t t0 = ~m1 & 0x7FFF, t1 = ~m2 & 0x7FFF;
        const uint32_t o0 = (t0 >> 7) * (8 * XR_SIZE * 16) + (t0 & 0x70) * 64, o1 = (t1 >> 7) * (8 * XR_SIZE * 16) + (t1 & 0x70) * 64 + ((t0 ^ t1) < 16 ? 256 : 0);
        asm volatile(ELECT "st.shared.v4.u32 [%0], {%1,%2,%3,%4};\n}" ::"r"(sb + OFF_MISC), "r"(o0), "r"(o1), "r"(m1), "r"(m2) : "memory");
        e_arrive(B(B_OUT2));
        if (rid == 127) { g_cnt[lane] = 0; g_cnt[32 + lane] = 0; }
      }
    } else {
      if (warp >= 2) {
#pragma unroll 1
        for (int i = tid - 64; i < XR_CAND; i += 64) xr[i] = make_uint4(~0u, ~0u, ~0u, ~0u);
        if (warp == 2) { __syncwarp(); if (lane == 0) mbar_arrive(B(B_WR)); }
      }
      if (warp == 3) {
        float ws = 0.f;
#pragma unroll 1
        for (int j = 0; j < 4; j++) {
          const uint4 q = __ldg(reinterpret_cast<const uint4*>(w_r) + j * 32 + lane);
          ws += bf_lo(q.x) + bf_hi(q.x) + bf_lo(q.y) + bf_hi(q.y) + bf_lo(q.z) + bf_hi(q.z) + bf_lo(q.w) + bf_hi(q.w);
        }
#pragma unroll
        for (int o = 16; o; o >>= 1) ws += __shfl_xor_sync(~0u, ws, o);
        uint2* tab = reinterpret_cast<uint2*>(sp + OFF_MISC + 512);
        tab[lane] = make_uint2(0x3F803F80u, 0x3F803F80u);
        tab[32 + lane] = __ldg(reinterpret_cast<const uint2*>(w_r + gq * 128) + lane);
        if (lane == 0) *reinterpret_cast<float*>(sp + OFF_MISC + 1024) = ws;
        __syncwarp();
        if (lane == 0) mbar_arrive(B(B_WR));
      }
      __syncwarp();
      mbar_wait_u(B(B_LNGO), 0);
#pragma unroll 1
      for (int r = warp == 2 ? 0 : (warp + 1) >> 1; r < 16; r += 3) {
        const uint4* src = reinterpret_cast<const uint4*>(x + (size_t)(cta * 16 + r) * DM) + lane;
        uint4 v[4];
#pragma unroll
        for (int j = 0; j < 4; j++) v[j] = __ldcs(src + j * 32);
        float a0 = 0.f, a1 = 0.f, b0 = 0.f, b1 = 0.f;
#pragma unroll
        for (int j = 0; j < 4; j++) {
          const uint32_t u[4] = {v[j].x, v[j].y, v[j].z, v[j].w};
#pragma unroll
          for (int i = 0; i < 4; i++) { const float a = bf_lo(u[i]), b = bf_hi(u[i]); a0 += a; a1 += b; b0 = fmaf(a, a, b0); b1 = fmaf(b, b, b1); }
        }
        a0 += a1; b0 += b1;
#pragma unroll
        for (int o = 16; o; o >>= 1) { a0 += __shfl_xor_sync(~0u, a0, o); b0 += __shfl_xor_sync(~0u, b0, o); }
        const float mean = a0 * (1.f / DM);
        float mb, inv;
        ln_round(mean, fmaxf(fmaf(b0, 1.f / DM, -mean * mean), 0.f), mb, inv);
        const uint32_t nm2 = pack_bf16(-mb, -mb);
        uint4* dst = reinterpret_cast<uint4*>(g_xn + (size_t)(cta * 16 + r) * DM) + lane;
#pragma unroll
        for (int j = 0; j < 4; j++) {
          dst[j * 32] = make_uint4(ln_apply(v[j].x, nm2, inv), ln_apply(v[j].y, nm2, inv), ln_apply(v[j].z, nm2, inv), ln_apply(v[j].w, nm2, inv));
          sched_fence();
        }
      }
      __syncwarp();
      if (lane == 0) {
        fence_gpu();
        red_add(&g_cnt[C_LN + (cta >> 3)], 1);
        TL(0, 20 + warp, true);
        if (warp == 3) {
          spin_until_ge<true>(&g_cnt[C_LN + gq], 24);
#pragma unroll 1
          for (int i = 0; i < 5; i++) {
            const int c = i == 0 ? C_LN + qa : (i < 3 ? C_KV + (i - 1) * 8 + mp : C_CTX + (i - 3) * 16 + mt);
            spin_until_ge<true>(&g_cnt[c], i == 0 ? 24 : 16);
            fence_async_all();
            mbar_arrive(B(B_DEP + i));
          }
        } else if (warp == 1) {
          mbar_wait(B(B_WR), 0);
#pragma unroll 1
          for (int i = 0; i < 6; i++) {
            const int c = i < 2 ? C_KV + gq + (i ^ 1) * 8 : C_CTX + ((i - 2) >> 1) * 16 + ((i & 1) ? tb : ta);
            mbar_wait(B(B_PUB + i), 0);
            fence_gpu();
            red_add(&g_cnt[c], 1);
          }
        }
      }
      __syncwarp();
      if (warp == 2) {
#pragma unroll 1
        for (int c = 2; c < WIN + 4; c++) {
          mbar_wait_u(B(B_WE + (c & 1)), ((c >> 1) & 1) ^ 1);
          if (c == WIN || c == WIN + 1) {
            e_expect(B(B_WF + (c & 1)), UNIT);
            tma_ld3_ef(sb + OFF_SIDE + (c & 1) * UNIT, &p.x, B(B_WF + (c & 1)), 0, mt * 128 + (c & 1) * 64, gq * 2);
          } else if (ffn) {
#pragma unroll 1
            for (int i = 0; i < 4; i++) { side_piece(c < WIN ? c : c - 2, i); __nanosleep(SIDE_NS); }
          }
        }
      } else if (warp == 1) {
        mbar_wait_u(B(B_SET), 0);
#pragma unroll 1
        for (int i = XR_CAND + lane; i < XR_SIZE; i += 32) { xr[i] = make_uint4(~0u, ~0u, ~0u, ~0u); __nanosleep(SET_NS); }
        __syncwarp();
        if (lane == 0) { fence_gpu(); mbar_arrive(B(B_SET2)); }
      } else {
        mbar_wait_u(B(B_PF), 0);
#pragma unroll 1
        for (int i = 0; i < PF_N; i++) {
          asm volatile("prefetch.global.L2 [%0];" ::"l"((const char*)wdown + (size_t)cta * 57344 + (i * 32 + lane) * 128));
          __nanosleep(PF_NS);
        }
      }
      __syncwarp();
      mbar_wait_u(B(B_OUT), 0);
      {
        const int sub = lane >> 4;
        const uint32_t src = sb + OFF_STG + ((lane & 15) >> 3) * 8192 + sub * 128;
        __nv_bfloat16* dst = out + (size_t)(mt * 128 + sub) * DM + gq * 128 + (lane & 15) * 8;
        auto ld = [&](int r, uint2& rs, uint4& v) {
          asm volatile("ld.shared.v2.u32 {%0,%1}, [%2];" : "=r"(rs.x), "=r"(rs.y) : "r"(sb + OFF_RSTAT + ((r + sub) & 127) * 8));
          v = lds128(src + ((r >> 6) & 1) * 16384 + (r & 63) * 128 + (((lane ^ (r + sub)) & 7) << 4));
        };
        uint2 rs; uint4 v;
        ld(2 * warp - 2, rs, v);
#pragma unroll 1
        for (int r = 2 * warp - 2; r < 128; r += 6) {
          const uint2 cs = rs; const uint4 c = v;
          ld(r + 6, rs, v);
          const float inv = __uint_as_float(cs.y);
          asm volatile("{\n.reg .pred p;\nsetp.ge.s32 p, %5, 0;\n@p st.global.v4.u32 [%0], {%1,%2,%3,%4};\n}" ::"l"(dst + (size_t)r * DM),
                       "r"(hadd2_bf(c.x, ln_apply(c.x, cs.x, inv))), "r"(hadd2_bf(c.y, ln_apply(c.y, cs.x, inv))),
                       "r"(hadd2_bf(c.z, ln_apply(c.z, cs.x, inv))), "r"(hadd2_bf(c.w, ln_apply(c.w, cs.x, inv))), "r"(cs.y) : "memory");
        }
      }
      TL(2, 25, warp == 1);
    }
    __syncwarp();
    cluster_arrive();
    cluster_wait();
  } else {
    reg_alloc<232>();
    const int rid_c = rid0 + zero, warp_c = warp0 + zero;
    const int lane = fresh_lane(), rid = rid_c, mt = rid >> 3, gq = rid & 7, qa = 15 - gq, ta = gq ? gq : 15, tb = 15 - ta;
    const int warp = warp_c, cw = warp - 4, w = cw >> 2;
    cluster_wait();
    auto publish = [&](int i) { __syncwarp(); e_arrive(B(B_PUB + i)); };
    auto release2 = [&](uint32_t b, bool cond = true) { mbar_arrive_both(b, lane, cond); };
    AtState s;
    const uint32_t dA = mk_desc(sb + w * 8192, 16);
    const uint32_t dW = mk_desc(sb, 8192);
    auto mma_kb = [&](float (&d)[64], uint32_t a, uint32_t b, int accum) {
      static_for<4>([&](auto k) { mma_n128_ss<1, k * 32, k * 2048>(d, dA + (a >> 4), dW + (b >> 4), k == 0 ? accum : 1); });
    };
    auto mma_kc = [&](float (&d)[64], auto a, auto b, int accum) {
      static_for<4>([&](auto k) { mma_n128_ss<1, decltype(a)::value + k * 32, decltype(b)::value + k * 2048>(d, dA, dW, k == 0 ? accum : 1); });
    };
    auto issue_q = [&](int kb, auto accum) {
      const int st = kb & 3;
      mbar_wait_c(B(B_FULLQ + st), (kb >> 2) & 1);
      wg_fence();
      mma_kb(s.S, q_aw(st), q_aw(st) + UNIT, accum);
      wg_commit();
      if (accum) {
        wg_wait<1>();
        release2(B(B_EMPTYQ + ((kb - 1) & 3)));
        wg_fence();
      }
      mma_kb(s.O, q_b(st), q_aw(st) + UNIT, accum);
      wg_commit();
    };
    {
      uint4 pk[16];
      __nv_bfloat16* pdst = g_kv;
      auto put = [&](int i) { __stcs(reinterpret_cast<uint4*>(pdst + (i & 1) * 256 + ((i >> 1) & 3) * 4096 + (i >> 3) * 16 * KV_TILE), pk[i]); };
      float acc1[128];
      TL(0, 1, warp == 4);
      int st = 0; uint32_t ph = 0;
      auto issue = [&](int kb, int accum) {
        mbar_wait_c(B(B_FULL1 + st), ph);
        wg_fence();
        static_for<4>([&](auto k) { mma_n256_ss<1, k * 32, k * 2048>(acc1, dA + (kv_a(kb) >> 4), dW + (kv_b(st) >> 4), k == 0 ? accum : 1); });
        wg_commit();
      };
#pragma unroll 1
      for (int t = 0; t < 4; t++) {
        issue(0, 0);
        TL(0, 2 + 2 * t, warp == 4);
        if (t > 0) { put(0); put(1); }
        int prev = st;
        if (++st == 3) { st = 0; ph ^= 1; }
#pragma unroll 1
        for (int kb = 1; kb < 8; kb++) {
          if (kb == 7 && w == 1) bar_sync(5, 256);
          issue(kb, 1);
          if (kb == 7 && w == 0) bar_arrive(5, 256);
          if (t > 0) {
#pragma unroll
            for (int i = 1; i < 8; i++) if (kb == i) { put(2 * i); put(2 * i + 1); }
            if (kb == 7 && t == 2) publish(0);
          }
          wg_wait<1>();
          TK(24 + t * 8 + kb - 1);
          release2(B(B_EMPTY1 + prev));
          prev = st;
          if (++st == 3) { st = 0; ph ^= 1; }
        }
        pdst = g_kv + (size_t)(((t & 1) * 32 + (gq + ((t >> 1) ^ 1) * 8) * 2) * 16 + mt) * KV_TILE + (cw * 16 + (lane >> 2)) * 32 + ((lane ^ (lane >> 3)) & 3) * 8;
        wg_wait<0>();
        TK(24 + t * 8 + 7);
        fence_regs(acc1);
        release2(B(B_EMPTY1 + prev));
        TL(0, 3 + 2 * t, warp == 4);
#pragma unroll
        for (int a = 0; a < 8; a++)
#pragma unroll
          for (int h = 0; h < 2; h++)
            pk[2 * a + h] = make_uint4(pack_bf16(acc1[16 * a + 2 * h], acc1[16 * a + 2 * h + 1]), pack_bf16(acc1[16 * a + 4 + 2 * h], acc1[16 * a + 5 + 2 * h]),
                                       pack_bf16(acc1[16 * a + 8 + 2 * h], acc1[16 * a + 9 + 2 * h]), pack_bf16(acc1[16 * a + 12 + 2 * h], acc1[16 * a + 13 + 2 * h]));
      }
      issue_q(0, IC<0>{});
      TL(0, 10, warp == 4);
      put(0); put(1);
#pragma unroll 1
      for (int kb = 1; kb < 8; kb++) {
        issue_q(kb, IC<1>{});
        TK(66 + kb - 1);
#pragma unroll
        for (int i = 1; i < 8; i++) if (kb == i) { put(2 * i); put(2 * i + 1); }
      }
      publish(1);
      TL(0, 11, warp == 4);
    }
    __nv_bfloat16* cdst;
    uint32_t redo = 0;
    auto put_ctx = [&](int i, bool cond) {
      asm volatile("{\n.reg .pred p;\nsetp.ne.u32 p, %5, 0;\n@p st.global.cs.v4.u32 [%0], {%1,%2,%3,%4};\n}" ::"l"(cdst + (i & 1) * 8 * NQ + (i >> 1) * 32),
                   "r"(s.P[4 * i]), "r"(s.P[4 * i + 1]), "r"(s.P[4 * i + 2]), "r"(s.P[4 * i + 3]), "r"((uint32_t)(cond && !(redo & 2))) : "memory");
    };
    {
      const int wrow = cw * 16;
      const uint32_t dK = mk_desc(sb, 16), dV = mk_desc(sb, 8192);
      uint32_t kph = 0, vph = 0;
      auto q_store = [&](const float (&d)[64]) {
        const int r0 = lane >> 2;
        const uint32_t a = sb + SLOT + (wrow + r0) * 128 + (((lane & 3) ^ (((r0 & 1) << 2) | (r0 >> 1))) << 4);
#pragma unroll
        for (int i = 0; i < 8; i++) {
          const float* o = d + 16 * (i >> 1) + 2 * (i & 1);
          asm volatile("st.shared.v4.u32 [%0], {%1,%2,%3,%4};" ::"r"((a ^ ((i & 2) << 5)) + (i >> 2) * UNIT + (i & 1) * 1024),
                       "r"(pack_bf16(o[0] * AT_C, o[1] * AT_C)), "r"(pack_bf16(o[4] * AT_C, o[5] * AT_C)),
                       "r"(pack_bf16(o[8] * AT_C, o[9] * AT_C)), "r"(pack_bf16(o[12] * AT_C, o[13] * AT_C)) : "memory");
        }
        __syncwarp();
      };
      auto q_load = [&](auto k0, auto k1) {
        const uint32_t a = sb + SLOT + (wrow + (lane & 15)) * 128 + (((lane >> 4) ^ (((lane & 1) << 2) | ((lane >> 1) & 3))) << 4);
#pragma unroll
        for (int k = k0; k < k1; k++)
          asm volatile("ldmatrix.sync.aligned.m8n8.x4.shared.b16 {%0,%1,%2,%3}, [%4];"
                       : "=r"(s.Q[4 * k]), "=r"(s.Q[4 * k + 1]), "=r"(s.Q[4 * k + 2]), "=r"(s.Q[4 * k + 3]) : "r"((a ^ ((k & 3) << 5)) + (k >> 2) * UNIT) : "memory");
      };
      auto q_load_if = [&](auto k, bool cond, float after) {
        const uint32_t a = sb + SLOT + (wrow + (lane & 15)) * 128 + (((lane >> 4) ^ (((lane & 1) << 2) | ((lane >> 1) & 3))) << 4);
        asm volatile("{\n.reg .pred p;\nsetp.ne.u32 p, %5, 0;\n@p ldmatrix.sync.aligned.m8n8.x4.shared.b16 {%0,%1,%2,%3}, [%4];\n}"
                     : "+r"(s.Q[4 * k]), "+r"(s.Q[4 * k + 1]), "+r"(s.Q[4 * k + 2]), "+r"(s.Q[4 * k + 3])
                     : "r"((a ^ ((k & 3) << 5)) + (k >> 2) * UNIT + (__float_as_uint(after) >> 31)), "r"((uint32_t)cond) : "memory");
      };
      auto issue_s = [&](uint32_t dk) {
        mma_n128_rs0<0>(s.S, s.Q, dk);
        static_for<7>([&](auto i) { constexpr int k = i + 1; mma_n128_rs<0, (k >> 1) * 8192 + (k & 1) * 32>(s.S, s.Q + 4 * k, dk, 1); });
        wg_commit();
      };
      auto wait_v = [&](int jv) {
        mbar_wait_c(B(B_VF + (jv & 1)), (vph >> (jv & 1)) & 1);
        vph ^= 1 << (jv & 1);
      };
      auto issue_pva = [&](int jv, int accum) {
        wg_fence();
        static_for<4>([&](auto k) { mma_n128_rs<1, k * 1024>(s.O, s.P + 4 * k, dV + (v_slot(jv) >> 4), k == 0 ? accum : 1); });
        wg_commit();
      };
      auto issue_pvb = [&](int jv, bool upper) {
        if (upper) {
          wg_fence();
          static_for<4>([&](auto k) { mma_n128_rs<1, (k + 4) * 1024>(s.O, s.P + 16 + 4 * k, dV + (v_slot(jv) >> 4), 1); });
          wg_commit();
        } else {
          asm volatile("wgmma.fence.sync.aligned;\nwgmma.commit_group.sync.aligned;" ::: "memory");
        }
      };
      auto issue_pv = [&](int jv, int accum, bool upper) { wait_v(jv); issue_pva(jv, accum); issue_pvb(jv, upper); };
      if (w == 1) bar_arrive(1, 256);
#pragma unroll 1
      for (int half = 0; half < 2; half++) {
        const int head = mt + 16 * half;
        redo = 0;
        float inv[2];
        auto ep_prep = [&]() {
          float l0 = s.l[0] + s.l[1], l1 = s.l[2] + s.l[3];
          l0 += __shfl_xor_sync(~0u, l0, 1); l1 += __shfl_xor_sync(~0u, l1, 1);
          l0 += __shfl_xor_sync(~0u, l0, 2); l1 += __shfl_xor_sync(~0u, l1, 2);
          asm("rcp.approx.ftz.f32 %0, %1;" : "=f"(inv[0]) : "f"(l0));
          asm("rcp.approx.ftz.f32 %0, %1;" : "=f"(inv[1]) : "f"(l1));
          return __any_sync(~0u, !(fminf(l0, l1) >= L_MIN && l0 + l1 <= L_MAX));
        };
        auto ep_out = [&](auto i0, auto i1) {
          __nv_bfloat16* dst = g_ctx + (size_t)(ta * 128 + wrow + (lane >> 2)) * NQ + head * 128 + (lane & 3) * 8;
#pragma unroll
          for (int i = i0; i < i1; i++) {
            const float* o = s.O + 16 * (i >> 1) + 2 * (i & 1);
            const float c = inv[i & 1];
            asm volatile("st.global.cs.v4.u32 [%0], {%1,%2,%3,%4};" ::"l"(dst + (i & 1) * 8 * NQ + (i >> 1) * 32), "r"(pack_bf16(o[0] * c, o[1] * c)),
                         "r"(pack_bf16(o[4] * c, o[5] * c)), "r"(pack_bf16(o[8] * c, o[9] * c)), "r"(pack_bf16(o[12] * c, o[13] * c)) : "memory");
          }
        };
        auto ep_rest = [&]() {
          ep_out(IC<EP1>{}, IC<8>{});
          if (!__any_sync(~0u, redo)) publish(2 + 2 * half);
          fence_regs(s.O);
        };
#pragma unroll 1
        for (int kb = 8; kb < 14; kb++) {
          issue_q(kb, IC<1>{});
          TK(66 + half * 24 + kb - 1);
        }
        TL(1, 20 * half + 0, warp == 4);
        mbar_wait_c(B(B_FULLQ + 2), 1);
        mbar_wait_c(B(B_FULLQ + 3), 1);
        bar_sync(1 + w, 256);
        wg_fence();
        mma_kc(s.S, IC<q_aw(2)>{}, IC<q_aw(2) + UNIT>{}, 1);
        wg_commit();
        wg_wait<1>();
        TK(66 + half * 24 + 13);
        release2(B(B_EMPTYQ + 1));
        wg_fence();
        mma_kc(s.S, IC<q_aw(3)>{}, IC<q_aw(3) + UNIT>{}, 1);
        wg_commit();
        bar_arrive(2 - w, 256);
        bar_sync(6 + w, 128);
        wg_wait<0>();
        TK(66 + half * 24 + 14);
        fence_regs(s.S);
        q_store(s.S);
        q_load(IC<0>{}, IC<8>{});
        TL(1, 20 * half + 1, warp == 4);
        TC(w, 17 * half, 0);
        mbar_wait_c(B(B_KF), kph & 1);
        kph ^= 1;
        bar_sync(1 + w, 256);
        TC(w, 17 * half, 2);
        fence_regs(s.O); fence_regs(s.Q);
        wg_fence();
        issue_s(dK);
        mma_kc(s.O, IC<q_b(2)>{}, IC<q_aw(2) + UNIT>{}, 1);
        mma_kc(s.O, IC<q_b(3)>{}, IC<q_aw(3) + UNIT>{}, 1);
        wg_commit();
        bar_arrive(2 - w, 256);
        wg_wait<1>();
        TC(w, 17 * half, 4);
        fence_regs(s.S);
        e_arrive(B(B_KE));
        s.l[0] = s.l[1] = s.l[2] = s.l[3] = 0.f;
        at_exp<0, 48>(s);
        at_pack<0, 22>(s);
        sched_fence();
        wg_wait<0>();
        fence_regs(s.O); fence_regs(s.Q);
        release2(B(B_EMPTYQ + 2)); release2(B(B_EMPTYQ + 3));
        at_exp<48, 64>(s);
        at_pack<22, 32>(s);
        q_store(s.O);
        TL(1, 20 * half + 2, warp == 4);
        int kr = 1;
        bool kok = false;
        inv[0] = inv[1] = 0.f;
        const int db = gq ? qa : 16;
#pragma unroll 1
        for (int j = 1; j < 17; j++) {
          const bool diag = j == ta || j == db;
          TC(w, j + 17 * half, 0);
          if (!kok) mbar_wait_c(B(B_KF + kr), (kph >> kr) & 1);
          kph ^= 1 << kr;
          if (j == ta + 2) ep_out(IC<0>{}, IC<EP1>{});
          bar_sync(1 + w, 256);
          TC(w, j + 17 * half, 2);
          fence_regs(s.O); fence_regs(s.P); fence_regs(s.Q);
          const uint32_t ke = B(B_KE + kr), dk = dK + (k_slot(j, kr) >> 4);
          if (++kr == 3) kr = 0;
          auto issue_rest = [&](auto trimmed) {
            TC(w, j + 17 * half, 1);
            if (j == ta + 1) {
              if (ep_prep()) redo = 1;
              s.l[0] = s.l[1] = s.l[2] = s.l[3] = 0.f;
            }
            if (!trimmed && j == ta + 2) ep_rest();
            TC(w, j + 17 * half, 3);
            issue_pv(j - 1, j != 1 && j != ta + 2, w == 1 || (j != ta + 1 && j != db + 1));
            bar_arrive(2 - w, 256);
          };
          auto s_done = [&](auto n) {
            wg_wait<2>();
            TC(w, j + 17 * half, 4);
            fence_part<0, n>(s.S); fence_regs(s.Q);
            e_arrive(ke);
            release2(B(B_X + j - 14), j == 14 || j == 15);
          };
          auto pv_half = [&]() { sched_fence(); wg_wait<1>(); fence_regs(s.P); };
          auto pv_done = [&]() {
            sched_fence();
            wg_wait<0>();
            fence_regs(s.O); fence_regs(s.P);
            e_arrive(B(B_VE + ((j - 1) & 1)));
            release2(B(B_X + 2), j == 16);
            kok = mbar_test(B(B_KF + kr), (kph >> kr) & 1);
          };
          if (diag && w == 0) {
            wg_fence();
            static_for<8>([&](auto k) { mma_n64_rs<0, (k >> 1) * 8192 + (k & 1) * 32, k != 0>(s.S, s.Q + 4 * k, dk); });
            wg_commit();
            issue_rest(IC<1>{});
            s_done(IC<32>{});
            at_mask<0>(s, wrow, lane);
            pv_half();
            static_for<8>([&](auto k) {
              at_exp<4 * k, 4 * k + 4>(s);
              q_load_if(k, j == ta, s.S[4 * k]);
            });
            at_pack<0, 16>(s);
            pv_done();
          } else {
            wg_fence();
            issue_s(dk);
            issue_rest(IC<0>{});
            if (!diag) {
              s_done(IC<64>{});
              at_exp<0, 24>(s);
              pv_half();
              at_exp<24, 48>(s);
              at_pack<0, 16>(s);
              pv_done();
              at_exp<48, 64>(s);
              at_pack<16, 32>(s);
            } else {
              s_done(IC<64>{});
              at_mask<8>(s, wrow - 64, lane);
              static_for<8>([&](auto k) {
                at_exp<7 * k, 7 * k + 7>(s);
                q_load_if(k, j == ta, s.S[7 * k + 3]);
                if (k == 2) pv_half();
                if (k == 5) { at_pack<0, 16>(s); pv_done(); }
              });
              at_exp<56, 64>(s);
              at_pack<16, 32>(s);
            }
          }
          TL(1, 20 * half + 2 + j, warp == 4);
        }
        TK(84 + half * 24);
        mbar_wait_c(B(half ? B_FULL3 : B_FULLQ), 0);
        if (gq == 0) ep_out(IC<0>{}, IC<EP1>{});
        bar_sync(1 + w, 256);
        fence_regs(s.O); fence_regs(s.P);
        wg_fence();
        mma_n128_ss0<1, 0, UNIT>(s.S, dA, dW);
        static_for<3>([&](auto k) { mma_n128_ss<1, k * 32 + 32, UNIT + k * 2048 + 2048>(s.S, dA, dW, 1); });
        mbar_wait_c(B(half ? B_FULL3 + 1 : B_FULLQ + 1), 0);
        wg_fence();
        mma_kb(s.S, (2 + half) * SLOT, (2 + half) * SLOT + UNIT, 1);
        wg_commit();
        TK(85 + half * 24);
        if (gq == 0) ep_rest();
        issue_pv(16, gq != 0, w == 1 || gq != 0);
        if (w == 0 || half == 0) bar_arrive(2 - w, 256);
        TK(86 + half * 24);
        wg_wait<2>();
        release2(B(B_EMPTY3), half); release2(B(B_EMPTY3 + 1), half);
        if (ep_prep()) redo |= 2;
        sched_fence();
        wg_wait<0>();
        TK(87 + half * 24);
        fence_regs(s.S);
        fence_regs(s.O);
        e_arrive(B(B_VE));
        release2(B(B_X + 3));
        fence_regs(s.P);
        {
          const int r = fresh_lane();
          cdst = g_ctx + (size_t)(tb * 128 + wrow + (r >> 2)) * NQ + head * 128 + (r & 3) * 8;
        }
#pragma unroll
        for (int i = 0; i < 32; i++) {
          const float* o = s.O + 16 * (i >> 3) + 2 * ((i >> 2) & 1) + 4 * (i & 3);
          s.P[i] = pack_bf16(o[0] * inv[(i >> 2) & 1], o[1] * inv[(i >> 2) & 1]);
        }
        fence_regs(s.P);
        if (__builtin_expect(__any_sync(~0u, redo != 0), 0)) {
#pragma unroll
          for (int i = 0; i < 8; i++) put_ctx(i, true);
#pragma unroll 1
          for (int t = 0; t < 2; t++) {
            if (__any_sync(~0u, (redo >> t) & 1)) slow_rows(wq, head, (t ? tb : ta) * 128 + wrow);
          }
          if (__any_sync(~0u, redo & 1)) publish(2 + 2 * half);
#pragma unroll
          for (int i = 0; i < 32; i++) s.P[i] = 0;
          redo = 2;
        }
        TL(1, 20 * half + 19, warp == 4);
        TK(88 + half * 24);
        if (half) break;
        mbar_wait_c(B(B_FULLB), 0);
        TK(89);
        wg_fence();
        mma_n128_ss0<1, q_b(0), UNIT>(s.O, dA, dW);
        static_for<3>([&](auto k) { mma_n128_ss<1, q_b(0) + k * 32 + 32, UNIT + k * 2048 + 2048>(s.O, dA, dW, 1); });
        wg_commit();
        mma_kc(s.O, IC<q_b(1)>{}, IC<q_aw(1) + UNIT>{}, 1);
        wg_commit();
        wg_wait<1>();
        release2(B(B_EMPTYQ));
        put_ctx(0, true);
#pragma unroll 1
        for (int kb = 2; kb < 8; kb++) {
          issue_q(kb, IC<1>{});
          TK(90 + kb - 1);
#pragma unroll
          for (int i = 1; i < 8; i++) put_ctx(i, kb == (i < 7 ? i + 1 : 7));
        }
        publish(3);
      }
    }
    const int rid_ = rid + zero, cw_ = cw + zero;
    {
    const int lane = fresh_lane(), rid = rid_, mt = rid >> 3, gq = rid & 7, cw = cw_, w = cw >> 2, ct = cw * 32 + lane;
    const int fid = mt * 7 + gq;
    const bool ffn = gq < 7;
    const uint32_t stg = sb + OFF_STG + w * 16384 + (cw & 3) * 2048;
    const int wr_ = w * 64 + (lane & 7) + (lane >> 4) * 8;
    const uint32_t wl = sb + ((lane >> 3) & 1) * 8192 + wr_ * 64 + (((cw ^ (wr_ >> 1)) & 3) << 4);
    __syncwarp();
    float (&acc)[64] = s.S;
    uint32_t wf[128];
    auto grab = [&](auto c, uint32_t off) {
#pragma unroll
      for (int m = 0; m < 4; m++)
        asm volatile("ldmatrix.sync.aligned.m8n8.x4.trans.shared.b16 {%0,%1,%2,%3}, [%4];"
                     : "=r"(wf[16 * c + 4 * m]), "=r"(wf[16 * c + 4 * m + 1]), "=r"(wf[16 * c + 4 * m + 2]), "=r"(wf[16 * c + 4 * m + 3])
                     : "r"(wl + off + m * 1024) : "memory");
    };
    const int r0 = lane >> 2;
    uint32_t hp[32], rt[16];
    {
      uint32_t dep = 0;
      auto hand = [&](uint32_t b, int n) {
        asm volatile("{\n.reg .pred p;\n.reg .b32 t;\nsetp.lt.u32 p, %1, %4;\nmad.lo.u32 t, %2, %3, %0;\n@p mbarrier.arrive.shared::cta.b64 _, [t];\n}"
                     ::"r"(b + 8 * lane), "r"(lane), "r"(dep), "r"(zero), "r"(n) : "memory");
      };
      auto kblock = [&](auto st, uint32_t ph, bool rel) {
        mbar_wait_c(B(B_FULL3 + st), ph);
        wg_fence();
        mma_kc(acc, IC<r3(st)>{}, IC<r3(st) + UNIT>{}, 1);
        wg_commit();
        wg_wait<1>();
        release2(B(B_EMPTY3 + (st + 5) % 6), rel);
      };
      auto ldsm_if = [&](uint32_t* r, uint32_t a, bool c, auto trans) {
        if (trans) asm volatile("{\n.reg .pred p;\nsetp.ne.u32 p, %5, 0;\n@p ldmatrix.sync.aligned.m8n8.x4.trans.shared.b16 {%0,%1,%2,%3}, [%4];\n}"
                                : "+r"(r[0]), "+r"(r[1]), "+r"(r[2]), "+r"(r[3]) : "r"(a), "r"((uint32_t)c) : "memory");
        else asm volatile("{\n.reg .pred p;\nsetp.ne.u32 p, %5, 0;\n@p ldmatrix.sync.aligned.m8n8.x4.shared.b16 {%0,%1,%2,%3}, [%4];\n}"
                          : "+r"(r[0]), "+r"(r[1]), "+r"(r[2]), "+r"(r[3]) : "r"(a), "r"((uint32_t)c) : "memory");
      };
#pragma unroll
      for (int i = 0; i < 48; i++) wf[i] = 0;
#pragma unroll 1
      for (int lap = 0; lap < 3; lap++) {
        kblock(IC<2>{}, lap & 1, lap > 0);
#pragma unroll
        for (int i = 0; i < 3; i++) put_ctx(3 * i, lap == i);
        kblock(IC<3>{}, lap & 1, true);
        if (ffn) mbar_wait_c(B(B_WF + (lap & 1)), lap >> 1);
#pragma unroll
        for (int i = 0; i < 12; i++) ldsm_if(wf + 4 * i, wl + OFF_SIDE + ((i >> 2) & 1) * UNIT + (i & 3) * 1024, lap == (i >> 2), IC<1>{});
        kblock(IC<4>{}, lap & 1, true);
        sched_fence();
        dep = 0;
#pragma unroll
        for (int i = 0; i < 12; i++) dep ^= wf[4 * i];
        hand(B(B_WE + (lap & 1)), 1);
#pragma unroll
        for (int i = 0; i < 3; i++) put_ctx(3 * i + 1, lap == i);
        kblock(IC<5>{}, lap & 1, true);
        if (lap == 2) publish(5);
        kblock(IC<0>{}, (lap & 1) ^ 1, true);
#pragma unroll
        for (int i = 0; i < 2; i++) put_ctx(3 * i + 2, lap == i);
        kblock(IC<1>{}, (lap & 1) ^ 1, true);
        TL(2, 40 + lap, warp == 4);
      }
#pragma unroll
      for (int i = 48; i < 96; i++) wf[i] = 0;
#pragma unroll
      for (int i = 0; i < 32; i++) { hp[i] = 0; rt[i >> 1] = 0; }
      const uint32_t xa = sb + OFF_SIDE + w * UNIT + (cw & 3) * 2048 + (lane & 15) * 128 + (((lane >> 4) ^ (lane & 7)) << 4);
#pragma unroll 1
      for (int lap = 3; lap < 11; lap++) {
        kblock(IC<2>{}, lap & 1, true);
        kblock(IC<3>{}, lap & 1, true);
        if (lap == 10) break;
        if (lap < WIN) {
          if (ffn) mbar_wait_c(B(B_WF + (lap & 1)), (lap >> 1) & 1);
#pragma unroll
          for (int i = 12; i < 24; i++) ldsm_if(wf + 4 * i, wl + OFF_SIDE + ((i >> 2) & 1) * UNIT + (i & 3) * 1024, lap == (i >> 2), IC<1>{});
        } else if (lap == WIN) {
          mbar_wait_c(B(B_WF), ffn ? (WIN >> 1) & 1 : 0);
          mbar_wait_c(B(B_WF + 1), ffn ? (WIN >> 1) & 1 : 0);
#pragma unroll
          for (int j = 0; j < 8; j++) ldsm_if(hp + 4 * j, (xa ^ ((j & 3) << 5)) + (j >> 2) * 8192, true, IC<0>{});
        } else if (lap == 9) {
          mbar_wait_c(B(B_WR), 0);
          mbar_wait_c(B(B_SET2), 0);
#pragma unroll
          for (int j = 0; j < 4; j++) ldsm_if(rt + 4 * j, sb + OFF_MISC + 512 + (lane & 1) * 256 + (lane >> 3) * 16 + j * 64, true, IC<0>{});
        }
        kblock(IC<4>{}, lap & 1, true);
        sched_fence();
        dep = 0;
#pragma unroll
        for (int i = 0; i < 20; i++) dep ^= i < 12 ? wf[48 + 4 * i] : hp[4 * (i - 12)];
        hand(B(B_WE + (lap < WIN ? lap & 1 : 0)), lap < WIN ? 1 : (lap == WIN ? 2 : 0));
        kblock(IC<5>{}, lap & 1, true);
        kblock(IC<0>{}, (lap & 1) ^ 1, true);
        kblock(IC<1>{}, (lap & 1) ^ 1, true);
        TL(2, 40 + lap, warp == 4);
      }
    }
    uint4* const xr = g_xr + rid * XR_SIZE;
    uint4* const psd = xr + XR_PS + cw * 16 + r0;
    settle(psd, zero);
    sched_fence();
    wg_wait<0>();
    fence_regs(acc);
    TL(2, 10, warp == 4);
    {
      float d[4] = {0.f, 0.f, 0.f, 0.f}, qa[4] = {0.f, 0.f, 0.f, 0.f}, qb[4] = {0.f, 0.f, 0.f, 0.f};
#pragma unroll
      for (int j = 0; j < 16; j++) {
        hp[2 * j] = hadd2_bf(hp[2 * j], pack_bf16(acc[4 * j], acc[4 * j + 1]));
        hp[2 * j + 1] = hadd2_bf(hp[2 * j + 1], pack_bf16(acc[4 * j + 2], acc[4 * j + 3]));
        if (j & 1) {
          mma16816(d, hp[2 * j - 2], hp[2 * j - 1], hp[2 * j], hp[2 * j + 1], rt[j - 1], rt[j]);
          mma16816(qa, hp[2 * j - 2], hp[2 * j - 1], hp[2 * j], hp[2 * j + 1], hp[2 * j - 2], hp[2 * j]);
          mma16816(qb, hp[2 * j - 2], hp[2 * j - 1], hp[2 * j], hp[2 * j + 1], hp[2 * j - 1], hp[2 * j + 1]);
        }
      }
      asm volatile("{\n.reg .pred p;\nsetp.eq.u32 p, %7, %8;\n@p st.global.cg.v4.f32 [%0], {%1,%2,%3,%3};\n@p st.global.cg.v4.f32 [%0 + 128], {%4,%5,%6,%6};\n}"
                   ::"l"(psd), "f"(d[0]), "f"(d[1]), "f"((r0 & 1) ? qa[1] : qa[0]), "f"(d[2]), "f"(d[3]), "f"((r0 & 1) ? qb[3] : qb[2]),
                   "r"(lane & 3), "r"(r0 >> 1) : "memory");
      sched_fence();
    }
    mbar_wait_c(B(B_EMPTY3), 0);
    __syncwarp();
    stage_store_128(stg, lane, hp);
    TL(2, 11, warp == 4);
    __syncwarp();
    uint4 cout;
    uint32_t ckey;
    {
      const float wsum = *reinterpret_cast<const float*>(sp + OFF_MISC + 1024);
      const uint4* pp = g_xr + (mt * 8 + (ct & 1) * 4) * XR_SIZE + XR_PS + (ct >> 1);
      uint2* kd = reinterpret_cast<uint2*>(xr + XR_KEY) + cw;
      const uint32_t tok = 0x7FFFu - (mt * 128 + (ct >> 1));
      settle(pp, zero); settle(kd, zero); settle(tok, zero);
      spin_clk(PS_DLY);
      float s1, s2, s3;
#pragma unroll 1
      for (int n = 0; n < 0x400000; n++) {
        float4 z[4];
#pragma unroll
        for (int i = 0; i < 4; i++)
          asm volatile("ld.relaxed.gpu.global.v4.f32 {%0,%1,%2,%3}, [%4];" : "=f"(z[i].x), "=f"(z[i].y), "=f"(z[i].z), "=f"(z[i].w) : "l"(pp + i * XR_SIZE) : "memory");
        s1 = (z[0].x + z[1].x) + (z[2].x + z[3].x); s3 = (z[0].y + z[1].y) + (z[2].y + z[3].y); s2 = (z[0].z + z[1].z) + (z[2].z + z[3].z);
        const float t = s1 + s2 + s3;
        s1 += __shfl_xor_sync(~0u, s1, 1); s2 += __shfl_xor_sync(~0u, s2, 1); s3 += __shfl_xor_sync(~0u, s3, 1);
        if (__all_sync(~0u, t == t)) break;
        uint32_t m = 0;
#pragma unroll
        for (int i = 0; i < 4; i++) m = max(max(m, __float_as_uint(z[i].x)), max(__float_as_uint(z[i].y), __float_as_uint(z[i].z)));
        if (__all_sync(~0u, m != 0xFFFFFFFFu)) break;
      }
      TL(2, 12, warp == 4);
      const float mean = s1 * (1.f / DM);
      float mb, inv;
      ln_round(mean, fmaxf(fmaf(s2, 1.f / DM, -mean * mean), 0.f), mb, inv);
      const uint32_t u = pack_bf16(0.f, fmaf(s3 - mb * wsum, inv, 0.f));
      const uint32_t key = ((u ^ (((int)u >> 31) | 0x80000000u)) & 0xFFFF0000u) | tok;
      const uint32_t c1 = __reduce_max_sync(~0u, key);
      const uint32_t c2 = __reduce_max_sync(~0u, key == c1 ? 0u : key);
      asm volatile(ELECT "st.global.cg.v2.u32 [%0], {%1,%2};\n}" ::"l"(kd), "r"(c1), "r"(c2) : "memory");
      sched_fence();
      const uint32_t nm2 = pack_bf16(-mb, -mb);
      if (!(ct & 1)) *reinterpret_cast<uint2*>(sp + OFF_RSTAT + (ct >> 1) * 8) = make_uint2(nm2, __float_as_uint(inv) | (key >= c2 ? 0x80000000u : 0u));
      ckey = (lane >> 4) ? c2 : c1;
      const int row = (0x7FFF - (ckey & 0x7FFF)) & 15;
      const uint32_t rn = __shfl_sync(~0u, nm2, row * 2);
      const float ri = __shfl_sync(~0u, inv, row * 2);
      const uint4 v = lds128(stg + ((lane & 15) >> 3) * 8192 + row * 128 + (((lane & 7) ^ (row & 7)) << 4));
      const uint4 n = make_uint4(ln_apply(v.x, rn, ri), ln_apply(v.y, rn, ri), ln_apply(v.z, rn, ri), ln_apply(v.w, rn, ri));
      __stcg(xr + XR_CAND + cw * 64 + 32 + lane, n);
      __stcg(xr + XR_CAND + cw * 64 + lane, v);
      cdst = out + (size_t)(0x7FFF - (ckey & 0x7FFF)) * DM + gq * 128 + (lane & 15) * 8;
      cout = make_uint4(hadd2_bf(v.x, n.x), hadd2_bf(v.y, n.y), hadd2_bf(v.z, n.z), hadd2_bf(v.w, n.w));
    }
    publish(B_OUT - B_PUB);
    cluster_arrive();
    TL(2, 13, warp == 4);
    uint32_t wd[16][4];
    if (ffn) {
      static_for<2>([&](auto i) {
        mbar_wait_b(B(B_WF + i), ((WIN >> 1) & 1) ^ 1);
        grab(IC<WIN + i>{}, OFF_SIDE + i * UNIT);
      });
      mbar_wait_b(B(B_FULL3 + 4 + w), 0);
#pragma unroll
      for (int i = 0; i < 16; i++) {
        const int k = (i & 1) * 16 + (lane & 7) + (lane >> 4) * 8;
        asm volatile("ldmatrix.sync.aligned.m8n8.x4.trans.shared.b16 {%0,%1,%2,%3}, [%4];"
                     : "=r"(wd[i][0]), "=r"(wd[i][1]), "=r"(wd[i][2]), "=r"(wd[i][3])
                     : "r"(sb + r3(4) + w * SLOT + (2 * (cw & 3) + (i >> 3)) * 4096 + k * 128 + (((2 * ((i >> 1) & 3) + ((lane >> 3) & 1)) ^ (lane & 7)) << 4)) : "memory");
      }
    }
    const int fc = 16 * (rid >> 1) + 4 * (rid & 1) + (lane & 3) + 8 * (lane >> 4), ft = (lane >> 3) & 1;
    const char* pc = reinterpret_cast<const char*>(g_xr + ((ct & 127) >> 4) * XR_SIZE + XR_CAND + 32 + (ct & 15));
    const char* pf = reinterpret_cast<const char*>(g_xr + (fc >> 7) * XR_SIZE + XR_CAND) + (fc & 127) * 2;
    const uint32_t xs = sb + OFF_SCR + w * 2112 + ((ct & 127) >> 2) * 64 + (((ct >> 3) & 3) << 4) + (ct & 3) * 4;
    const uint32_t xb = sb + OFF_SCR + (r0 & 1) * 2112 + w * 128 + (((lane ^ w) & 3) << 4);
    settle(pc, zero); settle(pf, zero); settle(cdst, zero); settle(xs, zero); settle(xb, zero);
    mbar_wait_b(B(B_OUT2), 0);
    const uint4 top = lds128(sb + OFF_MISC);
    TL(2, 14, warp == 4);
    uint32_t fh, fn;
    {
      pc += w ? top.y : top.x;
      pf += ft ? top.y : top.x;
      uint4 v;
#pragma unroll 1
      for (int n = 0; n < 0x400000; n++) {
        asm volatile("ld.relaxed.gpu.global.v4.u32 {%0,%1,%2,%3}, [%4];" : "=r"(v.x), "=r"(v.y), "=r"(v.z), "=r"(v.w) : "l"(pc) : "memory");
        asm volatile("ld.relaxed.gpu.global.u16 %0, [%1];" : "=r"(fh) : "l"(pf) : "memory");
        asm volatile("ld.relaxed.gpu.global.u16 %0, [%1 + 512];" : "=r"(fn) : "l"(pf) : "memory");
        asm volatile("st.shared.u32 [%0], %1;" ::"r"(xs), "r"(v.x) : "memory");
        asm volatile("st.shared.u32 [%0], %1;" ::"r"(xs ^ 16), "r"(v.y) : "memory");
        asm volatile("st.shared.u32 [%0], %1;" ::"r"(xs ^ 32), "r"(v.z) : "memory");
        asm volatile("st.shared.u32 [%0], %1;" ::"r"(xs ^ 48), "r"(v.w) : "memory");
        if (__all_sync(~0u, max(max(v.x, v.y), max(v.z, v.w)) != 0xFFFFFFFFu && max(fh, fn) != 0xFFFFu)) break;
      }
    }
    bar_sync(3, 256);
    asm volatile("{\n.reg .pred p;\nsetp.lt.u32 p, %5, %6;\n@p st.global.v4.u32 [%0], {%1,%2,%3,%4};\n}" ::"l"(cdst), "r"(cout.x), "r"(cout.y), "r"(cout.z),
                 "r"(cout.w), "r"(ckey), "r"(top.w) : "memory");
    if (ffn) {
      TL(2, 15, warp == 4);
      float d[4][4] = {};
      auto xl = [&](int i) { return lds128((xb ^ ((i & 2) << 4)) + (i >> 1) * 256 + (i & 1) * 64); };
      uint4 b0 = xl(0), b1 = xl(1);
#pragma unroll
      for (int i = 0; i < 16; i += 2) {
        const uint4 c0 = b0, c1 = b1;
        if (i < 14) { b0 = xl(i + 2); b1 = xl(i + 3); }
        mma16816(d[0], wf[8 * i], wf[8 * i + 1], wf[8 * i + 2], wf[8 * i + 3], c0.x, c0.y);
        mma16816(d[1], wf[8 * i + 4], wf[8 * i + 5], wf[8 * i + 6], wf[8 * i + 7], c0.z, c0.w);
        mma16816(d[2], wf[8 * i + 8], wf[8 * i + 9], wf[8 * i + 10], wf[8 * i + 11], c1.x, c1.y);
        mma16816(d[3], wf[8 * i + 12], wf[8 * i + 13], wf[8 * i + 14], wf[8 * i + 15], c1.z, c1.w);
      }
      const float e0 = (d[0][0] + d[1][0]) + (d[2][0] + d[3][0]), e1 = (d[0][1] + d[1][1]) + (d[2][1] + d[3][1]);
      const float e2 = (d[0][2] + d[1][2]) + (d[2][2] + d[3][2]), e3 = (d[0][3] + d[1][3]) + (d[2][3] + d[3][3]);
      asm volatile("st.shared.v2.f32 [%0], {%1,%2};" ::"r"(sb + OFF_SCR + 8192 + ((w * 2 + (lane & 1)) * 32 + (cw & 3) * 8 + r0) * 8),
                   "f"((lane & 1) ? e1 : e0), "f"((lane & 1) ? e3 : e2) : "memory");
      bar_sync(3, 256);
      TL(2, 16, warp == 4);
      const uint32_t ra = sb + OFF_SCR + 8192 + (r0 & 1) * 256 + (r0 >> 1) * 64 + (lane & 3) * 16;
      const uint4 p0 = lds128(ra), p1 = lds128(ra + 512);
      auto act = [](uint32_t u0, uint32_t u1, uint32_t g0, uint32_t g1) {
        const uint32_t ug = pack_bf16(__uint_as_float(u0) + __uint_as_float(u1), __uint_as_float(g0) + __uint_as_float(g1));
        const float g = bf_hi(ug);
        return bf_round(__fdividef(g, 1.f + __expf(-g))) * bf_lo(ug);
      };
      const uint32_t av = pack_bf16(act(p0.x, p1.x, p0.y, p1.y), act(p0.z, p1.z, p0.w, p1.w));
      uint32_t b[4];
#pragma unroll
      for (int i = 0; i < 4; i++) b[i] = __shfl_sync(~0u, av, 8 * i + (lane & 7));
      TL(2, 17, warp == 4);
      float y[2][4] = {{0.f, 0.f, 0.f, 0.f}, {0.f, 0.f, 0.f, 0.f}};
#pragma unroll
      for (int c = 0; c < 4; c++) {
        const bool on = (lane >> 3) == c;
        const uint32_t b0 = on ? b[0] : 0, b1 = on ? b[1] : 0, b2 = on ? b[2] : 0, b3 = on ? b[3] : 0;
#pragma unroll
        for (int a = 0; a < 2; a++) {
          const int i = 8 * a + 2 * c;
          mma16816(y[a], wd[i][0], wd[i][1], wd[i][2], wd[i][3], b0, b1);
          mma16816(y[a], wd[i + 1][0], wd[i + 1][1], wd[i + 1][2], wd[i + 1][3], b2, b3);
        }
      }
      float4* yd = reinterpret_cast<float4*>(g_xr + (cw * 16 + (lane & 3) * 2 + (lane >> 4)) * XR_SIZE + XR_Y + fid * 4 + (r0 & 3));
      __stcg(yd, make_float4(y[0][0], y[0][1], y[0][2], y[0][3]));
      __stcg(yd + 8 * XR_SIZE, make_float4(y[1][0], y[1][1], y[1][2], y[1][3]));
    }
    TL(2, 18, warp == 4);
    if (cw == 0) {
      const uint32_t fk = ft ? top.w : top.z;
      uint32_t u = fk >> 16;
      u = (u & 0x8000u) ? (u & 0x7FFFu) : (~u & 0xFFFFu);
      float rs = bf_round(__fdividef(1.f, 1.f + __expf(-__uint_as_float(u << 16))));
      uint16_t* op = reinterpret_cast<uint16_t*>(out) + (size_t)(~fk & 0x7FFF) * DM + fc;
      settle(op, zero); settle(__float_as_uint(rs), zero);
      spin_clk(ffn ? Y_DLY : Y_DLY + Y_DLY0);
      float v[4];
#pragma unroll 1
      for (int n = 0; n < 0x400000; n++) {
        float4 z[14];
#pragma unroll
        for (int i = 0; i < 14; i++)
          asm volatile("ld.relaxed.gpu.global.v4.f32 {%0,%1,%2,%3}, [%4];" : "=f"(z[i].x), "=f"(z[i].y), "=f"(z[i].z), "=f"(z[i].w) : "l"(xr + XR_Y + lane + 32 * i) : "memory");
        float a[4] = {z[0].x, z[0].y, z[0].z, z[0].w}, b[4] = {z[1].x, z[1].y, z[1].z, z[1].w};
#pragma unroll
        for (int i = 2; i < 14; i += 2) {
          a[0] += z[i].x; a[1] += z[i].y; a[2] += z[i].z; a[3] += z[i].w;
          b[0] += z[i + 1].x; b[1] += z[i + 1].y; b[2] += z[i + 1].z; b[3] += z[i + 1].w;
        }
#pragma unroll
        for (int i = 0; i < 4; i++) v[i] = a[i] + b[i];
        const float t = (v[0] + v[1]) + (v[2] + v[3]);
        if (__all_sync(~0u, t == t)) break;
        uint32_t m = 0;
#pragma unroll
        for (int i = 0; i < 14; i++) m = max(max(m, max(__float_as_uint(z[i].x), __float_as_uint(z[i].y))), max(__float_as_uint(z[i].z), __float_as_uint(z[i].w)));
        if (__all_sync(~0u, m != 0xFFFFFFFFu)) break;
      }
      TL(2, 30, true);
      const bool hi = lane & 16, odd = lane & 8;
      const float a0 = (hi ? v[2] : v[0]) + __shfl_xor_sync(~0u, hi ? v[0] : v[2], 16), a1 = (hi ? v[3] : v[1]) + __shfl_xor_sync(~0u, hi ? v[1] : v[3], 16);
      float yv = (odd ? a1 : a0) + __shfl_xor_sync(~0u, odd ? a0 : a1, 8);
      yv += __shfl_xor_sync(~0u, yv, 4);
      const uint32_t o = hadd2_bf(fh, hadd2_bf(fn, pack_bf16(bf_round(yv) * rs, 0.f)));
      if (!(lane & 4)) *op = (uint16_t)o;
      TL(2, 21, true);
    }
    TL(2, 20, warp == 4);
    }
    __syncwarp();
    cluster_wait();
  }
}

typedef CUresult (*EncodeFn)(CUtensorMap*, CUtensorMapDataType, cuuint32_t, void*, const cuuint64_t*, const cuuint64_t*, const cuuint32_t*,
                             const cuuint32_t*, CUtensorMapInterleave, CUtensorMapSwizzle, CUtensorMapL2promotion, CUtensorMapFloatOOBfill);
EncodeFn g_enc = nullptr;

void map2(CUtensorMap* m, const void* ptr, uint64_t rows, uint64_t cols, uint32_t bc, uint32_t br) {
  const CUtensorMapSwizzle sw = bc == 64 ? CU_TENSOR_MAP_SWIZZLE_128B : CU_TENSOR_MAP_SWIZZLE_64B;
  cuuint64_t gd[2] = {cols, rows}, gs[1] = {cols * 2};
  cuuint32_t bd[2] = {bc, br}, es[2] = {1, 1};
  g_enc(m, CU_TENSOR_MAP_DATA_TYPE_BFLOAT16, 2, (void*)ptr, gd, gs, bd, es, CU_TENSOR_MAP_INTERLEAVE_NONE, sw,
        CU_TENSOR_MAP_L2_PROMOTION_L2_128B, CU_TENSOR_MAP_FLOAT_OOB_FILL_NONE);
}
void map3(CUtensorMap* m, const void* ptr, uint64_t rows, uint64_t cols, uint32_t br, uint32_t bch) {
  cuuint64_t gd[3] = {64, rows, cols / 64}, gs[2] = {cols * 2, 128};
  cuuint32_t bd[3] = {64, br, bch}, es[3] = {1, 1, 1};
  g_enc(m, CU_TENSOR_MAP_DATA_TYPE_BFLOAT16, 3, (void*)ptr, gd, gs, bd, es, CU_TENSOR_MAP_INTERLEAVE_NONE, CU_TENSOR_MAP_SWIZZLE_128B,
        CU_TENSOR_MAP_L2_PROMOTION_L2_128B, CU_TENSOR_MAP_FLOAT_OOB_FILL_NONE);
}

}

extern "C" void kernel_launch(void* const* d_in, const int* in_sizes, int n_in, void* d_out, int out_size) {
  const __nv_bfloat16* x = (const __nv_bfloat16*)d_in[0];
  const __nv_bfloat16* ckv = (const __nv_bfloat16*)d_in[1];
  const __nv_bfloat16* wq = (const __nv_bfloat16*)d_in[2];
  const __nv_bfloat16* wk = (const __nv_bfloat16*)d_in[3];
  const __nv_bfloat16* wv = (const __nv_bfloat16*)d_in[4];
  const __nv_bfloat16* wo = (const __nv_bfloat16*)d_in[5];
  const __nv_bfloat16* w_r = (const __nv_bfloat16*)d_in[7];
  const __nv_bfloat16* wgate = (const __nv_bfloat16*)d_in[8];
  const __nv_bfloat16* wup = (const __nv_bfloat16*)d_in[9];
  const __nv_bfloat16* wdown = (const __nv_bfloat16*)d_in[10];
  __nv_bfloat16* out = (__nv_bfloat16*)d_out;

  if (!g_enc) {
    void* fn = nullptr;
    cudaDriverEntryPointQueryResult qr;
    cudaGetDriverEntryPoint("cuTensorMapEncodeTiled", &fn, cudaEnableDefault, &qr);
    g_enc = (EncodeFn)fn;
    cudaFuncSetAttribute(fused_kernel, cudaFuncAttributeMaxDynamicSharedMemorySize, SMEM_BYTES);
  }
  void *xn, *kv, *ctx, *xr, *cnt;
  cudaGetSymbolAddress(&xr, g_xr);
  cudaGetSymbolAddress(&cnt, g_cnt);
  cudaGetSymbolAddress(&xn, g_xn);
  cudaGetSymbolAddress(&kv, g_kv);
  cudaGetSymbolAddress(&ctx, g_ctx);

  Params p;
  map2(&p.xn, xn, SEQ, DM, 64, 64);
  map2(&p.ckv, ckv, SEQ, DC, 64, 128);
  map3(&p.wq, wq, DM, NQ, 64, 2);
  map3(&p.wk, wk, DC, NQ, 64, 2);
  map3(&p.wv, wv, DC, NQ, 64, 2);
  map2(&p.ctx_ld, ctx, SEQ, NQ, 64, 128);
  map3(&p.wo, wo, NQ, DM, 64, 1);
  map3(&p.x, x, SEQ, DM, 64, 2);
  map3(&p.wd, wdown, FF, DM, 32, 8);
  map2(&p.wg, wgate, DM, FF, 32, 64);
  map2(&p.wu, wup, DM, FF, 32, 64);
  fused_kernel<<<128, 384, SMEM_BYTES, cudaStreamPerThread>>>(0u, x, (__nv_bfloat16*)kv, (__nv_bfloat16*)ctx, (uint4*)xr, out, (__nv_bfloat16*)xn,
                                                               (unsigned*)cnt, w_r, wdown, wq, p);
}
```

```cpp
#include <cuda_runtime.h>
#include <cuda_bf16.h>
#include <cuda.h>
#include <stdint.h>
#include <utility>

#pragma nv_diag_suppress 549
#pragma nv_diag_suppress 177
namespace {

constexpr int SEQ = 2048, DM = 1024, NH = 32, HD = 128, DC = 512, NQ = NH * HD, FF = 3584;

__device__ __align__(1024) __nv_bfloat16 g_xn[SEQ * DM];
constexpr int KV_TILE = 128 * 128;
__device__ __align__(1024) __nv_bfloat16 g_kv[2 * SEQ * NQ];
__device__ __align__(1024) __nv_bfloat16 g_ctx[SEQ * NQ];
constexpr int XR_PS = 0;
constexpr int XR_KEY = 128;
constexpr int XR_CAND = 136;
constexpr int XR_Y = 648;
constexpr int XR_SIZE = 1104;
__device__ __align__(1024) uint4 g_xr[128 * XR_SIZE];
constexpr int C_LN = 0, C_KV = 16, C_CTX = 32, C_NUM = 64;
__device__ unsigned g_cnt[C_NUM];

#define TL(k, i, cond) do {} while (0)
#define TC(w, g, i) do {} while (0)
#define TL_EXTRA 0
#define TK(i) do {} while (0)

__device__ __forceinline__ uint32_t s2u(const void* p) { return (uint32_t)__cvta_generic_to_shared(p); }
__device__ __forceinline__ void mbar_arrive(uint32_t b) { asm volatile("mbarrier.arrive.shared::cta.b64 _, [%0];" ::"r"(b) : "memory"); }
__device__ __forceinline__ void mbar_arrive_both(uint32_t b, uint32_t lane, bool cond) {
  asm volatile("{\n.reg .pred p;\n.reg .b32 r;\nsetp.lt.u32 p, %1, %2;\nmapa.shared::cluster.u32 r, %0, %1;\n@p mbarrier.arrive.shared::cluster.b64 _, [r];\n}"
               ::"r"(b), "r"(lane), "r"(cond ? 2 : 0) : "memory");
}
__device__ __forceinline__ bool mbar_test(uint32_t b, uint32_t ph) {
  uint32_t ok;
  asm volatile("{\n.reg .pred p;\nmbarrier.test_wait.parity.shared::cta.b64 p, [%1], %2;\nselp.u32 %0, 1, 0, p;\n}" : "=r"(ok) : "r"(b), "r"(ph) : "memory");
  return __all_sync(~0u, ok);
}
__device__ __forceinline__ void mbar_wait(uint32_t b, uint32_t ph) {
  asm volatile(
      "{\n.reg .pred p;\n.reg .u32 n;\nmov.u32 n, 0;\n"
      "LW:\nmbarrier.try_wait.parity.shared::cta.b64 p, [%0], %1, 20000;\n@p bra LD;\n"
      "add.u32 n, n, 1;\nsetp.lt.u32 p, n, 0x40000;\n@p bra LW;\ntrap;\nLD:\n}" ::"r"(b), "r"(ph) : "memory");
}
__device__ __forceinline__ void mbar_wait_u(uint32_t b, uint32_t ph) {
  asm volatile(
      "{\n.reg .pred p;\n.reg .u32 n;\nmov.u32 n, 0;\n"
      "LW:\nmbarrier.try_wait.parity.shared::cta.b64 p, [%0], %1, 20000;\n@p bra.uni LD;\n"
      "add.u32 n, n, 1;\nsetp.lt.u32 p, n, 0x40000;\n@p bra.uni LW;\ntrap;\nLD:\n}" ::"r"(b), "r"(ph) : "memory");
}
__device__ __forceinline__ void mbar_wait_c(uint32_t b, uint32_t ph) {
  asm volatile("{\n.reg .pred p;\nLW:\nmbarrier.try_wait.parity.shared::cta.b64 p, [%0], %1;\n@!p bra.uni LW;\n}" ::"r"(b), "r"(ph) : "memory");
}
__device__ __forceinline__ void mbar_wait_b(uint32_t b, uint32_t ph) {
  asm volatile(
      "{\n.reg .pred p;\n.reg .u32 n;\nmov.u32 n, 0;\n"
      "LW:\nmbarrier.try_wait.parity.shared::cta.b64 p, [%0], %1;\n@p bra.uni LD;\n"
      "add.u32 n, n, 1;\nsetp.lt.u32 p, n, 0x1000000;\n@p bra.uni LW;\ntrap;\nLD:\n}" ::"r"(b), "r"(ph) : "memory");
}
template <bool SLEEP = false>
__device__ __forceinline__ void spin_until_ge(const unsigned* p, unsigned target) {
  asm volatile(
      "{\n.reg .pred p, q;\n.reg .u32 n, v;\nmov.u32 n, 0;\nsetp.ne.u32 q, %2, 0;\n"
      "LW:\nld.acquire.gpu.global.u32 v, [%0];\nsetp.ge.u32 p, v, %1;\n@p bra LD;\n@q nanosleep.u32 200;\n"
      "add.u32 n, n, 1;\nsetp.lt.u32 p, n, 0x400000;\n@p bra LW;\ntrap;\nLD:\n}" ::"l"(p), "r"(target), "n"((int)SLEEP) : "memory");
}
template <int N>
__device__ __forceinline__ void poll_chunks(uint4 (&v)[N], const uint4* p, int stride) {
#pragma unroll 1
  for (int n = 0; n < 0x400000; n++) {
    uint32_t m = 0;
#pragma unroll
    for (int i = 0; i < N; i++) {
      asm volatile("ld.relaxed.gpu.global.v4.u32 {%0,%1,%2,%3}, [%4];" : "=r"(v[i].x), "=r"(v[i].y), "=r"(v[i].z), "=r"(v[i].w) : "l"(p + i * stride) : "memory");
    }
#pragma unroll
    for (int i = 0; i < N; i++) m = max(max(m, max(v[i].x, v[i].y)), max(v[i].z, v[i].w));
    if (__all_sync(~0u, m != 0xFFFFFFFFu)) break;
  }
}
__device__ __forceinline__ void spin_clk(uint32_t n) {
  asm volatile("{\n.reg .pred p;\n.reg .u32 a, b;\nmov.u32 a, %%clock;\nLW:\nmov.u32 b, %%clock;\nsub.u32 b, b, a;\nsetp.lt.u32 p, b, %0;\n@p bra.uni LW;\n}" ::"r"(n) : "memory");
}
__device__ __forceinline__ int fresh_lane() {
  int r;
  asm volatile("mov.u32 %0, %%laneid;" : "=r"(r));
  return r;
}
__device__ __forceinline__ void settle(const void* a, uint32_t zero) {
  asm volatile("{\n.reg .pred p;\nsetp.ne.u32 p, %1, 0;\n@p st.global.u32 [%0], %1;\n}" ::"l"(a), "r"(zero) : "memory");
}
__device__ __forceinline__ void settle(uint32_t a, uint32_t zero) {
  asm volatile("{\n.reg .pred p;\nsetp.ne.u32 p, %1, 0;\n@p st.shared.u32 [%0], %1;\n}" ::"r"(a), "r"(zero) : "memory");
}
__device__ __forceinline__ void fence_async_all() { asm volatile("fence.proxy.async;" ::: "memory"); }
__device__ __forceinline__ void bar_sync(int id, int n) { asm volatile("bar.sync %0, %1;" ::"r"(id), "r"(n) : "memory"); }
__device__ __forceinline__ void bar_arrive(int id, int n) { asm volatile("bar.arrive %0, %1;" ::"r"(id), "r"(n) : "memory"); }
__device__ __forceinline__ void cluster_arrive() { asm volatile("barrier.cluster.arrive.relaxed.aligned;" ::: "memory"); }
__device__ __forceinline__ void cluster_wait() { asm volatile("barrier.cluster.wait.acquire.aligned;" ::: "memory"); }
__device__ __forceinline__ void fence_gpu() { asm volatile("fence.acq_rel.gpu;" ::: "memory"); }
__device__ __forceinline__ void red_add(unsigned* p, unsigned v) { asm volatile("red.relaxed.gpu.global.add.u32 [%0], %1;" ::"l"(p), "r"(v) : "memory"); }
#define ELECT "{\n.reg .pred E;\nelect.sync _|E, 0xFFFFFFFF;\n@E "
__device__ __forceinline__ void e_init(uint32_t b, uint32_t c) { asm volatile(ELECT "mbarrier.init.shared::cta.b64 [%0], %1;\n}" ::"r"(b), "r"(c) : "memory"); }
__device__ __forceinline__ void e_expect(uint32_t b, uint32_t bytes) { asm volatile(ELECT "mbarrier.arrive.expect_tx.shared::cta.b64 _, [%0], %1;\n}" ::"r"(b), "r"(bytes) : "memory"); }
__device__ __forceinline__ void e_arrive(uint32_t b) { asm volatile(ELECT "mbarrier.arrive.shared::cta.b64 _, [%0];\n}" ::"r"(b) : "memory"); }
__device__ __forceinline__ void prefetch_tm(const CUtensorMap* m) { asm volatile(ELECT "prefetch.tensormap [%0];\n}" ::"l"(m) : "memory"); }
__device__ __forceinline__ void tma_ld2(uint32_t dst, const CUtensorMap* m, uint32_t bar, int c0, int c1) {
  asm volatile(ELECT "cp.async.bulk.tensor.2d.shared::cta.global.mbarrier::complete_tx::bytes [%0], [%1, {%3,%4}], [%2];\n}" ::"r"(dst), "l"(m), "r"(bar), "r"(c0), "r"(c1) : "memory");
}
__device__ __forceinline__ void tma_ld3(uint32_t dst, const CUtensorMap* m, uint32_t bar, int c0, int c1, int c2) {
  asm volatile(ELECT "cp.async.bulk.tensor.3d.shared::cta.global.mbarrier::complete_tx::bytes [%0], [%1, {%3,%4,%5}], [%2];\n}" ::"r"(dst), "l"(m), "r"(bar), "r"(c0), "r"(c1), "r"(c2) : "memory");
}
__device__ __forceinline__ void tma_ld2_mc(uint32_t dst, const CUtensorMap* m, uint32_t bar, int c0, int c1, uint16_t mask) {
  asm volatile(ELECT "cp.async.bulk.tensor.2d.shared::cluster.global.mbarrier::complete_tx::bytes.multicast::cluster [%0], [%1, {%3,%4}], [%2], %5;\n}" ::"r"(dst), "l"(m), "r"(bar), "r"(c0), "r"(c1), "h"(mask) : "memory");
}
__device__ __forceinline__ void tma_ld3_mc(uint32_t dst, const CUtensorMap* m, uint32_t bar, int c0, int c1, int c2, uint16_t mask) {
  asm volatile(ELECT "cp.async.bulk.tensor.3d.shared::cluster.global.mbarrier::complete_tx::bytes.multicast::cluster [%0], [%1, {%3,%4,%5}], [%2], %6;\n}" ::"r"(dst), "l"(m), "r"(bar), "r"(c0), "r"(c1), "r"(c2), "h"(mask) : "memory");
}
__device__ __forceinline__ uint64_t policy_evict_first() {
  uint64_t p;
  asm("createpolicy.fractional.L2::evict_first.b64 %0, 1.0;" : "=l"(p));
  return p;
}
__device__ __forceinline__ void tma_ld2_ef(uint32_t dst, const CUtensorMap* m, uint32_t bar, int c0, int c1) {
  asm volatile(ELECT "cp.async.bulk.tensor.2d.shared::cta.global.mbarrier::complete_tx::bytes.L2::cache_hint [%0], [%1, {%3,%4}], [%2], %5;\n}" ::"r"(dst), "l"(m), "r"(bar), "r"(c0), "r"(c1), "l"(policy_evict_first()) : "memory");
}
__device__ __forceinline__ void tma_ld3_ef(uint32_t dst, const CUtensorMap* m, uint32_t bar, int c0, int c1, int c2) {
  asm volatile(ELECT "cp.async.bulk.tensor.3d.shared::cta.global.mbarrier::complete_tx::bytes.L2::cache_hint [%0], [%1, {%3,%4,%5}], [%2], %6;\n}" ::"r"(dst), "l"(m), "r"(bar), "r"(c0), "r"(c1), "r"(c2), "l"(policy_evict_first()) : "memory");
}
__device__ __forceinline__ void bulk_ld(uint32_t dst, const void* src, uint32_t bytes, uint32_t bar) {
  asm volatile(ELECT "cp.async.bulk.shared::cta.global.mbarrier::complete_tx::bytes [%0], [%1], %2, [%3];\n}" ::"r"(dst), "l"(src), "r"(bytes), "r"(bar) : "memory");
}
__device__ __forceinline__ void tma_pf2(const CUtensorMap* m, int c0, int c1) { asm volatile(ELECT "cp.async.bulk.prefetch.tensor.2d.L2.global [%0, {%1,%2}];\n}" ::"l"(m), "r"(c0), "r"(c1) : "memory"); }
__device__ __forceinline__ void tma_pf3(const CUtensorMap* m, int c0, int c1, int c2) { asm volatile(ELECT "cp.async.bulk.prefetch.tensor.3d.L2.global [%0, {%1,%2,%3}];\n}" ::"l"(m), "r"(c0), "r"(c1), "r"(c2) : "memory"); }
__device__ __forceinline__ void sched_fence() { asm volatile("pmevent 0;" ::: "memory"); }
__device__ __forceinline__ void l2_prefetch(const void* p, uint32_t bytes) { asm volatile(ELECT "cp.async.bulk.prefetch.L2.global [%0], %1;\n}" ::"l"(p), "r"(bytes) : "memory"); }

__device__ __forceinline__ void wg_fence() { asm volatile("wgmma.fence.sync.aligned;" ::: "memory"); }
__device__ __forceinline__ void wg_commit() { asm volatile("wgmma.commit_group.sync.aligned;" ::: "memory"); }
template <int N> __device__ __forceinline__ void wg_wait() { asm volatile("wgmma.wait_group.sync.aligned %0;" ::"n"(N) : "memory"); }
template <int N> __device__ __forceinline__ void reg_alloc() { asm volatile("setmaxnreg.inc.sync.aligned.u32 %0;" ::"n"(N)); }
template <int N> __device__ __forceinline__ void reg_dealloc() { asm volatile("setmaxnreg.dec.sync.aligned.u32 %0;" ::"n"(N)); }
template <int N> __device__ __forceinline__ void fence_regs(float (&d)[N]) {
#pragma unroll
  for (int i = 0; i < N; i++) asm volatile("" : "+f"(d[i])::"memory");
}
template <int I0, int I1, int N> __device__ __forceinline__ void fence_part(float (&d)[N]) {
#pragma unroll
  for (int i = I0; i < I1; i++) asm volatile("" : "+f"(d[i])::"memory");
}
template <int N> __device__ __forceinline__ void fence_regs(uint32_t (&d)[N]) {
#pragma unroll
  for (int i = 0; i < N; i++) asm volatile("" : "+r"(d[i])::"memory");
}

__device__ __forceinline__ uint32_t mk_desc(uint32_t addr, uint32_t lbo) { return ((addr & 0x3FFFF) >> 4) | ((lbo >> 4) << 16); }

#define R8(b) "+f"(d[b + 0]), "+f"(d[b + 1]), "+f"(d[b + 2]), "+f"(d[b + 3]), "+f"(d[b + 4]), "+f"(d[b + 5]), "+f"(d[b + 6]), "+f"(d[b + 7])
#define REGS64 "%0,%1,%2,%3,%4,%5,%6,%7,%8,%9,%10,%11,%12,%13,%14,%15,%16,%17,%18,%19,%20,%21,%22,%23,%24,%25,%26,%27,%28,%29,%30,%31," \
               "%32,%33,%34,%35,%36,%37,%38,%39,%40,%41,%42,%43,%44,%45,%46,%47,%48,%49,%50,%51,%52,%53,%54,%55,%56,%57,%58,%59,%60,%61,%62,%63"
#define REGS128 REGS64 ",%64,%65,%66,%67,%68,%69,%70,%71,%72,%73,%74,%75,%76,%77,%78,%79,%80,%81,%82,%83,%84,%85,%86,%87,%88,%89,%90,%91,%92,%93,%94,%95," \
               "%96,%97,%98,%99,%100,%101,%102,%103,%104,%105,%106,%107,%108,%109,%110,%111,%112,%113,%114,%115,%116,%117,%118,%119,%120,%121,%122,%123,%124,%125,%126,%127"

#define DESC(d, r, o) "add.u32 t, " r ", " o ";\nmov.b64 " d ", {t, h};\n"
#define MMA_PRE_(acc, hi) "{\n.reg .pred p;\n.reg .b32 t, h;\n.reg .b64 da, db;\nmov.b32 h, " hi ";\nsetp.ne.b32 p, " acc ", 0;\n"
#define MMA_PRE(acc) MMA_PRE_(acc, "0x40000040")
#define MMA_PRE64(acc) MMA_PRE_(acc, "0x80000020")
template <int TB, int OA, int OB>
__device__ __forceinline__ void mma_n256_ss(float (&d)[128], uint32_t a, uint32_t b, int acc) {
  asm volatile(MMA_PRE("%130") DESC("da", "%128", "%132") DESC("db", "%129", "%133")
               "wgmma.mma_async.sync.aligned.m64n256k16.f32.bf16.bf16 {" REGS128 "}, da, db, p, 1, 1, 0, %131;\n}\n"
               : R8(0), R8(8), R8(16), R8(24), R8(32), R8(40), R8(48), R8(56), R8(64), R8(72), R8(80), R8(88), R8(96), R8(104), R8(112), R8(120)
               : "r"(a), "r"(b), "r"(acc), "n"(TB), "n"(OA >> 4), "n"(OB >> 4));
}
template <int TB, int OA, int OB>
__device__ __forceinline__ void mma_n128_ss(float (&d)[64], uint32_t a, uint32_t b, int acc) {
  asm volatile(MMA_PRE("%66") DESC("da", "%64", "%68") DESC("db", "%65", "%69")
               "wgmma.mma_async.sync.aligned.m64n128k16.f32.bf16.bf16 {" REGS64 "}, da, db, p, 1, 1, 0, %67;\n}\n"
               : R8(0), R8(8), R8(16), R8(24), R8(32), R8(40), R8(48), R8(56)
               : "r"(a), "r"(b), "r"(acc), "n"(TB), "n"(OA >> 4), "n"(OB >> 4));
}
template <int TB, int OB>
__device__ __forceinline__ void mma_n128_rs(float (&d)[64], const uint32_t* a, uint32_t b, int acc) {
  asm volatile(MMA_PRE64("%69") DESC("db", "%68", "%71")
               "wgmma.mma_async.sync.aligned.m64n128k16.f32.bf16.bf16 {" REGS64 "}, {%64,%65,%66,%67}, db, p, 1, 1, %70;\n}\n"
               : R8(0), R8(8), R8(16), R8(24), R8(32), R8(40), R8(48), R8(56)
               : "r"(a[0]), "r"(a[1]), "r"(a[2]), "r"(a[3]), "r"(b), "r"(acc), "n"(TB), "n"(OB >> 4));
}
#define W8(b) "=f"(d[b + 0]), "=f"(d[b + 1]), "=f"(d[b + 2]), "=f"(d[b + 3]), "=f"(d[b + 4]), "=f"(d[b + 5]), "=f"(d[b + 6]), "=f"(d[b + 7])
#define MMA_N64 MMA_PRE64("%37") DESC("db", "%36", "%38") \
  "wgmma.mma_async.sync.aligned.m64n64k16.f32.bf16.bf16 {%0,%1,%2,%3,%4,%5,%6,%7,%8,%9,%10,%11,%12,%13,%14,%15,%16,%17,%18,%19,%20,%21," \
  "%22,%23,%24,%25,%26,%27,%28,%29,%30,%31}, {%32,%33,%34,%35}, db, p, 1, 1, 0;\n}\n"
template <int H, int OB, bool ACC>
__device__ __forceinline__ void mma_n64_rs(float (&d)[64], const uint32_t* a, uint32_t b) {
  if (ACC) asm volatile(MMA_N64 : R8(32 * H), R8(32 * H + 8), R8(32 * H + 16), R8(32 * H + 24) : "r"(a[0]), "r"(a[1]), "r"(a[2]), "r"(a[3]), "r"(b), "n"(1), "n"(OB >> 4));
  else asm volatile(MMA_N64 : W8(32 * H), W8(32 * H + 8), W8(32 * H + 16), W8(32 * H + 24) : "r"(a[0]), "r"(a[1]), "r"(a[2]), "r"(a[3]), "r"(b), "n"(0), "n"(OB >> 4));
}
template <int OB>
__device__ __forceinline__ void mma_n128_rs0(float (&d)[64], const uint32_t* a, uint32_t b) {
  asm volatile(MMA_PRE64("%69") DESC("db", "%68", "%70")
               "wgmma.mma_async.sync.aligned.m64n128k16.f32.bf16.bf16 {" REGS64 "}, {%64,%65,%66,%67}, db, p, 1, 1, 0;\n}\n"
               : W8(0), W8(8), W8(16), W8(24), W8(32), W8(40), W8(48), W8(56)
               : "r"(a[0]), "r"(a[1]), "r"(a[2]), "r"(a[3]), "r"(b), "n"(0), "n"(OB >> 4));
}
#define MMA_SSH MMA_PRE("%67") DESC("db", "%65", "%69") "add.u32 t, %64, %68;\nmov.b64 da, {t, %66};\n" \
  "wgmma.mma_async.sync.aligned.m64n128k16.f32.bf16.bf16 {" REGS64 "}, da, db, p, 1, 1, 0, 1;\n}\n"
template <int OA, int OB, bool ACC>
__device__ __forceinline__ void mma_n128_ssh(float (&d)[64], uint32_t a, uint32_t ahi, uint32_t b) {
  if (ACC) asm volatile(MMA_SSH : R8(0), R8(8), R8(16), R8(24), R8(32), R8(40), R8(48), R8(56) : "r"(a), "r"(b), "r"(ahi), "n"(1), "n"(OA >> 4), "n"(OB >> 4));
  else asm volatile(MMA_SSH : W8(0), W8(8), W8(16), W8(24), W8(32), W8(40), W8(48), W8(56) : "r"(a), "r"(b), "r"(ahi), "n"(0), "n"(OA >> 4), "n"(OB >> 4));
}
template <int TB, int OA, int OB>
__device__ __forceinline__ void mma_n128_ss0(float (&d)[64], uint32_t a, uint32_t b) {
  asm volatile(MMA_PRE("%66") DESC("da", "%64", "%68") DESC("db", "%65", "%69")
               "wgmma.mma_async.sync.aligned.m64n128k16.f32.bf16.bf16 {" REGS64 "}, da, db, p, 1, 1, 0, %67;\n}\n"
               : W8(0), W8(8), W8(16), W8(24), W8(32), W8(40), W8(48), W8(56)
               : "r"(a), "r"(b), "n"(0), "n"(TB), "n"(OA >> 4), "n"(OB >> 4));
}
template <int V> struct IC { static constexpr int value = V; __host__ __device__ constexpr operator int() const { return V; } };
template <int N, class F, int... I>
__device__ __forceinline__ void static_for_(F f, std::integer_sequence<int, I...>) { (f(IC<I>{}), ...); }
template <int N, class F>
__device__ __forceinline__ void static_for(F f) { static_for_<N>(f, std::make_integer_sequence<int, N>{}); }
__device__ __forceinline__ uint32_t pack_bf16(float lo, float hi) {
  uint32_t r;
  asm("cvt.rn.bf16x2.f32 %0, %1, %2;" : "=r"(r) : "f"(hi), "f"(lo));
  return r;
}
__device__ __forceinline__ float bf_lo(uint32_t v) { return __uint_as_float(v << 16); }
__device__ __forceinline__ float bf_hi(uint32_t v) { return __uint_as_float(v & 0xFFFF0000u); }
__device__ __forceinline__ float bf_round(float v) { return bf_lo(pack_bf16(v, v)); }
__device__ __forceinline__ void stsm4(uint32_t addr, uint32_t r0, uint32_t r1, uint32_t r2, uint32_t r3) {
  asm volatile("stmatrix.sync.aligned.m8n8.x4.shared.b16 [%0], {%1,%2,%3,%4};" ::"r"(addr), "r"(r0), "r"(r1), "r"(r2), "r"(r3) : "memory");
}
__device__ __forceinline__ uint4 lds128(uint32_t addr) {
  uint4 v;
  asm volatile("ld.shared.v4.u32 {%0,%1,%2,%3}, [%4];" : "=r"(v.x), "=r"(v.y), "=r"(v.z), "=r"(v.w) : "r"(addr));
  return v;
}
__device__ __forceinline__ float ex2(float x) {
  float y;
  asm("ex2.approx.ftz.f32 %0, %1;" : "=f"(y) : "f"(x));
  return y;
}
__device__ __forceinline__ void stage_store_128(uint32_t base, int lane, const uint32_t* pk) {
  const int row = (lane & 7) + ((lane >> 3) & 1) * 8;
  const uint32_t rb = base + row * 128;
  const int hi = lane >> 4;
#pragma unroll
  for (int j = 0; j < 8; j++) {
    const int chunk = 2 * j + hi;
    const uint32_t a = rb + (j >> 2) * 8192 + (((chunk & 7) ^ (lane & 7)) << 4);
    stsm4(a, pk[4 * j + 0], pk[4 * j + 1], pk[4 * j + 2], pk[4 * j + 3]);
  }
}
__device__ __forceinline__ void ln_round(float mean, float var, float& m_bf, float& inv_s) {
  const uint32_t mv = pack_bf16(mean, var);
  m_bf = bf_lo(mv);
  float sq, rc;
  asm("sqrt.approx.ftz.f32 %0, %1;" : "=f"(sq) : "f"(bf_round(bf_hi(mv) + 1e-5f)));
  asm("rcp.approx.ftz.f32 %0, %1;" : "=f"(rc) : "f"(bf_round(sq)));
  inv_s = rc;
}
__device__ __forceinline__ uint32_t hadd2_bf(uint32_t a, uint32_t b) {
  uint32_t r;
  asm("add.rn.bf16x2 %0, %1, %2;" : "=r"(r) : "r"(a), "r"(b));
  return r;
}
__device__ __forceinline__ uint32_t ln_apply(uint32_t h, uint32_t nm2, float inv_s) {
  const uint32_t d = hadd2_bf(h, nm2);
  return pack_bf16(bf_lo(d) * inv_s, bf_hi(d) * inv_s);
}
__device__ __forceinline__ void mma16816(float* d, uint32_t a0, uint32_t a1, uint32_t a2, uint32_t a3, uint32_t b0, uint32_t b1) {
  asm volatile("mma.sync.aligned.m16n8k16.row.col.f32.bf16.bf16.f32 {%0,%1,%2,%3}, {%4,%5,%6,%7}, {%8,%9}, {%0,%1,%2,%3};"
               : "+f"(d[0]), "+f"(d[1]), "+f"(d[2]), "+f"(d[3]) : "r"(a0), "r"(a1), "r"(a2), "r"(a3), "r"(b0), "r"(b1));
}

constexpr float AT_C = 0.08838834764831845f * 1.4426950408889634f;
#define L_MIN 2.3283064e-10f
#define L_MAX 1.0995116e12f
struct AtState {
  float S[64], O[64];
  uint32_t P[32], Q[32];
  float l[4];
};
template <int I0, int I1>
__device__ __forceinline__ void at_exp(AtState& s) {
#pragma unroll
  for (int i = I0; i < I1; i++) asm volatile("ex2.approx.ftz.f32 %0, %0;" : "+f"(s.S[i]));
#pragma unroll
  for (int i = I0; i < I1; i++) asm volatile("add.f32 %0, %0, %1;" : "+f"(s.l[i & 3]) : "f"(s.S[i]));
}
template <int I0, int I1>
__device__ __forceinline__ void at_pack(AtState& s) {
#pragma unroll
  for (int i = I0; i < I1; i++) asm volatile("cvt.rn.bf16x2.f32 %0, %1, %2;" : "=r"(s.P[i]) : "f"(s.S[2 * i + 1]), "f"(s.S[2 * i]));
}
template <int J0>
__device__ __forceinline__ void at_mask(AtState& s, int r, int lane) {
  const int d = r + (lane >> 2) - (lane & 3) * 2;
#pragma unroll
  for (int j = 0; j < 8; j++) {
    float dummy0 = 0.f, dummy1 = 0.f;
    float& lo0 = j < 7 ? s.S[4 * (J0 + (j < 7 ? j + 1 : j)) + 2] : dummy0;
    float& lo1 = j < 7 ? s.S[4 * (J0 + (j < 7 ? j + 1 : j)) + 3] : dummy1;
    asm("{\n.reg .pred p, q;\nsetp.lt.s32 p, %4, %5;\nsetp.le.s32 q, %4, %5;\n"
        "@p add.f32 %0, %0, 0fFF800000;\n@q add.f32 %1, %1, 0fFF800000;\n@p add.f32 %2, %2, 0fFF800000;\n@q add.f32 %3, %3, 0fFF800000;\n}"
        : "+f"(s.S[4 * (J0 + j)]), "+f"(s.S[4 * (J0 + j) + 1]), "+f"(lo0), "+f"(lo1) : "r"(d), "r"(8 * j));
  }
}
template <int D>
__device__ __forceinline__ uint32_t ld_pair(const __nv_bfloat16* p) {
  uint32_t r;
  asm volatile("{\n.reg .b16 a, b;\nld.global.cg.b16 a, [%1];\nld.global.cg.b16 b, [%1 + %2];\nmov.b32 %0, {a, b};\n}" : "=r"(r) : "l"(p), "n"(2 * D) : "memory");
  return r;
}
__device__ __forceinline__ uint32_t ld_word(const uint32_t* p) {
  uint32_t r;
  asm volatile("ld.global.cg.b32 %0, [%1];" : "=r"(r) : "l"(p) : "memory");
  return r;
}
__device__ __noinline__ void slow_rows(const __nv_bfloat16* wq, int head, int row0) {
  const int lane = fresh_lane(), r = lane >> 2, c = lane & 3;
  uint32_t q[32];
  float o[32];
#pragma unroll
  for (int i = 0; i < 32; i++) q[i] = 0;
  const uint32_t* xa = reinterpret_cast<const uint32_t*>(g_xn + (size_t)(row0 + r) * DM) + c;
#pragma unroll 1
  for (int h = 0; h < 2; h++) {
    const __nv_bfloat16* wb = wq + (size_t)2 * c * NQ + head * HD + 64 * h + 8 * (r >> 1) + (r & 1);
#pragma unroll
    for (int i = 0; i < 32; i++) o[i] = 0.f;
#pragma unroll 1
    for (int kk = 0; kk < DM / 16; kk++) {
      const uint32_t a0 = ld_word(xa + 8 * kk), a1 = ld_word(xa + 8 * kk + 4 * DM), a2 = ld_word(xa + 8 * kk + 4), a3 = ld_word(xa + 8 * kk + 4 * DM + 4);
#pragma unroll
      for (int n = 0; n < 8; n++) {
        const __nv_bfloat16* b = wb + (size_t)16 * kk * NQ + 32 * (n >> 2) + 2 * (n & 3);
        mma16816(o + 4 * n, a0, a1, a2, a3, ld_pair<NQ>(b), ld_pair<NQ>(b + 8 * NQ));
        if (n & 1) sched_fence();
      }
    }
#pragma unroll
    for (int i = 0; i < 16; i++) { q[i] = q[16 + i]; q[16 + i] = pack_bf16(o[2 * i] * AT_C, o[2 * i + 1] * AT_C); }
  }
#pragma unroll 1
  for (int h = 0; h < 2; h++) {
    float m0 = -INFINITY, m1 = -INFINITY, l0 = 0.f, l1 = 0.f;
#pragma unroll
    for (int i = 0; i < 32; i++) o[i] = 0.f;
#pragma unroll 1
    for (int k0 = 0; k0 <= row0; k0 += 16) {
      float e[8] = {0.f, 0.f, 0.f, 0.f, 0.f, 0.f, 0.f, 0.f};
      const __nv_bfloat16* kt = g_kv + (size_t)(head * 16 + (k0 >> 7)) * KV_TILE + (k0 & 127) * 32;
      const uint32_t* kp = reinterpret_cast<const uint32_t*>(kt + r * 32) + c;
#pragma unroll
      for (int kk = 0; kk < 8; kk++) {
        const uint32_t* k0p = kp + (kk >> 1) * 2048 + (((kk & 1) * 2) ^ (r >> 1)) * 4;
        const uint32_t* k1p = kp + (kk >> 1) * 2048 + (((kk & 1) * 2 + 1) ^ (r >> 1)) * 4;
        mma16816(e, q[4 * kk], q[4 * kk + 1], q[4 * kk + 2], q[4 * kk + 3], ld_word(k0p), ld_word(k1p));
        mma16816(e + 4, q[4 * kk], q[4 * kk + 1], q[4 * kk + 2], q[4 * kk + 3], ld_word(k0p + 128), ld_word(k1p + 128));
        if (kk & 1) sched_fence();
      }
      if (k0 == row0) {
#pragma unroll
        for (int i = 0; i < 8; i++) if ((i >> 2) * 8 + 2 * c + (i & 1) > r + (i & 2) * 4) e[i] = -INFINITY;
      }
      float a0 = fmaxf(fmaxf(e[0], e[1]), fmaxf(e[4], e[5])), a1 = fmaxf(fmaxf(e[2], e[3]), fmaxf(e[6], e[7]));
      a0 = fmaxf(a0, __shfl_xor_sync(~0u, a0, 1)); a1 = fmaxf(a1, __shfl_xor_sync(~0u, a1, 1));
      a0 = fmaxf(a0, __shfl_xor_sync(~0u, a0, 2)); a1 = fmaxf(a1, __shfl_xor_sync(~0u, a1, 2));
      a0 = fmaxf(a0, m0); a1 = fmaxf(a1, m1);
      const float sc0 = ex2(m0 - a0), sc1 = ex2(m1 - a1);
      m0 = a0; m1 = a1;
#pragma unroll
      for (int i = 0; i < 8; i++) e[i] = ex2(e[i] - ((i & 2) ? m1 : m0));
      l0 = l0 * sc0 + (e[0] + e[1]) + (e[4] + e[5]);
      l1 = l1 * sc1 + (e[2] + e[3]) + (e[6] + e[7]);
      const uint32_t p0 = pack_bf16(e[0], e[1]), p1 = pack_bf16(e[2], e[3]), p2 = pack_bf16(e[4], e[5]), p3 = pack_bf16(e[6], e[7]);
      const __nv_bfloat16* vp = kt + (size_t)512 * KV_TILE + h * 8192 + 2 * c * 32 + r;
#pragma unroll
      for (int n = 0; n < 8; n++) {
        o[4 * n] *= sc0; o[4 * n + 1] *= sc0; o[4 * n + 2] *= sc1; o[4 * n + 3] *= sc1;
        mma16816(o + 4 * n, p0, p1, p2, p3, ld_pair<32>(vp + (n >> 2) * 4096 + ((n ^ c) & 3) * 8), ld_pair<32>(vp + (n >> 2) * 4096 + ((n ^ c) & 3) * 8 + 256));
        if (n & 1) sched_fence();
      }
    }
    l0 += __shfl_xor_sync(~0u, l0, 1); l1 += __shfl_xor_sync(~0u, l1, 1);
    l0 += __shfl_xor_sync(~0u, l0, 2); l1 += __shfl_xor_sync(~0u, l1, 2);
#pragma unroll
    for (int i = 0; i < 4; i++) {
      const float* v = o + 16 * (i >> 1) + 2 * (i & 1);
      const float f = __fdividef(1.f, (i & 1) ? l1 : l0);
      *reinterpret_cast<uint4*>(g_ctx + (size_t)((row0 >> 7) * 32 + head) * KV_TILE + (2 * h + (i >> 1)) * 4096 + ((row0 & 127) + r + (i & 1) * 8) * 32 + (c ^ (r >> 1)) * 8) =
          make_uint4(pack_bf16(v[0] * f, v[1] * f), pack_bf16(v[4] * f, v[5] * f), pack_bf16(v[8] * f, v[9] * f), pack_bf16(v[12] * f, v[13] * f));
    }
  }
}

constexpr int UNIT = 16384, SLOT = 32768;
constexpr int OFF_SIDE = 2 * SLOT;
__host__ __device__ constexpr int kv_a(int kb) { return (kb < 6 ? kb : 3 * kb - 10) * UNIT; }
__host__ __device__ constexpr int kv_b(int s) { return (s == 2 ? 6 : 9 + 3 * s) * UNIT; }
__host__ __device__ constexpr int q_aw(int s) { return (3 * s + (s & 1)) * UNIT; }
__host__ __device__ constexpr int q_b(int s) { return (3 * s + 2 - 2 * (s & 1)) * UNIT; }
__host__ __device__ constexpr int k_slot(int j, int r) { return (j < 2 ? 2 * j : (r == 2 ? 0 : 3 + r)) * SLOT; }
__host__ __device__ constexpr int v_slot(int j) { return (6 - (j & 1)) * SLOT; }
__host__ __device__ constexpr int r3(int st) { return ((0x654130 >> (4 * st)) & 7) * SLOT; }
constexpr int OFF_BAR = 229376;
constexpr int OFF_MISC = OFF_BAR + 512;
constexpr int SMEM_BYTES = OFF_MISC + 2080 + TL_EXTRA;
constexpr int OFF_RSTAT = OFF_MISC + 1056;
enum : int {
  B_FULL1 = 0, B_FULLQ = 3, B_FULLB = 7, B_KF = 8, B_VF = 11, B_FULL3 = 13, B_WF = 19, B_DEP = 21, B_OUT2 = 26, B_PF = 27, B_SET = 28,
  B_SET2 = 29, B_LNGO = 30, B_WR = 31,
  B_KE = 32, B_VE = 35, B_WE = 37, B_PUB = 39, B_OUT = 45,
  B_EMPTY1 = 46, B_EMPTYQ = 49, B_X = 53, B_EMPTY3 = 57,
  B_NUM = 63
};
#define TUNABLE(name, v) constexpr int name = v
TUNABLE(LN_GO, 3);
TUNABLE(EP1, 3);
TUNABLE(SIDE_NS, 400);
TUNABLE(SET_KB, 44); TUNABLE(SET_NS, 40);
TUNABLE(PF_KB, 54); TUNABLE(PF_N, 7); TUNABLE(PF_NS, 300);
TUNABLE(PS_DLY, 120); TUNABLE(Y_DLY, 700); TUNABLE(Y_DLY0, 1500);
constexpr int PRE = 3;
constexpr int WIN = 6;
constexpr int OFF_STG = r3(0), OFF_SCR = r3(1);
struct Params {
  CUtensorMap xn, ckv, wq, wk, wv, wo, x, wd, wg, wu;
};

__global__ void __cluster_dims__(2, 1, 1) __launch_bounds__(384, 1)
fused_kernel(uint32_t zero, const __nv_bfloat16* __restrict__ x, __nv_bfloat16* g_kv, __nv_bfloat16* g_ctx, uint4* g_xr,
             __nv_bfloat16* __restrict__ out, __nv_bfloat16* g_xn, unsigned* g_cnt, const __nv_bfloat16* __restrict__ w_r,
             const __nv_bfloat16* __restrict__ wdown, const __nv_bfloat16* __restrict__ wq, const __grid_constant__ Params p) {
  extern __shared__ __align__(1024) uint8_t sp[];
  const uint32_t sb = s2u(sp);
  const uint32_t bar = sb + OFF_BAR;
  auto B = [&](int i) { return bar + 8 * i; };
  const int tid = threadIdx.x, warp = __shfl_sync(~0u, tid >> 5, 0), wg = warp >> 2, lane = tid & 31;
  const int cta = blockIdx.x, rank = cta & 1, cl = cta >> 1;
  const int mp = cl < 4 ? 1 : (cl < 36 ? (cl & 7) : (0x3207654 >> (4 * ((cl - 36) % 7))) & 7);
  const int gq = cl < 4 ? 4 + cl : (cl < 36 ? (cl - 4) >> 3 : 4 + (cl - 36) / 7);
  const int mt = 2 * mp + rank;
  const int qa = 15 - gq;
  const int ta = gq ? gq : 15, tb = 15 - ta;
  const int rid = mt * 8 + gq;
  const int fid = mt * 7 + gq;
  const bool ffn = gq < 7;
  TL(0, 0, warp == 4);
  auto load_pre = [&](int kb) {
    e_expect(B(B_FULL1 + kb), 3 * UNIT);
    tma_ld2(sb + kv_a(kb), &p.ckv, B(B_FULL1 + kb), kb * 64, mt * 128);
    tma_ld3(sb + kv_b(kb) + rank * UNIT, &p.wk, B(B_FULL1 + kb), 0, kb * 64, (gq + 8) * 4 + rank * 2);
    tma_ld3(sb + kv_b(kb) + UNIT - rank * UNIT, &p.wk, B(B_FULL1 + kb), 0, kb * 64, (gq + 8) * 4 + 2 - rank * 2);
  };
  if (warp == 0) {
    e_init(B(B_FULL1), 1);
    asm volatile("fence.mbarrier_init.release.cluster;" ::: "memory");
    TL(0, 16, true);
    load_pre(0);
    TL(0, 17, true);
#pragma unroll
    for (int kb = 1; kb < PRE; kb++) e_init(B(B_FULL1 + kb), 1);
  } else {
#pragma unroll 1
    for (int i = PRE - 1 + warp; i < B_NUM; i += 11) e_init(B(i), i >= B_EMPTY1 ? 16 : (i >= B_KE ? 8 : (i == B_WR ? 2 : 1)));
  }
  asm volatile("fence.mbarrier_init.release.cluster;" ::: "memory");
  cluster_arrive();
  const int rid0 = rid, warp0 = warp;
  if (wg == 0) {
    reg_dealloc<40>();
    if (warp == 0) {
      TL(0, 12, true);
#pragma unroll 1
      for (int kb = 1; kb < PRE; kb++) { load_pre(kb); TL(0, 12 + kb, true); }
      if (mt >= 2 * PRE) tma_pf3(&p.wk, 0, (mt >> 1) * 64, (gq + 8) * 4 + (mt & 1) * 2);
      if (gq >= PRE) tma_pf2(&p.ckv, gq * 64, mt * 128);
      TL(0, 15, true);
    }
    TL(0, 18, warp == 0);
    __syncwarp();
    cluster_wait();
    uint4* const xr = g_xr + rid * XR_SIZE;
    auto side_piece = [&](int c, int piece) {
      const uint32_t fb = B(B_WF + (c & 1));
      if (piece == 0) e_expect(fb, UNIT);
      tma_ld2_ef(sb + OFF_SIDE + (c & 1) * UNIT + piece * 4096, (piece & 2) ? &p.wg : &p.wu, fb, fid * 32, c * 128 + (piece & 1) * 64);
    };
    if (warp == 0) {
      {
        int st = 0; uint32_t ph = 1;
#pragma unroll 1
        for (int i = 0; i < 32; i++) {
          const int t = i >> 3, kb = i & 7;
          if (i >= PRE) {
            const uint32_t fb = B(B_FULL1 + st);
            mbar_wait_c(B(B_EMPTY1 + st), ph);
            e_expect(fb, t == 0 ? 3 * UNIT : 2 * UNIT);
            if (t == 0) tma_ld2(sb + kv_a(kb), &p.ckv, fb, kb * 64, mt * 128);
            tma_ld3_mc(sb + kv_b(st) + rank * UNIT, (t & 1) ? &p.wv : &p.wk, fb, 0, kb * 64, (gq + ((t >> 1) ^ 1) * 8) * 4 + rank * 2, 3);
          }
          if (i == LN_GO) e_arrive(B(B_LNGO));
          if (i == 12) { prefetch_tm(&p.wq); prefetch_tm(&p.xn); }
          if (kb == (t ? 0 : 4) && t < 3) tma_pf3((t & 1) ? &p.wk : &p.wv, 0, (mt >> 1) * 64, (gq + (((t + 1) >> 1) ^ 1) * 8) * 4 + (mt & 1) * 2);
          if (kb < 2 && t == 3) tma_pf3(&p.wq, 0, (gq + 8 * kb) * 64, mt * 2);
          if (++st == 3) { st = 0; ph ^= 1; }
        }
        prefetch_tm(&p.wo); prefetch_tm(&p.wd); prefetch_tm(&p.x); prefetch_tm(&p.wg); prefetch_tm(&p.wu);
        mbar_wait_c(B(B_DEP + 0), 0);
        uint32_t kpar = 7, vpar = 3;
        auto load_aw = [&](int kb, int head) {
          const uint32_t d = sb + q_aw(kb & 3), fb = B(B_FULLQ + (kb & 3));
          tma_ld2_mc(d + rank * 8192, &p.xn, fb, kb * 64, ta * 128 + rank * 64, 3);
          tma_ld3(d + UNIT, &p.wq, fb, 0, kb * 64, head * 2);
        };
        auto load_b = [&](int kb, uint32_t fb) { tma_ld2_mc(sb + q_b(kb & 3) + rank * 8192, &p.xn, fb, kb * 64, tb * 128 + rank * 64, 3); };
        auto load3 = [&](int kb, int s) {
          const uint32_t d = sb + r3(s), fb = B(B_FULL3 + s);
          e_expect(fb, SLOT);
          bulk_ld(d, g_ctx + (size_t)(mt * 64 + kb) * 8192, UNIT, fb);
          tma_ld3_mc(d + UNIT + rank * 8192, &p.wo, fb, 0, kb * 64, gq * 2 + rank, 3);
        };
#pragma unroll 1
        for (int half = 0; half < 2; half++) {
          const int head = mt + 16 * half;
#pragma unroll 1
          for (int kb = 2 * half; kb < 16; kb++) {
            if (kb >= 4) mbar_wait_c(B(B_EMPTYQ + (kb & 3)), ((kb >> 2) & 1) ^ 1);
            else if (half) mbar_wait_c(B(B_X + 2), 0);
            else if (kb > 0) mbar_wait_c(B(B_EMPTY1 + (kb + 1) % 3), kb == 1);
            e_expect(B(B_FULLQ + (kb & 3)), 3 * UNIT);
            load_aw(kb, head);
            load_b(kb, B(B_FULLQ + (kb & 3)));
          }
          mbar_wait_c(B(B_DEP + 1 + half), 0);
          const __nv_bfloat16* kt = g_kv + (size_t)head * 16 * KV_TILE;
          l2_prefetch(kt, SLOT);
          auto load_v = [&](int j) {
            const int r = j & 1;
            mbar_wait_c(B(B_VE + r), (vpar >> r) & 1);
            vpar ^= 1 << r;
            e_expect(B(B_VF + r), SLOT);
            bulk_ld(sb + v_slot(j), kt + (size_t)(512 + (j > qa ? 16 - j : j)) * KV_TILE, SLOT, B(B_VF + r));
          };
          int r = 0;
#pragma unroll 1
          for (int j = 0; j < 17; j++) {
            if (j < 2) mbar_wait_c(B(B_EMPTYQ + j), 1);
            if (j == 2) mbar_wait_c(B(B_KE), kpar & 1);
            mbar_wait_c(B(B_KE + r), (kpar >> r) & 1);
            kpar ^= 1 << r;
            e_expect(B(B_KF + r), SLOT);
            bulk_ld(sb + k_slot(j, r), kt + (j > qa ? 16 - j : j) * KV_TILE, SLOT, B(B_KF + r));
            if (++r == 3) r = 0;
            if (j == 2) mbar_wait_c(B(B_EMPTYQ + 3), 1);
            if (j != 1) load_v(j ? j - 1 : 0);
            if (half == 0) {
              if (j == 16) {
                tma_pf3(&p.wq, 0, (4 + gq) * 64, (mt + 16) * 2);
                tma_pf2(&p.xn, (4 + (mp & 3)) * 64, ((mp & 4) ? qa : gq) * 128 + rank * 64);
              }
            } else if (j >= 14) {
              tma_pf3(&p.wo, 0, (5 + mp + 8 * (16 - j)) * 64, gq * 2 + rank);
            } else if (ffn && j >= 5 && j < 13) {
              side_piece((j - 5) >> 2, (j - 5) & 3);
            }
          }
          mbar_wait_c(B(B_X + 0), half);
          if (half == 0) {
            for (int kb = 0; kb < 2; kb++) { e_expect(B(B_FULLQ + kb), 2 * UNIT); load_aw(kb, mt + 16); }
          } else {
            mbar_wait_c(B(B_DEP + 3), 0);
            load3(0, 0);
          }
          mbar_wait_c(B(B_X + 1), half);
          if (half) load3(1, 1);
          load_v(16);
          if (gq == 0) mbar_wait_c(B(B_X + 2), half);
          if (half == 0) { e_expect(B(B_FULLB), 2 * UNIT); load_b(0, B(B_FULLB)); load_b(1, B(B_FULLB)); }
        }
        st = 2; ph = 1;
#pragma unroll 1
        for (int kb = 2; kb < 64; kb++) {
          if (kb == 32) mbar_wait_c(B(B_DEP + 4), 0);
          if (kb >= 6) mbar_wait_c(B(B_EMPTY3 + st), ph);
          else if (kb == 3 || kb == 5) mbar_wait_c(B(B_X + (kb + 1) / 2), 1);
          load3(kb, st);
          if (++st == 6) { st = 0; ph ^= 1; }
          if (kb == PF_KB) e_arrive(B(B_PF));
          if (kb == SET_KB) e_arrive(B(B_SET));
          if (kb == 58) l2_prefetch(xr, XR_CAND * 16);
        }
        if (ffn) {
#pragma unroll 1
          for (int j = 0; j < 2; j++) {
            mbar_wait_c(B(B_EMPTY3 + 4 + j), 1);
            e_expect(B(B_FULL3 + 4 + j), SLOT);
            tma_ld3(sb + r3(4 + j), &p.wd, B(B_FULL3 + 4 + j), 0, fid * 32, 8 * j);
          }
        }
        const uint4* kp = g_xr + ((lane >> 1) * 8 + gq) * XR_SIZE + XR_KEY + (lane & 1) * 2;
        mbar_wait_c(B(B_OUT), 0);
        uint4 kv[2];
        poll_chunks(kv, kp, 1);
        const uint32_t a1 = max(kv[0].x, kv[0].z), a2 = max(min(kv[0].x, kv[0].z), max(kv[0].y, kv[0].w));
        const uint32_t b1 = max(kv[1].x, kv[1].z), b2 = max(min(kv[1].x, kv[1].z), max(kv[1].y, kv[1].w));
        const uint32_t k1 = max(a1, b1), k2 = max(min(a1, b1), max(a2, b2));
        const uint32_t m1 = __reduce_max_sync(~0u, k1);
        const uint32_t m2 = __reduce_max_sync(~0u, k1 == m1 ? k2 : k1);
        const uint32_t t0 = ~m1 & 0x7FFF, t1 = ~m2 & 0x7FFF;
        const uint32_t o0 = (t0 >> 7) * (8 * XR_SIZE * 16) + (t0 & 0x70) * 64, o1 = (t1 >> 7) * (8 * XR_SIZE * 16) + (t1 & 0x70) * 64 + ((t0 ^ t1) < 16 ? 256 : 0);
        asm volatile(ELECT "st.shared.v4.u32 [%0], {%1,%2,%3,%4};\n}" ::"r"(sb + OFF_MISC), "r"(o0), "r"(o1), "r"(m1), "r"(m2) : "memory");
        e_arrive(B(B_OUT2));
        if (rid == 127) { g_cnt[lane] = 0; g_cnt[32 + lane] = 0; }
      }
    } else {
      if (warp >= 2) {
#pragma unroll 1
        for (int i = tid - 64; i < XR_CAND; i += 64) xr[i] = make_uint4(~0u, ~0u, ~0u, ~0u);
        if (warp == 2) { __syncwarp(); if (lane == 0) mbar_arrive(B(B_WR)); }
      }
      if (warp == 3) {
        float ws = 0.f;
#pragma unroll 1
        for (int j = 0; j < 4; j++) {
          const uint4 q = __ldg(reinterpret_cast<const uint4*>(w_r) + j * 32 + lane);
          ws += bf_lo(q.x) + bf_hi(q.x) + bf_lo(q.y) + bf_hi(q.y) + bf_lo(q.z) + bf_hi(q.z) + bf_lo(q.w) + bf_hi(q.w);
        }
#pragma unroll
        for (int o = 16; o; o >>= 1) ws += __shfl_xor_sync(~0u, ws, o);
        uint2* tab = reinterpret_cast<uint2*>(sp + OFF_MISC + 512);
        tab[lane] = make_uint2(0x3F803F80u, 0x3F803F80u);
        tab[32 + lane] = __ldg(reinterpret_cast<const uint2*>(w_r + gq * 128) + lane);
        if (lane == 0) *reinterpret_cast<float*>(sp + OFF_MISC + 1024) = ws;
        __syncwarp();
        if (lane == 0) mbar_arrive(B(B_WR));
      }
      __syncwarp();
      mbar_wait_u(B(B_LNGO), 0);
#pragma unroll 1
      for (int r = warp == 2 ? 0 : (warp + 1) >> 1; r < 16; r += 3) {
        const uint4* src = reinterpret_cast<const uint4*>(x + (size_t)(cta * 16 + r) * DM) + lane;
        uint4 v[4];
#pragma unroll
        for (int j = 0; j < 4; j++) v[j] = __ldcs(src + j * 32);
        float a0 = 0.f, a1 = 0.f, b0 = 0.f, b1 = 0.f;
#pragma unroll
        for (int j = 0; j < 4; j++) {
          const uint32_t u[4] = {v[j].x, v[j].y, v[j].z, v[j].w};
#pragma unroll
          for (int i = 0; i < 4; i++) { const float a = bf_lo(u[i]), b = bf_hi(u[i]); a0 += a; a1 += b; b0 = fmaf(a, a, b0); b1 = fmaf(b, b, b1); }
        }
        a0 += a1; b0 += b1;
#pragma unroll
        for (int o = 16; o; o >>= 1) { a0 += __shfl_xor_sync(~0u, a0, o); b0 += __shfl_xor_sync(~0u, b0, o); }
        const float mean = a0 * (1.f / DM);
        float mb, inv;
        ln_round(mean, fmaxf(fmaf(b0, 1.f / DM, -mean * mean), 0.f), mb, inv);
        const uint32_t nm2 = pack_bf16(-mb, -mb);
        uint4* dst = reinterpret_cast<uint4*>(g_xn + (size_t)(cta * 16 + r) * DM) + lane;
#pragma unroll
        for (int j = 0; j < 4; j++) {
          dst[j * 32] = make_uint4(ln_apply(v[j].x, nm2, inv), ln_apply(v[j].y, nm2, inv), ln_apply(v[j].z, nm2, inv), ln_apply(v[j].w, nm2, inv));
          sched_fence();
        }
      }
      __syncwarp();
      if (lane == 0) {
        fence_gpu();
        red_add(&g_cnt[C_LN + (cta >> 3)], 1);
        TL(0, 20 + warp, true);
        if (warp == 3) {
          spin_until_ge<true>(&g_cnt[C_LN + gq], 24);
#pragma unroll 1
          for (int i = 0; i < 5; i++) {
            const int c = i == 0 ? C_LN + qa : (i < 3 ? C_KV + (i - 1) * 8 + mp : C_CTX + (i - 3) * 16 + mt);
            spin_until_ge<true>(&g_cnt[c], i == 0 ? 24 : 16);
            fence_async_all();
            mbar_arrive(B(B_DEP + i));
          }
        } else if (warp == 1) {
          mbar_wait(B(B_WR), 0);
#pragma unroll 1
          for (int i = 0; i < 6; i++) {
            const int c = i < 2 ? C_KV + gq + (i ^ 1) * 8 : C_CTX + ((i - 2) >> 1) * 16 + ((i & 1) ? tb : ta);
            mbar_wait(B(B_PUB + i), 0);
            fence_gpu();
            red_add(&g_cnt[c], 1);
          }
        }
      }
      __syncwarp();
      if (warp == 2) {
#pragma unroll 1
        for (int c = 2; c < WIN + 4; c++) {
          mbar_wait_u(B(B_WE + (c & 1)), ((c >> 1) & 1) ^ 1);
          if (c == WIN || c == WIN + 1) {
            e_expect(B(B_WF + (c & 1)), UNIT);
            tma_ld3_ef(sb + OFF_SIDE + (c & 1) * UNIT, &p.x, B(B_WF + (c & 1)), 0, mt * 128 + (c & 1) * 64, gq * 2);
          } else if (ffn) {
#pragma unroll 1
            for (int i = 0; i < 4; i++) { side_piece(c < WIN ? c : c - 2, i); __nanosleep(SIDE_NS); }
          }
        }
      } else if (warp == 1) {
        mbar_wait_u(B(B_SET), 0);
#pragma unroll 1
        for (int i = XR_CAND + lane; i < XR_SIZE; i += 32) { xr[i] = make_uint4(~0u, ~0u, ~0u, ~0u); __nanosleep(SET_NS); }
        __syncwarp();
        if (lane == 0) { fence_gpu(); mbar_arrive(B(B_SET2)); }
      } else {
        mbar_wait_u(B(B_PF), 0);
#pragma unroll 1
        for (int i = 0; i < PF_N; i++) {
          asm volatile("prefetch.global.L2 [%0];" ::"l"((const char*)wdown + (size_t)cta * 57344 + (i * 32 + lane) * 128));
          __nanosleep(PF_NS);
        }
      }
      __syncwarp();
      mbar_wait_u(B(B_OUT), 0);
      {
        const int sub = lane >> 4;
        const uint32_t src = sb + OFF_STG + ((lane & 15) >> 3) * 8192 + sub * 128;
        __nv_bfloat16* dst = out + (size_t)(mt * 128 + sub) * DM + gq * 128 + (lane & 15) * 8;
        auto ld = [&](int r, uint2& rs, uint4& v) {
          asm volatile("ld.shared.v2.u32 {%0,%1}, [%2];" : "=r"(rs.x), "=r"(rs.y) : "r"(sb + OFF_RSTAT + ((r + sub) & 127) * 8));
          v = lds128(src + ((r >> 6) & 1) * 16384 + (r & 63) * 128 + (((lane ^ (r + sub)) & 7) << 4));
        };
        uint2 rs; uint4 v;
        ld(2 * warp - 2, rs, v);
#pragma unroll 1
        for (int r = 2 * warp - 2; r < 128; r += 6) {
          const uint2 cs = rs; const uint4 c = v;
          ld(r + 6, rs, v);
          const float inv = __uint_as_float(cs.y);
          asm volatile("{\n.reg .pred p;\nsetp.ge.s32 p, %5, 0;\n@p st.global.v4.u32 [%0], {%1,%2,%3,%4};\n}" ::"l"(dst + (size_t)r * DM),
                       "r"(hadd2_bf(c.x, ln_apply(c.x, cs.x, inv))), "r"(hadd2_bf(c.y, ln_apply(c.y, cs.x, inv))),
                       "r"(hadd2_bf(c.z, ln_apply(c.z, cs.x, inv))), "r"(hadd2_bf(c.w, ln_apply(c.w, cs.x, inv))), "r"(cs.y) : "memory");
        }
      }
      TL(2, 25, warp == 1);
    }
    __syncwarp();
    cluster_arrive();
    cluster_wait();
  } else {
    reg_alloc<232>();
    const int rid_c = rid0 + zero, warp_c = warp0 + zero;
    const int lane = fresh_lane(), rid = rid_c, mt = rid >> 3, gq = rid & 7, qa = 15 - gq, ta = gq ? gq : 15, tb = 15 - ta;
    const int warp = warp_c, cw = warp - 4, w = cw >> 2;
    cluster_wait();
    auto publish = [&](int i) { __syncwarp(); e_arrive(B(B_PUB + i)); };
    auto release2 = [&](uint32_t b, bool cond = true) { mbar_arrive_both(b, lane, cond); };
    AtState s;
    const uint32_t dA = mk_desc(sb + w * 8192, 16);
    const uint32_t dW = mk_desc(sb, 8192);
    auto mma_kb = [&](float (&d)[64], uint32_t a, uint32_t b, int accum) {
      static_for<4>([&](auto k) { mma_n128_ss<1, k * 32, k * 2048>(d, dA + (a >> 4), dW + (b >> 4), k == 0 ? accum : 1); });
    };
    auto mma_kc = [&](float (&d)[64], auto a, auto b, int accum) {
      static_for<4>([&](auto k) { mma_n128_ss<1, decltype(a)::value + k * 32, decltype(b)::value + k * 2048>(d, dA, dW, k == 0 ? accum : 1); });
    };
    auto issue_q = [&](int kb, auto accum) {
      const int st = kb & 3;
      mbar_wait_c(B(B_FULLQ + st), (kb >> 2) & 1);
      wg_fence();
      mma_kb(s.S, q_aw(st), q_aw(st) + UNIT, accum);
      wg_commit();
      if (accum) {
        wg_wait<1>();
        release2(B(B_EMPTYQ + ((kb - 1) & 3)));
        wg_fence();
      }
      mma_kb(s.O, q_b(st), q_aw(st) + UNIT, accum);
      wg_commit();
    };
    {
      uint4 pk[16];
      __nv_bfloat16* pdst = g_kv;
      auto put = [&](int i) { __stcs(reinterpret_cast<uint4*>(pdst + (i & 1) * 256 + ((i >> 1) & 3) * 4096 + (i >> 3) * 16 * KV_TILE), pk[i]); };
      float acc1[128];
      TL(0, 1, warp == 4);
      int st = 0; uint32_t ph = 0;
      auto issue = [&](int kb, int accum) {
        mbar_wait_c(B(B_FULL1 + st), ph);
        wg_fence();
        static_for<4>([&](auto k) { mma_n256_ss<1, k * 32, k * 2048>(acc1, dA + (kv_a(kb) >> 4), dW + (kv_b(st) >> 4), k == 0 ? accum : 1); });
        wg_commit();
      };
#pragma unroll 1
      for (int t = 0; t < 4; t++) {
        issue(0, 0);
        TL(0, 2 + 2 * t, warp == 4);
        if (t > 0) { put(0); put(1); }
        int prev = st;
        if (++st == 3) { st = 0; ph ^= 1; }
#pragma unroll 1
        for (int kb = 1; kb < 8; kb++) {
          if (kb == 7 && w == 1) bar_sync(5, 256);
          issue(kb, 1);
          if (kb == 7 && w == 0) bar_arrive(5, 256);
          if (t > 0) {
#pragma unroll
            for (int i = 1; i < 8; i++) if (kb == i) { put(2 * i); put(2 * i + 1); }
            if (kb == 7 && t == 2) publish(0);
          }
          wg_wait<1>();
          TK(24 + t * 8 + kb - 1);
          release2(B(B_EMPTY1 + prev));
          prev = st;
          if (++st == 3) { st = 0; ph ^= 1; }
        }
        pdst = g_kv + (size_t)(((t & 1) * 32 + (gq + ((t >> 1) ^ 1) * 8) * 2) * 16 + mt) * KV_TILE + (cw * 16 + (lane >> 2)) * 32 + ((lane ^ (lane >> 3)) & 3) * 8;
        wg_wait<0>();
        TK(24 + t * 8 + 7);
        fence_regs(acc1);
        release2(B(B_EMPTY1 + prev));
        TL(0, 3 + 2 * t, warp == 4);
#pragma unroll
        for (int a = 0; a < 8; a++)
#pragma unroll
          for (int h = 0; h < 2; h++)
            pk[2 * a + h] = make_uint4(pack_bf16(acc1[16 * a + 2 * h], acc1[16 * a + 2 * h + 1]), pack_bf16(acc1[16 * a + 4 + 2 * h], acc1[16 * a + 5 + 2 * h]),
                                       pack_bf16(acc1[16 * a + 8 + 2 * h], acc1[16 * a + 9 + 2 * h]), pack_bf16(acc1[16 * a + 12 + 2 * h], acc1[16 * a + 13 + 2 * h]));
      }
      issue_q(0, IC<0>{});
      TL(0, 10, warp == 4);
      put(0); put(1);
#pragma unroll 1
      for (int kb = 1; kb < 8; kb++) {
        issue_q(kb, IC<1>{});
        TK(66 + kb - 1);
#pragma unroll
        for (int i = 1; i < 8; i++) if (kb == i) { put(2 * i); put(2 * i + 1); }
      }
      publish(1);
      TL(0, 11, warp == 4);
    }
    __nv_bfloat16* cdst;
    uint32_t redo = 0;
    auto put_ctx = [&](int i, bool cond) {
      asm volatile("{\n.reg .pred p;\nsetp.ne.u32 p, %5, 0;\n@p st.global.cs.v4.u32 [%0], {%1,%2,%3,%4};\n}" ::"l"(cdst + (i & 1) * 256 + (i >> 1) * 4096),
                   "r"(s.P[4 * i]), "r"(s.P[4 * i + 1]), "r"(s.P[4 * i + 2]), "r"(s.P[4 * i + 3]), "r"((uint32_t)(cond && !(redo & 2))) : "memory");
    };
    {
      const int wrow = cw * 16;
      const uint32_t dK = mk_desc(sb, 16), dV = mk_desc(sb, 8192);
      uint32_t kph = 0, vph = 0;
      auto q_store = [&](const float (&d)[64]) {
        const int r0 = lane >> 2;
        const uint32_t a = sb + SLOT + (wrow + r0) * 128 + (((lane & 3) ^ (((r0 & 1) << 2) | (r0 >> 1))) << 4);
#pragma unroll
        for (int i = 0; i < 8; i++) {
          const float* o = d + 16 * (i >> 1) + 2 * (i & 1);
          asm volatile("st.shared.v4.u32 [%0], {%1,%2,%3,%4};" ::"r"((a ^ ((i & 2) << 5)) + (i >> 2) * UNIT + (i & 1) * 1024),
                       "r"(pack_bf16(o[0] * AT_C, o[1] * AT_C)), "r"(pack_bf16(o[4] * AT_C, o[5] * AT_C)),
                       "r"(pack_bf16(o[8] * AT_C, o[9] * AT_C)), "r"(pack_bf16(o[12] * AT_C, o[13] * AT_C)) : "memory");
        }
        __syncwarp();
      };
      auto q_load = [&](auto k0, auto k1) {
        const uint32_t a = sb + SLOT + (wrow + (lane & 15)) * 128 + (((lane >> 4) ^ (((lane & 1) << 2) | ((lane >> 1) & 3))) << 4);
#pragma unroll
        for (int k = k0; k < k1; k++)
          asm volatile("ldmatrix.sync.aligned.m8n8.x4.shared.b16 {%0,%1,%2,%3}, [%4];"
                       : "=r"(s.Q[4 * k]), "=r"(s.Q[4 * k + 1]), "=r"(s.Q[4 * k + 2]), "=r"(s.Q[4 * k + 3]) : "r"((a ^ ((k & 3) << 5)) + (k >> 2) * UNIT) : "memory");
      };
      auto q_load_if = [&](auto k, bool cond, float after) {
        const uint32_t a = sb + SLOT + (wrow + (lane & 15)) * 128 + (((lane >> 4) ^ (((lane & 1) << 2) | ((lane >> 1) & 3))) << 4);
        asm volatile("{\n.reg .pred p;\nsetp.ne.u32 p, %5, 0;\n@p ldmatrix.sync.aligned.m8n8.x4.shared.b16 {%0,%1,%2,%3}, [%4];\n}"
                     : "+r"(s.Q[4 * k]), "+r"(s.Q[4 * k + 1]), "+r"(s.Q[4 * k + 2]), "+r"(s.Q[4 * k + 3])
                     : "r"((a ^ ((k & 3) << 5)) + (k >> 2) * UNIT + (__float_as_uint(after) >> 31)), "r"((uint32_t)cond) : "memory");
      };
      auto issue_s = [&](uint32_t dk) {
        mma_n128_rs0<0>(s.S, s.Q, dk);
        static_for<7>([&](auto i) { constexpr int k = i + 1; mma_n128_rs<0, (k >> 1) * 8192 + (k & 1) * 32>(s.S, s.Q + 4 * k, dk, 1); });
        wg_commit();
      };
      auto wait_v = [&](int jv) {
        mbar_wait_c(B(B_VF + (jv & 1)), (vph >> (jv & 1)) & 1);
        vph ^= 1 << (jv & 1);
      };
      auto issue_pva = [&](int jv, int accum) {
        wg_fence();
        static_for<4>([&](auto k) { mma_n128_rs<1, k * 1024>(s.O, s.P + 4 * k, dV + (v_slot(jv) >> 4), k == 0 ? accum : 1); });
        wg_commit();
      };
      auto issue_pvb = [&](int jv, bool upper) {
        if (upper) {
          wg_fence();
          static_for<4>([&](auto k) { mma_n128_rs<1, (k + 4) * 1024>(s.O, s.P + 16 + 4 * k, dV + (v_slot(jv) >> 4), 1); });
          wg_commit();
        } else {
          asm volatile("wgmma.fence.sync.aligned;\nwgmma.commit_group.sync.aligned;" ::: "memory");
        }
      };
      auto issue_pv = [&](int jv, int accum, bool upper) { wait_v(jv); issue_pva(jv, accum); issue_pvb(jv, upper); };
      if (w == 1) bar_arrive(1, 256);
#pragma unroll 1
      for (int half = 0; half < 2; half++) {
        const int head = mt + 16 * half;
        redo = 0;
        float inv[2];
        auto ep_prep = [&]() {
          float l0 = s.l[0] + s.l[1], l1 = s.l[2] + s.l[3];
          l0 += __shfl_xor_sync(~0u, l0, 1); l1 += __shfl_xor_sync(~0u, l1, 1);
          l0 += __shfl_xor_sync(~0u, l0, 2); l1 += __shfl_xor_sync(~0u, l1, 2);
          asm("rcp.approx.ftz.f32 %0, %1;" : "=f"(inv[0]) : "f"(l0));
          asm("rcp.approx.ftz.f32 %0, %1;" : "=f"(inv[1]) : "f"(l1));
          return __any_sync(~0u, !(fminf(l0, l1) >= L_MIN && l0 + l1 <= L_MAX));
        };
        auto ep_out = [&](auto i0, auto i1) {
          __nv_bfloat16* dst = g_ctx + (size_t)(ta * 32 + head) * KV_TILE + (wrow + (lane >> 2)) * 32 + ((lane ^ (lane >> 3)) & 3) * 8;
#pragma unroll
          for (int i = i0; i < i1; i++) {
            const float* o = s.O + 16 * (i >> 1) + 2 * (i & 1);
            const float c = inv[i & 1];
            asm volatile("st.global.cs.v4.u32 [%0], {%1,%2,%3,%4};" ::"l"(dst + (i & 1) * 256 + (i >> 1) * 4096), "r"(pack_bf16(o[0] * c, o[1] * c)),
                         "r"(pack_bf16(o[4] * c, o[5] * c)), "r"(pack_bf16(o[8] * c, o[9] * c)), "r"(pack_bf16(o[12] * c, o[13] * c)) : "memory");
          }
        };
        auto ep_rest = [&]() {
          ep_out(IC<EP1>{}, IC<8>{});
          if (!__any_sync(~0u, redo)) publish(2 + 2 * half);
          fence_regs(s.O);
        };
#pragma unroll 1
        for (int kb = 8; kb < 14; kb++) {
          issue_q(kb, IC<1>{});
          TK(66 + half * 24 + kb - 1);
        }
        TL(1, 20 * half + 0, warp == 4);
        mbar_wait_c(B(B_FULLQ + 2), 1);
        mbar_wait_c(B(B_FULLQ + 3), 1);
        bar_sync(1 + w, 256);
        wg_fence();
        mma_kc(s.S, IC<q_aw(2)>{}, IC<q_aw(2) + UNIT>{}, 1);
        wg_commit();
        wg_wait<1>();
        TK(66 + half * 24 + 13);
        release2(B(B_EMPTYQ + 1));
        wg_fence();
        mma_kc(s.S, IC<q_aw(3)>{}, IC<q_aw(3) + UNIT>{}, 1);
        wg_commit();
        bar_arrive(2 - w, 256);
        bar_sync(6 + w, 128);
        wg_wait<0>();
        TK(66 + half * 24 + 14);
        fence_regs(s.S);
        q_store(s.S);
        q_load(IC<0>{}, IC<8>{});
        TL(1, 20 * half + 1, warp == 4);
        TC(w, 17 * half, 0);
        mbar_wait_c(B(B_KF), kph & 1);
        kph ^= 1;
        bar_sync(1 + w, 256);
        TC(w, 17 * half, 2);
        fence_regs(s.O); fence_regs(s.Q);
        wg_fence();
        issue_s(dK);
        mma_kc(s.O, IC<q_b(2)>{}, IC<q_aw(2) + UNIT>{}, 1);
        mma_kc(s.O, IC<q_b(3)>{}, IC<q_aw(3) + UNIT>{}, 1);
        wg_commit();
        bar_arrive(2 - w, 256);
        wg_wait<1>();
        TC(w, 17 * half, 4);
        fence_regs(s.S);
        e_arrive(B(B_KE));
        s.l[0] = s.l[1] = s.l[2] = s.l[3] = 0.f;
        at_exp<0, 48>(s);
        at_pack<0, 22>(s);
        sched_fence();
        wg_wait<0>();
        fence_regs(s.O); fence_regs(s.Q);
        release2(B(B_EMPTYQ + 2)); release2(B(B_EMPTYQ + 3));
        at_exp<48, 64>(s);
        at_pack<22, 32>(s);
        q_store(s.O);
        TL(1, 20 * half + 2, warp == 4);
        int kr = 1;
        bool kok = false;
        inv[0] = inv[1] = 0.f;
        const int db = gq ? qa : 16;
#pragma unroll 1
        for (int j = 1; j < 17; j++) {
          const bool diag = j == ta || j == db;
          TC(w, j + 17 * half, 0);
          if (!kok) mbar_wait_c(B(B_KF + kr), (kph >> kr) & 1);
          kph ^= 1 << kr;
          if (j == ta + 2) ep_out(IC<0>{}, IC<EP1>{});
          bar_sync(1 + w, 256);
          TC(w, j + 17 * half, 2);
          fence_regs(s.O); fence_regs(s.P); fence_regs(s.Q);
          const uint32_t ke = B(B_KE + kr), dk = dK + (k_slot(j, kr) >> 4);
          if (++kr == 3) kr = 0;
          auto issue_rest = [&](auto trimmed) {
            TC(w, j + 17 * half, 1);
            if (j == ta + 1) {
              if (ep_prep()) redo = 1;
              s.l[0] = s.l[1] = s.l[2] = s.l[3] = 0.f;
            }
            if (!trimmed && j == ta + 2) ep_rest();
            TC(w, j + 17 * half, 3);
            issue_pv(j - 1, j != 1 && j != ta + 2, w == 1 || (j != ta + 1 && j != db + 1));
            bar_arrive(2 - w, 256);
          };
          auto s_done = [&](auto n) {
            wg_wait<2>();
            TC(w, j + 17 * half, 4);
            fence_part<0, n>(s.S); fence_regs(s.Q);
            e_arrive(ke);
            release2(B(B_X + j - 14), j == 14 || j == 15);
          };
          auto pv_half = [&]() { sched_fence(); wg_wait<1>(); fence_regs(s.P); };
          auto pv_done = [&]() {
            sched_fence();
            wg_wait<0>();
            fence_regs(s.O); fence_regs(s.P);
            e_arrive(B(B_VE + ((j - 1) & 1)));
            release2(B(B_X + 2), j == 16);
            kok = mbar_test(B(B_KF + kr), (kph >> kr) & 1);
          };
          if (diag && w == 0) {
            wg_fence();
            static_for<8>([&](auto k) { mma_n64_rs<0, (k >> 1) * 8192 + (k & 1) * 32, k != 0>(s.S, s.Q + 4 * k, dk); });
            wg_commit();
            issue_rest(IC<1>{});
            s_done(IC<32>{});
            at_mask<0>(s, wrow, lane);
            pv_half();
            static_for<8>([&](auto k) {
              at_exp<4 * k, 4 * k + 4>(s);
              q_load_if(k, j == ta, s.S[4 * k]);
            });
            at_pack<0, 16>(s);
            pv_done();
          } else {
            wg_fence();
            issue_s(dk);
            issue_rest(IC<0>{});
            if (!diag) {
              s_done(IC<64>{});
              at_exp<0, 24>(s);
              pv_half();
              at_exp<24, 48>(s);
              at_pack<0, 16>(s);
              pv_done();
              at_exp<48, 64>(s);
              at_pack<16, 32>(s);
            } else {
              s_done(IC<64>{});
              at_mask<8>(s, wrow - 64, lane);
              static_for<8>([&](auto k) {
                at_exp<7 * k, 7 * k + 7>(s);
                q_load_if(k, j == ta, s.S[7 * k + 3]);
                if (k == 2) pv_half();
                if (k == 5) { at_pack<0, 16>(s); pv_done(); }
              });
              at_exp<56, 64>(s);
              at_pack<16, 32>(s);
            }
          }
          TL(1, 20 * half + 2 + j, warp == 4);
        }
        TK(84 + half * 24);
        mbar_wait_c(B(half ? B_FULL3 : B_FULLQ), 0);
        if (gq == 0) ep_out(IC<0>{}, IC<EP1>{});
        bar_sync(1 + w, 256);
        fence_regs(s.O); fence_regs(s.P);
        const uint32_t ga = dA - half * w * 256, gb = ga + (half ? 512 : 4), gh = half ? 0x80000020u : 0x40000040u, go = (2 + half) * (SLOT >> 4);
        wg_fence();
        static_for<4>([&](auto k) { mma_n128_ssh<(k & 1) * 32, UNIT + k * 2048, k != 0>(s.S, k < 2 ? ga : gb, gh, dW); });
        mbar_wait_c(B(half ? B_FULL3 + 1 : B_FULLQ + 1), 0);
        wg_fence();
        static_for<4>([&](auto k) { mma_n128_ssh<(k & 1) * 32, UNIT + k * 2048, true>(s.S, (k < 2 ? ga : gb) + go, gh, dW + go); });
        wg_commit();
        TK(85 + half * 24);
        if (gq == 0) ep_rest();
        issue_pv(16, gq != 0, w == 1 || gq != 0);
        if (w == 0 || half == 0) bar_arrive(2 - w, 256);
        TK(86 + half * 24);
        wg_wait<2>();
        release2(B(B_EMPTY3), half); release2(B(B_EMPTY3 + 1), half);
        if (ep_prep()) redo |= 2;
        sched_fence();
        wg_wait<0>();
        TK(87 + half * 24);
        fence_regs(s.S);
        fence_regs(s.O);
        e_arrive(B(B_VE));
        release2(B(B_X + 3));
        fence_regs(s.P);
        {
          const int r = fresh_lane();
          cdst = g_ctx + (size_t)(tb * 32 + head) * KV_TILE + (wrow + (r >> 2)) * 32 + ((r ^ (r >> 3)) & 3) * 8;
        }
#pragma unroll
        for (int i = 0; i < 32; i++) {
          const float* o = s.O + 16 * (i >> 3) + 2 * ((i >> 2) & 1) + 4 * (i & 3);
          s.P[i] = pack_bf16(o[0] * inv[(i >> 2) & 1], o[1] * inv[(i >> 2) & 1]);
        }
        fence_regs(s.P);
        if (__builtin_expect(__any_sync(~0u, redo != 0), 0)) {
#pragma unroll
          for (int i = 0; i < 8; i++) put_ctx(i, true);
#pragma unroll 1
          for (int t = 0; t < 2; t++) {
            if (__any_sync(~0u, (redo >> t) & 1)) slow_rows(wq, head, (t ? tb : ta) * 128 + wrow);
          }
          if (__any_sync(~0u, redo & 1)) publish(2 + 2 * half);
#pragma unroll
          for (int i = 0; i < 32; i++) s.P[i] = 0;
          redo = 2;
        }
        TL(1, 20 * half + 19, warp == 4);
        TK(88 + half * 24);
        if (half) break;
        mbar_wait_c(B(B_FULLB), 0);
        TK(89);
        wg_fence();
        mma_n128_ss0<1, q_b(0), UNIT>(s.O, dA, dW);
        static_for<3>([&](auto k) { mma_n128_ss<1, q_b(0) + k * 32 + 32, UNIT + k * 2048 + 2048>(s.O, dA, dW, 1); });
        wg_commit();
        mma_kc(s.O, IC<q_b(1)>{}, IC<q_aw(1) + UNIT>{}, 1);
        wg_commit();
        wg_wait<1>();
        release2(B(B_EMPTYQ));
        put_ctx(0, true);
#pragma unroll 1
        for (int kb = 2; kb < 8; kb++) {
          issue_q(kb, IC<1>{});
          TK(90 + kb - 1);
#pragma unroll
          for (int i = 1; i < 8; i++) put_ctx(i, kb == (i < 7 ? i + 1 : 7));
        }
        publish(3);
      }
    }
    const int rid_ = rid + zero, cw_ = cw + zero;
    {
    const int lane = fresh_lane(), rid = rid_, mt = rid >> 3, gq = rid & 7, cw = cw_, w = cw >> 2, ct = cw * 32 + lane;
    const int fid = mt * 7 + gq;
    const bool ffn = gq < 7;
    const uint32_t stg = sb + OFF_STG + w * 16384 + (cw & 3) * 2048;
    const int wr_ = w * 64 + (lane & 7) + (lane >> 4) * 8;
    const uint32_t wl = sb + ((lane >> 3) & 1) * 8192 + wr_ * 64 + (((cw ^ (wr_ >> 1)) & 3) << 4);
    __syncwarp();
    float (&acc)[64] = s.S;
    uint32_t wf[128];
    auto grab = [&](auto c, uint32_t off) {
#pragma unroll
      for (int m = 0; m < 4; m++)
        asm volatile("ldmatrix.sync.aligned.m8n8.x4.trans.shared.b16 {%0,%1,%2,%3}, [%4];"
                     : "=r"(wf[16 * c + 4 * m]), "=r"(wf[16 * c + 4 * m + 1]), "=r"(wf[16 * c + 4 * m + 2]), "=r"(wf[16 * c + 4 * m + 3])
                     : "r"(wl + off + m * 1024) : "memory");
    };
    const int r0 = lane >> 2;
    uint32_t hp[32], rt[16];
    {
      const uint32_t dC = mk_desc(sb + w * 4096, 16);
      uint32_t dep = 0;
      auto hand = [&](uint32_t b, int n) {
        asm volatile("{\n.reg .pred p;\n.reg .b32 t;\nsetp.lt.u32 p, %1, %4;\nmad.lo.u32 t, %2, %3, %0;\n@p mbarrier.arrive.shared::cta.b64 _, [t];\n}"
                     ::"r"(b + 8 * lane), "r"(lane), "r"(dep), "r"(zero), "r"(n) : "memory");
      };
      auto kblock = [&](auto st, uint32_t ph, bool rel) {
        mbar_wait_c(B(B_FULL3 + st), ph);
        wg_fence();
        static_for<4>([&](auto k) { mma_n128_ssh<r3(decltype(st)::value) + (k >> 1) * 8192 + (k & 1) * 32, r3(decltype(st)::value) + UNIT + k * 2048, true>(acc, dC, 0x80000020u, dW); });
        wg_commit();
        wg_wait<1>();
        release2(B(B_EMPTY3 + (st + 5) % 6), rel);
      };
      auto ldsm_if = [&](uint32_t* r, uint32_t a, bool c, auto trans) {
        if (trans) asm volatile("{\n.reg .pred p;\nsetp.ne.u32 p, %5, 0;\n@p ldmatrix.sync.aligned.m8n8.x4.trans.shared.b16 {%0,%1,%2,%3}, [%4];\n}"
                                : "+r"(r[0]), "+r"(r[1]), "+r"(r[2]), "+r"(r[3]) : "r"(a), "r"((uint32_t)c) : "memory");
        else asm volatile("{\n.reg .pred p;\nsetp.ne.u32 p, %5, 0;\n@p ldmatrix.sync.aligned.m8n8.x4.shared.b16 {%0,%1,%2,%3}, [%4];\n}"
                          : "+r"(r[0]), "+r"(r[1]), "+r"(r[2]), "+r"(r[3]) : "r"(a), "r"((uint32_t)c) : "memory");
      };
#pragma unroll
      for (int i = 0; i < 48; i++) wf[i] = 0;
#pragma unroll 1
      for (int lap = 0; lap < 3; lap++) {
        kblock(IC<2>{}, lap & 1, lap > 0);
#pragma unroll
        for (int i = 0; i < 3; i++) put_ctx(3 * i, lap == i);
        kblock(IC<3>{}, lap & 1, true);
        if (ffn) mbar_wait_c(B(B_WF + (lap & 1)), lap >> 1);
#pragma unroll
        for (int i = 0; i < 12; i++) ldsm_if(wf + 4 * i, wl + OFF_SIDE + ((i >> 2) & 1) * UNIT + (i & 3) * 1024, lap == (i >> 2), IC<1>{});
        kblock(IC<4>{}, lap & 1, true);
        sched_fence();
        dep = 0;
#pragma unroll
        for (int i = 0; i < 12; i++) dep ^= wf[4 * i];
        hand(B(B_WE + (lap & 1)), 1);
#pragma unroll
        for (int i = 0; i < 3; i++) put_ctx(3 * i + 1, lap == i);
        kblock(IC<5>{}, lap & 1, true);
        if (lap == 2) publish(5);
        kblock(IC<0>{}, (lap & 1) ^ 1, true);
#pragma unroll
        for (int i = 0; i < 2; i++) put_ctx(3 * i + 2, lap == i);
        kblock(IC<1>{}, (lap & 1) ^ 1, true);
        TL(2, 40 + lap, warp == 4);
      }
#pragma unroll
      for (int i = 48; i < 96; i++) wf[i] = 0;
#pragma unroll
      for (int i = 0; i < 32; i++) { hp[i] = 0; rt[i >> 1] = 0; }
      const uint32_t xa = sb + OFF_SIDE + w * UNIT + (cw & 3) * 2048 + (lane & 15) * 128 + (((lane >> 4) ^ (lane & 7)) << 4);
#pragma unroll 1
      for (int lap = 3; lap < 11; lap++) {
        kblock(IC<2>{}, lap & 1, true);
        kblock(IC<3>{}, lap & 1, true);
        if (lap == 10) break;
        if (lap < WIN) {
          if (ffn) mbar_wait_c(B(B_WF + (lap & 1)), (lap >> 1) & 1);
#pragma unroll
          for (int i = 12; i < 24; i++) ldsm_if(wf + 4 * i, wl + OFF_SIDE + ((i >> 2) & 1) * UNIT + (i & 3) * 1024, lap == (i >> 2), IC<1>{});
        } else if (lap == WIN) {
          mbar_wait_c(B(B_WF), ffn ? (WIN >> 1) & 1 : 0);
          mbar_wait_c(B(B_WF + 1), ffn ? (WIN >> 1) & 1 : 0);
#pragma unroll
          for (int j = 0; j < 8; j++) ldsm_if(hp + 4 * j, (xa ^ ((j & 3) << 5)) + (j >> 2) * 8192, true, IC<0>{});
        } else if (lap == 9) {
          mbar_wait_c(B(B_WR), 0);
          mbar_wait_c(B(B_SET2), 0);
#pragma unroll
          for (int j = 0; j < 4; j++) ldsm_if(rt + 4 * j, sb + OFF_MISC + 512 + (lane & 1) * 256 + (lane >> 3) * 16 + j * 64, true, IC<0>{});
        }
        kblock(IC<4>{}, lap & 1, true);
        sched_fence();
        dep = 0;
#pragma unroll
        for (int i = 0; i < 20; i++) dep ^= i < 12 ? wf[48 + 4 * i] : hp[4 * (i - 12)];
        hand(B(B_WE + (lap < WIN ? lap & 1 : 0)), lap < WIN ? 1 : (lap == WIN ? 2 : 0));
        kblock(IC<5>{}, lap & 1, true);
        kblock(IC<0>{}, (lap & 1) ^ 1, true);
        kblock(IC<1>{}, (lap & 1) ^ 1, true);
        TL(2, 40 + lap, warp == 4);
      }
    }
    uint4* const xr = g_xr + rid * XR_SIZE;
    uint4* const psd = xr + XR_PS + cw * 16 + r0;
    settle(psd, zero);
    sched_fence();
    wg_wait<0>();
    fence_regs(acc);
    TL(2, 10, warp == 4);
    {
      float d[4] = {0.f, 0.f, 0.f, 0.f}, qa[4] = {0.f, 0.f, 0.f, 0.f}, qb[4] = {0.f, 0.f, 0.f, 0.f};
#pragma unroll
      for (int j = 0; j < 16; j++) {
        hp[2 * j] = hadd2_bf(hp[2 * j], pack_bf16(acc[4 * j], acc[4 * j + 1]));
        hp[2 * j + 1] = hadd2_bf(hp[2 * j + 1], pack_bf16(acc[4 * j + 2], acc[4 * j + 3]));
        if (j & 1) {
          mma16816(d, hp[2 * j - 2], hp[2 * j - 1], hp[2 * j], hp[2 * j + 1], rt[j - 1], rt[j]);
          mma16816(qa, hp[2 * j - 2], hp[2 * j - 1], hp[2 * j], hp[2 * j + 1], hp[2 * j - 2], hp[2 * j]);
          mma16816(qb, hp[2 * j - 2], hp[2 * j - 1], hp[2 * j], hp[2 * j + 1], hp[2 * j - 1], hp[2 * j + 1]);
        }
      }
      asm volatile("{\n.reg .pred p;\nsetp.eq.u32 p, %7, %8;\n@p st.global.cg.v4.f32 [%0], {%1,%2,%3,%3};\n@p st.global.cg.v4.f32 [%0 + 128], {%4,%5,%6,%6};\n}"
                   ::"l"(psd), "f"(d[0]), "f"(d[1]), "f"((r0 & 1) ? qa[1] : qa[0]), "f"(d[2]), "f"(d[3]), "f"((r0 & 1) ? qb[3] : qb[2]),
                   "r"(lane & 3), "r"(r0 >> 1) : "memory");
      sched_fence();
    }
    mbar_wait_c(B(B_EMPTY3), 0);
    __syncwarp();
    stage_store_128(stg, lane, hp);
    TL(2, 11, warp == 4);
    __syncwarp();
    uint4 cout;
    uint32_t ckey;
    {
      const float wsum = *reinterpret_cast<const float*>(sp + OFF_MISC + 1024);
      const uint4* pp = g_xr + (mt * 8 + (ct & 1) * 4) * XR_SIZE + XR_PS + (ct >> 1);
      uint2* kd = reinterpret_cast<uint2*>(xr + XR_KEY) + cw;
      const uint32_t tok = 0x7FFFu - (mt * 128 + (ct >> 1));
      settle(pp, zero); settle(kd, zero); settle(tok, zero);
      spin_clk(PS_DLY);
      float s1, s2, s3;
#pragma unroll 1
      for (int n = 0; n < 0x400000; n++) {
        float4 z[4];
#pragma unroll
        for (int i = 0; i < 4; i++)
          asm volatile("ld.relaxed.gpu.global.v4.f32 {%0,%1,%2,%3}, [%4];" : "=f"(z[i].x), "=f"(z[i].y), "=f"(z[i].z), "=f"(z[i].w) : "l"(pp + i * XR_SIZE) : "memory");
        s1 = (z[0].x + z[1].x) + (z[2].x + z[3].x); s3 = (z[0].y + z[1].y) + (z[2].y + z[3].y); s2 = (z[0].z + z[1].z) + (z[2].z + z[3].z);
        const float t = s1 + s2 + s3;
        s1 += __shfl_xor_sync(~0u, s1, 1); s2 += __shfl_xor_sync(~0u, s2, 1); s3 += __shfl_xor_sync(~0u, s3, 1);
        if (__all_sync(~0u, t == t)) break;
        uint32_t m = 0;
#pragma unroll
        for (int i = 0; i < 4; i++) m = max(max(m, __float_as_uint(z[i].x)), max(__float_as_uint(z[i].y), __float_as_uint(z[i].z)));
        if (__all_sync(~0u, m != 0xFFFFFFFFu)) break;
      }
      TL(2, 12, warp == 4);
      const float mean = s1 * (1.f / DM);
      float mb, inv;
      ln_round(mean, fmaxf(fmaf(s2, 1.f / DM, -mean * mean), 0.f), mb, inv);
      const uint32_t u = pack_bf16(0.f, fmaf(s3 - mb * wsum, inv, 0.f));
      const uint32_t key = ((u ^ (((int)u >> 31) | 0x80000000u)) & 0xFFFF0000u) | tok;
      const uint32_t c1 = __reduce_max_sync(~0u, key);
      const uint32_t c2 = __reduce_max_sync(~0u, key == c1 ? 0u : key);
      asm volatile(ELECT "st.global.cg.v2.u32 [%0], {%1,%2};\n}" ::"l"(kd), "r"(c1), "r"(c2) : "memory");
      sched_fence();
      const uint32_t nm2 = pack_bf16(-mb, -mb);
      if (!(ct & 1)) *reinterpret_cast<uint2*>(sp + OFF_RSTAT + (ct >> 1) * 8) = make_uint2(nm2, __float_as_uint(inv) | (key >= c2 ? 0x80000000u : 0u));
      ckey = (lane >> 4) ? c2 : c1;
      const int row = (0x7FFF - (ckey & 0x7FFF)) & 15;
      const uint32_t rn = __shfl_sync(~0u, nm2, row * 2);
      const float ri = __shfl_sync(~0u, inv, row * 2);
      const uint4 v = lds128(stg + ((lane & 15) >> 3) * 8192 + row * 128 + (((lane & 7) ^ (row & 7)) << 4));
      const uint4 n = make_uint4(ln_apply(v.x, rn, ri), ln_apply(v.y, rn, ri), ln_apply(v.z, rn, ri), ln_apply(v.w, rn, ri));
      __stcg(xr + XR_CAND + cw * 64 + 32 + lane, n);
      __stcg(xr + XR_CAND + cw * 64 + lane, v);
      cdst = out + (size_t)(0x7FFF - (ckey & 0x7FFF)) * DM + gq * 128 + (lane & 15) * 8;
      cout = make_uint4(hadd2_bf(v.x, n.x), hadd2_bf(v.y, n.y), hadd2_bf(v.z, n.z), hadd2_bf(v.w, n.w));
    }
    publish(B_OUT - B_PUB);
    cluster_arrive();
    TL(2, 13, warp == 4);
    uint32_t wd[16][4];
    if (ffn) {
      static_for<2>([&](auto i) {
        mbar_wait_b(B(B_WF + i), ((WIN >> 1) & 1) ^ 1);
        grab(IC<WIN + i>{}, OFF_SIDE + i * UNIT);
      });
      mbar_wait_b(B(B_FULL3 + 4 + w), 0);
#pragma unroll
      for (int i = 0; i < 16; i++) {
        const int k = (i & 1) * 16 + (lane & 7) + (lane >> 4) * 8;
        asm volatile("ldmatrix.sync.aligned.m8n8.x4.trans.shared.b16 {%0,%1,%2,%3}, [%4];"
                     : "=r"(wd[i][0]), "=r"(wd[i][1]), "=r"(wd[i][2]), "=r"(wd[i][3])
                     : "r"(sb + r3(4) + w * SLOT + (2 * (cw & 3) + (i >> 3)) * 4096 + k * 128 + (((2 * ((i >> 1) & 3) + ((lane >> 3) & 1)) ^ (lane & 7)) << 4)) : "memory");
      }
    }
    const int fc = 16 * (rid >> 1) + 4 * (rid & 1) + (lane & 3) + 8 * (lane >> 4), ft = (lane >> 3) & 1;
    const char* pc = reinterpret_cast<const char*>(g_xr + ((ct & 127) >> 4) * XR_SIZE + XR_CAND + 32 + (ct & 15));
    const char* pf = reinterpret_cast<const char*>(g_xr + (fc >> 7) * XR_SIZE + XR_CAND) + (fc & 127) * 2;
    const uint32_t xs = sb + OFF_SCR + w * 2112 + ((ct & 127) >> 2) * 64 + (((ct >> 3) & 3) << 4) + (ct & 3) * 4;
    const uint32_t xb = sb + OFF_SCR + (r0 & 1) * 2112 + w * 128 + (((lane ^ w) & 3) << 4);
    settle(pc, zero); settle(pf, zero); settle(cdst, zero); settle(xs, zero); settle(xb, zero);
    mbar_wait_b(B(B_OUT2), 0);
    const uint4 top = lds128(sb + OFF_MISC);
    TL(2, 14, warp == 4);
    uint32_t fh, fn;
    {
      pc += w ? top.y : top.x;
      pf += ft ? top.y : top.x;
      uint4 v;
#pragma unroll 1
      for (int n = 0; n < 0x400000; n++) {
        asm volatile("ld.relaxed.gpu.global.v4.u32 {%0,%1,%2,%3}, [%4];" : "=r"(v.x), "=r"(v.y), "=r"(v.z), "=r"(v.w) : "l"(pc) : "memory");
        asm volatile("ld.relaxed.gpu.global.u16 %0, [%1];" : "=r"(fh) : "l"(pf) : "memory");
        asm volatile("ld.relaxed.gpu.global.u16 %0, [%1 + 512];" : "=r"(fn) : "l"(pf) : "memory");
        asm volatile("st.shared.u32 [%0], %1;" ::"r"(xs), "r"(v.x) : "memory");
        asm volatile("st.shared.u32 [%0], %1;" ::"r"(xs ^ 16), "r"(v.y) : "memory");
        asm volatile("st.shared.u32 [%0], %1;" ::"r"(xs ^ 32), "r"(v.z) : "memory");
        asm volatile("st.shared.u32 [%0], %1;" ::"r"(xs ^ 48), "r"(v.w) : "memory");
        if (__all_sync(~0u, max(max(v.x, v.y), max(v.z, v.w)) != 0xFFFFFFFFu && max(fh, fn) != 0xFFFFu)) break;
      }
    }
    bar_sync(3, 256);
    asm volatile("{\n.reg .pred p;\nsetp.lt.u32 p, %5, %6;\n@p st.global.v4.u32 [%0], {%1,%2,%3,%4};\n}" ::"l"(cdst), "r"(cout.x), "r"(cout.y), "r"(cout.z),
                 "r"(cout.w), "r"(ckey), "r"(top.w) : "memory");
    if (ffn) {
      TL(2, 15, warp == 4);
      float d[4][4] = {};
      auto xl = [&](int i) { return lds128((xb ^ ((i & 2) << 4)) + (i >> 1) * 256 + (i & 1) * 64); };
      uint4 b0 = xl(0), b1 = xl(1);
#pragma unroll
      for (int i = 0; i < 16; i += 2) {
        const uint4 c0 = b0, c1 = b1;
        if (i < 14) { b0 = xl(i + 2); b1 = xl(i + 3); }
        mma16816(d[0], wf[8 * i], wf[8 * i + 1], wf[8 * i + 2], wf[8 * i + 3], c0.x, c0.y);
        mma16816(d[1], wf[8 * i + 4], wf[8 * i + 5], wf[8 * i + 6], wf[8 * i + 7], c0.z, c0.w);
        mma16816(d[2], wf[8 * i + 8], wf[8 * i + 9], wf[8 * i + 10], wf[8 * i + 11], c1.x, c1.y);
        mma16816(d[3], wf[8 * i + 12], wf[8 * i + 13], wf[8 * i + 14], wf[8 * i + 15], c1.z, c1.w);
      }
      const float e0 = (d[0][0] + d[1][0]) + (d[2][0] + d[3][0]), e1 = (d[0][1] + d[1][1]) + (d[2][1] + d[3][1]);
      const float e2 = (d[0][2] + d[1][2]) + (d[2][2] + d[3][2]), e3 = (d[0][3] + d[1][3]) + (d[2][3] + d[3][3]);
      asm volatile("st.shared.v2.f32 [%0], {%1,%2};" ::"r"(sb + OFF_SCR + 8192 + ((w * 2 + (lane & 1)) * 32 + (cw & 3) * 8 + r0) * 8),
                   "f"((lane & 1) ? e1 : e0), "f"((lane & 1) ? e3 : e2) : "memory");
      bar_sync(3, 256);
      TL(2, 16, warp == 4);
      const uint32_t ra = sb + OFF_SCR + 8192 + (r0 & 1) * 256 + (r0 >> 1) * 64 + (lane & 3) * 16;
      const uint4 p0 = lds128(ra), p1 = lds128(ra + 512);
      auto act = [](uint32_t u0, uint32_t u1, uint32_t g0, uint32_t g1) {
        const uint32_t ug = pack_bf16(__uint_as_float(u0) + __uint_as_float(u1), __uint_as_float(g0) + __uint_as_float(g1));
        const float g = bf_hi(ug);
        return bf_round(__fdividef(g, 1.f + __expf(-g))) * bf_lo(ug);
      };
      const uint32_t av = pack_bf16(act(p0.x, p1.x, p0.y, p1.y), act(p0.z, p1.z, p0.w, p1.w));
      uint32_t b[4];
#pragma unroll
      for (int i = 0; i < 4; i++) b[i] = __shfl_sync(~0u, av, 8 * i + (lane & 7));
      TL(2, 17, warp == 4);
      float y[2][4] = {{0.f, 0.f, 0.f, 0.f}, {0.f, 0.f, 0.f, 0.f}};
#pragma unroll
      for (int c = 0; c < 4; c++) {
        const bool on = (lane >> 3) == c;
        const uint32_t b0 = on ? b[0] : 0, b1 = on ? b[1] : 0, b2 = on ? b[2] : 0, b3 = on ? b[3] : 0;
#pragma unroll
        for (int a = 0; a < 2; a++) {
          const int i = 8 * a + 2 * c;
          mma16816(y[a], wd[i][0], wd[i][1], wd[i][2], wd[i][3], b0, b1);
          mma16816(y[a], wd[i + 1][0], wd[i + 1][1], wd[i + 1][2], wd[i + 1][3], b2, b3);
        }
      }
      float4* yd = reinterpret_cast<float4*>(g_xr + (cw * 16 + (lane & 3) * 2 + (lane >> 4)) * XR_SIZE + XR_Y + fid * 4 + (r0 & 3));
      __stcg(yd, make_float4(y[0][0], y[0][1], y[0][2], y[0][3]));
      __stcg(yd + 8 * XR_SIZE, make_float4(y[1][0], y[1][1], y[1][2], y[1][3]));
    }
    TL(2, 18, warp == 4);
    if (cw == 0) {
      const uint32_t fk = ft ? top.w : top.z;
      uint32_t u = fk >> 16;
      u = (u & 0x8000u) ? (u & 0x7FFFu) : (~u & 0xFFFFu);
      float rs = bf_round(__fdividef(1.f, 1.f + __expf(-__uint_as_float(u << 16))));
      uint16_t* op = reinterpret_cast<uint16_t*>(out) + (size_t)(~fk & 0x7FFF) * DM + fc;
      settle(op, zero); settle(__float_as_uint(rs), zero);
      spin_clk(ffn ? Y_DLY : Y_DLY + Y_DLY0);
      float v[4];
#pragma unroll 1
      for (int n = 0; n < 0x400000; n++) {
        float4 z[14];
#pragma unroll
        for (int i = 0; i < 14; i++)
          asm volatile("ld.relaxed.gpu.global.v4.f32 {%0,%1,%2,%3}, [%4];" : "=f"(z[i].x), "=f"(z[i].y), "=f"(z[i].z), "=f"(z[i].w) : "l"(xr + XR_Y + lane + 32 * i) : "memory");
        float a[4] = {z[0].x, z[0].y, z[0].z, z[0].w}, b[4] = {z[1].x, z[1].y, z[1].z, z[1].w};
#pragma unroll
        for (int i = 2; i < 14; i += 2) {
          a[0] += z[i].x; a[1] += z[i].y; a[2] += z[i].z; a[3] += z[i].w;
          b[0] += z[i + 1].x; b[1] += z[i + 1].y; b[2] += z[i + 1].z; b[3] += z[i + 1].w;
        }
#pragma unroll
        for (int i = 0; i < 4; i++) v[i] = a[i] + b[i];
        const float t = (v[0] + v[1]) + (v[2] + v[3]);
        if (__all_sync(~0u, t == t)) break;
        uint32_t m = 0;
#pragma unroll
        for (int i = 0; i < 14; i++) m = max(max(m, max(__float_as_uint(z[i].x), __float_as_uint(z[i].y))), max(__float_as_uint(z[i].z), __float_as_uint(z[i].w)));
        if (__all_sync(~0u, m != 0xFFFFFFFFu)) break;
      }
      TL(2, 30, true);
      const bool hi = lane & 16, odd = lane & 8;
      const float a0 = (hi ? v[2] : v[0]) + __shfl_xor_sync(~0u, hi ? v[0] : v[2], 16), a1 = (hi ? v[3] : v[1]) + __shfl_xor_sync(~0u, hi ? v[1] : v[3], 16);
      float yv = (odd ? a1 : a0) + __shfl_xor_sync(~0u, odd ? a0 : a1, 8);
      yv += __shfl_xor_sync(~0u, yv, 4);
      const uint32_t o = hadd2_bf(fh, hadd2_bf(fn, pack_bf16(bf_round(yv) * rs, 0.f)));
      if (!(lane & 4)) *op = (uint16_t)o;
      TL(2, 21, true);
    }
    TL(2, 20, warp == 4);
    }
    __syncwarp();
    cluster_wait();
  }
}

typedef CUresult (*EncodeFn)(CUtensorMap*, CUtensorMapDataType, cuuint32_t, void*, const cuuint64_t*, const cuuint64_t*, const cuuint32_t*,
                             const cuuint32_t*, CUtensorMapInterleave, CUtensorMapSwizzle, CUtensorMapL2promotion, CUtensorMapFloatOOBfill);
EncodeFn g_enc = nullptr;

void map2(CUtensorMap* m, const void* ptr, uint64_t rows, uint64_t cols, uint32_t bc, uint32_t br) {
  const CUtensorMapSwizzle sw = bc == 64 ? CU_TENSOR_MAP_SWIZZLE_128B : CU_TENSOR_MAP_SWIZZLE_64B;
  cuuint64_t gd[2] = {cols, rows}, gs[1] = {cols * 2};
  cuuint32_t bd[2] = {bc, br}, es[2] = {1, 1};
  g_enc(m, CU_TENSOR_MAP_DATA_TYPE_BFLOAT16, 2, (void*)ptr, gd, gs, bd, es, CU_TENSOR_MAP_INTERLEAVE_NONE, sw,
        CU_TENSOR_MAP_L2_PROMOTION_L2_128B, CU_TENSOR_MAP_FLOAT_OOB_FILL_NONE);
}
void map3(CUtensorMap* m, const void* ptr, uint64_t rows, uint64_t cols, uint32_t br, uint32_t bch) {
  cuuint64_t gd[3] = {64, rows, cols / 64}, gs[2] = {cols * 2, 128};
  cuuint32_t bd[3] = {64, br, bch}, es[3] = {1, 1, 1};
  g_enc(m, CU_TENSOR_MAP_DATA_TYPE_BFLOAT16, 3, (void*)ptr, gd, gs, bd, es, CU_TENSOR_MAP_INTERLEAVE_NONE, CU_TENSOR_MAP_SWIZZLE_128B,
        CU_TENSOR_MAP_L2_PROMOTION_L2_128B, CU_TENSOR_MAP_FLOAT_OOB_FILL_NONE);
}

}

extern "C" void kernel_launch(void* const* d_in, const int* in_sizes, int n_in, void* d_out, int out_size) {
  const __nv_bfloat16* x = (const __nv_bfloat16*)d_in[0];
  const __nv_bfloat16* ckv = (const __nv_bfloat16*)d_in[1];
  const __nv_bfloat16* wq = (const __nv_bfloat16*)d_in[2];
  const __nv_bfloat16* wk = (const __nv_bfloat16*)d_in[3];
  const __nv_bfloat16* wv = (const __nv_bfloat16*)d_in[4];
  const __nv_bfloat16* wo = (const __nv_bfloat16*)d_in[5];
  const __nv_bfloat16* w_r = (const __nv_bfloat16*)d_in[7];
  const __nv_bfloat16* wgate = (const __nv_bfloat16*)d_in[8];
  const __nv_bfloat16* wup = (const __nv_bfloat16*)d_in[9];
  const __nv_bfloat16* wdown = (const __nv_bfloat16*)d_in[10];
  __nv_bfloat16* out = (__nv_bfloat16*)d_out;

  if (!g_enc) {
    void* fn = nullptr;
    cudaDriverEntryPointQueryResult qr;
    cudaGetDriverEntryPoint("cuTensorMapEncodeTiled", &fn, cudaEnableDefault, &qr);
    g_enc = (EncodeFn)fn;
    cudaFuncSetAttribute(fused_kernel, cudaFuncAttributeMaxDynamicSharedMemorySize, SMEM_BYTES);
  }
  void *xn, *kv, *ctx, *xr, *cnt;
  cudaGetSymbolAddress(&xr, g_xr);
  cudaGetSymbolAddress(&cnt, g_cnt);
  cudaGetSymbolAddress(&xn, g_xn);
  cudaGetSymbolAddress(&kv, g_kv);
  cudaGetSymbolAddress(&ctx, g_ctx);

  Params p;
  map2(&p.xn, xn, SEQ, DM, 64, 64);
  map2(&p.ckv, ckv, SEQ, DC, 64, 128);
  map3(&p.wq, wq, DM, NQ, 64, 2);
  map3(&p.wk, wk, DC, NQ, 64, 2);
  map3(&p.wv, wv, DC, NQ, 64, 2);
  map3(&p.wo, wo, NQ, DM, 64, 1);
  map3(&p.x, x, SEQ, DM, 64, 2);
  map3(&p.wd, wdown, FF, DM, 32, 8);
  map2(&p.wg, wgate, DM, FF, 32, 64);
  map2(&p.wu, wup, DM, FF, 32, 64);
  fused_kernel<<<128, 384, SMEM_BYTES, cudaStreamPerThread>>>(0u, x, (__nv_bfloat16*)kv, (__nv_bfloat16*)ctx, (uint4*)xr, out, (__nv_bfloat16*)xn,
                                                               (unsigned*)cnt, w_r, wdown, wq, p);
}
```

```cpp
#include <cuda_runtime.h>
#include <cuda_bf16.h>
#include <cuda.h>
#include <stdint.h>
#include <utility>

#pragma nv_diag_suppress 549
#pragma nv_diag_suppress 177
namespace {

constexpr int SEQ = 2048, DM = 1024, NH = 32, HD = 128, DC = 512, NQ = NH * HD, FF = 3584;

__device__ __align__(1024) __nv_bfloat16 g_xn[SEQ * DM];
constexpr int KV_TILE = 128 * 128;
__device__ __align__(1024) __nv_bfloat16 g_kv[2 * SEQ * NQ];
__device__ __align__(1024) __nv_bfloat16 g_ctx[SEQ * NQ];
constexpr int XR_PS = 0;
constexpr int XR_KEY = 128;
constexpr int XR_CAND = 136;
constexpr int XR_Y = 648;
constexpr int XR_SIZE = 1104;
__device__ __align__(1024) uint4 g_xr[128 * XR_SIZE];
constexpr int C_LN = 0, C_KV = 16, C_CTX = 32, C_NUM = 64;
__device__ unsigned g_cnt[C_NUM];

#define TL(k, i, cond) do {} while (0)
#define TC(w, g, i) do {} while (0)
#define TL_EXTRA 0
#define TK(i) do {} while (0)

__device__ __forceinline__ uint32_t s2u(const void* p) { return (uint32_t)__cvta_generic_to_shared(p); }
__device__ __forceinline__ void mbar_arrive(uint32_t b) { asm volatile("mbarrier.arrive.shared::cta.b64 _, [%0];" ::"r"(b) : "memory"); }
__device__ __forceinline__ void mbar_arrive_both(uint32_t b, uint32_t lane, bool cond) {
  asm volatile("{\n.reg .pred p;\n.reg .b32 r;\nsetp.lt.u32 p, %1, %2;\nmapa.shared::cluster.u32 r, %0, %1;\n@p mbarrier.arrive.shared::cluster.b64 _, [r];\n}"
               ::"r"(b), "r"(lane), "r"(cond ? 2 : 0) : "memory");
}
__device__ __forceinline__ bool mbar_test(uint32_t b, uint32_t ph) {
  uint32_t ok;
  asm volatile("{\n.reg .pred p;\nmbarrier.test_wait.parity.shared::cta.b64 p, [%1], %2;\nselp.u32 %0, 1, 0, p;\n}" : "=r"(ok) : "r"(b), "r"(ph) : "memory");
  return __all_sync(~0u, ok);
}
__device__ __forceinline__ void mbar_wait(uint32_t b, uint32_t ph) {
  asm volatile(
      "{\n.reg .pred p;\n.reg .u32 n;\nmov.u32 n, 0;\n"
      "LW:\nmbarrier.try_wait.parity.shared::cta.b64 p, [%0], %1, 20000;\n@p bra LD;\n"
      "add.u32 n, n, 1;\nsetp.lt.u32 p, n, 0x40000;\n@p bra LW;\ntrap;\nLD:\n}" ::"r"(b), "r"(ph) : "memory");
}
__device__ __forceinline__ void mbar_wait_u(uint32_t b, uint32_t ph) {
  asm volatile(
      "{\n.reg .pred p;\n.reg .u32 n;\nmov.u32 n, 0;\n"
      "LW:\nmbarrier.try_wait.parity.shared::cta.b64 p, [%0], %1, 20000;\n@p bra.uni LD;\n"
      "add.u32 n, n, 1;\nsetp.lt.u32 p, n, 0x40000;\n@p bra.uni LW;\ntrap;\nLD:\n}" ::"r"(b), "r"(ph) : "memory");
}
__device__ __forceinline__ void mbar_wait_c(uint32_t b, uint32_t ph) {
  asm volatile("{\n.reg .pred p;\nLW:\nmbarrier.try_wait.parity.shared::cta.b64 p, [%0], %1;\n@!p bra.uni LW;\n}" ::"r"(b), "r"(ph) : "memory");
}
__device__ __forceinline__ void mbar_wait_b(uint32_t b, uint32_t ph) {
  asm volatile(
      "{\n.reg .pred p;\n.reg .u32 n;\nmov.u32 n, 0;\n"
      "LW:\nmbarrier.try_wait.parity.shared::cta.b64 p, [%0], %1;\n@p bra.uni LD;\n"
      "add.u32 n, n, 1;\nsetp.lt.u32 p, n, 0x1000000;\n@p bra.uni LW;\ntrap;\nLD:\n}" ::"r"(b), "r"(ph) : "memory");
}
template <bool SLEEP = false>
__device__ __forceinline__ void spin_until_ge(const unsigned* p, unsigned target) {
  asm volatile(
      "{\n.reg .pred p, q;\n.reg .u32 n, v;\nmov.u32 n, 0;\nsetp.ne.u32 q, %2, 0;\n"
      "LW:\nld.acquire.gpu.global.u32 v, [%0];\nsetp.ge.u32 p, v, %1;\n@p bra LD;\n@q nanosleep.u32 200;\n"
      "add.u32 n, n, 1;\nsetp.lt.u32 p, n, 0x400000;\n@p bra LW;\ntrap;\nLD:\n}" ::"l"(p), "r"(target), "n"((int)SLEEP) : "memory");
}
template <int N>
__device__ __forceinline__ void poll_chunks(uint4 (&v)[N], const uint4* p, int stride) {
#pragma unroll 1
  for (int n = 0; n < 0x400000; n++) {
    uint32_t m = 0;
#pragma unroll
    for (int i = 0; i < N; i++) {
      asm volatile("ld.relaxed.gpu.global.v4.u32 {%0,%1,%2,%3}, [%4];" : "=r"(v[i].x), "=r"(v[i].y), "=r"(v[i].z), "=r"(v[i].w) : "l"(p + i * stride) : "memory");
    }
#pragma unroll
    for (int i = 0; i < N; i++) m = max(max(m, max(v[i].x, v[i].y)), max(v[i].z, v[i].w));
    if (__all_sync(~0u, m != 0xFFFFFFFFu)) break;
  }
}
__device__ __forceinline__ void spin_clk(uint32_t n) {
  asm volatile("{\n.reg .pred p;\n.reg .u32 a, b;\nmov.u32 a, %%clock;\nLW:\nmov.u32 b, %%clock;\nsub.u32 b, b, a;\nsetp.lt.u32 p, b, %0;\n@p bra.uni LW;\n}" ::"r"(n) : "memory");
}
__device__ __forceinline__ int fresh_lane() {
  int r;
  asm volatile("mov.u32 %0, %%laneid;" : "=r"(r));
  return r;
}
__device__ __forceinline__ void settle(const void* a, uint32_t zero) {
  asm volatile("{\n.reg .pred p;\nsetp.ne.u32 p, %1, 0;\n@p st.global.u32 [%0], %1;\n}" ::"l"(a), "r"(zero) : "memory");
}
__device__ __forceinline__ void settle(uint32_t a, uint32_t zero) {
  asm volatile("{\n.reg .pred p;\nsetp.ne.u32 p, %1, 0;\n@p st.shared.u32 [%0], %1;\n}" ::"r"(a), "r"(zero) : "memory");
}
__device__ __forceinline__ void fence_async_all() { asm volatile("fence.proxy.async;" ::: "memory"); }
__device__ __forceinline__ void bar_sync(int id, int n) { asm volatile("bar.sync %0, %1;" ::"r"(id), "r"(n) : "memory"); }
__device__ __forceinline__ void bar_arrive(int id, int n) { asm volatile("bar.arrive %0, %1;" ::"r"(id), "r"(n) : "memory"); }
__device__ __forceinline__ void cluster_arrive() { asm volatile("barrier.cluster.arrive.relaxed.aligned;" ::: "memory"); }
__device__ __forceinline__ void cluster_wait() { asm volatile("barrier.cluster.wait.acquire.aligned;" ::: "memory"); }
__device__ __forceinline__ void fence_gpu() { asm volatile("fence.acq_rel.gpu;" ::: "memory"); }
__device__ __forceinline__ void red_add(unsigned* p, unsigned v) { asm volatile("red.relaxed.gpu.global.add.u32 [%0], %1;" ::"l"(p), "r"(v) : "memory"); }
#define ELECT "{\n.reg .pred E;\nelect.sync _|E, 0xFFFFFFFF;\n@E "
__device__ __forceinline__ void e_init(uint32_t b, uint32_t c) { asm volatile(ELECT "mbarrier.init.shared::cta.b64 [%0], %1;\n}" ::"r"(b), "r"(c) : "memory"); }
__device__ __forceinline__ void e_expect(uint32_t b, uint32_t bytes) { asm volatile(ELECT "mbarrier.arrive.expect_tx.shared::cta.b64 _, [%0], %1;\n}" ::"r"(b), "r"(bytes) : "memory"); }
__device__ __forceinline__ void e_arrive(uint32_t b) { asm volatile(ELECT "mbarrier.arrive.shared::cta.b64 _, [%0];\n}" ::"r"(b) : "memory"); }
__device__ __forceinline__ void prefetch_tm(const CUtensorMap* m) { asm volatile(ELECT "prefetch.tensormap [%0];\n}" ::"l"(m) : "memory"); }
__device__ __forceinline__ void tma_ld2(uint32_t dst, const CUtensorMap* m, uint32_t bar, int c0, int c1) {
  asm volatile(ELECT "cp.async.bulk.tensor.2d.shared::cta.global.mbarrier::complete_tx::bytes [%0], [%1, {%3,%4}], [%2];\n}" ::"r"(dst), "l"(m), "r"(bar), "r"(c0), "r"(c1) : "memory");
}
__device__ __forceinline__ void tma_ld3(uint32_t dst, const CUtensorMap* m, uint32_t bar, int c0, int c1, int c2) {
  asm volatile(ELECT "cp.async.bulk.tensor.3d.shared::cta.global.mbarrier::complete_tx::bytes [%0], [%1, {%3,%4,%5}], [%2];\n}" ::"r"(dst), "l"(m), "r"(bar), "r"(c0), "r"(c1), "r"(c2) : "memory");
}
__device__ __forceinline__ void tma_ld2_mc(uint32_t dst, const CUtensorMap* m, uint32_t bar, int c0, int c1, uint16_t mask) {
  asm volatile(ELECT "cp.async.bulk.tensor.2d.shared::cluster.global.mbarrier::complete_tx::bytes.multicast::cluster [%0], [%1, {%3,%4}], [%2], %5;\n}" ::"r"(dst), "l"(m), "r"(bar), "r"(c0), "r"(c1), "h"(mask) : "memory");
}
__device__ __forceinline__ void tma_ld3_mc(uint32_t dst, const CUtensorMap* m, uint32_t bar, int c0, int c1, int c2, uint16_t mask) {
  asm volatile(ELECT "cp.async.bulk.tensor.3d.shared::cluster.global.mbarrier::complete_tx::bytes.multicast::cluster [%0], [%1, {%3,%4,%5}], [%2], %6;\n}" ::"r"(dst), "l"(m), "r"(bar), "r"(c0), "r"(c1), "r"(c2), "h"(mask) : "memory");
}
__device__ __forceinline__ uint64_t policy_evict_first() {
  uint64_t p;
  asm("createpolicy.fractional.L2::evict_first.b64 %0, 1.0;" : "=l"(p));
  return p;
}
__device__ __forceinline__ void tma_ld2_ef(uint32_t dst, const CUtensorMap* m, uint32_t bar, int c0, int c1) {
  asm volatile(ELECT "cp.async.bulk.tensor.2d.shared::cta.global.mbarrier::complete_tx::bytes.L2::cache_hint [%0], [%1, {%3,%4}], [%2], %5;\n}" ::"r"(dst), "l"(m), "r"(bar), "r"(c0), "r"(c1), "l"(policy_evict_first()) : "memory");
}
__device__ __forceinline__ void tma_ld3_ef(uint32_t dst, const CUtensorMap* m, uint32_t bar, int c0, int c1, int c2) {
  asm volatile(ELECT "cp.async.bulk.tensor.3d.shared::cta.global.mbarrier::complete_tx::bytes.L2::cache_hint [%0], [%1, {%3,%4,%5}], [%2], %6;\n}" ::"r"(dst), "l"(m), "r"(bar), "r"(c0), "r"(c1), "r"(c2), "l"(policy_evict_first()) : "memory");
}
__device__ __forceinline__ void bulk_ld(uint32_t dst, const void* src, uint32_t bytes, uint32_t bar) {
  asm volatile(ELECT "cp.async.bulk.shared::cta.global.mbarrier::complete_tx::bytes [%0], [%1], %2, [%3];\n}" ::"r"(dst), "l"(src), "r"(bytes), "r"(bar) : "memory");
}
__device__ __forceinline__ void tma_pf2(const CUtensorMap* m, int c0, int c1) { asm volatile(ELECT "cp.async.bulk.prefetch.tensor.2d.L2.global [%0, {%1,%2}];\n}" ::"l"(m), "r"(c0), "r"(c1) : "memory"); }
__device__ __forceinline__ void tma_pf3(const CUtensorMap* m, int c0, int c1, int c2) { asm volatile(ELECT "cp.async.bulk.prefetch.tensor.3d.L2.global [%0, {%1,%2,%3}];\n}" ::"l"(m), "r"(c0), "r"(c1), "r"(c2) : "memory"); }
__device__ __forceinline__ void sched_fence() { asm volatile("pmevent 0;" ::: "memory"); }
__device__ __forceinline__ void l2_prefetch(const void* p, uint32_t bytes) { asm volatile(ELECT "cp.async.bulk.prefetch.L2.global [%0], %1;\n}" ::"l"(p), "r"(bytes) : "memory"); }

__device__ __forceinline__ void wg_fence() { asm volatile("wgmma.fence.sync.aligned;" ::: "memory"); }
__device__ __forceinline__ void wg_commit() { asm volatile("wgmma.commit_group.sync.aligned;" ::: "memory"); }
template <int N> __device__ __forceinline__ void wg_wait() { asm volatile("wgmma.wait_group.sync.aligned %0;" ::"n"(N) : "memory"); }
template <int N> __device__ __forceinline__ void reg_alloc() { asm volatile("setmaxnreg.inc.sync.aligned.u32 %0;" ::"n"(N)); }
template <int N> __device__ __forceinline__ void reg_dealloc() { asm volatile("setmaxnreg.dec.sync.aligned.u32 %0;" ::"n"(N)); }
template <int N> __device__ __forceinline__ void fence_regs(float (&d)[N]) {
#pragma unroll
  for (int i = 0; i < N; i++) asm volatile("" : "+f"(d[i])::"memory");
}
template <int I0, int I1, int N> __device__ __forceinline__ void fence_part(float (&d)[N]) {
#pragma unroll
  for (int i = I0; i < I1; i++) asm volatile("" : "+f"(d[i])::"memory");
}
template <int N> __device__ __forceinline__ void fence_regs(uint32_t (&d)[N]) {
#pragma unroll
  for (int i = 0; i < N; i++) asm volatile("" : "+r"(d[i])::"memory");
}

__device__ __forceinline__ uint32_t mk_desc(uint32_t addr, uint32_t lbo) { return ((addr & 0x3FFFF) >> 4) | ((lbo >> 4) << 16); }

#define R8(b) "+f"(d[b + 0]), "+f"(d[b + 1]), "+f"(d[b + 2]), "+f"(d[b + 3]), "+f"(d[b + 4]), "+f"(d[b + 5]), "+f"(d[b + 6]), "+f"(d[b + 7])
#define REGS64 "%0,%1,%2,%3,%4,%5,%6,%7,%8,%9,%10,%11,%12,%13,%14,%15,%16,%17,%18,%19,%20,%21,%22,%23,%24,%25,%26,%27,%28,%29,%30,%31," \
               "%32,%33,%34,%35,%36,%37,%38,%39,%40,%41,%42,%43,%44,%45,%46,%47,%48,%49,%50,%51,%52,%53,%54,%55,%56,%57,%58,%59,%60,%61,%62,%63"
#define REGS128 REGS64 ",%64,%65,%66,%67,%68,%69,%70,%71,%72,%73,%74,%75,%76,%77,%78,%79,%80,%81,%82,%83,%84,%85,%86,%87,%88,%89,%90,%91,%92,%93,%94,%95," \
               "%96,%97,%98,%99,%100,%101,%102,%103,%104,%105,%106,%107,%108,%109,%110,%111,%112,%113,%114,%115,%116,%117,%118,%119,%120,%121,%122,%123,%124,%125,%126,%127"

#define DESC(d, r, o) "add.u32 t, " r ", " o ";\nmov.b64 " d ", {t, h};\n"
#define MMA_PRE_(acc, hi) "{\n.reg .pred p;\n.reg .b32 t, h;\n.reg .b64 da, db;\nmov.b32 h, " hi ";\nsetp.ne.b32 p, " acc ", 0;\n"
#define MMA_PRE(acc) MMA_PRE_(acc, "0x40000040")
#define MMA_PRE64(acc) MMA_PRE_(acc, "0x80000020")
template <int TB, int OA, int OB>
__device__ __forceinline__ void mma_n256_ss(float (&d)[128], uint32_t a, uint32_t b, int acc) {
  asm volatile(MMA_PRE("%130") DESC("da", "%128", "%132") DESC("db", "%129", "%133")
               "wgmma.mma_async.sync.aligned.m64n256k16.f32.bf16.bf16 {" REGS128 "}, da, db, p, 1, 1, 0, %131;\n}\n"
               : R8(0), R8(8), R8(16), R8(24), R8(32), R8(40), R8(48), R8(56), R8(64), R8(72), R8(80), R8(88), R8(96), R8(104), R8(112), R8(120)
               : "r"(a), "r"(b), "r"(acc), "n"(TB), "n"(OA >> 4), "n"(OB >> 4));
}
template <int TB, int OA, int OB>
__device__ __forceinline__ void mma_n128_ss(float (&d)[64], uint32_t a, uint32_t b, int acc) {
  asm volatile(MMA_PRE("%66") DESC("da", "%64", "%68") DESC("db", "%65", "%69")
               "wgmma.mma_async.sync.aligned.m64n128k16.f32.bf16.bf16 {" REGS64 "}, da, db, p, 1, 1, 0, %67;\n}\n"
               : R8(0), R8(8), R8(16), R8(24), R8(32), R8(40), R8(48), R8(56)
               : "r"(a), "r"(b), "r"(acc), "n"(TB), "n"(OA >> 4), "n"(OB >> 4));
}
template <int TB, int OB>
__device__ __forceinline__ void mma_n128_rs(float (&d)[64], const uint32_t* a, uint32_t b, int acc) {
  asm volatile(MMA_PRE64("%69") DESC("db", "%68", "%71")
               "wgmma.mma_async.sync.aligned.m64n128k16.f32.bf16.bf16 {" REGS64 "}, {%64,%65,%66,%67}, db, p, 1, 1, %70;\n}\n"
               : R8(0), R8(8), R8(16), R8(24), R8(32), R8(40), R8(48), R8(56)
               : "r"(a[0]), "r"(a[1]), "r"(a[2]), "r"(a[3]), "r"(b), "r"(acc), "n"(TB), "n"(OB >> 4));
}
#define W8(b) "=f"(d[b + 0]), "=f"(d[b + 1]), "=f"(d[b + 2]), "=f"(d[b + 3]), "=f"(d[b + 4]), "=f"(d[b + 5]), "=f"(d[b + 6]), "=f"(d[b + 7])
#define MMA_N64 MMA_PRE64("%37") DESC("db", "%36", "%38") \
  "wgmma.mma_async.sync.aligned.m64n64k16.f32.bf16.bf16 {%0,%1,%2,%3,%4,%5,%6,%7,%8,%9,%10,%11,%12,%13,%14,%15,%16,%17,%18,%19,%20,%21," \
  "%22,%23,%24,%25,%26,%27,%28,%29,%30,%31}, {%32,%33,%34,%35}, db, p, 1, 1, 0;\n}\n"
template <int H, int OB, bool ACC>
__device__ __forceinline__ void mma_n64_rs(float (&d)[64], const uint32_t* a, uint32_t b) {
  if (ACC) asm volatile(MMA_N64 : R8(32 * H), R8(32 * H + 8), R8(32 * H + 16), R8(32 * H + 24) : "r"(a[0]), "r"(a[1]), "r"(a[2]), "r"(a[3]), "r"(b), "n"(1), "n"(OB >> 4));
  else asm volatile(MMA_N64 : W8(32 * H), W8(32 * H + 8), W8(32 * H + 16), W8(32 * H + 24) : "r"(a[0]), "r"(a[1]), "r"(a[2]), "r"(a[3]), "r"(b), "n"(0), "n"(OB >> 4));
}
template <int OB>
__device__ __forceinline__ void mma_n128_rs0(float (&d)[64], const uint32_t* a, uint32_t b) {
  asm volatile(MMA_PRE64("%69") DESC("db", "%68", "%70")
               "wgmma.mma_async.sync.aligned.m64n128k16.f32.bf16.bf16 {" REGS64 "}, {%64,%65,%66,%67}, db, p, 1, 1, 0;\n}\n"
               : W8(0), W8(8), W8(16), W8(24), W8(32), W8(40), W8(48), W8(56)
               : "r"(a[0]), "r"(a[1]), "r"(a[2]), "r"(a[3]), "r"(b), "n"(0), "n"(OB >> 4));
}
#define MMA_SSH MMA_PRE("%67") DESC("db", "%65", "%69") "add.u32 t, %64, %68;\nmov.b64 da, {t, %66};\n" \
  "wgmma.mma_async.sync.aligned.m64n128k16.f32.bf16.bf16 {" REGS64 "}, da, db, p, 1, 1, 0, 1;\n}\n"
template <int OA, int OB, bool ACC>
__device__ __forceinline__ void mma_n128_ssh(float (&d)[64], uint32_t a, uint32_t ahi, uint32_t b) {
  if (ACC) asm volatile(MMA_SSH : R8(0), R8(8), R8(16), R8(24), R8(32), R8(40), R8(48), R8(56) : "r"(a), "r"(b), "r"(ahi), "n"(1), "n"(OA >> 4), "n"(OB >> 4));
  else asm volatile(MMA_SSH : W8(0), W8(8), W8(16), W8(24), W8(32), W8(40), W8(48), W8(56) : "r"(a), "r"(b), "r"(ahi), "n"(0), "n"(OA >> 4), "n"(OB >> 4));
}
template <int TB, int OA, int OB>
__device__ __forceinline__ void mma_n128_ss0(float (&d)[64], uint32_t a, uint32_t b) {
  asm volatile(MMA_PRE("%66") DESC("da", "%64", "%68") DESC("db", "%65", "%69")
               "wgmma.mma_async.sync.aligned.m64n128k16.f32.bf16.bf16 {" REGS64 "}, da, db, p, 1, 1, 0, %67;\n}\n"
               : W8(0), W8(8), W8(16), W8(24), W8(32), W8(40), W8(48), W8(56)
               : "r"(a), "r"(b), "n"(0), "n"(TB), "n"(OA >> 4), "n"(OB >> 4));
}
template <int V> struct IC { static constexpr int value = V; __host__ __device__ constexpr operator int() const { return V; } };
template <int N, class F, int... I>
__device__ __forceinline__ void static_for_(F f, std::integer_sequence<int, I...>) { (f(IC<I>{}), ...); }
template <int N, class F>
__device__ __forceinline__ void static_for(F f) { static_for_<N>(f, std::make_integer_sequence<int, N>{}); }
__device__ __forceinline__ uint32_t pack_bf16(float lo, float hi) {
  uint32_t r;
  asm("cvt.rn.bf16x2.f32 %0, %1, %2;" : "=r"(r) : "f"(hi), "f"(lo));
  return r;
}
__device__ __forceinline__ float bf_lo(uint32_t v) { return __uint_as_float(v << 16); }
__device__ __forceinline__ float bf_hi(uint32_t v) { return __uint_as_float(v & 0xFFFF0000u); }
__device__ __forceinline__ float bf_round(float v) { return bf_lo(pack_bf16(v, v)); }
__device__ __forceinline__ void stsm4(uint32_t addr, uint32_t r0, uint32_t r1, uint32_t r2, uint32_t r3) {
  asm volatile("stmatrix.sync.aligned.m8n8.x4.shared.b16 [%0], {%1,%2,%3,%4};" ::"r"(addr), "r"(r0), "r"(r1), "r"(r2), "r"(r3) : "memory");
}
__device__ __forceinline__ uint4 lds128(uint32_t addr) {
  uint4 v;
  asm volatile("ld.shared.v4.u32 {%0,%1,%2,%3}, [%4];" : "=r"(v.x), "=r"(v.y), "=r"(v.z), "=r"(v.w) : "r"(addr));
  return v;
}
__device__ __forceinline__ float ex2(float x) {
  float y;
  asm("ex2.approx.ftz.f32 %0, %1;" : "=f"(y) : "f"(x));
  return y;
}
__device__ __forceinline__ void stage_store_128(uint32_t base, int lane, const uint32_t* pk) {
  const int row = (lane & 7) + ((lane >> 3) & 1) * 8;
  const uint32_t rb = base + row * 128;
  const int hi = lane >> 4;
#pragma unroll
  for (int j = 0; j < 8; j++) {
    const int chunk = 2 * j + hi;
    const uint32_t a = rb + (j >> 2) * 8192 + (((chunk & 7) ^ (lane & 7)) << 4);
    stsm4(a, pk[4 * j + 0], pk[4 * j + 1], pk[4 * j + 2], pk[4 * j + 3]);
  }
}
__device__ __forceinline__ void ln_round(float mean, float var, float& m_bf, float& inv_s) {
  const uint32_t mv = pack_bf16(mean, var);
  m_bf = bf_lo(mv);
  float sq, rc;
  asm("sqrt.approx.ftz.f32 %0, %1;" : "=f"(sq) : "f"(bf_round(bf_hi(mv) + 1e-5f)));
  asm("rcp.approx.ftz.f32 %0, %1;" : "=f"(rc) : "f"(bf_round(sq)));
  inv_s = rc;
}
__device__ __forceinline__ uint32_t hadd2_bf(uint32_t a, uint32_t b) {
  uint32_t r;
  asm("add.rn.bf16x2 %0, %1, %2;" : "=r"(r) : "r"(a), "r"(b));
  return r;
}
__device__ __forceinline__ uint32_t ln_apply(uint32_t h, uint32_t nm2, float inv_s) {
  const uint32_t d = hadd2_bf(h, nm2);
  return pack_bf16(bf_lo(d) * inv_s, bf_hi(d) * inv_s);
}
__device__ __forceinline__ void mma16816(float* d, uint32_t a0, uint32_t a1, uint32_t a2, uint32_t a3, uint32_t b0, uint32_t b1) {
  asm volatile("mma.sync.aligned.m16n8k16.row.col.f32.bf16.bf16.f32 {%0,%1,%2,%3}, {%4,%5,%6,%7}, {%8,%9}, {%0,%1,%2,%3};"
               : "+f"(d[0]), "+f"(d[1]), "+f"(d[2]), "+f"(d[3]) : "r"(a0), "r"(a1), "r"(a2), "r"(a3), "r"(b0), "r"(b1));
}

constexpr float AT_C = 0.08838834764831845f * 1.4426950408889634f;
#define L_MIN 3.5527137e-15f
#define L_MAX 1.8446744e19f
struct AtState {
  float S[64], O[64];
  uint32_t P[32], Q[32];
  float l[4];
};
template <int I0, int I1>
__device__ __forceinline__ void at_exp(AtState& s) {
#pragma unroll
  for (int i = I0; i < I1; i++) asm volatile("ex2.approx.ftz.f32 %0, %0;" : "+f"(s.S[i]));
#pragma unroll
  for (int i = I0; i < I1; i++) asm volatile("add.f32 %0, %0, %1;" : "+f"(s.l[i & 3]) : "f"(s.S[i]));
}
template <int I0, int I1>
__device__ __forceinline__ void at_pack(AtState& s) {
#pragma unroll
  for (int i = I0; i < I1; i++) asm volatile("cvt.rn.bf16x2.f32 %0, %1, %2;" : "=r"(s.P[i]) : "f"(s.S[2 * i + 1]), "f"(s.S[2 * i]));
}
template <int J0>
__device__ __forceinline__ void at_mask(AtState& s, int r, int lane) {
  const int d = r + (lane >> 2) - (lane & 3) * 2;
#pragma unroll
  for (int j = 0; j < 8; j++) {
    float dummy0 = 0.f, dummy1 = 0.f;
    float& lo0 = j < 7 ? s.S[4 * (J0 + (j < 7 ? j + 1 : j)) + 2] : dummy0;
    float& lo1 = j < 7 ? s.S[4 * (J0 + (j < 7 ? j + 1 : j)) + 3] : dummy1;
    asm("{\n.reg .pred p, q;\nsetp.lt.s32 p, %4, %5;\nsetp.le.s32 q, %4, %5;\n"
        "@p add.f32 %0, %0, 0fFF800000;\n@q add.f32 %1, %1, 0fFF800000;\n@p add.f32 %2, %2, 0fFF800000;\n@q add.f32 %3, %3, 0fFF800000;\n}"
        : "+f"(s.S[4 * (J0 + j)]), "+f"(s.S[4 * (J0 + j) + 1]), "+f"(lo0), "+f"(lo1) : "r"(d), "r"(8 * j));
  }
}
template <int D>
__device__ __forceinline__ uint32_t ld_pair(const __nv_bfloat16* p) {
  uint32_t r;
  asm volatile("{\n.reg .b16 a, b;\nld.global.cg.b16 a, [%1];\nld.global.cg.b16 b, [%1 + %2];\nmov.b32 %0, {a, b};\n}" : "=r"(r) : "l"(p), "n"(2 * D) : "memory");
  return r;
}
__device__ __forceinline__ uint32_t ld_word(const uint32_t* p) {
  uint32_t r;
  asm volatile("ld.global.cg.b32 %0, [%1];" : "=r"(r) : "l"(p) : "memory");
  return r;
}
__device__ __noinline__ void slow_rows(const __nv_bfloat16* wq, int head, int row0) {
  const int lane = fresh_lane(), r = lane >> 2, c = lane & 3;
  uint32_t q[32];
  float o[32];
#pragma unroll
  for (int i = 0; i < 32; i++) q[i] = 0;
  const uint32_t* xa = reinterpret_cast<const uint32_t*>(g_xn + (size_t)(row0 + r) * DM) + c;
#pragma unroll 1
  for (int h = 0; h < 2; h++) {
    const __nv_bfloat16* wb = wq + (size_t)2 * c * NQ + head * HD + 64 * h + 8 * (r >> 1) + (r & 1);
#pragma unroll
    for (int i = 0; i < 32; i++) o[i] = 0.f;
#pragma unroll 1
    for (int kk = 0; kk < DM / 16; kk++) {
      const uint32_t a0 = ld_word(xa + 8 * kk), a1 = ld_word(xa + 8 * kk + 4 * DM), a2 = ld_word(xa + 8 * kk + 4), a3 = ld_word(xa + 8 * kk + 4 * DM + 4);
#pragma unroll
      for (int n = 0; n < 8; n++) {
        const __nv_bfloat16* b = wb + (size_t)16 * kk * NQ + 32 * (n >> 2) + 2 * (n & 3);
        mma16816(o + 4 * n, a0, a1, a2, a3, ld_pair<NQ>(b), ld_pair<NQ>(b + 8 * NQ));
        if (n & 1) sched_fence();
      }
    }
#pragma unroll
    for (int i = 0; i < 16; i++) { q[i] = q[16 + i]; q[16 + i] = pack_bf16(o[2 * i] * AT_C, o[2 * i + 1] * AT_C); }
  }
#pragma unroll 1
  for (int h = 0; h < 2; h++) {
    float m0 = -INFINITY, m1 = -INFINITY, l0 = 0.f, l1 = 0.f;
#pragma unroll
    for (int i = 0; i < 32; i++) o[i] = 0.f;
#pragma unroll 1
    for (int k0 = 0; k0 <= row0; k0 += 16) {
      float e[8] = {0.f, 0.f, 0.f, 0.f, 0.f, 0.f, 0.f, 0.f};
      const __nv_bfloat16* kt = g_kv + (size_t)(head * 16 + (k0 >> 7)) * KV_TILE + (k0 & 127) * 32;
      const uint32_t* kp = reinterpret_cast<const uint32_t*>(kt + r * 32) + c;
#pragma unroll
      for (int kk = 0; kk < 8; kk++) {
        const uint32_t* k0p = kp + (kk >> 1) * 2048 + (((kk & 1) * 2) ^ (r >> 1)) * 4;
        const uint32_t* k1p = kp + (kk >> 1) * 2048 + (((kk & 1) * 2 + 1) ^ (r >> 1)) * 4;
        mma16816(e, q[4 * kk], q[4 * kk + 1], q[4 * kk + 2], q[4 * kk + 3], ld_word(k0p), ld_word(k1p));
        mma16816(e + 4, q[4 * kk], q[4 * kk + 1], q[4 * kk + 2], q[4 * kk + 3], ld_word(k0p + 128), ld_word(k1p + 128));
        if (kk & 1) sched_fence();
      }
      if (k0 == row0) {
#pragma unroll
        for (int i = 0; i < 8; i++) if ((i >> 2) * 8 + 2 * c + (i & 1) > r + (i & 2) * 4) e[i] = -INFINITY;
      }
      float a0 = fmaxf(fmaxf(e[0], e[1]), fmaxf(e[4], e[5])), a1 = fmaxf(fmaxf(e[2], e[3]), fmaxf(e[6], e[7]));
      a0 = fmaxf(a0, __shfl_xor_sync(~0u, a0, 1)); a1 = fmaxf(a1, __shfl_xor_sync(~0u, a1, 1));
      a0 = fmaxf(a0, __shfl_xor_sync(~0u, a0, 2)); a1 = fmaxf(a1, __shfl_xor_sync(~0u, a1, 2));
      a0 = fmaxf(a0, m0); a1 = fmaxf(a1, m1);
      const float sc0 = ex2(m0 - a0), sc1 = ex2(m1 - a1);
      m0 = a0; m1 = a1;
#pragma unroll
      for (int i = 0; i < 8; i++) e[i] = ex2(e[i] - ((i & 2) ? m1 : m0));
      l0 = l0 * sc0 + (e[0] + e[1]) + (e[4] + e[5]);
      l1 = l1 * sc1 + (e[2] + e[3]) + (e[6] + e[7]);
      const uint32_t p0 = pack_bf16(e[0], e[1]), p1 = pack_bf16(e[2], e[3]), p2 = pack_bf16(e[4], e[5]), p3 = pack_bf16(e[6], e[7]);
      const __nv_bfloat16* vp = kt + (size_t)512 * KV_TILE + h * 8192 + 2 * c * 32 + r;
#pragma unroll
      for (int n = 0; n < 8; n++) {
        o[4 * n] *= sc0; o[4 * n + 1] *= sc0; o[4 * n + 2] *= sc1; o[4 * n + 3] *= sc1;
        mma16816(o + 4 * n, p0, p1, p2, p3, ld_pair<32>(vp + (n >> 2) * 4096 + ((n ^ c) & 3) * 8), ld_pair<32>(vp + (n >> 2) * 4096 + ((n ^ c) & 3) * 8 + 256));
        if (n & 1) sched_fence();
      }
    }
    l0 += __shfl_xor_sync(~0u, l0, 1); l1 += __shfl_xor_sync(~0u, l1, 1);
    l0 += __shfl_xor_sync(~0u, l0, 2); l1 += __shfl_xor_sync(~0u, l1, 2);
#pragma unroll
    for (int i = 0; i < 4; i++) {
      const float* v = o + 16 * (i >> 1) + 2 * (i & 1);
      const float f = __fdividef(1.f, (i & 1) ? l1 : l0);
      *reinterpret_cast<uint4*>(g_ctx + (size_t)((row0 >> 7) * 32 + head) * KV_TILE + (2 * h + (i >> 1)) * 4096 + ((row0 & 127) + r + (i & 1) * 8) * 32 + (c ^ (r >> 1)) * 8) =
          make_uint4(pack_bf16(v[0] * f, v[1] * f), pack_bf16(v[4] * f, v[5] * f), pack_bf16(v[8] * f, v[9] * f), pack_bf16(v[12] * f, v[13] * f));
    }
  }
}

constexpr int UNIT = 16384, SLOT = 32768;
constexpr int OFF_SIDE = 2 * SLOT;
__host__ __device__ constexpr int kv_a(int kb) { return (kb < 6 ? kb : 3 * kb - 10) * UNIT; }
__host__ __device__ constexpr int kv_b(int s) { return (s == 2 ? 6 : 9 + 3 * s) * UNIT; }
__host__ __device__ constexpr int q_aw(int s) { return (3 * s + (s & 1)) * UNIT; }
__host__ __device__ constexpr int q_b(int s) { return (3 * s + 2 - 2 * (s & 1)) * UNIT; }
__host__ __device__ constexpr int k_slot(int j, int r) { return (j < 2 ? 2 * j : (r == 2 ? 0 : 3 + r)) * SLOT; }
__host__ __device__ constexpr int v_slot(int j) { return (6 - (j & 1)) * SLOT; }
__host__ __device__ constexpr int r3(int st) { return ((0x654130 >> (4 * st)) & 7) * SLOT; }
constexpr int OFF_BAR = 229376;
constexpr int OFF_MISC = OFF_BAR + 512;
constexpr int SMEM_BYTES = OFF_MISC + 2080 + TL_EXTRA;
constexpr int OFF_RSTAT = OFF_MISC + 1056;
enum : int {
  B_FULL1 = 0, B_FULLQ = 3, B_FULLB = 7, B_KF = 8, B_VF = 11, B_FULL3 = 13, B_WF = 19, B_DEP = 21, B_OUT2 = 26, B_PF = 27, B_SET = 28,
  B_SET2 = 29, B_LNGO = 30, B_WR = 31,
  B_KE = 32, B_VE = 35, B_WE = 37, B_PUB = 39, B_OUT = 45,
  B_EMPTY1 = 46, B_EMPTYQ = 49, B_X = 53, B_EMPTY3 = 57,
  B_NUM = 63
};
#define TUNABLE(name, v) constexpr int name = v
TUNABLE(LN_GO, 3);
TUNABLE(EP1, 2);
TUNABLE(SIDE_NS, 400);
TUNABLE(SET_KB, 44); TUNABLE(SET_NS, 40);
TUNABLE(PF_KB, 54); TUNABLE(PF_N, 7); TUNABLE(PF_NS, 300);
TUNABLE(PS_DLY, 120); TUNABLE(Y_DLY, 700); TUNABLE(Y_DLY0, 1500);
constexpr int PRE = 3;
constexpr int WIN = 6;
constexpr int OFF_STG = r3(0), OFF_SCR = r3(1);
struct Params {
  CUtensorMap xn, ckv, wq, wk, wv, wo, x, wd, wg, wu;
};

__global__ void __cluster_dims__(2, 1, 1) __launch_bounds__(384, 1)
fused_kernel(uint32_t zero, const __nv_bfloat16* __restrict__ x, __nv_bfloat16* g_kv, __nv_bfloat16* g_ctx, uint4* g_xr,
             __nv_bfloat16* __restrict__ out, __nv_bfloat16* g_xn, unsigned* g_cnt, const __nv_bfloat16* __restrict__ w_r,
             const __nv_bfloat16* __restrict__ wdown, const __nv_bfloat16* __restrict__ wq, const __grid_constant__ Params p) {
  extern __shared__ __align__(1024) uint8_t sp[];
  const uint32_t sb = s2u(sp);
  const uint32_t bar = sb + OFF_BAR;
  auto B = [&](int i) { return bar + 8 * i; };
  const int tid = threadIdx.x, warp = __shfl_sync(~0u, tid >> 5, 0), wg = warp >> 2, lane = tid & 31;
  const int cta = blockIdx.x, rank = cta & 1, cl = cta >> 1;
  const int mp = cl < 4 ? 1 : (cl < 36 ? (cl & 7) : (0x3207654 >> (4 * ((cl - 36) % 7))) & 7);
  const int gq = cl < 4 ? 4 + cl : (cl < 36 ? (cl - 4) >> 3 : 4 + (cl - 36) / 7);
  const int mt = 2 * mp + rank;
  const int qa = 15 - gq;
  const int ta = gq ? gq : 15, tb = 15 - ta;
  const int rid = mt * 8 + gq;
  const int fid = mt * 7 + gq;
  const bool ffn = gq < 7;
  TL(0, 0, warp == 4);
  auto load_pre = [&](int kb) {
    e_expect(B(B_FULL1 + kb), 3 * UNIT);
    tma_ld2(sb + kv_a(kb), &p.ckv, B(B_FULL1 + kb), kb * 64, mt * 128);
    tma_ld3(sb + kv_b(kb) + rank * UNIT, &p.wk, B(B_FULL1 + kb), 0, kb * 64, (gq + 8) * 4 + rank * 2);
    tma_ld3(sb + kv_b(kb) + UNIT - rank * UNIT, &p.wk, B(B_FULL1 + kb), 0, kb * 64, (gq + 8) * 4 + 2 - rank * 2);
  };
  if (warp == 0) {
    e_init(B(B_FULL1), 1);
    asm volatile("fence.mbarrier_init.release.cluster;" ::: "memory");
    TL(0, 16, true);
    load_pre(0);
    TL(0, 17, true);
#pragma unroll
    for (int kb = 1; kb < PRE; kb++) e_init(B(B_FULL1 + kb), 1);
  } else {
#pragma unroll 1
    for (int i = PRE - 1 + warp; i < B_NUM; i += 11) e_init(B(i), i >= B_EMPTY1 ? 16 : (i >= B_KE ? 8 : (i == B_WR ? 2 : 1)));
  }
  asm volatile("fence.mbarrier_init.release.cluster;" ::: "memory");
  cluster_arrive();
  const int rid0 = rid, warp0 = warp;
  if (wg == 0) {
    reg_dealloc<40>();
    if (warp == 0) {
      TL(0, 12, true);
#pragma unroll 1
      for (int kb = 1; kb < PRE; kb++) { load_pre(kb); TL(0, 12 + kb, true); }
      if (mt >= 2 * PRE) tma_pf3(&p.wk, 0, (mt >> 1) * 64, (gq + 8) * 4 + (mt & 1) * 2);
      if (gq >= PRE) tma_pf2(&p.ckv, gq * 64, mt * 128);
      TL(0, 15, true);
    }
    TL(0, 18, warp == 0);
    __syncwarp();
    cluster_wait();
    uint4* const xr = g_xr + rid * XR_SIZE;
    auto side_piece = [&](int c, int piece) {
      const uint32_t fb = B(B_WF + (c & 1));
      if (piece == 0) e_expect(fb, UNIT);
      tma_ld2_ef(sb + OFF_SIDE + (c & 1) * UNIT + piece * 4096, (piece & 2) ? &p.wg : &p.wu, fb, fid * 32, c * 128 + (piece & 1) * 64);
    };
    if (warp == 0) {
      {
        int st = 0; uint32_t ph = 1;
#pragma unroll 1
        for (int i = 0; i < 32; i++) {
          const int t = i >> 3, kb = i & 7;
          if (i >= PRE) {
            const uint32_t fb = B(B_FULL1 + st);
            mbar_wait_c(B(B_EMPTY1 + st), ph);
            e_expect(fb, t == 0 ? 3 * UNIT : 2 * UNIT);
            if (t == 0) tma_ld2(sb + kv_a(kb), &p.ckv, fb, kb * 64, mt * 128);
            tma_ld3_mc(sb + kv_b(st) + rank * UNIT, (t & 1) ? &p.wv : &p.wk, fb, 0, kb * 64, (gq + ((t >> 1) ^ 1) * 8) * 4 + rank * 2, 3);
          }
          if (i == LN_GO) e_arrive(B(B_LNGO));
          if (i == 12) { prefetch_tm(&p.wq); prefetch_tm(&p.xn); }
          if (kb == (t ? 0 : 4) && t < 3) tma_pf3((t & 1) ? &p.wk : &p.wv, 0, (mt >> 1) * 64, (gq + (((t + 1) >> 1) ^ 1) * 8) * 4 + (mt & 1) * 2);
          if (kb < 2 && t == 3) tma_pf3(&p.wq, 0, (gq + 8 * kb) * 64, mt * 2);
          if (++st == 3) { st = 0; ph ^= 1; }
        }
        prefetch_tm(&p.wo); prefetch_tm(&p.wd); prefetch_tm(&p.x); prefetch_tm(&p.wg); prefetch_tm(&p.wu);
        mbar_wait_c(B(B_DEP + 0), 0);
        uint32_t kpar = 7, vpar = 3;
        auto load_aw = [&](int kb, int head) {
          const uint32_t d = sb + q_aw(kb & 3), fb = B(B_FULLQ + (kb & 3));
          tma_ld2_mc(d + rank * 8192, &p.xn, fb, kb * 64, ta * 128 + rank * 64, 3);
          tma_ld3(d + UNIT, &p.wq, fb, 0, kb * 64, head * 2);
        };
        auto load_b = [&](int kb, uint32_t fb) { tma_ld2_mc(sb + q_b(kb & 3) + rank * 8192, &p.xn, fb, kb * 64, tb * 128 + rank * 64, 3); };
        auto load3 = [&](int kb, int s) {
          const uint32_t d = sb + r3(s), fb = B(B_FULL3 + s);
          e_expect(fb, SLOT);
          bulk_ld(d, g_ctx + (size_t)(mt * 64 + kb) * 8192, UNIT, fb);
          tma_ld3_mc(d + UNIT + rank * 8192, &p.wo, fb, 0, kb * 64, gq * 2 + rank, 3);
        };
#pragma unroll 1
        for (int half = 0; half < 2; half++) {
          const int head = mt + 16 * half;
#pragma unroll 1
          for (int kb = 2 * half; kb < 16; kb++) {
            if (kb >= 4) mbar_wait_c(B(B_EMPTYQ + (kb & 3)), ((kb >> 2) & 1) ^ 1);
            else if (half) mbar_wait_c(B(B_X + 2), 0);
            else if (kb > 0) mbar_wait_c(B(B_EMPTY1 + (kb + 1) % 3), kb == 1);
            e_expect(B(B_FULLQ + (kb & 3)), 3 * UNIT);
            load_aw(kb, head);
            load_b(kb, B(B_FULLQ + (kb & 3)));
          }
          mbar_wait_c(B(B_DEP + 1 + half), 0);
          const __nv_bfloat16* kt = g_kv + (size_t)head * 16 * KV_TILE;
          l2_prefetch(kt, SLOT);
          auto load_v = [&](int j) {
            const int r = j & 1;
            mbar_wait_c(B(B_VE + r), (vpar >> r) & 1);
            vpar ^= 1 << r;
            e_expect(B(B_VF + r), SLOT);
            bulk_ld(sb + v_slot(j), kt + (size_t)(512 + (j > qa ? 16 - j : j)) * KV_TILE, SLOT, B(B_VF + r));
          };
          int r = 0;
#pragma unroll 1
          for (int j = 0; j < 17; j++) {
            if (j < 2) mbar_wait_c(B(B_EMPTYQ + j), 1);
            if (j == 2) mbar_wait_c(B(B_KE), kpar & 1);
            mbar_wait_c(B(B_KE + r), (kpar >> r) & 1);
            kpar ^= 1 << r;
            e_expect(B(B_KF + r), SLOT);
            bulk_ld(sb + k_slot(j, r), kt + (j > qa ? 16 - j : j) * KV_TILE, SLOT, B(B_KF + r));
            if (++r == 3) r = 0;
            if (j == 2) mbar_wait_c(B(B_EMPTYQ + 3), 1);
            if (j != 1) load_v(j ? j - 1 : 0);
            if (half == 0) {
              if (j == 16) {
                tma_pf3(&p.wq, 0, (4 + gq) * 64, (mt + 16) * 2);
                tma_pf2(&p.xn, (4 + (mp & 3)) * 64, ((mp & 4) ? qa : gq) * 128 + rank * 64);
              }
            } else if (j >= 14) {
              tma_pf3(&p.wo, 0, (5 + mp + 8 * (16 - j)) * 64, gq * 2 + rank);
            } else if (ffn && j >= 5 && j < 13) {
              side_piece((j - 5) >> 2, (j - 5) & 3);
            }
          }
          mbar_wait_c(B(B_X + 0), half);
          if (half == 0) {
            for (int kb = 0; kb < 2; kb++) { e_expect(B(B_FULLQ + kb), 2 * UNIT); load_aw(kb, mt + 16); }
          } else {
            mbar_wait_c(B(B_DEP + 3), 0);
            load3(0, 0);
          }
          mbar_wait_c(B(B_X + 1), half);
          if (half) load3(1, 1);
          load_v(16);
          if (gq == 0) mbar_wait_c(B(B_X + 2), half);
          if (half == 0) { e_expect(B(B_FULLB), 2 * UNIT); load_b(0, B(B_FULLB)); load_b(1, B(B_FULLB)); }
        }
        st = 2; ph = 1;
#pragma unroll 1
        for (int kb = 2; kb < 64; kb++) {
          if (kb == 32) mbar_wait_c(B(B_DEP + 4), 0);
          if (kb >= 6) mbar_wait_c(B(B_EMPTY3 + st), ph);
          else if (kb == 3 || kb == 5) mbar_wait_c(B(B_X + (kb + 1) / 2), 1);
          load3(kb, st);
          if (++st == 6) { st = 0; ph ^= 1; }
          if (kb == PF_KB) e_arrive(B(B_PF));
          if (kb == SET_KB) e_arrive(B(B_SET));
          if (kb == 58) l2_prefetch(xr, XR_CAND * 16);
        }
        if (ffn) {
#pragma unroll 1
          for (int j = 0; j < 2; j++) {
            mbar_wait_c(B(B_EMPTY3 + 4 + j), 1);
            e_expect(B(B_FULL3 + 4 + j), SLOT);
            tma_ld3(sb + r3(4 + j), &p.wd, B(B_FULL3 + 4 + j), 0, fid * 32, 8 * j);
          }
        }
        const uint4* kp = g_xr + ((lane >> 1) * 8 + gq) * XR_SIZE + XR_KEY + (lane & 1) * 2;
        mbar_wait_c(B(B_OUT), 0);
        uint4 kv[2];
        poll_chunks(kv, kp, 1);
        const uint32_t a1 = max(kv[0].x, kv[0].z), a2 = max(min(kv[0].x, kv[0].z), max(kv[0].y, kv[0].w));
        const uint32_t b1 = max(kv[1].x, kv[1].z), b2 = max(min(kv[1].x, kv[1].z), max(kv[1].y, kv[1].w));
        const uint32_t k1 = max(a1, b1), k2 = max(min(a1, b1), max(a2, b2));
        const uint32_t m1 = __reduce_max_sync(~0u, k1);
        const uint32_t m2 = __reduce_max_sync(~0u, k1 == m1 ? k2 : k1);
        const uint32_t t0 = ~m1 & 0x7FFF, t1 = ~m2 & 0x7FFF;
        const uint32_t o0 = (t0 >> 7) * (8 * XR_SIZE * 16) + (t0 & 0x70) * 64, o1 = (t1 >> 7) * (8 * XR_SIZE * 16) + (t1 & 0x70) * 64 + ((t0 ^ t1) < 16 ? 256 : 0);
        asm volatile(ELECT "st.shared.v4.u32 [%0], {%1,%2,%3,%4};\n}" ::"r"(sb + OFF_MISC), "r"(o0), "r"(o1), "r"(m1), "r"(m2) : "memory");
        e_arrive(B(B_OUT2));
        if (rid == 127) { g_cnt[lane] = 0; g_cnt[32 + lane] = 0; }
      }
    } else {
      if (warp >= 2) {
#pragma unroll 1
        for (int i = tid - 64; i < XR_CAND; i += 64) xr[i] = make_uint4(~0u, ~0u, ~0u, ~0u);
        if (warp == 2) { __syncwarp(); if (lane == 0) mbar_arrive(B(B_WR)); }
      }
      if (warp == 3) {
        float ws = 0.f;
#pragma unroll 1
        for (int j = 0; j < 4; j++) {
          const uint4 q = __ldg(reinterpret_cast<const uint4*>(w_r) + j * 32 + lane);
          ws += bf_lo(q.x) + bf_hi(q.x) + bf_lo(q.y) + bf_hi(q.y) + bf_lo(q.z) + bf_hi(q.z) + bf_lo(q.w) + bf_hi(q.w);
        }
#pragma unroll
        for (int o = 16; o; o >>= 1) ws += __shfl_xor_sync(~0u, ws, o);
        uint2* tab = reinterpret_cast<uint2*>(sp + OFF_MISC + 512);
        tab[lane] = make_uint2(0x3F803F80u, 0x3F803F80u);
        tab[32 + lane] = __ldg(reinterpret_cast<const uint2*>(w_r + gq * 128) + lane);
        if (lane == 0) *reinterpret_cast<float*>(sp + OFF_MISC + 1024) = ws;
        __syncwarp();
        if (lane == 0) mbar_arrive(B(B_WR));
      }
      __syncwarp();
      mbar_wait_u(B(B_LNGO), 0);
#pragma unroll 1
      for (int r = warp == 2 ? 0 : (warp + 1) >> 1; r < 16; r += 3) {
        const uint4* src = reinterpret_cast<const uint4*>(x + (size_t)(cta * 16 + r) * DM) + lane;
        uint4 v[4];
#pragma unroll
        for (int j = 0; j < 4; j++) v[j] = __ldcs(src + j * 32);
        float a0 = 0.f, a1 = 0.f, b0 = 0.f, b1 = 0.f;
#pragma unroll
        for (int j = 0; j < 4; j++) {
          const uint32_t u[4] = {v[j].x, v[j].y, v[j].z, v[j].w};
#pragma unroll
          for (int i = 0; i < 4; i++) { const float a = bf_lo(u[i]), b = bf_hi(u[i]); a0 += a; a1 += b; b0 = fmaf(a, a, b0); b1 = fmaf(b, b, b1); }
        }
        a0 += a1; b0 += b1;
#pragma unroll
        for (int o = 16; o; o >>= 1) { a0 += __shfl_xor_sync(~0u, a0, o); b0 += __shfl_xor_sync(~0u, b0, o); }
        const float mean = a0 * (1.f / DM);
        float mb, inv;
        ln_round(mean, fmaxf(fmaf(b0, 1.f / DM, -mean * mean), 0.f), mb, inv);
        const uint32_t nm2 = pack_bf16(-mb, -mb);
        uint4* dst = reinterpret_cast<uint4*>(g_xn + (size_t)(cta * 16 + r) * DM) + lane;
#pragma unroll
        for (int j = 0; j < 4; j++) {
          dst[j * 32] = make_uint4(ln_apply(v[j].x, nm2, inv), ln_apply(v[j].y, nm2, inv), ln_apply(v[j].z, nm2, inv), ln_apply(v[j].w, nm2, inv));
          sched_fence();
        }
      }
      __syncwarp();
      if (lane == 0) {
        fence_gpu();
        red_add(&g_cnt[C_LN + (cta >> 3)], 1);
        TL(0, 20 + warp, true);
        if (warp == 3) {
          spin_until_ge<true>(&g_cnt[C_LN + gq], 24);
#pragma unroll 1
          for (int i = 0; i < 5; i++) {
            const int c = i == 0 ? C_LN + qa : (i < 3 ? C_KV + (i - 1) * 8 + mp : C_CTX + (i - 3) * 16 + mt);
            spin_until_ge<true>(&g_cnt[c], i == 0 ? 24 : 16);
            fence_async_all();
            mbar_arrive(B(B_DEP + i));
          }
        } else if (warp == 1) {
          mbar_wait(B(B_WR), 0);
#pragma unroll 1
          for (int i = 0; i < 6; i++) {
            const int c = i < 2 ? C_KV + gq + (i ^ 1) * 8 : C_CTX + ((i - 2) >> 1) * 16 + ((i & 1) ? tb : ta);
            mbar_wait(B(B_PUB + i), 0);
            fence_gpu();
            red_add(&g_cnt[c], 1);
          }
        }
      }
      __syncwarp();
      if (warp == 2) {
#pragma unroll 1
        for (int c = 2; c < WIN + 4; c++) {
          mbar_wait_u(B(B_WE + (c & 1)), ((c >> 1) & 1) ^ 1);
          if (c == WIN || c == WIN + 1) {
            e_expect(B(B_WF + (c & 1)), UNIT);
            tma_ld3_ef(sb + OFF_SIDE + (c & 1) * UNIT, &p.x, B(B_WF + (c & 1)), 0, mt * 128 + (c & 1) * 64, gq * 2);
          } else if (ffn) {
#pragma unroll 1
            for (int i = 0; i < 4; i++) { side_piece(c < WIN ? c : c - 2, i); __nanosleep(SIDE_NS); }
          }
        }
      } else if (warp == 1) {
        mbar_wait_u(B(B_SET), 0);
#pragma unroll 1
        for (int i = XR_CAND + lane; i < XR_SIZE; i += 32) { xr[i] = make_uint4(~0u, ~0u, ~0u, ~0u); __nanosleep(SET_NS); }
        __syncwarp();
        if (lane == 0) { fence_gpu(); mbar_arrive(B(B_SET2)); }
      } else {
        mbar_wait_u(B(B_PF), 0);
#pragma unroll 1
        for (int i = 0; i < PF_N; i++) {
          asm volatile("prefetch.global.L2 [%0];" ::"l"((const char*)wdown + (size_t)cta * 57344 + (i * 32 + lane) * 128));
          __nanosleep(PF_NS);
        }
      }
      __syncwarp();
      mbar_wait_u(B(B_OUT), 0);
      {
        const int sub = lane >> 4;
        const uint32_t src = sb + OFF_STG + ((lane & 15) >> 3) * 8192 + sub * 128;
        __nv_bfloat16* dst = out + (size_t)(mt * 128 + sub) * DM + gq * 128 + (lane & 15) * 8;
        auto ld = [&](int r, uint2& rs, uint4& v) {
          asm volatile("ld.shared.v2.u32 {%0,%1}, [%2];" : "=r"(rs.x), "=r"(rs.y) : "r"(sb + OFF_RSTAT + ((r + sub) & 127) * 8));
          v = lds128(src + ((r >> 6) & 1) * 16384 + (r & 63) * 128 + (((lane ^ (r + sub)) & 7) << 4));
        };
        uint2 rs; uint4 v;
        ld(2 * warp - 2, rs, v);
#pragma unroll 1
        for (int r = 2 * warp - 2; r < 128; r += 6) {
          const uint2 cs = rs; const uint4 c = v;
          ld(r + 6, rs, v);
          const float inv = __uint_as_float(cs.y);
          asm volatile("{\n.reg .pred p;\nsetp.ge.s32 p, %5, 0;\n@p st.global.v4.u32 [%0], {%1,%2,%3,%4};\n}" ::"l"(dst + (size_t)r * DM),
                       "r"(hadd2_bf(c.x, ln_apply(c.x, cs.x, inv))), "r"(hadd2_bf(c.y, ln_apply(c.y, cs.x, inv))),
                       "r"(hadd2_bf(c.z, ln_apply(c.z, cs.x, inv))), "r"(hadd2_bf(c.w, ln_apply(c.w, cs.x, inv))), "r"(cs.y) : "memory");
        }
      }
      TL(2, 25, warp == 1);
    }
    __syncwarp();
    cluster_arrive();
    cluster_wait();
  } else {
    reg_alloc<232>();
    const int rid_c = rid0 + zero, warp_c = warp0 + zero;
    const int lane = fresh_lane(), rid = rid_c, mt = rid >> 3, gq = rid & 7, qa = 15 - gq, ta = gq ? gq : 15, tb = 15 - ta;
    const int warp = warp_c, cw = warp - 4, w = cw >> 2;
    cluster_wait();
    auto publish = [&](int i) { __syncwarp(); e_arrive(B(B_PUB + i)); };
    auto release2 = [&](uint32_t b, bool cond = true) { mbar_arrive_both(b, lane, cond); };
    AtState s;
    const uint32_t dA = mk_desc(sb + w * 8192, 16);
    const uint32_t dW = mk_desc(sb, 8192);
    auto mma_kb = [&](float (&d)[64], uint32_t a, uint32_t b, int accum) {
      static_for<4>([&](auto k) { mma_n128_ss<1, k * 32, k * 2048>(d, dA + (a >> 4), dW + (b >> 4), k == 0 ? accum : 1); });
    };
    auto mma_kc = [&](float (&d)[64], auto a, auto b, int accum) {
      static_for<4>([&](auto k) { mma_n128_ss<1, decltype(a)::value + k * 32, decltype(b)::value + k * 2048>(d, dA, dW, k == 0 ? accum : 1); });
    };
    auto issue_q = [&](int kb, auto accum) {
      const int st = kb & 3;
      mbar_wait_c(B(B_FULLQ + st), (kb >> 2) & 1);
      wg_fence();
      mma_kb(s.S, q_aw(st), q_aw(st) + UNIT, accum);
      wg_commit();
      if (accum) {
        wg_wait<1>();
        release2(B(B_EMPTYQ + ((kb - 1) & 3)));
        wg_fence();
      }
      mma_kb(s.O, q_b(st), q_aw(st) + UNIT, accum);
      wg_commit();
    };
    {
      uint4 pk[16];
      __nv_bfloat16* pdst = g_kv;
      auto put = [&](int i) { __stcs(reinterpret_cast<uint4*>(pdst + (i & 1) * 256 + ((i >> 1) & 3) * 4096 + (i >> 3) * 16 * KV_TILE), pk[i]); };
      float acc1[128];
      TL(0, 1, warp == 4);
      int st = 0; uint32_t ph = 0;
      auto issue = [&](int kb, int accum) {
        mbar_wait_c(B(B_FULL1 + st), ph);
        wg_fence();
        static_for<4>([&](auto k) { mma_n256_ss<1, k * 32, k * 2048>(acc1, dA + (kv_a(kb) >> 4), dW + (kv_b(st) >> 4), k == 0 ? accum : 1); });
        wg_commit();
      };
#pragma unroll 1
      for (int t = 0; t < 4; t++) {
        issue(0, 0);
        TL(0, 2 + 2 * t, warp == 4);
        if (t > 0) { put(0); put(1); }
        int prev = st;
        if (++st == 3) { st = 0; ph ^= 1; }
#pragma unroll 1
        for (int kb = 1; kb < 8; kb++) {
          if (kb == 7 && w == 1) bar_sync(5, 256);
          issue(kb, 1);
          if (kb == 7 && w == 0) bar_arrive(5, 256);
          if (t > 0) {
#pragma unroll
            for (int i = 1; i < 8; i++) if (kb == i) { put(2 * i); put(2 * i + 1); }
            if (kb == 7 && t == 2) publish(0);
          }
          wg_wait<1>();
          TK(24 + t * 8 + kb - 1);
          release2(B(B_EMPTY1 + prev));
          prev = st;
          if (++st == 3) { st = 0; ph ^= 1; }
        }
        pdst = g_kv + (size_t)(((t & 1) * 32 + (gq + ((t >> 1) ^ 1) * 8) * 2) * 16 + mt) * KV_TILE + (cw * 16 + (lane >> 2)) * 32 + ((lane ^ (lane >> 3)) & 3) * 8;
        wg_wait<0>();
        TK(24 + t * 8 + 7);
        fence_regs(acc1);
        release2(B(B_EMPTY1 + prev));
        TL(0, 3 + 2 * t, warp == 4);
#pragma unroll
        for (int a = 0; a < 8; a++)
#pragma unroll
          for (int h = 0; h < 2; h++)
            pk[2 * a + h] = make_uint4(pack_bf16(acc1[16 * a + 2 * h], acc1[16 * a + 2 * h + 1]), pack_bf16(acc1[16 * a + 4 + 2 * h], acc1[16 * a + 5 + 2 * h]),
                                       pack_bf16(acc1[16 * a + 8 + 2 * h], acc1[16 * a + 9 + 2 * h]), pack_bf16(acc1[16 * a + 12 + 2 * h], acc1[16 * a + 13 + 2 * h]));
      }
      issue_q(0, IC<0>{});
      TL(0, 10, warp == 4);
      put(0); put(1);
#pragma unroll 1
      for (int kb = 1; kb < 8; kb++) {
        issue_q(kb, IC<1>{});
        TK(66 + kb - 1);
#pragma unroll
        for (int i = 1; i < 8; i++) if (kb == i) { put(2 * i); put(2 * i + 1); }
      }
      publish(1);
      TL(0, 11, warp == 4);
    }
    __nv_bfloat16* cdst;
    uint32_t redo = 0;
    auto put_ctx = [&](int i, bool cond) {
      asm volatile("{\n.reg .pred p;\nsetp.ne.u32 p, %5, 0;\n@p st.global.cs.v4.u32 [%0], {%1,%2,%3,%4};\n}" ::"l"(cdst + (i & 1) * 256 + (i >> 1) * 4096),
                   "r"(s.P[4 * i]), "r"(s.P[4 * i + 1]), "r"(s.P[4 * i + 2]), "r"(s.P[4 * i + 3]), "r"((uint32_t)(cond && !(redo & 2))) : "memory");
    };
    {
      const int wrow = cw * 16;
      const uint32_t dK = mk_desc(sb, 16), dV = mk_desc(sb, 8192);
      uint32_t kph = 0, vph = 0;
      auto q_store = [&](const float (&d)[64]) {
        const int r0 = lane >> 2;
        const uint32_t a = sb + SLOT + (wrow + r0) * 128 + (((lane & 3) ^ (((r0 & 1) << 2) | (r0 >> 1))) << 4);
#pragma unroll
        for (int i = 0; i < 8; i++) {
          const float* o = d + 16 * (i >> 1) + 2 * (i & 1);
          asm volatile("st.shared.v4.u32 [%0], {%1,%2,%3,%4};" ::"r"((a ^ ((i & 2) << 5)) + (i >> 2) * UNIT + (i & 1) * 1024),
                       "r"(pack_bf16(o[0] * AT_C, o[1] * AT_C)), "r"(pack_bf16(o[4] * AT_C, o[5] * AT_C)),
                       "r"(pack_bf16(o[8] * AT_C, o[9] * AT_C)), "r"(pack_bf16(o[12] * AT_C, o[13] * AT_C)) : "memory");
        }
        __syncwarp();
      };
      auto q_load = [&](auto k0, auto k1) {
        const uint32_t a = sb + SLOT + (wrow + (lane & 15)) * 128 + (((lane >> 4) ^ (((lane & 1) << 2) | ((lane >> 1) & 3))) << 4);
#pragma unroll
        for (int k = k0; k < k1; k++)
          asm volatile("ldmatrix.sync.aligned.m8n8.x4.shared.b16 {%0,%1,%2,%3}, [%4];"
                       : "=r"(s.Q[4 * k]), "=r"(s.Q[4 * k + 1]), "=r"(s.Q[4 * k + 2]), "=r"(s.Q[4 * k + 3]) : "r"((a ^ ((k & 3) << 5)) + (k >> 2) * UNIT) : "memory");
      };
      auto q_load_if = [&](auto k, bool cond, float after) {
        const uint32_t a = sb + SLOT + (wrow + (lane & 15)) * 128 + (((lane >> 4) ^ (((lane & 1) << 2) | ((lane >> 1) & 3))) << 4);
        asm volatile("{\n.reg .pred p;\nsetp.ne.u32 p, %5, 0;\n@p ldmatrix.sync.aligned.m8n8.x4.shared.b16 {%0,%1,%2,%3}, [%4];\n}"
                     : "+r"(s.Q[4 * k]), "+r"(s.Q[4 * k + 1]), "+r"(s.Q[4 * k + 2]), "+r"(s.Q[4 * k + 3])
                     : "r"((a ^ ((k & 3) << 5)) + (k >> 2) * UNIT + (__float_as_uint(after) >> 31)), "r"((uint32_t)cond) : "memory");
      };
      auto issue_s = [&](uint32_t dk, auto mid) {
        mma_n128_rs0<0>(s.S, s.Q, dk);
        static_for<7>([&](auto i) {
          constexpr int k = i + 1;
          if (k == 4) mid();
          mma_n128_rs<0, (k >> 1) * 8192 + (k & 1) * 32>(s.S, s.Q + 4 * k, dk, 1);
        });
        wg_commit();
      };
      auto wait_v = [&](int jv) {
        mbar_wait_c(B(B_VF + (jv & 1)), (vph >> (jv & 1)) & 1);
        vph ^= 1 << (jv & 1);
      };
      auto issue_pva = [&](int jv, int accum) {
        wg_fence();
        static_for<4>([&](auto k) { mma_n128_rs<1, k * 1024>(s.O, s.P + 4 * k, dV + (v_slot(jv) >> 4), k == 0 ? accum : 1); });
        wg_commit();
      };
      auto issue_pvb = [&](int jv, bool upper) {
        if (upper) {
          wg_fence();
          static_for<4>([&](auto k) { mma_n128_rs<1, (k + 4) * 1024>(s.O, s.P + 16 + 4 * k, dV + (v_slot(jv) >> 4), 1); });
          wg_commit();
        } else {
          asm volatile("wgmma.fence.sync.aligned;\nwgmma.commit_group.sync.aligned;" ::: "memory");
        }
      };
      auto issue_pv = [&](int jv, int accum, bool upper) { wait_v(jv); issue_pva(jv, accum); issue_pvb(jv, upper); };
      if (w == 1) bar_arrive(1, 256);
#pragma unroll 1
      for (int half = 0; half < 2; half++) {
        const int head = mt + 16 * half;
        redo = 0;
        float inv[2];
        auto ep_prep = [&]() {
          float l0 = s.l[0] + s.l[1], l1 = s.l[2] + s.l[3];
          l0 += __shfl_xor_sync(~0u, l0, 1); l1 += __shfl_xor_sync(~0u, l1, 1);
          l0 += __shfl_xor_sync(~0u, l0, 2); l1 += __shfl_xor_sync(~0u, l1, 2);
          asm("rcp.approx.ftz.f32 %0, %1;" : "=f"(inv[0]) : "f"(l0));
          asm("rcp.approx.ftz.f32 %0, %1;" : "=f"(inv[1]) : "f"(l1));
          return __any_sync(~0u, !(fminf(l0, l1) >= L_MIN && l0 + l1 <= L_MAX));
        };
        auto ep_out = [&](auto i0, auto i1) {
          __nv_bfloat16* dst = g_ctx + (size_t)(ta * 32 + head) * KV_TILE + (wrow + (lane >> 2)) * 32 + ((lane ^ (lane >> 3)) & 3) * 8;
#pragma unroll
          for (int i = i0; i < i1; i++) {
            const float* o = s.O + 16 * (i >> 1) + 2 * (i & 1);
            const float c = inv[i & 1];
            asm volatile("st.global.cs.v4.u32 [%0], {%1,%2,%3,%4};" ::"l"(dst + (i & 1) * 256 + (i >> 1) * 4096), "r"(pack_bf16(o[0] * c, o[1] * c)),
                         "r"(pack_bf16(o[4] * c, o[5] * c)), "r"(pack_bf16(o[8] * c, o[9] * c)), "r"(pack_bf16(o[12] * c, o[13] * c)) : "memory");
          }
        };
        auto ep_rest = [&]() {
          ep_out(IC<EP1>{}, IC<8>{});
          if (!__any_sync(~0u, redo)) publish(2 + 2 * half);
          fence_regs(s.O);
        };
#pragma unroll 1
        for (int kb = 8; kb < 14; kb++) {
          issue_q(kb, IC<1>{});
          TK(66 + half * 24 + kb - 1);
        }
        TL(1, 20 * half + 0, warp == 4);
        mbar_wait_c(B(B_FULLQ + 2), 1);
        mbar_wait_c(B(B_FULLQ + 3), 1);
        bar_sync(1 + w, 256);
        wg_fence();
        mma_kc(s.S, IC<q_aw(2)>{}, IC<q_aw(2) + UNIT>{}, 1);
        wg_commit();
        wg_wait<1>();
        TK(66 + half * 24 + 13);
        release2(B(B_EMPTYQ + 1));
        wg_fence();
        mma_kc(s.S, IC<q_aw(3)>{}, IC<q_aw(3) + UNIT>{}, 1);
        wg_commit();
        bar_arrive(2 - w, 256);
        bar_sync(6 + w, 128);
        wg_wait<0>();
        TK(66 + half * 24 + 14);
        fence_regs(s.S);
        q_store(s.S);
        q_load(IC<0>{}, IC<8>{});
        TL(1, 20 * half + 1, warp == 4);
        TC(w, 17 * half, 0);
        mbar_wait_c(B(B_KF), kph & 1);
        kph ^= 1;
        bar_sync(1 + w, 256);
        TC(w, 17 * half, 2);
        fence_regs(s.O); fence_regs(s.Q);
        wg_fence();
        issue_s(dK, []() {});
        mma_kc(s.O, IC<q_b(2)>{}, IC<q_aw(2) + UNIT>{}, 1);
        mma_kc(s.O, IC<q_b(3)>{}, IC<q_aw(3) + UNIT>{}, 1);
        wg_commit();
        bar_arrive(2 - w, 256);
        wg_wait<1>();
        TC(w, 17 * half, 4);
        fence_regs(s.S);
        e_arrive(B(B_KE));
        s.l[0] = s.l[1] = s.l[2] = s.l[3] = 0.f;
        at_exp<0, 48>(s);
        at_pack<0, 22>(s);
        sched_fence();
        wg_wait<0>();
        fence_regs(s.O); fence_regs(s.Q);
        release2(B(B_EMPTYQ + 2)); release2(B(B_EMPTYQ + 3));
        at_exp<48, 64>(s);
        at_pack<22, 32>(s);
        q_store(s.O);
        TL(1, 20 * half + 2, warp == 4);
        int kr = 1;
        bool kok = false;
        inv[0] = inv[1] = 0.f;
        const int db = gq ? qa : 16;
#pragma unroll 1
        for (int j = 1; j < 17; j++) {
          const bool diag = j == ta || j == db;
          TC(w, j + 17 * half, 0);
          if (!kok) mbar_wait_c(B(B_KF + kr), (kph >> kr) & 1);
          kph ^= 1 << kr;
          if (j == ta + 2) ep_out(IC<0>{}, IC<EP1>{});
          bar_sync(1 + w, 256);
          TC(w, j + 17 * half, 2);
          fence_regs(s.O); fence_regs(s.P); fence_regs(s.Q);
          const uint32_t ke = B(B_KE + kr), dk = dK + (k_slot(j, kr) >> 4);
          if (++kr == 3) kr = 0;
          auto issue_rest = [&](auto trimmed) {
            TC(w, j + 17 * half, 1);
            if (j == ta + 1) {
              if (ep_prep()) redo = 1;
              s.l[0] = s.l[1] = s.l[2] = s.l[3] = 0.f;
            }
            if (!trimmed && j == ta + 2) ep_rest();
            TC(w, j + 17 * half, 3);
            if (trimmed) wait_v(j - 1);
            issue_pva(j - 1, j != 1 && j != ta + 2);
            issue_pvb(j - 1, w == 1 || (j != ta + 1 && j != db + 1));
            bar_arrive(2 - w, 256);
          };
          auto s_done = [&](auto n) {
            wg_wait<2>();
            TC(w, j + 17 * half, 4);
            fence_part<0, n>(s.S); fence_regs(s.Q);
            e_arrive(ke);
            release2(B(B_X + j - 14), j == 14 || j == 15);
          };
          auto pv_half = [&]() { sched_fence(); wg_wait<1>(); fence_regs(s.P); };
          auto pv_done = [&]() {
            sched_fence();
            wg_wait<0>();
            fence_regs(s.O); fence_regs(s.P);
            e_arrive(B(B_VE + ((j - 1) & 1)));
            release2(B(B_X + 2), j == 16);
            kok = mbar_test(B(B_KF + kr), (kph >> kr) & 1);
          };
          if (diag && w == 0) {
            wg_fence();
            static_for<8>([&](auto k) { mma_n64_rs<0, (k >> 1) * 8192 + (k & 1) * 32, k != 0>(s.S, s.Q + 4 * k, dk); });
            wg_commit();
            issue_rest(IC<1>{});
            s_done(IC<32>{});
            at_mask<0>(s, wrow, lane);
            pv_half();
            static_for<8>([&](auto k) {
              at_exp<4 * k, 4 * k + 4>(s);
              q_load_if(k, j == ta, s.S[4 * k]);
            });
            at_pack<0, 16>(s);
            pv_done();
          } else {
            wg_fence();
            issue_s(dk, [&]() { wait_v(j - 1); wg_fence(); });
            issue_rest(IC<0>{});
            if (!diag) {
              s_done(IC<64>{});
              at_exp<0, 24>(s);
              pv_half();
              at_exp<24, 48>(s);
              at_pack<0, 16>(s);
              pv_done();
              at_exp<48, 64>(s);
              at_pack<16, 32>(s);
            } else {
              s_done(IC<64>{});
              at_mask<8>(s, wrow - 64, lane);
              static_for<8>([&](auto k) {
                at_exp<7 * k, 7 * k + 7>(s);
                q_load_if(k, j == ta, s.S[7 * k + 3]);
                if (k == 2) pv_half();
                if (k == 5) { at_pack<0, 16>(s); pv_done(); }
              });
              at_exp<56, 64>(s);
              at_pack<16, 32>(s);
            }
          }
          TL(1, 20 * half + 2 + j, warp == 4);
        }
        TK(84 + half * 24);
        mbar_wait_c(B(half ? B_FULL3 : B_FULLQ), 0);
        if (gq == 0) ep_out(IC<0>{}, IC<EP1>{});
        bar_sync(1 + w, 256);
        fence_regs(s.O); fence_regs(s.P);
        const uint32_t ga = dA - half * w * 256, gb = ga + (half ? 512 : 4), gh = half ? 0x80000020u : 0x40000040u, go = (2 + half) * (SLOT >> 4);
        wg_fence();
        static_for<4>([&](auto k) { mma_n128_ssh<(k & 1) * 32, UNIT + k * 2048, k != 0>(s.S, k < 2 ? ga : gb, gh, dW); });
        mbar_wait_c(B(half ? B_FULL3 + 1 : B_FULLQ + 1), 0);
        wg_fence();
        static_for<4>([&](auto k) { mma_n128_ssh<(k & 1) * 32, UNIT + k * 2048, true>(s.S, (k < 2 ? ga : gb) + go, gh, dW + go); });
        wg_commit();
        TK(85 + half * 24);
        if (gq == 0) ep_rest();
        issue_pv(16, gq != 0, w == 1 || gq != 0);
        if (w == 0 || half == 0) bar_arrive(2 - w, 256);
        TK(86 + half * 24);
        wg_wait<2>();
        release2(B(B_EMPTY3), half); release2(B(B_EMPTY3 + 1), half);
        if (ep_prep()) redo |= 2;
        sched_fence();
        wg_wait<0>();
        TK(87 + half * 24);
        fence_regs(s.S);
        fence_regs(s.O);
        e_arrive(B(B_VE));
        release2(B(B_X + 3));
        fence_regs(s.P);
        {
          const int r = fresh_lane();
          cdst = g_ctx + (size_t)(tb * 32 + head) * KV_TILE + (wrow + (r >> 2)) * 32 + ((r ^ (r >> 3)) & 3) * 8;
        }
#pragma unroll
        for (int i = 0; i < 32; i++) {
          const float* o = s.O + 16 * (i >> 3) + 2 * ((i >> 2) & 1) + 4 * (i & 3);
          s.P[i] = pack_bf16(o[0] * inv[(i >> 2) & 1], o[1] * inv[(i >> 2) & 1]);
        }
        fence_regs(s.P);
        if (__builtin_expect(__any_sync(~0u, redo != 0), 0)) {
#pragma unroll
          for (int i = 0; i < 8; i++) put_ctx(i, true);
#pragma unroll 1
          for (int t = 0; t < 2; t++) {
            if (__any_sync(~0u, (redo >> t) & 1)) slow_rows(wq, head, (t ? tb : ta) * 128 + wrow);
          }
          if (__any_sync(~0u, redo & 1)) publish(2 + 2 * half);
#pragma unroll
          for (int i = 0; i < 32; i++) s.P[i] = 0;
          redo = 2;
        }
        TL(1, 20 * half + 19, warp == 4);
        TK(88 + half * 24);
        if (half) break;
        mbar_wait_c(B(B_FULLB), 0);
        TK(89);
        wg_fence();
        mma_n128_ss0<1, q_b(0), UNIT>(s.O, dA, dW);
        static_for<3>([&](auto k) { mma_n128_ss<1, q_b(0) + k * 32 + 32, UNIT + k * 2048 + 2048>(s.O, dA, dW, 1); });
        wg_commit();
        mma_kc(s.O, IC<q_b(1)>{}, IC<q_aw(1) + UNIT>{}, 1);
        wg_commit();
        wg_wait<1>();
        release2(B(B_EMPTYQ));
        put_ctx(0, true);
#pragma unroll 1
        for (int kb = 2; kb < 8; kb++) {
          issue_q(kb, IC<1>{});
          TK(90 + kb - 1);
#pragma unroll
          for (int i = 1; i < 8; i++) put_ctx(i, kb == (i < 7 ? i + 1 : 7));
        }
        publish(3);
      }
    }
    const int rid_ = rid + zero, cw_ = cw + zero;
    {
    const int lane = fresh_lane(), rid = rid_, mt = rid >> 3, gq = rid & 7, cw = cw_, w = cw >> 2, ct = cw * 32 + lane;
    const int fid = mt * 7 + gq;
    const bool ffn = gq < 7;
    const uint32_t stg = sb + OFF_STG + w * 16384 + (cw & 3) * 2048;
    const int wr_ = w * 64 + (lane & 7) + (lane >> 4) * 8;
    const uint32_t wl = sb + ((lane >> 3) & 1) * 8192 + wr_ * 64 + (((cw ^ (wr_ >> 1)) & 3) << 4);
    __syncwarp();
    float (&acc)[64] = s.S;
    uint32_t wf[128];
    auto grab = [&](auto c, uint32_t off) {
#pragma unroll
      for (int m = 0; m < 4; m++)
        asm volatile("ldmatrix.sync.aligned.m8n8.x4.trans.shared.b16 {%0,%1,%2,%3}, [%4];"
                     : "=r"(wf[16 * c + 4 * m]), "=r"(wf[16 * c + 4 * m + 1]), "=r"(wf[16 * c + 4 * m + 2]), "=r"(wf[16 * c + 4 * m + 3])
                     : "r"(wl + off + m * 1024) : "memory");
    };
    const int r0 = lane >> 2;
    uint32_t hp[32], rt[16];
    {
      const uint32_t dC = mk_desc(sb + w * 4096, 16);
      uint32_t dep = 0;
      auto hand = [&](uint32_t b, int n) {
        asm volatile("{\n.reg .pred p;\n.reg .b32 t;\nsetp.lt.u32 p, %1, %4;\nmad.lo.u32 t, %2, %3, %0;\n@p mbarrier.arrive.shared::cta.b64 _, [t];\n}"
                     ::"r"(b + 8 * lane), "r"(lane), "r"(dep), "r"(zero), "r"(n) : "memory");
      };
      auto kblock = [&](auto st, uint32_t ph, bool rel) {
        mbar_wait_c(B(B_FULL3 + st), ph);
        wg_fence();
        static_for<4>([&](auto k) { mma_n128_ssh<r3(decltype(st)::value) + (k >> 1) * 8192 + (k & 1) * 32, r3(decltype(st)::value) + UNIT + k * 2048, true>(acc, dC, 0x80000020u, dW); });
        wg_commit();
        wg_wait<1>();
        release2(B(B_EMPTY3 + (st + 5) % 6), rel);
      };
      auto ldsm_if = [&](uint32_t* r, uint32_t a, bool c, auto trans) {
        if (trans) asm volatile("{\n.reg .pred p;\nsetp.ne.u32 p, %5, 0;\n@p ldmatrix.sync.aligned.m8n8.x4.trans.shared.b16 {%0,%1,%2,%3}, [%4];\n}"
                                : "+r"(r[0]), "+r"(r[1]), "+r"(r[2]), "+r"(r[3]) : "r"(a), "r"((uint32_t)c) : "memory");
        else asm volatile("{\n.reg .pred p;\nsetp.ne.u32 p, %5, 0;\n@p ldmatrix.sync.aligned.m8n8.x4.shared.b16 {%0,%1,%2,%3}, [%4];\n}"
                          : "+r"(r[0]), "+r"(r[1]), "+r"(r[2]), "+r"(r[3]) : "r"(a), "r"((uint32_t)c) : "memory");
      };
#pragma unroll
      for (int i = 0; i < 48; i++) wf[i] = 0;
#pragma unroll 1
      for (int lap = 0; lap < 3; lap++) {
        kblock(IC<2>{}, lap & 1, lap > 0);
#pragma unroll
        for (int i = 0; i < 3; i++) put_ctx(3 * i, lap == i);
        kblock(IC<3>{}, lap & 1, true);
        if (ffn) mbar_wait_c(B(B_WF + (lap & 1)), lap >> 1);
#pragma unroll
        for (int i = 0; i < 12; i++) ldsm_if(wf + 4 * i, wl + OFF_SIDE + ((i >> 2) & 1) * UNIT + (i & 3) * 1024, lap == (i >> 2), IC<1>{});
        kblock(IC<4>{}, lap & 1, true);
        sched_fence();
        dep = 0;
#pragma unroll
        for (int i = 0; i < 12; i++) dep ^= wf[4 * i];
        hand(B(B_WE + (lap & 1)), 1);
#pragma unroll
        for (int i = 0; i < 3; i++) put_ctx(3 * i + 1, lap == i);
        kblock(IC<5>{}, lap & 1, true);
        if (lap == 2) publish(5);
        kblock(IC<0>{}, (lap & 1) ^ 1, true);
#pragma unroll
        for (int i = 0; i < 2; i++) put_ctx(3 * i + 2, lap == i);
        kblock(IC<1>{}, (lap & 1) ^ 1, true);
        TL(2, 40 + lap, warp == 4);
      }
#pragma unroll
      for (int i = 48; i < 96; i++) wf[i] = 0;
#pragma unroll
      for (int i = 0; i < 32; i++) { hp[i] = 0; rt[i >> 1] = 0; }
      const uint32_t xa = sb + OFF_SIDE + w * UNIT + (cw & 3) * 2048 + (lane & 15) * 128 + (((lane >> 4) ^ (lane & 7)) << 4);
#pragma unroll 1
      for (int lap = 3; lap < 11; lap++) {
        kblock(IC<2>{}, lap & 1, true);
        kblock(IC<3>{}, lap & 1, true);
        if (lap == 10) break;
        if (lap < WIN) {
          if (ffn) mbar_wait_c(B(B_WF + (lap & 1)), (lap >> 1) & 1);
#pragma unroll
          for (int i = 12; i < 24; i++) ldsm_if(wf + 4 * i, wl + OFF_SIDE + ((i >> 2) & 1) * UNIT + (i & 3) * 1024, lap == (i >> 2), IC<1>{});
        } else if (lap == WIN) {
          mbar_wait_c(B(B_WF), ffn ? (WIN >> 1) & 1 : 0);
          mbar_wait_c(B(B_WF + 1), ffn ? (WIN >> 1) & 1 : 0);
#pragma unroll
          for (int j = 0; j < 8; j++) ldsm_if(hp + 4 * j, (xa ^ ((j & 3) << 5)) + (j >> 2) * 8192, true, IC<0>{});
        } else if (lap == 9) {
          mbar_wait_c(B(B_WR), 0);
          mbar_wait_c(B(B_SET2), 0);
#pragma unroll
          for (int j = 0; j < 4; j++) ldsm_if(rt + 4 * j, sb + OFF_MISC + 512 + (lane & 1) * 256 + (lane >> 3) * 16 + j * 64, true, IC<0>{});
        }
        kblock(IC<4>{}, lap & 1, true);
        sched_fence();
        dep = 0;
#pragma unroll
        for (int i = 0; i < 20; i++) dep ^= i < 12 ? wf[48 + 4 * i] : hp[4 * (i - 12)];
        hand(B(B_WE + (lap < WIN ? lap & 1 : 0)), lap < WIN ? 1 : (lap == WIN ? 2 : 0));
        kblock(IC<5>{}, lap & 1, true);
        kblock(IC<0>{}, (lap & 1) ^ 1, true);
        kblock(IC<1>{}, (lap & 1) ^ 1, true);
        TL(2, 40 + lap, warp == 4);
      }
    }
    uint4* const xr = g_xr + rid * XR_SIZE;
    uint4* const psd = xr + XR_PS + cw * 16 + r0;
    settle(psd, zero);
    sched_fence();
    wg_wait<0>();
    fence_regs(acc);
    TL(2, 10, warp == 4);
    {
      float d[4] = {0.f, 0.f, 0.f, 0.f}, qa[4] = {0.f, 0.f, 0.f, 0.f}, qb[4] = {0.f, 0.f, 0.f, 0.f};
#pragma unroll
      for (int j = 0; j < 16; j++) {
        hp[2 * j] = hadd2_bf(hp[2 * j], pack_bf16(acc[4 * j], acc[4 * j + 1]));
        hp[2 * j + 1] = hadd2_bf(hp[2 * j + 1], pack_bf16(acc[4 * j + 2], acc[4 * j + 3]));
        if (j & 1) {
          mma16816(d, hp[2 * j - 2], hp[2 * j - 1], hp[2 * j], hp[2 * j + 1], rt[j - 1], rt[j]);
          mma16816(qa, hp[2 * j - 2], hp[2 * j - 1], hp[2 * j], hp[2 * j + 1], hp[2 * j - 2], hp[2 * j]);
          mma16816(qb, hp[2 * j - 2], hp[2 * j - 1], hp[2 * j], hp[2 * j + 1], hp[2 * j - 1], hp[2 * j + 1]);
        }
      }
      asm volatile("{\n.reg .pred p;\nsetp.eq.u32 p, %7, %8;\n@p st.global.cg.v4.f32 [%0], {%1,%2,%3,%3};\n@p st.global.cg.v4.f32 [%0 + 128], {%4,%5,%6,%6};\n}"
                   ::"l"(psd), "f"(d[0]), "f"(d[1]), "f"((r0 & 1) ? qa[1] : qa[0]), "f"(d[2]), "f"(d[3]), "f"((r0 & 1) ? qb[3] : qb[2]),
                   "r"(lane & 3), "r"(r0 >> 1) : "memory");
      sched_fence();
    }
    mbar_wait_c(B(B_EMPTY3), 0);
    __syncwarp();
    stage_store_128(stg, lane, hp);
    TL(2, 11, warp == 4);
    __syncwarp();
    uint4 cout;
    uint32_t ckey;
    {
      const float wsum = *reinterpret_cast<const float*>(sp + OFF_MISC + 1024);
      const uint4* pp = g_xr + (mt * 8 + (ct & 1) * 4) * XR_SIZE + XR_PS + (ct >> 1);
      uint2* kd = reinterpret_cast<uint2*>(xr + XR_KEY) + cw;
      const uint32_t tok = 0x7FFFu - (mt * 128 + (ct >> 1));
      settle(pp, zero); settle(kd, zero); settle(tok, zero);
      spin_clk(PS_DLY);
      float s1, s2, s3;
#pragma unroll 1
      for (int n = 0; n < 0x400000; n++) {
        float4 z[4];
#pragma unroll
        for (int i = 0; i < 4; i++)
          asm volatile("ld.relaxed.gpu.global.v4.f32 {%0,%1,%2,%3}, [%4];" : "=f"(z[i].x), "=f"(z[i].y), "=f"(z[i].z), "=f"(z[i].w) : "l"(pp + i * XR_SIZE) : "memory");
        s1 = (z[0].x + z[1].x) + (z[2].x + z[3].x); s3 = (z[0].y + z[1].y) + (z[2].y + z[3].y); s2 = (z[0].z + z[1].z) + (z[2].z + z[3].z);
        const float t = s1 + s2 + s3;
        s1 += __shfl_xor_sync(~0u, s1, 1); s2 += __shfl_xor_sync(~0u, s2, 1); s3 += __shfl_xor_sync(~0u, s3, 1);
        if (__all_sync(~0u, t == t)) break;
        uint32_t m = 0;
#pragma unroll
        for (int i = 0; i < 4; i++) m = max(max(m, __float_as_uint(z[i].x)), max(__float_as_uint(z[i].y), __float_as_uint(z[i].z)));
        if (__all_sync(~0u, m != 0xFFFFFFFFu)) break;
      }
      TL(2, 12, warp == 4);
      const float mean = s1 * (1.f / DM);
      float mb, inv;
      ln_round(mean, fmaxf(fmaf(s2, 1.f / DM, -mean * mean), 0.f), mb, inv);
      const uint32_t u = pack_bf16(0.f, fmaf(s3 - mb * wsum, inv, 0.f));
      const uint32_t key = ((u ^ (((int)u >> 31) | 0x80000000u)) & 0xFFFF0000u) | tok;
      const uint32_t c1 = __reduce_max_sync(~0u, key);
      const uint32_t c2 = __reduce_max_sync(~0u, key == c1 ? 0u : key);
      asm volatile(ELECT "st.global.cg.v2.u32 [%0], {%1,%2};\n}" ::"l"(kd), "r"(c1), "r"(c2) : "memory");
      sched_fence();
      const uint32_t nm2 = pack_bf16(-mb, -mb);
      if (!(ct & 1)) *reinterpret_cast<uint2*>(sp + OFF_RSTAT + (ct >> 1) * 8) = make_uint2(nm2, __float_as_uint(inv) | (key >= c2 ? 0x80000000u : 0u));
      ckey = (lane >> 4) ? c2 : c1;
      const int row = (0x7FFF - (ckey & 0x7FFF)) & 15;
      const uint32_t rn = __shfl_sync(~0u, nm2, row * 2);
      const float ri = __shfl_sync(~0u, inv, row * 2);
      const uint4 v = lds128(stg + ((lane & 15) >> 3) * 8192 + row * 128 + (((lane & 7) ^ (row & 7)) << 4));
      const uint4 n = make_uint4(ln_apply(v.x, rn, ri), ln_apply(v.y, rn, ri), ln_apply(v.z, rn, ri), ln_apply(v.w, rn, ri));
      __stcg(xr + XR_CAND + cw * 64 + 32 + lane, n);
      __stcg(xr + XR_CAND + cw * 64 + lane, v);
      cdst = out + (size_t)(0x7FFF - (ckey & 0x7FFF)) * DM + gq * 128 + (lane & 15) * 8;
      cout = make_uint4(hadd2_bf(v.x, n.x), hadd2_bf(v.y, n.y), hadd2_bf(v.z, n.z), hadd2_bf(v.w, n.w));
    }
    publish(B_OUT - B_PUB);
    cluster_arrive();
    TL(2, 13, warp == 4);
    uint32_t wd[16][4];
    if (ffn) {
      static_for<2>([&](auto i) {
        mbar_wait_b(B(B_WF + i), ((WIN >> 1) & 1) ^ 1);
        grab(IC<WIN + i>{}, OFF_SIDE + i * UNIT);
      });
      mbar_wait_b(B(B_FULL3 + 4 + w), 0);
#pragma unroll
      for (int i = 0; i < 16; i++) {
        const int k = (i & 1) * 16 + (lane & 7) + (lane >> 4) * 8;
        asm volatile("ldmatrix.sync.aligned.m8n8.x4.trans.shared.b16 {%0,%1,%2,%3}, [%4];"
                     : "=r"(wd[i][0]), "=r"(wd[i][1]), "=r"(wd[i][2]), "=r"(wd[i][3])
                     : "r"(sb + r3(4) + w * SLOT + (2 * (cw & 3) + (i >> 3)) * 4096 + k * 128 + (((2 * ((i >> 1) & 3) + ((lane >> 3) & 1)) ^ (lane & 7)) << 4)) : "memory");
      }
    }
    const int fc = 16 * (rid >> 1) + 4 * (rid & 1) + (lane & 3) + 8 * (lane >> 4), ft = (lane >> 3) & 1;
    const char* pc = reinterpret_cast<const char*>(g_xr + ((ct & 127) >> 4) * XR_SIZE + XR_CAND + 32 + (ct & 15));
    const char* pf = reinterpret_cast<const char*>(g_xr + (fc >> 7) * XR_SIZE + XR_CAND) + (fc & 127) * 2;
    const uint32_t xs = sb + OFF_SCR + w * 2112 + ((ct & 127) >> 2) * 64 + (((ct >> 3) & 3) << 4) + (ct & 3) * 4;
    const uint32_t xb = sb + OFF_SCR + (r0 & 1) * 2112 + w * 128 + (((lane ^ w) & 3) << 4);
    settle(pc, zero); settle(pf, zero); settle(cdst, zero); settle(xs, zero); settle(xb, zero);
    mbar_wait_b(B(B_OUT2), 0);
    const uint4 top = lds128(sb + OFF_MISC);
    TL(2, 14, warp == 4);
    uint32_t fh, fn;
    {
      pc += w ? top.y : top.x;
      pf += ft ? top.y : top.x;
      uint4 v;
#pragma unroll 1
      for (int n = 0; n < 0x400000; n++) {
        asm volatile("ld.relaxed.gpu.global.v4.u32 {%0,%1,%2,%3}, [%4];" : "=r"(v.x), "=r"(v.y), "=r"(v.z), "=r"(v.w) : "l"(pc) : "memory");
        asm volatile("ld.relaxed.gpu.global.u16 %0, [%1];" : "=r"(fh) : "l"(pf) : "memory");
        asm volatile("ld.relaxed.gpu.global.u16 %0, [%1 + 512];" : "=r"(fn) : "l"(pf) : "memory");
        asm volatile("st.shared.u32 [%0], %1;" ::"r"(xs), "r"(v.x) : "memory");
        asm volatile("st.shared.u32 [%0], %1;" ::"r"(xs ^ 16), "r"(v.y) : "memory");
        asm volatile("st.shared.u32 [%0], %1;" ::"r"(xs ^ 32), "r"(v.z) : "memory");
        asm volatile("st.shared.u32 [%0], %1;" ::"r"(xs ^ 48), "r"(v.w) : "memory");
        if (__all_sync(~0u, max(max(v.x, v.y), max(v.z, v.w)) != 0xFFFFFFFFu && max(fh, fn) != 0xFFFFu)) break;
      }
    }
    bar_sync(3, 256);
    asm volatile("{\n.reg .pred p;\nsetp.lt.u32 p, %5, %6;\n@p st.global.v4.u32 [%0], {%1,%2,%3,%4};\n}" ::"l"(cdst), "r"(cout.x), "r"(cout.y), "r"(cout.z),
                 "r"(cout.w), "r"(ckey), "r"(top.w) : "memory");
    if (ffn) {
      TL(2, 15, warp == 4);
      float d[4][4] = {};
      auto xl = [&](int i) { return lds128((xb ^ ((i & 2) << 4)) + (i >> 1) * 256 + (i & 1) * 64); };
      uint4 b0 = xl(0), b1 = xl(1);
#pragma unroll
      for (int i = 0; i < 16; i += 2) {
        const uint4 c0 = b0, c1 = b1;
        if (i < 14) { b0 = xl(i + 2); b1 = xl(i + 3); }
        mma16816(d[0], wf[8 * i], wf[8 * i + 1], wf[8 * i + 2], wf[8 * i + 3], c0.x, c0.y);
        mma16816(d[1], wf[8 * i + 4], wf[8 * i + 5], wf[8 * i + 6], wf[8 * i + 7], c0.z, c0.w);
        mma16816(d[2], wf[8 * i + 8], wf[8 * i + 9], wf[8 * i + 10], wf[8 * i + 11], c1.x, c1.y);
        mma16816(d[3], wf[8 * i + 12], wf[8 * i + 13], wf[8 * i + 14], wf[8 * i + 15], c1.z, c1.w);
      }
      const float e0 = (d[0][0] + d[1][0]) + (d[2][0] + d[3][0]), e1 = (d[0][1] + d[1][1]) + (d[2][1] + d[3][1]);
      const float e2 = (d[0][2] + d[1][2]) + (d[2][2] + d[3][2]), e3 = (d[0][3] + d[1][3]) + (d[2][3] + d[3][3]);
      asm volatile("st.shared.v2.f32 [%0], {%1,%2};" ::"r"(sb + OFF_SCR + 8192 + ((w * 2 + (lane & 1)) * 32 + (cw & 3) * 8 + r0) * 8),
                   "f"((lane & 1) ? e1 : e0), "f"((lane & 1) ? e3 : e2) : "memory");
      bar_sync(3, 256);
      TL(2, 16, warp == 4);
      const uint32_t ra = sb + OFF_SCR + 8192 + (r0 & 1) * 256 + (r0 >> 1) * 64 + (lane & 3) * 16;
      const uint4 p0 = lds128(ra), p1 = lds128(ra + 512);
      auto act = [](uint32_t u0, uint32_t u1, uint32_t g0, uint32_t g1) {
        const uint32_t ug = pack_bf16(__uint_as_float(u0) + __uint_as_float(u1), __uint_as_float(g0) + __uint_as_float(g1));
        const float g = bf_hi(ug);
        return bf_round(__fdividef(g, 1.f + __expf(-g))) * bf_lo(ug);
      };
      const uint32_t av = pack_bf16(act(p0.x, p1.x, p0.y, p1.y), act(p0.z, p1.z, p0.w, p1.w));
      uint32_t b[4];
#pragma unroll
      for (int i = 0; i < 4; i++) b[i] = __shfl_sync(~0u, av, 8 * i + (lane & 7));
      TL(2, 17, warp == 4);
      float y[2][4] = {{0.f, 0.f, 0.f, 0.f}, {0.f, 0.f, 0.f, 0.f}};
#pragma unroll
      for (int c = 0; c < 4; c++) {
        const bool on = (lane >> 3) == c;
        const uint32_t b0 = on ? b[0] : 0, b1 = on ? b[1] : 0, b2 = on ? b[2] : 0, b3 = on ? b[3] : 0;
#pragma unroll
        for (int a = 0; a < 2; a++) {
          const int i = 8 * a + 2 * c;
          mma16816(y[a], wd[i][0], wd[i][1], wd[i][2], wd[i][3], b0, b1);
          mma16816(y[a], wd[i + 1][0], wd[i + 1][1], wd[i + 1][2], wd[i + 1][3], b2, b3);
        }
      }
      float4* yd = reinterpret_cast<float4*>(g_xr + (cw * 16 + (lane & 3) * 2 + (lane >> 4)) * XR_SIZE + XR_Y + fid * 4 + (r0 & 3));
      __stcg(yd, make_float4(y[0][0], y[0][1], y[0][2], y[0][3]));
      __stcg(yd + 8 * XR_SIZE, make_float4(y[1][0], y[1][1], y[1][2], y[1][3]));
    }
    TL(2, 18, warp == 4);
    if (cw == 0) {
      const uint32_t fk = ft ? top.w : top.z;
      uint32_t u = fk >> 16;
      u = (u & 0x8000u) ? (u & 0x7FFFu) : (~u & 0xFFFFu);
      float rs = bf_round(__fdividef(1.f, 1.f + __expf(-__uint_as_float(u << 16))));
      uint16_t* op = reinterpret_cast<uint16_t*>(out) + (size_t)(~fk & 0x7FFF) * DM + fc;
      settle(op, zero); settle(__float_as_uint(rs), zero);
      spin_clk(ffn ? Y_DLY : Y_DLY + Y_DLY0);
      float v[4];
#pragma unroll 1
      for (int n = 0; n < 0x400000; n++) {
        float4 z[14];
#pragma unroll
        for (int i = 0; i < 14; i++)
          asm volatile("ld.relaxed.gpu.global.v4.f32 {%0,%1,%2,%3}, [%4];" : "=f"(z[i].x), "=f"(z[i].y), "=f"(z[i].z), "=f"(z[i].w) : "l"(xr + XR_Y + lane + 32 * i) : "memory");
        float a[4] = {z[0].x, z[0].y, z[0].z, z[0].w}, b[4] = {z[1].x, z[1].y, z[1].z, z[1].w};
#pragma unroll
        for (int i = 2; i < 14; i += 2) {
          a[0] += z[i].x; a[1] += z[i].y; a[2] += z[i].z; a[3] += z[i].w;
          b[0] += z[i + 1].x; b[1] += z[i + 1].y; b[2] += z[i + 1].z; b[3] += z[i + 1].w;
        }
#pragma unroll
        for (int i = 0; i < 4; i++) v[i] = a[i] + b[i];
        const float t = (v[0] + v[1]) + (v[2] + v[3]);
        if (__all_sync(~0u, t == t)) break;
        uint32_t m = 0;
#pragma unroll
        for (int i = 0; i < 14; i++) m = max(max(m, max(__float_as_uint(z[i].x), __float_as_uint(z[i].y))), max(__float_as_uint(z[i].z), __float_as_uint(z[i].w)));
        if (__all_sync(~0u, m != 0xFFFFFFFFu)) break;
      }
      TL(2, 30, true);
      const bool hi = lane & 16, odd = lane & 8;
      const float a0 = (hi ? v[2] : v[0]) + __shfl_xor_sync(~0u, hi ? v[0] : v[2], 16), a1 = (hi ? v[3] : v[1]) + __shfl_xor_sync(~0u, hi ? v[1] : v[3], 16);
      float yv = (odd ? a1 : a0) + __shfl_xor_sync(~0u, odd ? a0 : a1, 8);
      yv += __shfl_xor_sync(~0u, yv, 4);
      const uint32_t o = hadd2_bf(fh, hadd2_bf(fn, pack_bf16(bf_round(yv) * rs, 0.f)));
      if (!(lane & 4)) *op = (uint16_t)o;
      TL(2, 21, true);
    }
    TL(2, 20, warp == 4);
    }
    __syncwarp();
    cluster_wait();
  }
}

typedef CUresult (*EncodeFn)(CUtensorMap*, CUtensorMapDataType, cuuint32_t, void*, const cuuint64_t*, const cuuint64_t*, const cuuint32_t*,
                             const cuuint32_t*, CUtensorMapInterleave, CUtensorMapSwizzle, CUtensorMapL2promotion, CUtensorMapFloatOOBfill);
EncodeFn g_enc = nullptr;

void map2(CUtensorMap* m, const void* ptr, uint64_t rows, uint64_t cols, uint32_t bc, uint32_t br) {
  const CUtensorMapSwizzle sw = bc == 64 ? CU_TENSOR_MAP_SWIZZLE_128B : CU_TENSOR_MAP_SWIZZLE_64B;
  cuuint64_t gd[2] = {cols, rows}, gs[1] = {cols * 2};
  cuuint32_t bd[2] = {bc, br}, es[2] = {1, 1};
  g_enc(m, CU_TENSOR_MAP_DATA_TYPE_BFLOAT16, 2, (void*)ptr, gd, gs, bd, es, CU_TENSOR_MAP_INTERLEAVE_NONE, sw,
        CU_TENSOR_MAP_L2_PROMOTION_L2_128B, CU_TENSOR_MAP_FLOAT_OOB_FILL_NONE);
}
void map3(CUtensorMap* m, const void* ptr, uint64_t rows, uint64_t cols, uint32_t br, uint32_t bch) {
  cuuint64_t gd[3] = {64, rows, cols / 64}, gs[2] = {cols * 2, 128};
  cuuint32_t bd[3] = {64, br, bch}, es[3] = {1, 1, 1};
  g_enc(m, CU_TENSOR_MAP_DATA_TYPE_BFLOAT16, 3, (void*)ptr, gd, gs, bd, es, CU_TENSOR_MAP_INTERLEAVE_NONE, CU_TENSOR_MAP_SWIZZLE_128B,
        CU_TENSOR_MAP_L2_PROMOTION_L2_128B, CU_TENSOR_MAP_FLOAT_OOB_FILL_NONE);
}

}

extern "C" void kernel_launch(void* const* d_in, const int* in_sizes, int n_in, void* d_out, int out_size) {
  const __nv_bfloat16* x = (const __nv_bfloat16*)d_in[0];
  const __nv_bfloat16* ckv = (const __nv_bfloat16*)d_in[1];
  const __nv_bfloat16* wq = (const __nv_bfloat16*)d_in[2];
  const __nv_bfloat16* wk = (const __nv_bfloat16*)d_in[3];
  const __nv_bfloat16* wv = (const __nv_bfloat16*)d_in[4];
  const __nv_bfloat16* wo = (const __nv_bfloat16*)d_in[5];
  const __nv_bfloat16* w_r = (const __nv_bfloat16*)d_in[7];
  const __nv_bfloat16* wgate = (const __nv_bfloat16*)d_in[8];
  const __nv_bfloat16* wup = (const __nv_bfloat16*)d_in[9];
  const __nv_bfloat16* wdown = (const __nv_bfloat16*)d_in[10];
  __nv_bfloat16* out = (__nv_bfloat16*)d_out;

  if (!g_enc) {
    void* fn = nullptr;
    cudaDriverEntryPointQueryResult qr;
    cudaGetDriverEntryPoint("cuTensorMapEncodeTiled", &fn, cudaEnableDefault, &qr);
    g_enc = (EncodeFn)fn;
    cudaFuncSetAttribute(fused_kernel, cudaFuncAttributeMaxDynamicSharedMemorySize, SMEM_BYTES);
  }
  void *xn, *kv, *ctx, *xr, *cnt;
  cudaGetSymbolAddress(&xr, g_xr);
  cudaGetSymbolAddress(&cnt, g_cnt);
  cudaGetSymbolAddress(&xn, g_xn);
  cudaGetSymbolAddress(&kv, g_kv);
  cudaGetSymbolAddress(&ctx, g_ctx);

  Params p;
  map2(&p.xn, xn, SEQ, DM, 64, 64);
  map2(&p.ckv, ckv, SEQ, DC, 64, 128);
  map3(&p.wq, wq, DM, NQ, 64, 2);
  map3(&p.wk, wk, DC, NQ, 64, 2);
  map3(&p.wv, wv, DC, NQ, 64, 2);
  map3(&p.wo, wo, NQ, DM, 64, 1);
  map3(&p.x, x, SEQ, DM, 64, 2);
  map3(&p.wd, wdown, FF, DM, 32, 8);
  map2(&p.wg, wgate, DM, FF, 32, 64);
  map2(&p.wu, wup, DM, FF, 32, 64);
  fused_kernel<<<128, 384, SMEM_BYTES, cudaStreamPerThread>>>(0u, x, (__nv_bfloat16*)kv, (__nv_bfloat16*)ctx, (uint4*)xr, out, (__nv_bfloat16*)xn,
                                                               (unsigned*)cnt, w_r, wdown, wq, p);
}
```

```cpp
#include <cuda_runtime.h>
#include <cuda_bf16.h>
#include <cuda.h>
#include <stdint.h>
#include <utility>

#pragma nv_diag_suppress 549
#pragma nv_diag_suppress 177
namespace {

constexpr int SEQ = 2048, DM = 1024, NH = 32, HD = 128, DC = 512, NQ = NH * HD, FF = 3584;

__device__ __align__(1024) __nv_bfloat16 g_xn[SEQ * DM];
constexpr int KV_TILE = 128 * 128;
__device__ __align__(1024) __nv_bfloat16 g_kv[2 * SEQ * NQ];
__device__ __align__(1024) __nv_bfloat16 g_ctx[SEQ * NQ];
constexpr int XR_PS = 0;
constexpr int XR_KEY = 128;
constexpr int XR_CAND = 136;
constexpr int XR_Y = 648;
constexpr int XR_SIZE = 1104;
__device__ __align__(1024) uint4 g_xr[128 * XR_SIZE];
constexpr int C_LN = 0, C_KV = 16, C_CTX = 32, C_NUM = 64;
__device__ unsigned g_cnt[C_NUM];

#define TL(k, i, cond) do {} while (0)
#define TC(w, g, i) do {} while (0)
#define TL_EXTRA 0
#define TK(i) do {} while (0)

__device__ __forceinline__ uint32_t s2u(const void* p) { return (uint32_t)__cvta_generic_to_shared(p); }
__device__ __forceinline__ void mbar_arrive(uint32_t b) { asm volatile("mbarrier.arrive.shared::cta.b64 _, [%0];" ::"r"(b) : "memory"); }
__device__ __forceinline__ void mbar_arrive_both(uint32_t b, uint32_t lane, bool cond) {
  asm volatile("{\n.reg .pred p;\n.reg .b32 r;\nsetp.lt.u32 p, %1, %2;\nmapa.shared::cluster.u32 r, %0, %1;\n@p mbarrier.arrive.shared::cluster.b64 _, [r];\n}"
               ::"r"(b), "r"(lane), "r"(cond ? 2 : 0) : "memory");
}
__device__ __forceinline__ bool mbar_test(uint32_t b, uint32_t ph) {
  uint32_t ok;
  asm volatile("{\n.reg .pred p;\nmbarrier.test_wait.parity.shared::cta.b64 p, [%1], %2;\nselp.u32 %0, 1, 0, p;\n}" : "=r"(ok) : "r"(b), "r"(ph) : "memory");
  return __all_sync(~0u, ok);
}
__device__ __forceinline__ void mbar_wait(uint32_t b, uint32_t ph) {
  asm volatile(
      "{\n.reg .pred p;\n.reg .u32 n;\nmov.u32 n, 0;\n"
      "LW:\nmbarrier.try_wait.parity.shared::cta.b64 p, [%0], %1, 20000;\n@p bra LD;\n"
      "add.u32 n, n, 1;\nsetp.lt.u32 p, n, 0x40000;\n@p bra LW;\ntrap;\nLD:\n}" ::"r"(b), "r"(ph) : "memory");
}
__device__ __forceinline__ void mbar_wait_u(uint32_t b, uint32_t ph) {
  asm volatile(
      "{\n.reg .pred p;\n.reg .u32 n;\nmov.u32 n, 0;\n"
      "LW:\nmbarrier.try_wait.parity.shared::cta.b64 p, [%0], %1, 20000;\n@p bra.uni LD;\n"
      "add.u32 n, n, 1;\nsetp.lt.u32 p, n, 0x40000;\n@p bra.uni LW;\ntrap;\nLD:\n}" ::"r"(b), "r"(ph) : "memory");
}
__device__ __forceinline__ void mbar_wait_c(uint32_t b, uint32_t ph) {
  asm volatile("{\n.reg .pred p;\nLW:\nmbarrier.try_wait.parity.shared::cta.b64 p, [%0], %1;\n@!p bra.uni LW;\n}" ::"r"(b), "r"(ph) : "memory");
}
__device__ __forceinline__ void mbar_wait_b(uint32_t b, uint32_t ph) {
  asm volatile(
      "{\n.reg .pred p;\n.reg .u32 n;\nmov.u32 n, 0;\n"
      "LW:\nmbarrier.try_wait.parity.shared::cta.b64 p, [%0], %1;\n@p bra.uni LD;\n"
      "add.u32 n, n, 1;\nsetp.lt.u32 p, n, 0x1000000;\n@p bra.uni LW;\ntrap;\nLD:\n}" ::"r"(b), "r"(ph) : "memory");
}
template <bool SLEEP = false>
__device__ __forceinline__ void spin_until_ge(const unsigned* p, unsigned target) {
  asm volatile(
      "{\n.reg .pred p, q;\n.reg .u32 n, v;\nmov.u32 n, 0;\nsetp.ne.u32 q, %2, 0;\n"
      "LW:\nld.acquire.gpu.global.u32 v, [%0];\nsetp.ge.u32 p, v, %1;\n@p bra LD;\n@q nanosleep.u32 200;\n"
      "add.u32 n, n, 1;\nsetp.lt.u32 p, n, 0x400000;\n@p bra LW;\ntrap;\nLD:\n}" ::"l"(p), "r"(target), "n"((int)SLEEP) : "memory");
}
__device__ __forceinline__ void spin_clk(uint32_t n) {
  asm volatile("{\n.reg .pred p;\n.reg .u32 a, b;\nmov.u32 a, %%clock;\nLW:\nmov.u32 b, %%clock;\nsub.u32 b, b, a;\nsetp.lt.u32 p, b, %0;\n@p bra.uni LW;\n}" ::"r"(n) : "memory");
}
__device__ __forceinline__ int fresh_lane() {
  int r;
  asm volatile("mov.u32 %0, %%laneid;" : "=r"(r));
  return r;
}
__device__ __forceinline__ void settle(const void* a, uint32_t zero) {
  asm volatile("{\n.reg .pred p;\nsetp.ne.u32 p, %1, 0;\n@p st.global.u32 [%0], %1;\n}" ::"l"(a), "r"(zero) : "memory");
}
__device__ __forceinline__ void settle(uint32_t a, uint32_t zero) {
  asm volatile("{\n.reg .pred p;\nsetp.ne.u32 p, %1, 0;\n@p st.shared.u32 [%0], %1;\n}" ::"r"(a), "r"(zero) : "memory");
}
__device__ __forceinline__ void fence_async_all() { asm volatile("fence.proxy.async;" ::: "memory"); }
__device__ __forceinline__ void bar_sync(int id, int n) { asm volatile("bar.sync %0, %1;" ::"r"(id), "r"(n) : "memory"); }
__device__ __forceinline__ void bar_arrive(int id, int n) { asm volatile("bar.arrive %0, %1;" ::"r"(id), "r"(n) : "memory"); }
__device__ __forceinline__ void cluster_arrive() { asm volatile("barrier.cluster.arrive.relaxed.aligned;" ::: "memory"); }
__device__ __forceinline__ void cluster_wait() { asm volatile("barrier.cluster.wait.acquire.aligned;" ::: "memory"); }
__device__ __forceinline__ void fence_gpu() { asm volatile("fence.acq_rel.gpu;" ::: "memory"); }
__device__ __forceinline__ void red_add(unsigned* p, unsigned v) { asm volatile("red.relaxed.gpu.global.add.u32 [%0], %1;" ::"l"(p), "r"(v) : "memory"); }
#define ELECT "{\n.reg .pred E;\nelect.sync _|E, 0xFFFFFFFF;\n@E "
__device__ __forceinline__ void e_init(uint32_t b, uint32_t c) { asm volatile(ELECT "mbarrier.init.shared::cta.b64 [%0], %1;\n}" ::"r"(b), "r"(c) : "memory"); }
__device__ __forceinline__ void e_expect(uint32_t b, uint32_t bytes) { asm volatile(ELECT "mbarrier.arrive.expect_tx.shared::cta.b64 _, [%0], %1;\n}" ::"r"(b), "r"(bytes) : "memory"); }
__device__ __forceinline__ void e_arrive(uint32_t b) { asm volatile(ELECT "mbarrier.arrive.shared::cta.b64 _, [%0];\n}" ::"r"(b) : "memory"); }
__device__ __forceinline__ void prefetch_tm(const CUtensorMap* m) { asm volatile(ELECT "prefetch.tensormap [%0];\n}" ::"l"(m) : "memory"); }
__device__ __forceinline__ void tma_ld2(uint32_t dst, const CUtensorMap* m, uint32_t bar, int c0, int c1) {
  asm volatile(ELECT "cp.async.bulk.tensor.2d.shared::cta.global.mbarrier::complete_tx::bytes [%0], [%1, {%3,%4}], [%2];\n}" ::"r"(dst), "l"(m), "r"(bar), "r"(c0), "r"(c1) : "memory");
}
__device__ __forceinline__ void tma_ld3(uint32_t dst, const CUtensorMap* m, uint32_t bar, int c0, int c1, int c2) {
  asm volatile(ELECT "cp.async.bulk.tensor.3d.shared::cta.global.mbarrier::complete_tx::bytes [%0], [%1, {%3,%4,%5}], [%2];\n}" ::"r"(dst), "l"(m), "r"(bar), "r"(c0), "r"(c1), "r"(c2) : "memory");
}
__device__ __forceinline__ void tma_ld2_mc(uint32_t dst, const CUtensorMap* m, uint32_t bar, int c0, int c1, uint16_t mask) {
  asm volatile(ELECT "cp.async.bulk.tensor.2d.shared::cluster.global.mbarrier::complete_tx::bytes.multicast::cluster [%0], [%1, {%3,%4}], [%2], %5;\n}" ::"r"(dst), "l"(m), "r"(bar), "r"(c0), "r"(c1), "h"(mask) : "memory");
}
__device__ __forceinline__ void tma_ld3_mc(uint32_t dst, const CUtensorMap* m, uint32_t bar, int c0, int c1, int c2, uint16_t mask) {
  asm volatile(ELECT "cp.async.bulk.tensor.3d.shared::cluster.global.mbarrier::complete_tx::bytes.multicast::cluster [%0], [%1, {%3,%4,%5}], [%2], %6;\n}" ::"r"(dst), "l"(m), "r"(bar), "r"(c0), "r"(c1), "r"(c2), "h"(mask) : "memory");
}
__device__ __forceinline__ uint64_t policy_evict_first() {
  uint64_t p;
  asm("createpolicy.fractional.L2::evict_first.b64 %0, 1.0;" : "=l"(p));
  return p;
}
__device__ __forceinline__ void tma_ld2_ef(uint32_t dst, const CUtensorMap* m, uint32_t bar, int c0, int c1) {
  asm volatile(ELECT "cp.async.bulk.tensor.2d.shared::cta.global.mbarrier::complete_tx::bytes.L2::cache_hint [%0], [%1, {%3,%4}], [%2], %5;\n}" ::"r"(dst), "l"(m), "r"(bar), "r"(c0), "r"(c1), "l"(policy_evict_first()) : "memory");
}
__device__ __forceinline__ void tma_ld3_ef(uint32_t dst, const CUtensorMap* m, uint32_t bar, int c0, int c1, int c2) {
  asm volatile(ELECT "cp.async.bulk.tensor.3d.shared::cta.global.mbarrier::complete_tx::bytes.L2::cache_hint [%0], [%1, {%3,%4,%5}], [%2], %6;\n}" ::"r"(dst), "l"(m), "r"(bar), "r"(c0), "r"(c1), "r"(c2), "l"(policy_evict_first()) : "memory");
}
__device__ __forceinline__ void bulk_ld(uint32_t dst, const void* src, uint32_t bytes, uint32_t bar) {
  asm volatile(ELECT "cp.async.bulk.shared::cta.global.mbarrier::complete_tx::bytes [%0], [%1], %2, [%3];\n}" ::"r"(dst), "l"(src), "r"(bytes), "r"(bar) : "memory");
}
__device__ __forceinline__ void tma_pf2(const CUtensorMap* m, int c0, int c1) { asm volatile(ELECT "cp.async.bulk.prefetch.tensor.2d.L2.global [%0, {%1,%2}];\n}" ::"l"(m), "r"(c0), "r"(c1) : "memory"); }
__device__ __forceinline__ void tma_pf3(const CUtensorMap* m, int c0, int c1, int c2) { asm volatile(ELECT "cp.async.bulk.prefetch.tensor.3d.L2.global [%0, {%1,%2,%3}];\n}" ::"l"(m), "r"(c0), "r"(c1), "r"(c2) : "memory"); }
__device__ __forceinline__ void sched_fence() { asm volatile("pmevent 0;" ::: "memory"); }
__device__ __forceinline__ void l2_prefetch(const void* p, uint32_t bytes) { asm volatile(ELECT "cp.async.bulk.prefetch.L2.global [%0], %1;\n}" ::"l"(p), "r"(bytes) : "memory"); }

__device__ __forceinline__ void wg_fence() { asm volatile("wgmma.fence.sync.aligned;" ::: "memory"); }
__device__ __forceinline__ void wg_commit() { asm volatile("wgmma.commit_group.sync.aligned;" ::: "memory"); }
template <int N> __device__ __forceinline__ void wg_wait() { asm volatile("wgmma.wait_group.sync.aligned %0;" ::"n"(N) : "memory"); }
template <int N> __device__ __forceinline__ void reg_alloc() { asm volatile("setmaxnreg.inc.sync.aligned.u32 %0;" ::"n"(N)); }
template <int N> __device__ __forceinline__ void reg_dealloc() { asm volatile("setmaxnreg.dec.sync.aligned.u32 %0;" ::"n"(N)); }
template <int N> __device__ __forceinline__ void fence_regs(float (&d)[N]) {
#pragma unroll
  for (int i = 0; i < N; i++) asm volatile("" : "+f"(d[i])::"memory");
}
template <int I0, int I1, int N> __device__ __forceinline__ void fence_part(float (&d)[N]) {
#pragma unroll
  for (int i = I0; i < I1; i++) asm volatile("" : "+f"(d[i])::"memory");
}
template <int N> __device__ __forceinline__ void fence_regs(uint32_t (&d)[N]) {
#pragma unroll
  for (int i = 0; i < N; i++) asm volatile("" : "+r"(d[i])::"memory");
}

__device__ __forceinline__ uint32_t mk_desc(uint32_t addr, uint32_t lbo) { return ((addr & 0x3FFFF) >> 4) | ((lbo >> 4) << 16); }

#define R8(b) "+f"(d[b + 0]), "+f"(d[b + 1]), "+f"(d[b + 2]), "+f"(d[b + 3]), "+f"(d[b + 4]), "+f"(d[b + 5]), "+f"(d[b + 6]), "+f"(d[b + 7])
#define REGS64 "%0,%1,%2,%3,%4,%5,%6,%7,%8,%9,%10,%11,%12,%13,%14,%15,%16,%17,%18,%19,%20,%21,%22,%23,%24,%25,%26,%27,%28,%29,%30,%31," \
               "%32,%33,%34,%35,%36,%37,%38,%39,%40,%41,%42,%43,%44,%45,%46,%47,%48,%49,%50,%51,%52,%53,%54,%55,%56,%57,%58,%59,%60,%61,%62,%63"
#define REGS128 REGS64 ",%64,%65,%66,%67,%68,%69,%70,%71,%72,%73,%74,%75,%76,%77,%78,%79,%80,%81,%82,%83,%84,%85,%86,%87,%88,%89,%90,%91,%92,%93,%94,%95," \
               "%96,%97,%98,%99,%100,%101,%102,%103,%104,%105,%106,%107,%108,%109,%110,%111,%112,%113,%114,%115,%116,%117,%118,%119,%120,%121,%122,%123,%124,%125,%126,%127"

#define DESC(d, r, o) "add.u32 t, " r ", " o ";\nmov.b64 " d ", {t, h};\n"
#define MMA_PRE_(acc, hi) "{\n.reg .pred p;\n.reg .b32 t, h;\n.reg .b64 da, db;\nmov.b32 h, " hi ";\nsetp.ne.b32 p, " acc ", 0;\n"
#define MMA_PRE(acc) MMA_PRE_(acc, "0x40000040")
#define MMA_PRE64(acc) MMA_PRE_(acc, "0x80000020")
template <int TB, int OA, int OB>
__device__ __forceinline__ void mma_n256_ss(float (&d)[128], uint32_t a, uint32_t b, int acc) {
  asm volatile(MMA_PRE("%130") DESC("da", "%128", "%132") DESC("db", "%129", "%133")
               "wgmma.mma_async.sync.aligned.m64n256k16.f32.bf16.bf16 {" REGS128 "}, da, db, p, 1, 1, 0, %131;\n}\n"
               : R8(0), R8(8), R8(16), R8(24), R8(32), R8(40), R8(48), R8(56), R8(64), R8(72), R8(80), R8(88), R8(96), R8(104), R8(112), R8(120)
               : "r"(a), "r"(b), "r"(acc), "n"(TB), "n"(OA >> 4), "n"(OB >> 4));
}
template <int TB, int OA, int OB>
__device__ __forceinline__ void mma_n128_ss(float (&d)[64], uint32_t a, uint32_t b, int acc) {
  asm volatile(MMA_PRE("%66") DESC("da", "%64", "%68") DESC("db", "%65", "%69")
               "wgmma.mma_async.sync.aligned.m64n128k16.f32.bf16.bf16 {" REGS64 "}, da, db, p, 1, 1, 0, %67;\n}\n"
               : R8(0), R8(8), R8(16), R8(24), R8(32), R8(40), R8(48), R8(56)
               : "r"(a), "r"(b), "r"(acc), "n"(TB), "n"(OA >> 4), "n"(OB >> 4));
}
template <int TB, int OB>
__device__ __forceinline__ void mma_n128_rs(float (&d)[64], const uint32_t* a, uint32_t b, int acc) {
  asm volatile(MMA_PRE64("%69") DESC("db", "%68", "%71")
               "wgmma.mma_async.sync.aligned.m64n128k16.f32.bf16.bf16 {" REGS64 "}, {%64,%65,%66,%67}, db, p, 1, 1, %70;\n}\n"
               : R8(0), R8(8), R8(16), R8(24), R8(32), R8(40), R8(48), R8(56)
               : "r"(a[0]), "r"(a[1]), "r"(a[2]), "r"(a[3]), "r"(b), "r"(acc), "n"(TB), "n"(OB >> 4));
}
#define W8(b) "=f"(d[b + 0]), "=f"(d[b + 1]), "=f"(d[b + 2]), "=f"(d[b + 3]), "=f"(d[b + 4]), "=f"(d[b + 5]), "=f"(d[b + 6]), "=f"(d[b + 7])
#define MMA_N64 MMA_PRE64("%37") DESC("db", "%36", "%38") \
  "wgmma.mma_async.sync.aligned.m64n64k16.f32.bf16.bf16 {%0,%1,%2,%3,%4,%5,%6,%7,%8,%9,%10,%11,%12,%13,%14,%15,%16,%17,%18,%19,%20,%21," \
  "%22,%23,%24,%25,%26,%27,%28,%29,%30,%31}, {%32,%33,%34,%35}, db, p, 1, 1, 0;\n}\n"
template <int H, int OB, bool ACC>
__device__ __forceinline__ void mma_n64_rs(float (&d)[64], const uint32_t* a, uint32_t b) {
  if (ACC) asm volatile(MMA_N64 : R8(32 * H), R8(32 * H + 8), R8(32 * H + 16), R8(32 * H + 24) : "r"(a[0]), "r"(a[1]), "r"(a[2]), "r"(a[3]), "r"(b), "n"(1), "n"(OB >> 4));
  else asm volatile(MMA_N64 : W8(32 * H), W8(32 * H + 8), W8(32 * H + 16), W8(32 * H + 24) : "r"(a[0]), "r"(a[1]), "r"(a[2]), "r"(a[3]), "r"(b), "n"(0), "n"(OB >> 4));
}
template <int OB>
__device__ __forceinline__ void mma_n128_rs0(float (&d)[64], const uint32_t* a, uint32_t b) {
  asm volatile(MMA_PRE64("%69") DESC("db", "%68", "%70")
               "wgmma.mma_async.sync.aligned.m64n128k16.f32.bf16.bf16 {" REGS64 "}, {%64,%65,%66,%67}, db, p, 1, 1, 0;\n}\n"
               : W8(0), W8(8), W8(16), W8(24), W8(32), W8(40), W8(48), W8(56)
               : "r"(a[0]), "r"(a[1]), "r"(a[2]), "r"(a[3]), "r"(b), "n"(0), "n"(OB >> 4));
}
#define MMA_SSH MMA_PRE("%67") DESC("db", "%65", "%69") "add.u32 t, %64, %68;\nmov.b64 da, {t, %66};\n" \
  "wgmma.mma_async.sync.aligned.m64n128k16.f32.bf16.bf16 {" REGS64 "}, da, db, p, 1, 1, 0, 1;\n}\n"
template <int OA, int OB, bool ACC>
__device__ __forceinline__ void mma_n128_ssh(float (&d)[64], uint32_t a, uint32_t ahi, uint32_t b) {
  if (ACC) asm volatile(MMA_SSH : R8(0), R8(8), R8(16), R8(24), R8(32), R8(40), R8(48), R8(56) : "r"(a), "r"(b), "r"(ahi), "n"(1), "n"(OA >> 4), "n"(OB >> 4));
  else asm volatile(MMA_SSH : W8(0), W8(8), W8(16), W8(24), W8(32), W8(40), W8(48), W8(56) : "r"(a), "r"(b), "r"(ahi), "n"(0), "n"(OA >> 4), "n"(OB >> 4));
}
template <int TB, int OA, int OB>
__device__ __forceinline__ void mma_n128_ss0(float (&d)[64], uint32_t a, uint32_t b) {
  asm volatile(MMA_PRE("%66") DESC("da", "%64", "%68") DESC("db", "%65", "%69")
               "wgmma.mma_async.sync.aligned.m64n128k16.f32.bf16.bf16 {" REGS64 "}, da, db, p, 1, 1, 0, %67;\n}\n"
               : W8(0), W8(8), W8(16), W8(24), W8(32), W8(40), W8(48), W8(56)
               : "r"(a), "r"(b), "n"(0), "n"(TB), "n"(OA >> 4), "n"(OB >> 4));
}
template <int V> struct IC { static constexpr int value = V; __host__ __device__ constexpr operator int() const { return V; } };
template <int N, class F, int... I>
__device__ __forceinline__ void static_for_(F f, std::integer_sequence<int, I...>) { (f(IC<I>{}), ...); }
template <int N, class F>
__device__ __forceinline__ void static_for(F f) { static_for_<N>(f, std::make_integer_sequence<int, N>{}); }
__device__ __forceinline__ uint32_t pack_bf16(float lo, float hi) {
  uint32_t r;
  asm("cvt.rn.bf16x2.f32 %0, %1, %2;" : "=r"(r) : "f"(hi), "f"(lo));
  return r;
}
__device__ __forceinline__ float bf_lo(uint32_t v) { return __uint_as_float(v << 16); }
__device__ __forceinline__ float bf_hi(uint32_t v) { return __uint_as_float(v & 0xFFFF0000u); }
__device__ __forceinline__ float bf_round(float v) { return bf_lo(pack_bf16(v, v)); }
__device__ __forceinline__ void stsm4(uint32_t addr, uint32_t r0, uint32_t r1, uint32_t r2, uint32_t r3) {
  asm volatile("stmatrix.sync.aligned.m8n8.x4.shared.b16 [%0], {%1,%2,%3,%4};" ::"r"(addr), "r"(r0), "r"(r1), "r"(r2), "r"(r3) : "memory");
}
__device__ __forceinline__ uint4 lds128(uint32_t addr) {
  uint4 v;
  asm volatile("ld.shared.v4.u32 {%0,%1,%2,%3}, [%4];" : "=r"(v.x), "=r"(v.y), "=r"(v.z), "=r"(v.w) : "r"(addr));
  return v;
}
__device__ __forceinline__ float ex2(float x) {
  float y;
  asm("ex2.approx.ftz.f32 %0, %1;" : "=f"(y) : "f"(x));
  return y;
}
__device__ __forceinline__ void stage_store_128(uint32_t base, int lane, const uint32_t* pk) {
  const int row = (lane & 7) + ((lane >> 3) & 1) * 8;
  const uint32_t rb = base + row * 128;
  const int hi = lane >> 4;
#pragma unroll
  for (int j = 0; j < 8; j++) {
    const int chunk = 2 * j + hi;
    const uint32_t a = rb + (j >> 2) * 8192 + (((chunk & 7) ^ (lane & 7)) << 4);
    stsm4(a, pk[4 * j + 0], pk[4 * j + 1], pk[4 * j + 2], pk[4 * j + 3]);
  }
}
__device__ __forceinline__ void ln_round(float mean, float var, float& m_bf, float& inv_s) {
  const uint32_t mv = pack_bf16(mean, var);
  m_bf = bf_lo(mv);
  float sq, rc;
  asm("sqrt.approx.ftz.f32 %0, %1;" : "=f"(sq) : "f"(bf_round(bf_hi(mv) + 1e-5f)));
  asm("rcp.approx.ftz.f32 %0, %1;" : "=f"(rc) : "f"(bf_round(sq)));
  inv_s = rc;
}
__device__ __forceinline__ uint32_t hadd2_bf(uint32_t a, uint32_t b) {
  uint32_t r;
  asm("add.rn.bf16x2 %0, %1, %2;" : "=r"(r) : "r"(a), "r"(b));
  return r;
}
__device__ __forceinline__ uint32_t ln_apply(uint32_t h, uint32_t nm2, float inv_s) {
  const uint32_t d = hadd2_bf(h, nm2);
  return pack_bf16(bf_lo(d) * inv_s, bf_hi(d) * inv_s);
}
__device__ __forceinline__ void mma16816(float* d, uint32_t a0, uint32_t a1, uint32_t a2, uint32_t a3, uint32_t b0, uint32_t b1) {
  asm volatile("mma.sync.aligned.m16n8k16.row.col.f32.bf16.bf16.f32 {%0,%1,%2,%3}, {%4,%5,%6,%7}, {%8,%9}, {%0,%1,%2,%3};"
               : "+f"(d[0]), "+f"(d[1]), "+f"(d[2]), "+f"(d[3]) : "r"(a0), "r"(a1), "r"(a2), "r"(a3), "r"(b0), "r"(b1));
}

constexpr float AT_C = 0.08838834764831845f * 1.4426950408889634f;
#define L_MIN 3.5527137e-15f
#define L_MAX 1.8446744e19f
struct AtState {
  float S[64], O[64];
  uint32_t P[32], Q[32];
  float l[4];
};
template <int I0, int I1>
__device__ __forceinline__ void at_exp(AtState& s) {
#pragma unroll
  for (int i = I0; i < I1; i++) asm volatile("ex2.approx.ftz.f32 %0, %0;" : "+f"(s.S[i]));
#pragma unroll
  for (int i = I0; i < I1; i++) asm volatile("add.f32 %0, %0, %1;" : "+f"(s.l[i & 3]) : "f"(s.S[i]));
}
template <int I0, int I1>
__device__ __forceinline__ void at_pack(AtState& s) {
#pragma unroll
  for (int i = I0; i < I1; i++) asm volatile("cvt.rn.bf16x2.f32 %0, %1, %2;" : "=r"(s.P[i]) : "f"(s.S[2 * i + 1]), "f"(s.S[2 * i]));
}
template <int J0>
__device__ __forceinline__ void at_mask(AtState& s, int r, int lane) {
  const int d = r + (lane >> 2) - (lane & 3) * 2;
#pragma unroll
  for (int j = 0; j < 8; j++) {
    float dummy0 = 0.f, dummy1 = 0.f;
    float& lo0 = j < 7 ? s.S[4 * (J0 + (j < 7 ? j + 1 : j)) + 2] : dummy0;
    float& lo1 = j < 7 ? s.S[4 * (J0 + (j < 7 ? j + 1 : j)) + 3] : dummy1;
    asm("{\n.reg .pred p, q;\nsetp.lt.s32 p, %4, %5;\nsetp.le.s32 q, %4, %5;\n"
        "@p add.f32 %0, %0, 0fFF800000;\n@q add.f32 %1, %1, 0fFF800000;\n@p add.f32 %2, %2, 0fFF800000;\n@q add.f32 %3, %3, 0fFF800000;\n}"
        : "+f"(s.S[4 * (J0 + j)]), "+f"(s.S[4 * (J0 + j) + 1]), "+f"(lo0), "+f"(lo1) : "r"(d), "r"(8 * j));
  }
}
template <int D>
__device__ __forceinline__ uint32_t ld_pair(const __nv_bfloat16* p) {
  uint32_t r;
  asm volatile("{\n.reg .b16 a, b;\nld.global.cg.b16 a, [%1];\nld.global.cg.b16 b, [%1 + %2];\nmov.b32 %0, {a, b};\n}" : "=r"(r) : "l"(p), "n"(2 * D) : "memory");
  return r;
}
__device__ __forceinline__ uint32_t ld_word(const uint32_t* p) {
  uint32_t r;
  asm volatile("ld.global.cg.b32 %0, [%1];" : "=r"(r) : "l"(p) : "memory");
  return r;
}
__device__ __noinline__ void slow_rows(const __nv_bfloat16* wq, int head, int row0) {
  const int lane = fresh_lane(), r = lane >> 2, c = lane & 3;
  uint32_t q[32];
  float o[32];
#pragma unroll
  for (int i = 0; i < 32; i++) q[i] = 0;
  const uint32_t* xa = reinterpret_cast<const uint32_t*>(g_xn + (size_t)(row0 + r) * DM) + c;
#pragma unroll 1
  for (int h = 0; h < 2; h++) {
    const __nv_bfloat16* wb = wq + (size_t)2 * c * NQ + head * HD + 64 * h + 8 * (r >> 1) + (r & 1);
#pragma unroll
    for (int i = 0; i < 32; i++) o[i] = 0.f;
#pragma unroll 1
    for (int kk = 0; kk < DM / 16; kk++) {
      const uint32_t a0 = ld_word(xa + 8 * kk), a1 = ld_word(xa + 8 * kk + 4 * DM), a2 = ld_word(xa + 8 * kk + 4), a3 = ld_word(xa + 8 * kk + 4 * DM + 4);
#pragma unroll
      for (int n = 0; n < 8; n++) {
        const __nv_bfloat16* b = wb + (size_t)16 * kk * NQ + 32 * (n >> 2) + 2 * (n & 3);
        mma16816(o + 4 * n, a0, a1, a2, a3, ld_pair<NQ>(b), ld_pair<NQ>(b + 8 * NQ));
        if (n & 1) sched_fence();
      }
    }
#pragma unroll
    for (int i = 0; i < 16; i++) { q[i] = q[16 + i]; q[16 + i] = pack_bf16(o[2 * i] * AT_C, o[2 * i + 1] * AT_C); }
  }
#pragma unroll 1
  for (int h = 0; h < 2; h++) {
    float m0 = -INFINITY, m1 = -INFINITY, l0 = 0.f, l1 = 0.f;
#pragma unroll
    for (int i = 0; i < 32; i++) o[i] = 0.f;
#pragma unroll 1
    for (int k0 = 0; k0 <= row0; k0 += 16) {
      float e[8] = {0.f, 0.f, 0.f, 0.f, 0.f, 0.f, 0.f, 0.f};
      const __nv_bfloat16* kt = g_kv + (size_t)(head * 16 + (k0 >> 7)) * KV_TILE + (k0 & 127) * 32;
      const uint32_t* kp = reinterpret_cast<const uint32_t*>(kt + r * 32) + c;
#pragma unroll
      for (int kk = 0; kk < 8; kk++) {
        const uint32_t* k0p = kp + (kk >> 1) * 2048 + (((kk & 1) * 2) ^ (r >> 1)) * 4;
        const uint32_t* k1p = kp + (kk >> 1) * 2048 + (((kk & 1) * 2 + 1) ^ (r >> 1)) * 4;
        mma16816(e, q[4 * kk], q[4 * kk + 1], q[4 * kk + 2], q[4 * kk + 3], ld_word(k0p), ld_word(k1p));
        mma16816(e + 4, q[4 * kk], q[4 * kk + 1], q[4 * kk + 2], q[4 * kk + 3], ld_word(k0p + 128), ld_word(k1p + 128));
        if (kk & 1) sched_fence();
      }
      if (k0 == row0) {
#pragma unroll
        for (int i = 0; i < 8; i++) if ((i >> 2) * 8 + 2 * c + (i & 1) > r + (i & 2) * 4) e[i] = -INFINITY;
      }
      float a0 = fmaxf(fmaxf(e[0], e[1]), fmaxf(e[4], e[5])), a1 = fmaxf(fmaxf(e[2], e[3]), fmaxf(e[6], e[7]));
      a0 = fmaxf(a0, __shfl_xor_sync(~0u, a0, 1)); a1 = fmaxf(a1, __shfl_xor_sync(~0u, a1, 1));
      a0 = fmaxf(a0, __shfl_xor_sync(~0u, a0, 2)); a1 = fmaxf(a1, __shfl_xor_sync(~0u, a1, 2));
      a0 = fmaxf(a0, m0); a1 = fmaxf(a1, m1);
      const float sc0 = ex2(m0 - a0), sc1 = ex2(m1 - a1);
      m0 = a0; m1 = a1;
#pragma unroll
      for (int i = 0; i < 8; i++) e[i] = ex2(e[i] - ((i & 2) ? m1 : m0));
      l0 = l0 * sc0 + (e[0] + e[1]) + (e[4] + e[5]);
      l1 = l1 * sc1 + (e[2] + e[3]) + (e[6] + e[7]);
      const uint32_t p0 = pack_bf16(e[0], e[1]), p1 = pack_bf16(e[2], e[3]), p2 = pack_bf16(e[4], e[5]), p3 = pack_bf16(e[6], e[7]);
      const __nv_bfloat16* vp = kt + (size_t)512 * KV_TILE + h * 8192 + 2 * c * 32 + r;
#pragma unroll
      for (int n = 0; n < 8; n++) {
        o[4 * n] *= sc0; o[4 * n + 1] *= sc0; o[4 * n + 2] *= sc1; o[4 * n + 3] *= sc1;
        mma16816(o + 4 * n, p0, p1, p2, p3, ld_pair<32>(vp + (n >> 2) * 4096 + ((n ^ c) & 3) * 8), ld_pair<32>(vp + (n >> 2) * 4096 + ((n ^ c) & 3) * 8 + 256));
        if (n & 1) sched_fence();
      }
    }
    l0 += __shfl_xor_sync(~0u, l0, 1); l1 += __shfl_xor_sync(~0u, l1, 1);
    l0 += __shfl_xor_sync(~0u, l0, 2); l1 += __shfl_xor_sync(~0u, l1, 2);
#pragma unroll
    for (int i = 0; i < 4; i++) {
      const float* v = o + 16 * (i >> 1) + 2 * (i & 1);
      const float f = __fdividef(1.f, (i & 1) ? l1 : l0);
      *reinterpret_cast<uint4*>(g_ctx + (size_t)((row0 >> 7) * 32 + head) * KV_TILE + (2 * h + (i >> 1)) * 4096 + ((row0 & 127) + r + (i & 1) * 8) * 32 + (c ^ (r >> 1)) * 8) =
          make_uint4(pack_bf16(v[0] * f, v[1] * f), pack_bf16(v[4] * f, v[5] * f), pack_bf16(v[8] * f, v[9] * f), pack_bf16(v[12] * f, v[13] * f));
    }
  }
}

constexpr int UNIT = 16384, SLOT = 32768;
constexpr int OFF_SIDE = 2 * SLOT;
__host__ __device__ constexpr int kv_a(int kb) { return (kb < 6 ? kb : 3 * kb - 10) * UNIT; }
__host__ __device__ constexpr int kv_b(int s) { return ((0x76DCA9 >> (4 * s)) & 15) * UNIT; }
__host__ __device__ constexpr int q_aw(int s) { return (3 * s + (s & 1)) * UNIT; }
__host__ __device__ constexpr int q_b(int s) { return (3 * s + 2 - 2 * (s & 1)) * UNIT; }
__host__ __device__ constexpr int k_slot(int j, int r) { return (j < 2 ? 2 * j : (r == 2 ? 0 : 3 + r)) * SLOT; }
__host__ __device__ constexpr int v_slot(int j) { return (6 - (j & 1)) * SLOT; }
__host__ __device__ constexpr int r3(int st) { return ((0x654130 >> (4 * st)) & 7) * SLOT; }
constexpr int OFF_BAR = 229376;
constexpr int OFF_MISC = OFF_BAR + 512;
constexpr int SMEM_BYTES = OFF_MISC + 2080 + TL_EXTRA;
constexpr int OFF_RSTAT = OFF_MISC + 1056;
enum : int {
  B_FULL1 = 0, B_FULLQ = 6, B_FULLB = 10, B_KF = 11, B_VF = 14, B_FULL3 = 16, B_WF = 22, B_DEP = 24, B_OUT2 = 29, B_PF = 30, B_SET = 31,
  B_SET2 = 32, B_LNGO = 33, B_WR = 34,
  B_KE = 35, B_VE = 38, B_WE = 40, B_PUB = 42, B_OUT = 48,
  B_EMPTY1 = 49, B_EMPTYQ = 55, B_X = 59, B_EMPTY3 = 63,
  B_NUM = 69
};
#define TUNABLE(name, v) constexpr int name = v
TUNABLE(LN_GO, 3);
TUNABLE(EP1, 2);
TUNABLE(SIDE_NS, 400);
TUNABLE(SET_KB, 44); TUNABLE(SET_NS, 40);
TUNABLE(PF_KB, 54); TUNABLE(PF_N, 7); TUNABLE(PF_NS, 300);
TUNABLE(PS_DLY, 120); TUNABLE(Y_DLY, 700); TUNABLE(Y_DLY0, 1500);
constexpr int PRE = 6;
constexpr int WIN = 6;
constexpr int OFF_STG = r3(0), OFF_SCR = r3(1);
struct Params {
  CUtensorMap xn, ckv, wq, wk, wv, wo, x, wd, wg, wu;
};

__global__ void __cluster_dims__(2, 1, 1) __launch_bounds__(384, 1)
fused_kernel(uint32_t zero, const __nv_bfloat16* __restrict__ x, __nv_bfloat16* g_kv, __nv_bfloat16* g_ctx, uint4* g_xr,
             __nv_bfloat16* __restrict__ out, __nv_bfloat16* g_xn, unsigned* g_cnt, const __nv_bfloat16* __restrict__ w_r,
             const __nv_bfloat16* __restrict__ wdown, const __nv_bfloat16* __restrict__ wq, const __grid_constant__ Params p) {
  extern __shared__ __align__(1024) uint8_t sp[];
  const uint32_t sb = s2u(sp);
  const uint32_t bar = sb + OFF_BAR;
  auto B = [&](int i) { return bar + 8 * i; };
  const int tid = threadIdx.x, warp = __shfl_sync(~0u, tid >> 5, 0), wg = warp >> 2, lane = tid & 31;
  const int cta = blockIdx.x, rank = cta & 1, cl = cta >> 1;
  const int mp = cl < 4 ? 1 : (cl < 36 ? (cl & 7) : (0x3207654 >> (4 * ((cl - 36) % 7))) & 7);
  const int gq = cl < 4 ? 4 + cl : (cl < 36 ? (cl - 4) >> 3 : 4 + (cl - 36) / 7);
  const int mt = 2 * mp + rank;
  const int qa = 15 - gq;
  const int ta = gq ? gq : 15, tb = 15 - ta;
  const int rid = mt * 8 + gq;
  const int fid = mt * 7 + gq;
  const bool ffn = gq < 7;
  TL(0, 0, warp == 4);
  auto load_pre = [&](int i) {
    e_expect(B(B_FULL1 + i), (i & 1) ? UNIT : 2 * UNIT);
    if (!(i & 1)) tma_ld2(sb + kv_a(i >> 1), &p.ckv, B(B_FULL1 + i), i * 32, mt * 128);
    tma_ld3(sb + kv_b(i) + rank * 8192, &p.wk, B(B_FULL1 + i), 0, i * 32, (gq + 8) * 4 + rank * 2);
    tma_ld3(sb + kv_b(i) + 8192 - rank * 8192, &p.wk, B(B_FULL1 + i), 0, i * 32, (gq + 8) * 4 + 2 - rank * 2);
  };
  if (warp == 0) {
    e_init(B(B_FULL1), 1);
    asm volatile("fence.mbarrier_init.release.cluster;" ::: "memory");
    TL(0, 16, true);
    load_pre(0);
    TL(0, 17, true);
#pragma unroll
    for (int kb = 1; kb < PRE; kb++) e_init(B(B_FULL1 + kb), 1);
  } else {
#pragma unroll 1
    for (int i = PRE - 1 + warp; i < B_NUM; i += 11) e_init(B(i), i >= B_EMPTY1 ? 16 : (i >= B_KE ? 8 : (i == B_WR ? 2 : 1)));
  }
  asm volatile("fence.mbarrier_init.release.cluster;" ::: "memory");
  cluster_arrive();
  const int rid0 = rid, warp0 = warp;
  if (wg == 0) {
    reg_dealloc<40>();
    if (warp == 0) {
      TL(0, 12, true);
#pragma unroll 1
      for (int kb = 1; kb < PRE; kb++) load_pre(kb);
      if (mt >= PRE) { tma_pf3(&p.wk, 0, mt * 32, (gq + 8) * 4); tma_pf3(&p.wk, 0, mt * 32, (gq + 8) * 4 + 2); }
      if (gq >= PRE / 2) tma_pf2(&p.ckv, gq * 64, mt * 128);
      TL(0, 15, true);
    }
    TL(0, 18, warp == 0);
    __syncwarp();
    cluster_wait();
    uint4* const xr = g_xr + rid * XR_SIZE;
    auto side_piece = [&](int c, int piece) {
      const uint32_t fb = B(B_WF + (c & 1));
      if (piece == 0) e_expect(fb, UNIT);
      tma_ld2_ef(sb + OFF_SIDE + (c & 1) * UNIT + piece * 4096, (piece & 2) ? &p.wg : &p.wu, fb, fid * 32, c * 128 + (piece & 1) * 64);
    };
    if (warp == 0) {
      {
        int st = 0; uint32_t ph = 0;
#pragma unroll 1
        for (int i = PRE; i < 64; i++) {
          const int t = i >> 4, h = i & 15;
          const uint32_t fb = B(B_FULL1 + st);
          const bool with_a = (i & 0x31) == 0;
          mbar_wait_c(B(B_EMPTY1 + st), ph);
          e_expect(fb, with_a ? 2 * UNIT : UNIT);
          if (with_a) tma_ld2(sb + kv_a(h >> 1), &p.ckv, fb, h * 32, mt * 128);
          tma_ld3_mc(sb + kv_b(st) + rank * 8192, (t & 1) ? &p.wv : &p.wk, fb, 0, h * 32, (gq + ((t >> 1) ^ 1) * 8) * 4 + rank * 2, 3);
          if (i == 2 * LN_GO) e_arrive(B(B_LNGO));
          if (i == 24) { prefetch_tm(&p.wq); prefetch_tm(&p.xn); }
          if ((h >> 1) == (t ? 0 : 4) && t < 3) tma_pf3((t & 1) ? &p.wk : &p.wv, 0, mt * 32, (gq + (((t + 1) >> 1) ^ 1) * 8) * 4 + (h & 1) * 2);
          if ((i | 2) == 50) tma_pf3(&p.wq, 0, (gq + 4 * h) * 64, mt * 2);
          if (++st == 6) { st = 0; ph ^= 1; }
        }
        prefetch_tm(&p.wo); prefetch_tm(&p.wd); prefetch_tm(&p.x); prefetch_tm(&p.wg); prefetch_tm(&p.wu);
        mbar_wait_c(B(B_DEP + 0), 0);
        uint32_t kpar = 7, vpar = 3;
        auto load_aw = [&](int kb, int head) {
          const uint32_t d = sb + q_aw(kb & 3), fb = B(B_FULLQ + (kb & 3));
          tma_ld2_mc(d + rank * 8192, &p.xn, fb, kb * 64, ta * 128 + rank * 64, 3);
          tma_ld3(d + UNIT, &p.wq, fb, 0, kb * 64, head * 2);
        };
        auto load_b = [&](int kb, uint32_t fb) { tma_ld2_mc(sb + q_b(kb & 3) + rank * 8192, &p.xn, fb, kb * 64, tb * 128 + rank * 64, 3); };
        auto load3 = [&](int kb, int s) {
          const uint32_t d = sb + r3(s), fb = B(B_FULL3 + s);
          e_expect(fb, SLOT);
          bulk_ld(d, g_ctx + (size_t)(mt * 64 + kb) * 8192, UNIT, fb);
          tma_ld3_mc(d + UNIT + rank * 8192, &p.wo, fb, 0, kb * 64, gq * 2 + rank, 3);
        };
#pragma unroll 1
        for (int half = 0; half < 2; half++) {
          const int head = mt + 16 * half;
#pragma unroll 1
          for (int kb = 2 * half; kb < 16; kb++) {
            if (kb >= 4) mbar_wait_c(B(B_EMPTYQ + (kb & 3)), ((kb >> 2) & 1) ^ 1);
            else if (half) mbar_wait_c(B(B_X + 2), 0);
            else if (kb > 0) mbar_wait_c(B(B_EMPTY1 + (2 * kb + 3) % 6), kb == 1);
            e_expect(B(B_FULLQ + (kb & 3)), 3 * UNIT);
            load_aw(kb, head);
            load_b(kb, B(B_FULLQ + (kb & 3)));
          }
          mbar_wait_c(B(B_DEP + 1 + half), 0);
          const __nv_bfloat16* kt = g_kv + (size_t)head * 16 * KV_TILE;
          l2_prefetch(kt, SLOT);
          auto load_v = [&](int j) {
            const int r = j & 1;
            mbar_wait_c(B(B_VE + r), (vpar >> r) & 1);
            vpar ^= 1 << r;
            e_expect(B(B_VF + r), SLOT);
            bulk_ld(sb + v_slot(j), kt + (size_t)(512 + (j > qa ? 16 - j : j)) * KV_TILE, SLOT, B(B_VF + r));
          };
          int r = 0;
#pragma unroll 1
          for (int j = 0; j < 17; j++) {
            if (j < 2) mbar_wait_c(B(B_EMPTYQ + j), 1);
            if (j == 2) mbar_wait_c(B(B_KE), kpar & 1);
            mbar_wait_c(B(B_KE + r), (kpar >> r) & 1);
            kpar ^= 1 << r;
            e_expect(B(B_KF + r), SLOT);
            bulk_ld(sb + k_slot(j, r), kt + (j > qa ? 16 - j : j) * KV_TILE, SLOT, B(B_KF + r));
            if (++r == 3) r = 0;
            if (j == 2) mbar_wait_c(B(B_EMPTYQ + 3), 1);
            if (j != 1) load_v(j ? j - 1 : 0);
            if (half == 0) {
              if (j == 16) {
                tma_pf3(&p.wq, 0, (4 + gq) * 64, (mt + 16) * 2);
                tma_pf2(&p.xn, (4 + (mp & 3)) * 64, ((mp & 4) ? qa : gq) * 128 + rank * 64);
              }
            } else if (j >= 14) {
              tma_pf3(&p.wo, 0, (5 + mp + 8 * (16 - j)) * 64, gq * 2 + rank);
            } else if (ffn && j >= 5 && j < 13) {
              side_piece((j - 5) >> 2, (j - 5) & 3);
            }
          }
          mbar_wait_c(B(B_X + 0), half);
          if (half == 0) {
            for (int kb = 0; kb < 2; kb++) { e_expect(B(B_FULLQ + kb), 2 * UNIT); load_aw(kb, mt + 16); }
          } else {
            mbar_wait_c(B(B_DEP + 3), 0);
            load3(0, 0);
          }
          mbar_wait_c(B(B_X + 1), half);
          if (half) load3(1, 1);
          load_v(16);
          if (gq == 0) mbar_wait_c(B(B_X + 2), half);
          if (half == 0) { e_expect(B(B_FULLB), 2 * UNIT); load_b(0, B(B_FULLB)); load_b(1, B(B_FULLB)); }
        }
        st = 2; ph = 1;
#pragma unroll 1
        for (int kb = 2; kb < 64; kb++) {
          if (kb == 32) mbar_wait_c(B(B_DEP + 4), 0);
          if (kb >= 6) mbar_wait_c(B(B_EMPTY3 + st), ph);
          else if (kb == 3 || kb == 5) mbar_wait_c(B(B_X + (kb + 1) / 2), 1);
          load3(kb, st);
          if (++st == 6) { st = 0; ph ^= 1; }
          if (kb == PF_KB) e_arrive(B(B_PF));
          if (kb == SET_KB) e_arrive(B(B_SET));
          if (kb == 58) l2_prefetch(xr, XR_CAND * 16);
        }
        if (ffn) {
#pragma unroll 1
          for (int j = 0; j < 2; j++) {
            mbar_wait_c(B(B_EMPTY3 + 4 + j), 1);
            e_expect(B(B_FULL3 + 4 + j), SLOT);
            tma_ld3(sb + r3(4 + j), &p.wd, B(B_FULL3 + 4 + j), 0, fid * 32, 8 * j);
          }
        }
        const uint4* kp = g_xr + ((lane >> 1) * 8 + gq) * XR_SIZE + XR_KEY + (lane & 1) * 2;
        mbar_wait_c(B(B_OUT), 0);
        uint32_t k1, k2, m1;
#pragma unroll 1
        for (int n = 0; n < 0x400000; n++) {
          uint4 a, b;
          asm volatile("ld.relaxed.gpu.global.v4.u32 {%0,%1,%2,%3}, [%4];" : "=r"(a.x), "=r"(a.y), "=r"(a.z), "=r"(a.w) : "l"(kp) : "memory");
          asm volatile("ld.relaxed.gpu.global.v4.u32 {%0,%1,%2,%3}, [%4 + 16];" : "=r"(b.x), "=r"(b.y), "=r"(b.z), "=r"(b.w) : "l"(kp) : "memory");
          const uint32_t a1 = max(a.x, a.z), a2 = max(min(a.x, a.z), max(a.y, a.w));
          const uint32_t b1 = max(b.x, b.z), b2 = max(min(b.x, b.z), max(b.y, b.w));
          k1 = max(a1, b1); k2 = max(min(a1, b1), max(a2, b2));
          m1 = __reduce_max_sync(~0u, max(k1, k2));
          if (m1 != 0xFFFFFFFFu) break;
        }
        const uint32_t m2 = __reduce_max_sync(~0u, k1 == m1 ? k2 : k1);
        const uint32_t t0 = ~m1 & 0x7FFF, t1 = ~m2 & 0x7FFF;
        const uint32_t o0 = (t0 >> 7) * (8 * XR_SIZE * 16) + (t0 & 0x70) * 64, o1 = (t1 >> 7) * (8 * XR_SIZE * 16) + (t1 & 0x70) * 64 + ((t0 ^ t1) < 16 ? 256 : 0);
        asm volatile(ELECT "st.shared.v4.u32 [%0], {%1,%2,%3,%4};\n}" ::"r"(sb + OFF_MISC + 256), "r"(o0), "r"(o1), "r"(m1), "r"(m2) : "memory");
        e_arrive(B(B_OUT2));
        if (rid == 127) { g_cnt[lane] = 0; g_cnt[32 + lane] = 0; }
      }
    } else {
      if (warp >= 2) {
#pragma unroll 1
        for (int i = tid - 64; i < XR_CAND; i += 64) xr[i] = make_uint4(~0u, ~0u, ~0u, ~0u);
        if (warp == 2) { __syncwarp(); if (lane == 0) mbar_arrive(B(B_WR)); }
      }
      if (warp == 3) {
        float ws = 0.f;
#pragma unroll 1
        for (int j = 0; j < 4; j++) {
          const uint4 q = __ldg(reinterpret_cast<const uint4*>(w_r) + j * 32 + lane);
          ws += bf_lo(q.x) + bf_hi(q.x) + bf_lo(q.y) + bf_hi(q.y) + bf_lo(q.z) + bf_hi(q.z) + bf_lo(q.w) + bf_hi(q.w);
        }
#pragma unroll
        for (int o = 16; o; o >>= 1) ws += __shfl_xor_sync(~0u, ws, o);
        uint2* tab = reinterpret_cast<uint2*>(sp + OFF_MISC + 512);
        tab[lane] = make_uint2(0x3F803F80u, 0x3F803F80u);
        tab[32 + lane] = __ldg(reinterpret_cast<const uint2*>(w_r + gq * 128) + lane);
        if (lane == 0) *reinterpret_cast<float*>(sp + OFF_MISC + 1024) = ws;
        __syncwarp();
        if (lane == 0) mbar_arrive(B(B_WR));
      }
      __syncwarp();
      mbar_wait_u(B(B_LNGO), 0);
#pragma unroll 1
      for (int r = warp == 2 ? 0 : (warp + 1) >> 1; r < 16; r += 3) {
        const uint4* src = reinterpret_cast<const uint4*>(x + (size_t)(cta * 16 + r) * DM) + lane;
        uint4 v[4];
#pragma unroll
        for (int j = 0; j < 4; j++) v[j] = __ldcs(src + j * 32);
        float a0 = 0.f, a1 = 0.f, b0 = 0.f, b1 = 0.f;
#pragma unroll
        for (int j = 0; j < 4; j++) {
          const uint32_t u[4] = {v[j].x, v[j].y, v[j].z, v[j].w};
#pragma unroll
          for (int i = 0; i < 4; i++) { const float a = bf_lo(u[i]), b = bf_hi(u[i]); a0 += a; a1 += b; b0 = fmaf(a, a, b0); b1 = fmaf(b, b, b1); }
        }
        a0 += a1; b0 += b1;
#pragma unroll
        for (int o = 16; o; o >>= 1) { a0 += __shfl_xor_sync(~0u, a0, o); b0 += __shfl_xor_sync(~0u, b0, o); }
        const float mean = a0 * (1.f / DM);
        float mb, inv;
        ln_round(mean, fmaxf(fmaf(b0, 1.f / DM, -mean * mean), 0.f), mb, inv);
        const uint32_t nm2 = pack_bf16(-mb, -mb);
        uint4* dst = reinterpret_cast<uint4*>(g_xn + (size_t)(cta * 16 + r) * DM) + lane;
#pragma unroll
        for (int j = 0; j < 4; j++) {
          dst[j * 32] = make_uint4(ln_apply(v[j].x, nm2, inv), ln_apply(v[j].y, nm2, inv), ln_apply(v[j].z, nm2, inv), ln_apply(v[j].w, nm2, inv));
          sched_fence();
        }
      }
      __syncwarp();
      if (lane == 0) {
        fence_gpu();
        red_add(&g_cnt[C_LN + (cta >> 3)], 1);
        TL(0, 20 + warp, true);
        if (warp == 3) {
          spin_until_ge<true>(&g_cnt[C_LN + gq], 24);
#pragma unroll 1
          for (int i = 0; i < 5; i++) {
            const int c = i == 0 ? C_LN + qa : (i < 3 ? C_KV + (i - 1) * 8 + mp : C_CTX + (i - 3) * 16 + mt);
            spin_until_ge<true>(&g_cnt[c], i == 0 ? 24 : 16);
            fence_async_all();
            mbar_arrive(B(B_DEP + i));
          }
        } else if (warp == 1) {
          mbar_wait(B(B_WR), 0);
#pragma unroll 1
          for (int i = 0; i < 6; i++) {
            const int c = i < 2 ? C_KV + gq + (i ^ 1) * 8 : C_CTX + ((i - 2) >> 1) * 16 + ((i & 1) ? tb : ta);
            mbar_wait(B(B_PUB + i), 0);
            fence_gpu();
            red_add(&g_cnt[c], 1);
          }
        }
      }
      __syncwarp();
      if (warp == 2) {
#pragma unroll 1
        for (int c = 2; c < WIN + 4; c++) {
          mbar_wait_u(B(B_WE + (c & 1)), ((c >> 1) & 1) ^ 1);
          if (c == WIN || c == WIN + 1) {
            e_expect(B(B_WF + (c & 1)), UNIT);
            tma_ld3_ef(sb + OFF_SIDE + (c & 1) * UNIT, &p.x, B(B_WF + (c & 1)), 0, mt * 128 + (c & 1) * 64, gq * 2);
          } else if (ffn) {
#pragma unroll 1
            for (int i = 0; i < 4; i++) { side_piece(c < WIN ? c : c - 2, i); __nanosleep(SIDE_NS); }
          }
        }
      } else if (warp == 1) {
        mbar_wait_u(B(B_SET), 0);
#pragma unroll 1
        for (int i = XR_CAND + lane; i < XR_SIZE; i += 32) { xr[i] = make_uint4(~0u, ~0u, ~0u, ~0u); __nanosleep(SET_NS); }
        __syncwarp();
        if (lane == 0) { fence_gpu(); mbar_arrive(B(B_SET2)); }
      } else {
        mbar_wait_u(B(B_PF), 0);
#pragma unroll 1
        for (int i = 0; i < PF_N; i++) {
          asm volatile("prefetch.global.L2 [%0];" ::"l"((const char*)wdown + (size_t)cta * 57344 + (i * 32 + lane) * 128));
          __nanosleep(PF_NS);
        }
      }
      __syncwarp();
      mbar_wait_u(B(B_OUT), 0);
      {
        const int sub = lane >> 4;
        const uint32_t src = sb + OFF_STG + ((lane & 15) >> 3) * 8192 + sub * 128;
        __nv_bfloat16* dst = out + (size_t)(mt * 128 + sub) * DM + gq * 128 + (lane & 15) * 8;
        auto ld = [&](int r, uint2& rs, uint4& v) {
          asm volatile("ld.shared.v2.u32 {%0,%1}, [%2];" : "=r"(rs.x), "=r"(rs.y) : "r"(sb + OFF_RSTAT + ((r + sub) & 127) * 8));
          v = lds128(src + ((r >> 6) & 1) * 16384 + (r & 63) * 128 + (((lane ^ (r + sub)) & 7) << 4));
        };
        uint2 rs; uint4 v;
        ld(2 * warp - 2, rs, v);
#pragma unroll 1
        for (int r = 2 * warp - 2; r < 128; r += 6) {
          const uint2 cs = rs; const uint4 c = v;
          ld(r + 6, rs, v);
          const float inv = __uint_as_float(cs.y);
          asm volatile("{\n.reg .pred p;\nsetp.ge.s32 p, %5, 0;\n@p st.global.v4.u32 [%0], {%1,%2,%3,%4};\n}" ::"l"(dst + (size_t)r * DM),
                       "r"(hadd2_bf(c.x, ln_apply(c.x, cs.x, inv))), "r"(hadd2_bf(c.y, ln_apply(c.y, cs.x, inv))),
                       "r"(hadd2_bf(c.z, ln_apply(c.z, cs.x, inv))), "r"(hadd2_bf(c.w, ln_apply(c.w, cs.x, inv))), "r"(cs.y) : "memory");
        }
      }
      TL(2, 25, warp == 1);
    }
    __syncwarp();
    cluster_arrive();
    cluster_wait();
  } else {
    reg_alloc<232>();
    const int rid_c = rid0 + zero, warp_c = warp0 + zero;
    const int lane = fresh_lane(), rid = rid_c, mt = rid >> 3, gq = rid & 7, qa = 15 - gq, ta = gq ? gq : 15, tb = 15 - ta;
    const int warp = warp_c, cw = warp - 4, w = cw >> 2;
    cluster_wait();
    auto publish = [&](int i) { __syncwarp(); e_arrive(B(B_PUB + i)); };
    auto release2 = [&](uint32_t b, bool cond = true) { mbar_arrive_both(b, lane, cond); };
    AtState s;
    const uint32_t dA = mk_desc(sb + w * 8192, 16);
    const uint32_t dW = mk_desc(sb, 8192);
    auto mma_kb = [&](float (&d)[64], uint32_t a, uint32_t b, int accum) {
      static_for<4>([&](auto k) { mma_n128_ss<1, k * 32, k * 2048>(d, dA + (a >> 4), dW + (b >> 4), k == 0 ? accum : 1); });
    };
    auto mma_kc = [&](float (&d)[64], auto a, auto b, int accum) {
      static_for<4>([&](auto k) { mma_n128_ss<1, decltype(a)::value + k * 32, decltype(b)::value + k * 2048>(d, dA, dW, k == 0 ? accum : 1); });
    };
    auto issue_q = [&](int kb, auto accum) {
      const int st = kb & 3;
      if (accum) mbar_wait_c(B(B_FULLQ + st), (kb >> 2) & 1);
      wg_fence();
      mma_kb(s.S, q_aw(st), q_aw(st) + UNIT, accum);
      wg_commit();
      if (accum) {
        wg_wait<1>();
        release2(B(B_EMPTYQ + ((kb - 1) & 3)));
        wg_fence();
      }
      mma_kb(s.O, q_b(st), q_aw(st) + UNIT, accum);
      wg_commit();
    };
    {
      uint4 pk[16];
      __nv_bfloat16* pdst = g_kv;
      auto put = [&](int i) { __stcs(reinterpret_cast<uint4*>(pdst + (i & 1) * 256 + ((i >> 1) & 3) * 4096 + (i >> 3) * 16 * KV_TILE), pk[i]); };
      float acc1[128];
      TL(0, 1, warp == 4);
      int st = 0; uint32_t ph = 0;
      const uint32_t dH = mk_desc(sb, 4096);
      mbar_wait_c(B(B_FULL1), 0);
      auto issue = [&](int h, auto accum) {
        if (accum) mbar_wait_c(B(B_FULL1 + st), ph);
        wg_fence();
        static_for<2>([&](auto k) { mma_n256_ss<1, k * 32, k * 2048>(acc1, dA + (kv_a(h >> 1) >> 4) + (h & 1) * 4, dH + (kv_b(st) >> 4), k == 0 ? (int)accum : 1); });
        wg_commit();
      };
#pragma unroll 1
      for (int t = 0; t < 4; t++) {
        issue(0, IC<0>{});
        TL(0, 2 + 2 * t, warp == 4);
        if (t > 0) { put(0); put(1); }
        int prev = st;
        if (++st == 6) { st = 0; ph ^= 1; }
#pragma unroll 1
        for (int h = 1; h < 16; h++) {
          if (h == 14 && w == 1) bar_sync(5, 256);
          issue(h, IC<1>{});
          if (h == 15 && w == 0) bar_arrive(5, 256);
          if (t > 0) {
#pragma unroll
            for (int i = 2; i < 16; i++) if (h == (i < 4 ? 1 : i - 2)) put(i);
            if (h == 13 && t == 2) publish(0);
          }
          wg_wait<1>();
          if (!(h & 1)) TK(24 + t * 8 + (h >> 1) - 1);
          release2(B(B_EMPTY1 + prev));
          prev = st;
          if (++st == 6) { st = 0; ph ^= 1; }
        }
        pdst = g_kv + (size_t)(((t & 1) * 32 + (gq + ((t >> 1) ^ 1) * 8) * 2) * 16 + mt) * KV_TILE + (cw * 16 + (lane >> 2)) * 32 + ((lane ^ (lane >> 3)) & 3) * 8;
        mbar_wait_c(B(t < 3 ? B_FULL1 + st : B_FULLQ), t < 3 ? ph : 0);
        wg_wait<0>();
        TK(24 + t * 8 + 7);
        fence_regs(acc1);
        release2(B(B_EMPTY1 + prev));
        TL(0, 3 + 2 * t, warp == 4);
#pragma unroll
        for (int a = 0; a < 8; a++)
#pragma unroll
          for (int h = 0; h < 2; h++)
            pk[2 * a + h] = make_uint4(pack_bf16(acc1[16 * a + 2 * h], acc1[16 * a + 2 * h + 1]), pack_bf16(acc1[16 * a + 4 + 2 * h], acc1[16 * a + 5 + 2 * h]),
                                       pack_bf16(acc1[16 * a + 8 + 2 * h], acc1[16 * a + 9 + 2 * h]), pack_bf16(acc1[16 * a + 12 + 2 * h], acc1[16 * a + 13 + 2 * h]));
      }
      issue_q(0, IC<0>{});
      TL(0, 10, warp == 4);
      put(0); put(1);
#pragma unroll 1
      for (int kb = 1; kb < 8; kb++) {
        issue_q(kb, IC<1>{});
        TK(66 + kb - 1);
#pragma unroll
        for (int i = 1; i < 8; i++) if (kb == i) { put(2 * i); put(2 * i + 1); }
      }
      publish(1);
      TL(0, 11, warp == 4);
    }
    __nv_bfloat16* cdst;
    uint32_t redo = 0;
    auto put_ctx = [&](int i, bool cond) {
      asm volatile("{\n.reg .pred p;\nsetp.ne.u32 p, %5, 0;\n@p st.global.cs.v4.u32 [%0], {%1,%2,%3,%4};\n}" ::"l"(cdst + (i & 1) * 256 + (i >> 1) * 4096),
                   "r"(s.P[4 * i]), "r"(s.P[4 * i + 1]), "r"(s.P[4 * i + 2]), "r"(s.P[4 * i + 3]), "r"((uint32_t)(cond && !(redo & 2))) : "memory");
    };
    {
      const int wrow = cw * 16;
      const uint32_t dK = mk_desc(sb, 16), dV = mk_desc(sb, 8192);
      uint32_t kph = 0, vph = 0;
      auto q_store = [&](const float (&d)[64]) {
        const int r0 = lane >> 2;
        const uint32_t a = sb + SLOT + (wrow + r0) * 128 + (((lane & 3) ^ (((r0 & 1) << 2) | (r0 >> 1))) << 4);
#pragma unroll
        for (int i = 0; i < 8; i++) {
          const float* o = d + 16 * (i >> 1) + 2 * (i & 1);
          asm volatile("st.shared.v4.u32 [%0], {%1,%2,%3,%4};" ::"r"((a ^ ((i & 2) << 5)) + (i >> 2) * UNIT + (i & 1) * 1024),
                       "r"(pack_bf16(o[0] * AT_C, o[1] * AT_C)), "r"(pack_bf16(o[4] * AT_C, o[5] * AT_C)),
                       "r"(pack_bf16(o[8] * AT_C, o[9] * AT_C)), "r"(pack_bf16(o[12] * AT_C, o[13] * AT_C)) : "memory");
        }
        __syncwarp();
      };
      auto q_load = [&](auto k0, auto k1) {
        const uint32_t a = sb + SLOT + (wrow + (lane & 15)) * 128 + (((lane >> 4) ^ (((lane & 1) << 2) | ((lane >> 1) & 3))) << 4);
#pragma unroll
        for (int k = k0; k < k1; k++)
          asm volatile("ldmatrix.sync.aligned.m8n8.x4.shared.b16 {%0,%1,%2,%3}, [%4];"
                       : "=r"(s.Q[4 * k]), "=r"(s.Q[4 * k + 1]), "=r"(s.Q[4 * k + 2]), "=r"(s.Q[4 * k + 3]) : "r"((a ^ ((k & 3) << 5)) + (k >> 2) * UNIT) : "memory");
      };
      auto q_load_if = [&](auto k, bool cond, float after) {
        const uint32_t a = sb + SLOT + (wrow + (lane & 15)) * 128 + (((lane >> 4) ^ (((lane & 1) << 2) | ((lane >> 1) & 3))) << 4);
        asm volatile("{\n.reg .pred p;\nsetp.ne.u32 p, %5, 0;\n@p ldmatrix.sync.aligned.m8n8.x4.shared.b16 {%0,%1,%2,%3}, [%4];\n}"
                     : "+r"(s.Q[4 * k]), "+r"(s.Q[4 * k + 1]), "+r"(s.Q[4 * k + 2]), "+r"(s.Q[4 * k + 3])
                     : "r"((a ^ ((k & 3) << 5)) + (k >> 2) * UNIT + (__float_as_uint(after) >> 31)), "r"((uint32_t)cond) : "memory");
      };
      auto issue_s = [&](uint32_t dk, auto mid) {
        mma_n128_rs0<0>(s.S, s.Q, dk);
        static_for<7>([&](auto i) {
          constexpr int k = i + 1;
          if (k == 4) mid();
          mma_n128_rs<0, (k >> 1) * 8192 + (k & 1) * 32>(s.S, s.Q + 4 * k, dk, 1);
        });
        wg_commit();
      };
      auto wait_v = [&](int jv) {
        mbar_wait_c(B(B_VF + (jv & 1)), (vph >> (jv & 1)) & 1);
        vph ^= 1 << (jv & 1);
      };
      auto issue_pva = [&](int jv, int accum) {
        wg_fence();
        static_for<4>([&](auto k) { mma_n128_rs<1, k * 1024>(s.O, s.P + 4 * k, dV + (v_slot(jv) >> 4), k == 0 ? accum : 1); });
        wg_commit();
      };
      auto issue_pvb = [&](int jv, bool upper) {
        if (upper) {
          wg_fence();
          static_for<4>([&](auto k) { mma_n128_rs<1, (k + 4) * 1024>(s.O, s.P + 16 + 4 * k, dV + (v_slot(jv) >> 4), 1); });
          wg_commit();
        } else {
          asm volatile("wgmma.fence.sync.aligned;\nwgmma.commit_group.sync.aligned;" ::: "memory");
        }
      };
      auto issue_pv = [&](int jv, int accum, bool upper) { wait_v(jv); issue_pva(jv, accum); issue_pvb(jv, upper); };
      if (w == 1) bar_arrive(1, 256);
#pragma unroll 1
      for (int half = 0; half < 2; half++) {
        const int head = mt + 16 * half;
        redo = 0;
        float inv[2];
        auto ep_prep = [&]() {
          float l0 = s.l[0] + s.l[1], l1 = s.l[2] + s.l[3];
          l0 += __shfl_xor_sync(~0u, l0, 1); l1 += __shfl_xor_sync(~0u, l1, 1);
          l0 += __shfl_xor_sync(~0u, l0, 2); l1 += __shfl_xor_sync(~0u, l1, 2);
          asm("rcp.approx.ftz.f32 %0, %1;" : "=f"(inv[0]) : "f"(l0));
          asm("rcp.approx.ftz.f32 %0, %1;" : "=f"(inv[1]) : "f"(l1));
          return __any_sync(~0u, !(fminf(l0, l1) >= L_MIN && l0 + l1 <= L_MAX));
        };
        auto ep_out = [&](auto i0, auto i1) {
          __nv_bfloat16* dst = g_ctx + (size_t)(ta * 32 + head) * KV_TILE + (wrow + (lane >> 2)) * 32 + ((lane ^ (lane >> 3)) & 3) * 8;
#pragma unroll
          for (int i = i0; i < i1; i++) {
            const float* o = s.O + 16 * (i >> 1) + 2 * (i & 1);
            const float c = inv[i & 1];
            asm volatile("st.global.cs.v4.u32 [%0], {%1,%2,%3,%4};" ::"l"(dst + (i & 1) * 256 + (i >> 1) * 4096), "r"(pack_bf16(o[0] * c, o[1] * c)),
                         "r"(pack_bf16(o[4] * c, o[5] * c)), "r"(pack_bf16(o[8] * c, o[9] * c)), "r"(pack_bf16(o[12] * c, o[13] * c)) : "memory");
          }
        };
        auto ep_rest = [&]() {
          ep_out(IC<EP1>{}, IC<8>{});
          if (!__any_sync(~0u, redo)) publish(2 + 2 * half);
          fence_regs(s.O);
        };
#pragma unroll 1
        for (int kb = 8; kb < 14; kb++) {
          issue_q(kb, IC<1>{});
          TK(66 + half * 24 + kb - 1);
        }
        TL(1, 20 * half + 0, warp == 4);
        mbar_wait_c(B(B_FULLQ + 2), 1);
        mbar_wait_c(B(B_FULLQ + 3), 1);
        bar_sync(1 + w, 256);
        wg_fence();
        mma_kc(s.S, IC<q_aw(2)>{}, IC<q_aw(2) + UNIT>{}, 1);
        wg_commit();
        wg_wait<1>();
        TK(66 + half * 24 + 13);
        release2(B(B_EMPTYQ + 1));
        wg_fence();
        mma_kc(s.S, IC<q_aw(3)>{}, IC<q_aw(3) + UNIT>{}, 1);
        wg_commit();
        bar_arrive(2 - w, 256);
        bar_sync(6 + w, 128);
        wg_wait<0>();
        TK(66 + half * 24 + 14);
        fence_regs(s.S);
        q_store(s.S);
        q_load(IC<0>{}, IC<8>{});
        TL(1, 20 * half + 1, warp == 4);
        TC(w, 17 * half, 0);
        mbar_wait_c(B(B_KF), kph & 1);
        kph ^= 1;
        bar_sync(1 + w, 256);
        TC(w, 17 * half, 2);
        fence_regs(s.O); fence_regs(s.Q);
        wg_fence();
        issue_s(dK, []() {});
        mma_kc(s.O, IC<q_b(2)>{}, IC<q_aw(2) + UNIT>{}, 1);
        mma_kc(s.O, IC<q_b(3)>{}, IC<q_aw(3) + UNIT>{}, 1);
        wg_commit();
        bar_arrive(2 - w, 256);
        wg_wait<1>();
        TC(w, 17 * half, 4);
        fence_regs(s.S);
        e_arrive(B(B_KE));
        s.l[0] = s.l[1] = s.l[2] = s.l[3] = 0.f;
        at_exp<0, 48>(s);
        at_pack<0, 22>(s);
        sched_fence();
        wg_wait<0>();
        fence_regs(s.O); fence_regs(s.Q);
        release2(B(B_EMPTYQ + 2)); release2(B(B_EMPTYQ + 3));
        at_exp<48, 64>(s);
        at_pack<22, 32>(s);
        q_store(s.O);
        TL(1, 20 * half + 2, warp == 4);
        int kr = 1;
        bool kok = false;
        inv[0] = inv[1] = 0.f;
        const int db = gq ? qa : 16;
#pragma unroll 1
        for (int j = 1; j < 17; j++) {
          const bool diag = j == ta || j == db;
          TC(w, j + 17 * half, 0);
          if (!kok) mbar_wait_c(B(B_KF + kr), (kph >> kr) & 1);
          kph ^= 1 << kr;
          if (j == ta + 2) ep_out(IC<0>{}, IC<EP1>{});
          bar_sync(1 + w, 256);
          TC(w, j + 17 * half, 2);
          fence_regs(s.O); fence_regs(s.P); fence_regs(s.Q);
          const uint32_t ke = B(B_KE + kr), dk = dK + (k_slot(j, kr) >> 4);
          if (++kr == 3) kr = 0;
          auto issue_rest = [&](auto trimmed) {
            TC(w, j + 17 * half, 1);
            if (j == ta + 1) {
              if (ep_prep()) redo = 1;
              s.l[0] = s.l[1] = s.l[2] = s.l[3] = 0.f;
            }
            if (!trimmed && j == ta + 2) ep_rest();
            TC(w, j + 17 * half, 3);
            if (trimmed) wait_v(j - 1);
            issue_pva(j - 1, j != 1 && j != ta + 2);
            issue_pvb(j - 1, w == 1 || (j != ta + 1 && j != db + 1));
            bar_arrive(2 - w, 256);
          };
          auto s_done = [&](auto n) {
            wg_wait<2>();
            TC(w, j + 17 * half, 4);
            fence_part<0, n>(s.S); fence_regs(s.Q);
            e_arrive(ke);
            release2(B(B_X + j - 14), j == 14 || j == 15);
          };
          auto pv_half = [&]() { sched_fence(); wg_wait<1>(); fence_regs(s.P); };
          auto pv_done = [&]() {
            sched_fence();
            wg_wait<0>();
            fence_regs(s.O); fence_regs(s.P);
            e_arrive(B(B_VE + ((j - 1) & 1)));
            release2(B(B_X + 2), j == 16);
            kok = mbar_test(B(B_KF + kr), (kph >> kr) & 1);
          };
          if (diag && w == 0) {
            wg_fence();
            static_for<8>([&](auto k) { mma_n64_rs<0, (k >> 1) * 8192 + (k & 1) * 32, k != 0>(s.S, s.Q + 4 * k, dk); });
            wg_commit();
            issue_rest(IC<1>{});
            s_done(IC<32>{});
            at_mask<0>(s, wrow, lane);
            pv_half();
            static_for<8>([&](auto k) {
              at_exp<4 * k, 4 * k + 4>(s);
              q_load_if(k, j == ta, s.S[4 * k]);
            });
            at_pack<0, 16>(s);
            pv_done();
          } else {
            wg_fence();
            issue_s(dk, [&]() { wait_v(j - 1); wg_fence(); });
            issue_rest(IC<0>{});
            if (!diag) {
              s_done(IC<64>{});
              at_exp<0, 24>(s);
              pv_half();
              at_exp<24, 48>(s);
              at_pack<0, 16>(s);
              pv_done();
              at_exp<48, 64>(s);
              at_pack<16, 32>(s);
            } else {
              s_done(IC<64>{});
              at_mask<8>(s, wrow - 64, lane);
              static_for<8>([&](auto k) {
                at_exp<7 * k, 7 * k + 7>(s);
                q_load_if(k, j == ta, s.S[7 * k + 3]);
                if (k == 2) pv_half();
                if (k == 5) { at_pack<0, 16>(s); pv_done(); }
              });
              at_exp<56, 64>(s);
              at_pack<16, 32>(s);
            }
          }
          TL(1, 20 * half + 2 + j, warp == 4);
        }
        TK(84 + half * 24);
        mbar_wait_c(B(half ? B_FULL3 : B_FULLQ), 0);
        if (gq == 0) ep_out(IC<0>{}, IC<EP1>{});
        bar_sync(1 + w, 256);
        fence_regs(s.O); fence_regs(s.P);
        const uint32_t ga = dA - half * w * 256, gb = ga + (half ? 512 : 4), gh = half ? 0x80000020u : 0x40000040u, go = (2 + half) * (SLOT >> 4);
        wg_fence();
        static_for<4>([&](auto k) { mma_n128_ssh<(k & 1) * 32, UNIT + k * 2048, k != 0>(s.S, k < 2 ? ga : gb, gh, dW); });
        mbar_wait_c(B(half ? B_FULL3 + 1 : B_FULLQ + 1), 0);
        wg_fence();
        static_for<4>([&](auto k) { mma_n128_ssh<(k & 1) * 32, UNIT + k * 2048, true>(s.S, (k < 2 ? ga : gb) + go, gh, dW + go); });
        wg_commit();
        TK(85 + half * 24);
        if (gq == 0) ep_rest();
        issue_pv(16, gq != 0, w == 1 || gq != 0);
        if (w == 0 || half == 0) bar_arrive(2 - w, 256);
        TK(86 + half * 24);
        wg_wait<2>();
        release2(B(B_EMPTY3), half); release2(B(B_EMPTY3 + 1), half);
        if (ep_prep()) redo |= 2;
        sched_fence();
        wg_wait<0>();
        TK(87 + half * 24);
        fence_regs(s.S);
        fence_regs(s.O);
        e_arrive(B(B_VE));
        release2(B(B_X + 3));
        fence_regs(s.P);
        {
          const int r = fresh_lane();
          cdst = g_ctx + (size_t)(tb * 32 + head) * KV_TILE + (wrow + (r >> 2)) * 32 + ((r ^ (r >> 3)) & 3) * 8;
        }
#pragma unroll
        for (int i = 0; i < 32; i++) {
          const float* o = s.O + 16 * (i >> 3) + 2 * ((i >> 2) & 1) + 4 * (i & 3);
          s.P[i] = pack_bf16(o[0] * inv[(i >> 2) & 1], o[1] * inv[(i >> 2) & 1]);
        }
        fence_regs(s.P);
        if (__builtin_expect(__any_sync(~0u, redo != 0), 0)) {
#pragma unroll
          for (int i = 0; i < 8; i++) put_ctx(i, true);
#pragma unroll 1
          for (int t = 0; t < 2; t++) {
            if (__any_sync(~0u, (redo >> t) & 1)) slow_rows(wq, head, (t ? tb : ta) * 128 + wrow);
          }
          if (__any_sync(~0u, redo & 1)) publish(2 + 2 * half);
#pragma unroll
          for (int i = 0; i < 32; i++) s.P[i] = 0;
          redo = 2;
        }
        TL(1, 20 * half + 19, warp == 4);
        TK(88 + half * 24);
        if (half) break;
        mbar_wait_c(B(B_FULLB), 0);
        TK(89);
        wg_fence();
        mma_n128_ss0<1, q_b(0), UNIT>(s.O, dA, dW);
        static_for<3>([&](auto k) { mma_n128_ss<1, q_b(0) + k * 32 + 32, UNIT + k * 2048 + 2048>(s.O, dA, dW, 1); });
        wg_commit();
        mma_kc(s.O, IC<q_b(1)>{}, IC<q_aw(1) + UNIT>{}, 1);
        wg_commit();
        wg_wait<1>();
        release2(B(B_EMPTYQ));
        put_ctx(0, true);
#pragma unroll 1
        for (int kb = 2; kb < 8; kb++) {
          issue_q(kb, IC<1>{});
          TK(90 + kb - 1);
#pragma unroll
          for (int i = 1; i < 8; i++) put_ctx(i, kb == (i < 7 ? i + 1 : 7));
        }
        publish(3);
      }
    }
    const int rid_ = rid + zero, cw_ = cw + zero;
    {
    const int lane = fresh_lane(), rid = rid_, mt = rid >> 3, gq = rid & 7, cw = cw_, w = cw >> 2, ct = cw * 32 + lane;
    const int fid = mt * 7 + gq;
    const bool ffn = gq < 7;
    const uint32_t stg = sb + OFF_STG + w * 16384 + (cw & 3) * 2048;
    const int wr_ = w * 64 + (lane & 7) + (lane >> 4) * 8;
    const uint32_t wl = sb + ((lane >> 3) & 1) * 8192 + wr_ * 64 + (((cw ^ (wr_ >> 1)) & 3) << 4);
    __syncwarp();
    float (&acc)[64] = s.S;
    uint32_t wf[128];
    auto grab = [&](auto c, uint32_t off) {
#pragma unroll
      for (int m = 0; m < 4; m++)
        asm volatile("ldmatrix.sync.aligned.m8n8.x4.trans.shared.b16 {%0,%1,%2,%3}, [%4];"
                     : "=r"(wf[16 * c + 4 * m]), "=r"(wf[16 * c + 4 * m + 1]), "=r"(wf[16 * c + 4 * m + 2]), "=r"(wf[16 * c + 4 * m + 3])
                     : "r"(wl + off + m * 1024) : "memory");
    };
    const int r0 = lane >> 2;
    uint32_t hp[32], rt[16];
    {
      const uint32_t dC = mk_desc(sb + w * 4096, 16);
      uint32_t dep = 0;
      auto hand = [&](uint32_t b, int n) {
        asm volatile("{\n.reg .pred p;\n.reg .b32 t;\nsetp.lt.u32 p, %1, %4;\nmad.lo.u32 t, %2, %3, %0;\n@p mbarrier.arrive.shared::cta.b64 _, [t];\n}"
                     ::"r"(b + 8 * lane), "r"(lane), "r"(dep), "r"(zero), "r"(n) : "memory");
      };
      auto kblock = [&](auto st, uint32_t ph, bool rel) {
        mbar_wait_c(B(B_FULL3 + st), ph);
        wg_fence();
        static_for<4>([&](auto k) { mma_n128_ssh<r3(decltype(st)::value) + (k >> 1) * 8192 + (k & 1) * 32, r3(decltype(st)::value) + UNIT + k * 2048, true>(acc, dC, 0x80000020u, dW); });
        wg_commit();
        wg_wait<1>();
        release2(B(B_EMPTY3 + (st + 5) % 6), rel);
      };
      auto ldsm_if = [&](uint32_t* r, uint32_t a, bool c, auto trans) {
        if (trans) asm volatile("{\n.reg .pred p;\nsetp.ne.u32 p, %5, 0;\n@p ldmatrix.sync.aligned.m8n8.x4.trans.shared.b16 {%0,%1,%2,%3}, [%4];\n}"
                                : "+r"(r[0]), "+r"(r[1]), "+r"(r[2]), "+r"(r[3]) : "r"(a), "r"((uint32_t)c) : "memory");
        else asm volatile("{\n.reg .pred p;\nsetp.ne.u32 p, %5, 0;\n@p ldmatrix.sync.aligned.m8n8.x4.shared.b16 {%0,%1,%2,%3}, [%4];\n}"
                          : "+r"(r[0]), "+r"(r[1]), "+r"(r[2]), "+r"(r[3]) : "r"(a), "r"((uint32_t)c) : "memory");
      };
#pragma unroll
      for (int i = 0; i < 48; i++) wf[i] = 0;
#pragma unroll 1
      for (int lap = 0; lap < 3; lap++) {
        kblock(IC<2>{}, lap & 1, lap > 0);
#pragma unroll
        for (int i = 0; i < 3; i++) put_ctx(3 * i, lap == i);
        kblock(IC<3>{}, lap & 1, true);
        if (ffn) mbar_wait_c(B(B_WF + (lap & 1)), lap >> 1);
#pragma unroll
        for (int i = 0; i < 12; i++) ldsm_if(wf + 4 * i, wl + OFF_SIDE + ((i >> 2) & 1) * UNIT + (i & 3) * 1024, lap == (i >> 2), IC<1>{});
        kblock(IC<4>{}, lap & 1, true);
        sched_fence();
        dep = 0;
#pragma unroll
        for (int i = 0; i < 12; i++) dep ^= wf[4 * i];
        hand(B(B_WE + (lap & 1)), 1);
#pragma unroll
        for (int i = 0; i < 3; i++) put_ctx(3 * i + 1, lap == i);
        kblock(IC<5>{}, lap & 1, true);
        if (lap == 2) publish(5);
        kblock(IC<0>{}, (lap & 1) ^ 1, true);
#pragma unroll
        for (int i = 0; i < 2; i++) put_ctx(3 * i + 2, lap == i);
        kblock(IC<1>{}, (lap & 1) ^ 1, true);
        TL(2, 40 + lap, warp == 4);
      }
#pragma unroll
      for (int i = 48; i < 96; i++) wf[i] = 0;
#pragma unroll
      for (int i = 0; i < 32; i++) { hp[i] = 0; rt[i >> 1] = 0; }
      const uint32_t xa = sb + OFF_SIDE + w * UNIT + (cw & 3) * 2048 + (lane & 15) * 128 + (((lane >> 4) ^ (lane & 7)) << 4);
#pragma unroll 1
      for (int lap = 3; lap < 11; lap++) {
        if (lap == 10 && w == 1) bar_sync(5, 256);
        kblock(IC<2>{}, lap & 1, true);
        if (lap == 10 && w == 0) bar_arrive(5, 256);
        kblock(IC<3>{}, lap & 1, true);
        if (lap == 10) break;
        if (lap < WIN) {
          if (ffn) mbar_wait_c(B(B_WF + (lap & 1)), (lap >> 1) & 1);
#pragma unroll
          for (int i = 12; i < 24; i++) ldsm_if(wf + 4 * i, wl + OFF_SIDE + ((i >> 2) & 1) * UNIT + (i & 3) * 1024, lap == (i >> 2), IC<1>{});
        } else if (lap == WIN) {
          mbar_wait_c(B(B_WF), ffn ? (WIN >> 1) & 1 : 0);
          mbar_wait_c(B(B_WF + 1), ffn ? (WIN >> 1) & 1 : 0);
#pragma unroll
          for (int j = 0; j < 8; j++) ldsm_if(hp + 4 * j, (xa ^ ((j & 3) << 5)) + (j >> 2) * 8192, true, IC<0>{});
        } else if (lap == 9) {
          mbar_wait_c(B(B_WR), 0);
          mbar_wait_c(B(B_SET2), 0);
#pragma unroll
          for (int j = 0; j < 4; j++) ldsm_if(rt + 4 * j, sb + OFF_MISC + 512 + (lane & 1) * 256 + (lane >> 3) * 16 + j * 64, true, IC<0>{});
        }
        kblock(IC<4>{}, lap & 1, true);
        sched_fence();
        dep = 0;
#pragma unroll
        for (int i = 0; i < 20; i++) dep ^= i < 12 ? wf[48 + 4 * i] : hp[4 * (i - 12)];
        hand(B(B_WE + (lap < WIN ? lap & 1 : 0)), lap < WIN ? 1 : (lap == WIN ? 2 : 0));
        kblock(IC<5>{}, lap & 1, true);
        kblock(IC<0>{}, (lap & 1) ^ 1, true);
        kblock(IC<1>{}, (lap & 1) ^ 1, true);
        TL(2, 40 + lap, warp == 4);
      }
    }
    uint4* const xr = g_xr + rid * XR_SIZE;
    uint4* const psd = xr + XR_PS + cw * 16 + r0;
    settle(psd, zero);
    sched_fence();
    wg_wait<0>();
    fence_regs(acc);
    TL(2, 10, warp == 4);
    {
      float d[4] = {0.f, 0.f, 0.f, 0.f}, qa[4] = {0.f, 0.f, 0.f, 0.f}, qb[4] = {0.f, 0.f, 0.f, 0.f};
#pragma unroll
      for (int j = 0; j < 16; j++) {
        hp[2 * j] = hadd2_bf(hp[2 * j], pack_bf16(acc[4 * j], acc[4 * j + 1]));
        hp[2 * j + 1] = hadd2_bf(hp[2 * j + 1], pack_bf16(acc[4 * j + 2], acc[4 * j + 3]));
        if (j & 1) {
          mma16816(d, hp[2 * j - 2], hp[2 * j - 1], hp[2 * j], hp[2 * j + 1], rt[j - 1], rt[j]);
          mma16816(qa, hp[2 * j - 2], hp[2 * j - 1], hp[2 * j], hp[2 * j + 1], hp[2 * j - 2], hp[2 * j]);
          mma16816(qb, hp[2 * j - 2], hp[2 * j - 1], hp[2 * j], hp[2 * j + 1], hp[2 * j - 1], hp[2 * j + 1]);
        }
      }
      asm volatile("{\n.reg .pred p;\nsetp.eq.u32 p, %7, %8;\n@p st.global.cg.v4.f32 [%0], {%1,%2,%3,%3};\n@p st.global.cg.v4.f32 [%0 + 128], {%4,%5,%6,%6};\n}"
                   ::"l"(psd), "f"(d[0]), "f"(d[1]), "f"((r0 & 1) ? qa[1] : qa[0]), "f"(d[2]), "f"(d[3]), "f"((r0 & 1) ? qb[3] : qb[2]),
                   "r"(lane & 3), "r"(r0 >> 1) : "memory");
      sched_fence();
    }
    mbar_wait_c(B(B_EMPTY3), 0);
    __syncwarp();
    stage_store_128(stg, lane, hp);
    TL(2, 11, warp == 4);
    __syncwarp();
    uint4 cout;
    uint32_t ckey;
    {
      const float wsum = *reinterpret_cast<const float*>(sp + OFF_MISC + 1024);
      const uint4* pp = g_xr + (mt * 8 + (ct & 1) * 4) * XR_SIZE + XR_PS + (ct >> 1);
      uint2* kd = reinterpret_cast<uint2*>(xr + XR_KEY) + cw;
      const uint32_t tok = 0x7FFFu - (mt * 128 + (ct >> 1));
      settle(pp, zero); settle(kd, zero); settle(tok, zero);
      spin_clk(PS_DLY);
      float s1, s2, s3;
#pragma unroll 1
      for (int n = 0; n < 0x400000; n++) {
        float4 z[4];
#pragma unroll
        for (int i = 0; i < 4; i++)
          asm volatile("ld.relaxed.gpu.global.v4.f32 {%0,%1,%2,%3}, [%4];" : "=f"(z[i].x), "=f"(z[i].y), "=f"(z[i].z), "=f"(z[i].w) : "l"(pp + i * XR_SIZE) : "memory");
        s1 = (z[0].x + z[1].x) + (z[2].x + z[3].x); s3 = (z[0].y + z[1].y) + (z[2].y + z[3].y); s2 = (z[0].z + z[1].z) + (z[2].z + z[3].z);
        const float t = s1 + s2 + s3;
        s1 += __shfl_xor_sync(~0u, s1, 1); s2 += __shfl_xor_sync(~0u, s2, 1); s3 += __shfl_xor_sync(~0u, s3, 1);
        if (__all_sync(~0u, t == t)) break;
        uint32_t m = 0;
#pragma unroll
        for (int i = 0; i < 4; i++) m = max(max(m, __float_as_uint(z[i].x)), max(__float_as_uint(z[i].y), __float_as_uint(z[i].z)));
        if (__all_sync(~0u, m != 0xFFFFFFFFu)) break;
      }
      TL(2, 12, warp == 4);
      const float mean = s1 * (1.f / DM);
      float mb, inv;
      ln_round(mean, fmaxf(fmaf(s2, 1.f / DM, -mean * mean), 0.f), mb, inv);
      const uint32_t u = pack_bf16(0.f, fmaf(s3 - mb * wsum, inv, 0.f));
      const uint32_t key = ((u ^ (((int)u >> 31) | 0x80000000u)) & 0xFFFF0000u) | tok;
      const uint32_t c1 = __reduce_max_sync(~0u, key);
      const uint32_t c2 = __reduce_max_sync(~0u, key == c1 ? 0u : key);
      asm volatile(ELECT "st.global.cg.v2.u32 [%0], {%1,%2};\n}" ::"l"(kd), "r"(c1), "r"(c2) : "memory");
      sched_fence();
      const uint32_t nm2 = pack_bf16(-mb, -mb);
      if (!(ct & 1)) *reinterpret_cast<uint2*>(sp + OFF_RSTAT + (ct >> 1) * 8) = make_uint2(nm2, __float_as_uint(inv) | (key >= c2 ? 0x80000000u : 0u));
      ckey = (lane >> 4) ? c2 : c1;
      const int row = (0x7FFF - (ckey & 0x7FFF)) & 15;
      const uint32_t rn = __shfl_sync(~0u, nm2, row * 2);
      const float ri = __shfl_sync(~0u, inv, row * 2);
      const uint4 v = lds128(stg + ((lane & 15) >> 3) * 8192 + row * 128 + (((lane & 7) ^ (row & 7)) << 4));
      const uint4 n = make_uint4(ln_apply(v.x, rn, ri), ln_apply(v.y, rn, ri), ln_apply(v.z, rn, ri), ln_apply(v.w, rn, ri));
      __stcg(xr + XR_CAND + cw * 64 + 32 + lane, n);
      __stcg(xr + XR_CAND + cw * 64 + lane, v);
      cdst = out + (size_t)(0x7FFF - (ckey & 0x7FFF)) * DM + gq * 128 + (lane & 15) * 8;
      cout = make_uint4(hadd2_bf(v.x, n.x), hadd2_bf(v.y, n.y), hadd2_bf(v.z, n.z), hadd2_bf(v.w, n.w));
    }
    publish(B_OUT - B_PUB);
    cluster_arrive();
    TL(2, 13, warp == 4);
    uint32_t wd[16][4];
    if (ffn) {
      static_for<2>([&](auto i) {
        mbar_wait_b(B(B_WF + i), ((WIN >> 1) & 1) ^ 1);
        grab(IC<WIN + i>{}, OFF_SIDE + i * UNIT);
      });
      mbar_wait_b(B(B_FULL3 + 4 + w), 0);
#pragma unroll
      for (int i = 0; i < 16; i++) {
        const int k = (i & 1) * 16 + (lane & 7) + (lane >> 4) * 8;
        asm volatile("ldmatrix.sync.aligned.m8n8.x4.trans.shared.b16 {%0,%1,%2,%3}, [%4];"
                     : "=r"(wd[i][0]), "=r"(wd[i][1]), "=r"(wd[i][2]), "=r"(wd[i][3])
                     : "r"(sb + r3(4) + w * SLOT + (2 * (cw & 3) + (i >> 3)) * 4096 + k * 128 + (((2 * ((i >> 1) & 3) + ((lane >> 3) & 1)) ^ (lane & 7)) << 4)) : "memory");
      }
    }
    const int fc = 16 * (rid >> 1) + 4 * (rid & 1) + (lane & 3) + 8 * (lane >> 4), ft = (lane >> 3) & 1;
    const char* pc = reinterpret_cast<const char*>(g_xr + ((ct & 127) >> 4) * XR_SIZE + XR_CAND + 32 + (ct & 15));
    const char* pf = reinterpret_cast<const char*>(g_xr + (fc >> 7) * XR_SIZE + XR_CAND) + (fc & 127) * 2;
    const uint32_t xs = sb + OFF_SCR + w * 2112 + ((ct & 127) >> 2) * 64 + (((ct >> 3) & 3) << 4) + (ct & 3) * 4;
    const uint32_t xb = sb + OFF_SCR + (r0 & 1) * 2112 + w * 128 + (((lane ^ w) & 3) << 4);
    settle(pc, zero); settle(pf, zero); settle(cdst, zero); settle(xs, zero); settle(xb, zero);
    mbar_wait_b(B(B_OUT2), 0);
    const uint4 top = lds128(sb + OFF_MISC + 256);
    TL(2, 14, warp == 4);
    uint32_t fh, fn;
    {
      pc += w ? top.y : top.x;
      pf += ft ? top.y : top.x;
      uint4 v;
#pragma unroll 1
      for (int n = 0; n < 0x400000; n++) {
        asm volatile("ld.relaxed.gpu.global.v4.u32 {%0,%1,%2,%3}, [%4];" : "=r"(v.x), "=r"(v.y), "=r"(v.z), "=r"(v.w) : "l"(pc) : "memory");
        asm volatile("ld.relaxed.gpu.global.u16 %0, [%1];" : "=r"(fh) : "l"(pf) : "memory");
        asm volatile("ld.relaxed.gpu.global.u16 %0, [%1 + 512];" : "=r"(fn) : "l"(pf) : "memory");
        asm volatile("st.shared.u32 [%0], %1;" ::"r"(xs), "r"(v.x) : "memory");
        asm volatile("st.shared.u32 [%0], %1;" ::"r"(xs ^ 16), "r"(v.y) : "memory");
        asm volatile("st.shared.u32 [%0], %1;" ::"r"(xs ^ 32), "r"(v.z) : "memory");
        asm volatile("st.shared.u32 [%0], %1;" ::"r"(xs ^ 48), "r"(v.w) : "memory");
        if (__all_sync(~0u, max(max(v.x, v.y), max(v.z, v.w)) != 0xFFFFFFFFu && max(fh, fn) != 0xFFFFu)) break;
      }
    }
    bar_sync(3, 256);
    asm volatile("{\n.reg .pred p;\nsetp.lt.u32 p, %5, %6;\n@p st.global.v4.u32 [%0], {%1,%2,%3,%4};\n}" ::"l"(cdst), "r"(cout.x), "r"(cout.y), "r"(cout.z),
                 "r"(cout.w), "r"(ckey), "r"(top.w) : "memory");
    if (ffn) {
      TL(2, 15, warp == 4);
      float d[4][4] = {};
      auto xl = [&](int i) { return lds128((xb ^ ((i & 2) << 4)) + (i >> 1) * 256 + (i & 1) * 64); };
      uint4 b0 = xl(0), b1 = xl(1);
#pragma unroll
      for (int i = 0; i < 16; i += 2) {
        const uint4 c0 = b0, c1 = b1;
        if (i < 14) { b0 = xl(i + 2); b1 = xl(i + 3); }
        mma16816(d[0], wf[8 * i], wf[8 * i + 1], wf[8 * i + 2], wf[8 * i + 3], c0.x, c0.y);
        mma16816(d[1], wf[8 * i + 4], wf[8 * i + 5], wf[8 * i + 6], wf[8 * i + 7], c0.z, c0.w);
        mma16816(d[2], wf[8 * i + 8], wf[8 * i + 9], wf[8 * i + 10], wf[8 * i + 11], c1.x, c1.y);
        mma16816(d[3], wf[8 * i + 12], wf[8 * i + 13], wf[8 * i + 14], wf[8 * i + 15], c1.z, c1.w);
      }
      const float e0 = (d[0][0] + d[1][0]) + (d[2][0] + d[3][0]), e1 = (d[0][1] + d[1][1]) + (d[2][1] + d[3][1]);
      const float e2 = (d[0][2] + d[1][2]) + (d[2][2] + d[3][2]), e3 = (d[0][3] + d[1][3]) + (d[2][3] + d[3][3]);
      asm volatile("st.shared.v2.f32 [%0], {%1,%2};" ::"r"(sb + OFF_SCR + 8192 + ((w * 2 + (lane & 1)) * 32 + (cw & 3) * 8 + r0) * 8),
                   "f"((lane & 1) ? e1 : e0), "f"((lane & 1) ? e3 : e2) : "memory");
      bar_sync(3, 256);
      TL(2, 16, warp == 4);
      const uint32_t ra = sb + OFF_SCR + 8192 + (r0 & 1) * 256 + (r0 >> 1) * 64 + (lane & 3) * 16;
      const uint4 p0 = lds128(ra), p1 = lds128(ra + 512);
      auto act = [](uint32_t u0, uint32_t u1, uint32_t g0, uint32_t g1) {
        const uint32_t ug = pack_bf16(__uint_as_float(u0) + __uint_as_float(u1), __uint_as_float(g0) + __uint_as_float(g1));
        const float g = bf_hi(ug);
        float r;
        asm("rcp.approx.ftz.f32 %0, %1;" : "=f"(r) : "f"(1.f + ex2(g * -1.4426950408889634f)));
        return bf_round(g * r) * bf_lo(ug);
      };
      const uint32_t av = pack_bf16(act(p0.x, p1.x, p0.y, p1.y), act(p0.z, p1.z, p0.w, p1.w));
      uint32_t b[4];
#pragma unroll
      for (int i = 0; i < 4; i++) b[i] = __shfl_sync(~0u, av, 8 * i + (lane & 7));
      TL(2, 17, warp == 4);
      float y[2][4] = {{0.f, 0.f, 0.f, 0.f}, {0.f, 0.f, 0.f, 0.f}};
#pragma unroll
      for (int c = 0; c < 4; c++) {
        const bool on = (lane >> 3) == c;
        const uint32_t b0 = on ? b[0] : 0, b1 = on ? b[1] : 0, b2 = on ? b[2] : 0, b3 = on ? b[3] : 0;
#pragma unroll
        for (int a = 0; a < 2; a++) {
          const int i = 8 * a + 2 * c;
          mma16816(y[a], wd[i][0], wd[i][1], wd[i][2], wd[i][3], b0, b1);
          mma16816(y[a], wd[i + 1][0], wd[i + 1][1], wd[i + 1][2], wd[i + 1][3], b2, b3);
        }
      }
      float4* yd = reinterpret_cast<float4*>(g_xr + (cw * 16 + (lane & 3) * 2 + (lane >> 4)) * XR_SIZE + XR_Y + fid * 4 + (r0 & 3));
      __stcg(yd, make_float4(y[0][0], y[0][1], y[0][2], y[0][3]));
      __stcg(yd + 8 * XR_SIZE, make_float4(y[1][0], y[1][1], y[1][2], y[1][3]));
    }
    TL(2, 18, warp == 4);
    if (cw == 0) {
      const uint32_t fk = ft ? top.w : top.z;
      uint32_t u = fk >> 16;
      u = (u & 0x8000u) ? (u & 0x7FFFu) : (~u & 0xFFFFu);
      float rs = bf_round(__fdividef(1.f, 1.f + __expf(-__uint_as_float(u << 16))));
      uint16_t* op = reinterpret_cast<uint16_t*>(out) + (size_t)(~fk & 0x7FFF) * DM + fc;
      settle(op, zero); settle(__float_as_uint(rs), zero);
      spin_clk(ffn ? Y_DLY : Y_DLY + Y_DLY0);
      float v[4];
#pragma unroll 1
      for (int n = 0; n < 0x400000; n++) {
        float4 z[14];
#pragma unroll
        for (int i = 0; i < 14; i++)
          asm volatile("ld.relaxed.gpu.global.v4.f32 {%0,%1,%2,%3}, [%4];" : "=f"(z[i].x), "=f"(z[i].y), "=f"(z[i].z), "=f"(z[i].w) : "l"(xr + XR_Y + lane + 32 * i) : "memory");
        float a[4] = {z[0].x, z[0].y, z[0].z, z[0].w}, b[4] = {z[1].x, z[1].y, z[1].z, z[1].w};
#pragma unroll
        for (int i = 2; i < 14; i += 2) {
          a[0] += z[i].x; a[1] += z[i].y; a[2] += z[i].z; a[3] += z[i].w;
          b[0] += z[i + 1].x; b[1] += z[i + 1].y; b[2] += z[i + 1].z; b[3] += z[i + 1].w;
        }
#pragma unroll
        for (int i = 0; i < 4; i++) v[i] = a[i] + b[i];
        const float t = (v[0] + v[1]) + (v[2] + v[3]);
        if (__all_sync(~0u, t == t)) break;
        uint32_t m = 0;
#pragma unroll
        for (int i = 0; i < 14; i++) m = max(max(m, max(__float_as_uint(z[i].x), __float_as_uint(z[i].y))), max(__float_as_uint(z[i].z), __float_as_uint(z[i].w)));
        if (__all_sync(~0u, m != 0xFFFFFFFFu)) break;
      }
      TL(2, 30, true);
      const bool hi = lane & 16, odd = lane & 8;
      const float a0 = (hi ? v[2] : v[0]) + __shfl_xor_sync(~0u, hi ? v[0] : v[2], 16), a1 = (hi ? v[3] : v[1]) + __shfl_xor_sync(~0u, hi ? v[1] : v[3], 16);
      float yv = (odd ? a1 : a0) + __shfl_xor_sync(~0u, odd ? a0 : a1, 8);
      yv += __shfl_xor_sync(~0u, yv, 4);
      const uint32_t o = hadd2_bf(fh, hadd2_bf(fn, pack_bf16(bf_round(yv) * rs, 0.f)));
      if (!(lane & 4)) *op = (uint16_t)o;
      TL(2, 21, true);
    }
    TL(2, 20, warp == 4);
    }
    __syncwarp();
    cluster_wait();
  }
}

typedef CUresult (*EncodeFn)(CUtensorMap*, CUtensorMapDataType, cuuint32_t, void*, const cuuint64_t*, const cuuint64_t*, const cuuint32_t*,
                             const cuuint32_t*, CUtensorMapInterleave, CUtensorMapSwizzle, CUtensorMapL2promotion, CUtensorMapFloatOOBfill);
EncodeFn g_enc = nullptr;

void map2(CUtensorMap* m, const void* ptr, uint64_t rows, uint64_t cols, uint32_t bc, uint32_t br) {
  const CUtensorMapSwizzle sw = bc == 64 ? CU_TENSOR_MAP_SWIZZLE_128B : CU_TENSOR_MAP_SWIZZLE_64B;
  cuuint64_t gd[2] = {cols, rows}, gs[1] = {cols * 2};
  cuuint32_t bd[2] = {bc, br}, es[2] = {1, 1};
  g_enc(m, CU_TENSOR_MAP_DATA_TYPE_BFLOAT16, 2, (void*)ptr, gd, gs, bd, es, CU_TENSOR_MAP_INTERLEAVE_NONE, sw,
        CU_TENSOR_MAP_L2_PROMOTION_L2_128B, CU_TENSOR_MAP_FLOAT_OOB_FILL_NONE);
}
void map3(CUtensorMap* m, const void* ptr, uint64_t rows, uint64_t cols, uint32_t br, uint32_t bch) {
  cuuint64_t gd[3] = {64, rows, cols / 64}, gs[2] = {cols * 2, 128};
  cuuint32_t bd[3] = {64, br, bch}, es[3] = {1, 1, 1};
  g_enc(m, CU_TENSOR_MAP_DATA_TYPE_BFLOAT16, 3, (void*)ptr, gd, gs, bd, es, CU_TENSOR_MAP_INTERLEAVE_NONE, CU_TENSOR_MAP_SWIZZLE_128B,
        CU_TENSOR_MAP_L2_PROMOTION_L2_128B, CU_TENSOR_MAP_FLOAT_OOB_FILL_NONE);
}

}

extern "C" void kernel_launch(void* const* d_in, const int* in_sizes, int n_in, void* d_out, int out_size) {
  const __nv_bfloat16* x = (const __nv_bfloat16*)d_in[0];
  const __nv_bfloat16* ckv = (const __nv_bfloat16*)d_in[1];
  const __nv_bfloat16* wq = (const __nv_bfloat16*)d_in[2];
  const __nv_bfloat16* wk = (const __nv_bfloat16*)d_in[3];
  const __nv_bfloat16* wv = (const __nv_bfloat16*)d_in[4];
  const __nv_bfloat16* wo = (const __nv_bfloat16*)d_in[5];
  const __nv_bfloat16* w_r = (const __nv_bfloat16*)d_in[7];
  const __nv_bfloat16* wgate = (const __nv_bfloat16*)d_in[8];
  const __nv_bfloat16* wup = (const __nv_bfloat16*)d_in[9];
  const __nv_bfloat16* wdown = (const __nv_bfloat16*)d_in[10];
  __nv_bfloat16* out = (__nv_bfloat16*)d_out;

  if (!g_enc) {
    void* fn = nullptr;
    cudaDriverEntryPointQueryResult qr;
    cudaGetDriverEntryPoint("cuTensorMapEncodeTiled", &fn, cudaEnableDefault, &qr);
    g_enc = (EncodeFn)fn;
    cudaFuncSetAttribute(fused_kernel, cudaFuncAttributeMaxDynamicSharedMemorySize, SMEM_BYTES);
  }
  void *xn, *kv, *ctx, *xr, *cnt;
  cudaGetSymbolAddress(&xr, g_xr);
  cudaGetSymbolAddress(&cnt, g_cnt);
  cudaGetSymbolAddress(&xn, g_xn);
  cudaGetSymbolAddress(&kv, g_kv);
  cudaGetSymbolAddress(&ctx, g_ctx);

  Params p;
  map2(&p.xn, xn, SEQ, DM, 64, 64);
  map2(&p.ckv, ckv, SEQ, DC, 64, 128);
  map3(&p.wq, wq, DM, NQ, 64, 2);
  map3(&p.wk, wk, DC, NQ, 32, 2);
  map3(&p.wv, wv, DC, NQ, 32, 2);
  map3(&p.wo, wo, NQ, DM, 64, 1);
  map3(&p.x, x, SEQ, DM, 64, 2);
  map3(&p.wd, wdown, FF, DM, 32, 8);
  map2(&p.wg, wgate, DM, FF, 32, 64);
  map2(&p.wu, wup, DM, FF, 32, 64);
  fused_kernel<<<128, 384, SMEM_BYTES, cudaStreamPerThread>>>(0u, x, (__nv_bfloat16*)kv, (__nv_bfloat16*)ctx, (uint4*)xr, out, (__nv_bfloat16*)xn,
                                                               (unsigned*)cnt, w_r, wdown, wq, p);
}
```

```cpp
#include <cuda_runtime.h>
#include <cuda_bf16.h>
#include <cuda.h>
#include <stdint.h>
#include <utility>

#pragma nv_diag_suppress 549
#pragma nv_diag_suppress 177
namespace {

constexpr int SEQ = 2048, DM = 1024, NH = 32, HD = 128, DC = 512, NQ = NH * HD, FF = 3584;

__device__ __align__(1024) __nv_bfloat16 g_xn[SEQ * DM];
constexpr int KV_TILE = 128 * 128;
__device__ __align__(1024) __nv_bfloat16 g_kv[2 * SEQ * NQ];
__device__ __align__(1024) __nv_bfloat16 g_ctx[SEQ * NQ];
constexpr int XR_PS = 0;
constexpr int XR_KEY = 128;
constexpr int XR_CAND = 136;
constexpr int XR_Y = 648;
constexpr int XR_SIZE = 1104;
__device__ __align__(1024) uint4 g_xr[128 * XR_SIZE];
constexpr int C_LN = 0, C_KV = 16, C_CTX = 32, C_NUM = 64;
__device__ unsigned g_cnt[C_NUM];

#define TL(k, i, cond) do {} while (0)
#define TC(w, g, i) do {} while (0)
#define TL_EXTRA 0
#define TK(i) do {} while (0)

__device__ __forceinline__ uint32_t s2u(const void* p) { return (uint32_t)__cvta_generic_to_shared(p); }
__device__ __forceinline__ void mbar_arrive(uint32_t b) { asm volatile("mbarrier.arrive.shared::cta.b64 _, [%0];" ::"r"(b) : "memory"); }
__device__ __forceinline__ void mbar_arrive_both(uint32_t b, uint32_t lane, bool cond) {
  asm volatile("{\n.reg .pred p;\n.reg .b32 r;\nsetp.lt.u32 p, %1, %2;\nmapa.shared::cluster.u32 r, %0, %1;\n@p mbarrier.arrive.shared::cluster.b64 _, [r];\n}"
               ::"r"(b), "r"(lane), "r"(cond ? 2 : 0) : "memory");
}
__device__ __forceinline__ bool mbar_test(uint32_t b, uint32_t ph) {
  uint32_t ok;
  asm volatile("{\n.reg .pred p;\nmbarrier.test_wait.parity.shared::cta.b64 p, [%1], %2;\nselp.u32 %0, 1, 0, p;\n}" : "=r"(ok) : "r"(b), "r"(ph) : "memory");
  return __all_sync(~0u, ok);
}
__device__ __forceinline__ void mbar_wait(uint32_t b, uint32_t ph) {
  asm volatile(
      "{\n.reg .pred p;\n.reg .u32 n;\nmov.u32 n, 0;\n"
      "LW:\nmbarrier.try_wait.parity.shared::cta.b64 p, [%0], %1, 20000;\n@p bra LD;\n"
      "add.u32 n, n, 1;\nsetp.lt.u32 p, n, 0x40000;\n@p bra LW;\ntrap;\nLD:\n}" ::"r"(b), "r"(ph) : "memory");
}
__device__ __forceinline__ void mbar_wait_u(uint32_t b, uint32_t ph) {
  asm volatile(
      "{\n.reg .pred p;\n.reg .u32 n;\nmov.u32 n, 0;\n"
      "LW:\nmbarrier.try_wait.parity.shared::cta.b64 p, [%0], %1, 20000;\n@p bra.uni LD;\n"
      "add.u32 n, n, 1;\nsetp.lt.u32 p, n, 0x40000;\n@p bra.uni LW;\ntrap;\nLD:\n}" ::"r"(b), "r"(ph) : "memory");
}
__device__ __forceinline__ void mbar_wait_c(uint32_t b, uint32_t ph) {
  asm volatile("{\n.reg .pred p;\nLW:\nmbarrier.try_wait.parity.shared::cta.b64 p, [%0], %1;\n@!p bra.uni LW;\n}" ::"r"(b), "r"(ph) : "memory");
}
__device__ __forceinline__ void mbar_wait_b(uint32_t b, uint32_t ph) {
  asm volatile(
      "{\n.reg .pred p;\n.reg .u32 n;\nmov.u32 n, 0;\n"
      "LW:\nmbarrier.try_wait.parity.shared::cta.b64 p, [%0], %1;\n@p bra.uni LD;\n"
      "add.u32 n, n, 1;\nsetp.lt.u32 p, n, 0x1000000;\n@p bra.uni LW;\ntrap;\nLD:\n}" ::"r"(b), "r"(ph) : "memory");
}
template <bool SLEEP = false>
__device__ __forceinline__ void spin_until_ge(const unsigned* p, unsigned target) {
  asm volatile(
      "{\n.reg .pred p, q;\n.reg .u32 n, v;\nmov.u32 n, 0;\nsetp.ne.u32 q, %2, 0;\n"
      "LW:\nld.acquire.gpu.global.u32 v, [%0];\nsetp.ge.u32 p, v, %1;\n@p bra LD;\n@q nanosleep.u32 200;\n"
      "add.u32 n, n, 1;\nsetp.lt.u32 p, n, 0x400000;\n@p bra LW;\ntrap;\nLD:\n}" ::"l"(p), "r"(target), "n"((int)SLEEP) : "memory");
}
__device__ __forceinline__ void spin_clk(uint32_t n) {
  asm volatile("{\n.reg .pred p;\n.reg .u32 a, b;\nmov.u32 a, %%clock;\nLW:\nmov.u32 b, %%clock;\nsub.u32 b, b, a;\nsetp.lt.u32 p, b, %0;\n@p bra.uni LW;\n}" ::"r"(n) : "memory");
}
__device__ __forceinline__ int fresh_lane() {
  int r;
  asm volatile("mov.u32 %0, %%laneid;" : "=r"(r));
  return r;
}
__device__ __forceinline__ void settle(const void* a, uint32_t zero) {
  asm volatile("{\n.reg .pred p;\nsetp.ne.u32 p, %1, 0;\n@p st.global.u32 [%0], %1;\n}" ::"l"(a), "r"(zero) : "memory");
}
__device__ __forceinline__ void settle(uint32_t a, uint32_t zero) {
  asm volatile("{\n.reg .pred p;\nsetp.ne.u32 p, %1, 0;\n@p st.shared.u32 [%0], %1;\n}" ::"r"(a), "r"(zero) : "memory");
}
__device__ __forceinline__ void fence_async_all() { asm volatile("fence.proxy.async;" ::: "memory"); }
__device__ __forceinline__ void bar_sync(int id, int n) { asm volatile("bar.sync %0, %1;" ::"r"(id), "r"(n) : "memory"); }
__device__ __forceinline__ void bar_arrive(int id, int n) { asm volatile("bar.arrive %0, %1;" ::"r"(id), "r"(n) : "memory"); }
__device__ __forceinline__ void cluster_arrive() { asm volatile("barrier.cluster.arrive.relaxed.aligned;" ::: "memory"); }
__device__ __forceinline__ void cluster_wait() { asm volatile("barrier.cluster.wait.acquire.aligned;" ::: "memory"); }
__device__ __forceinline__ void fence_gpu() { asm volatile("fence.acq_rel.gpu;" ::: "memory"); }
__device__ __forceinline__ void red_add(unsigned* p, unsigned v) { asm volatile("red.relaxed.gpu.global.add.u32 [%0], %1;" ::"l"(p), "r"(v) : "memory"); }
#define ELECT "{\n.reg .pred E;\nelect.sync _|E, 0xFFFFFFFF;\n@E "
__device__ __forceinline__ void e_init(uint32_t b, uint32_t c) { asm volatile(ELECT "mbarrier.init.shared::cta.b64 [%0], %1;\n}" ::"r"(b), "r"(c) : "memory"); }
__device__ __forceinline__ void e_expect(uint32_t b, uint32_t bytes) { asm volatile(ELECT "mbarrier.arrive.expect_tx.shared::cta.b64 _, [%0], %1;\n}" ::"r"(b), "r"(bytes) : "memory"); }
__device__ __forceinline__ void e_arrive(uint32_t b) { asm volatile(ELECT "mbarrier.arrive.shared::cta.b64 _, [%0];\n}" ::"r"(b) : "memory"); }
__device__ __forceinline__ void prefetch_tm(const CUtensorMap* m) { asm volatile(ELECT "prefetch.tensormap [%0];\n}" ::"l"(m) : "memory"); }
__device__ __forceinline__ void tma_ld2(uint32_t dst, const CUtensorMap* m, uint32_t bar, int c0, int c1) {
  asm volatile(ELECT "cp.async.bulk.tensor.2d.shared::cta.global.mbarrier::complete_tx::bytes [%0], [%1, {%3,%4}], [%2];\n}" ::"r"(dst), "l"(m), "r"(bar), "r"(c0), "r"(c1) : "memory");
}
__device__ __forceinline__ void tma_ld3(uint32_t dst, const CUtensorMap* m, uint32_t bar, int c0, int c1, int c2) {
  asm volatile(ELECT "cp.async.bulk.tensor.3d.shared::cta.global.mbarrier::complete_tx::bytes [%0], [%1, {%3,%4,%5}], [%2];\n}" ::"r"(dst), "l"(m), "r"(bar), "r"(c0), "r"(c1), "r"(c2) : "memory");
}
__device__ __forceinline__ void tma_ld2_mc(uint32_t dst, const CUtensorMap* m, uint32_t bar, int c0, int c1, uint16_t mask) {
  asm volatile(ELECT "cp.async.bulk.tensor.2d.shared::cluster.global.mbarrier::complete_tx::bytes.multicast::cluster [%0], [%1, {%3,%4}], [%2], %5;\n}" ::"r"(dst), "l"(m), "r"(bar), "r"(c0), "r"(c1), "h"(mask) : "memory");
}
__device__ __forceinline__ void tma_ld3_mc(uint32_t dst, const CUtensorMap* m, uint32_t bar, int c0, int c1, int c2, uint16_t mask) {
  asm volatile(ELECT "cp.async.bulk.tensor.3d.shared::cluster.global.mbarrier::complete_tx::bytes.multicast::cluster [%0], [%1, {%3,%4,%5}], [%2], %6;\n}" ::"r"(dst), "l"(m), "r"(bar), "r"(c0), "r"(c1), "r"(c2), "h"(mask) : "memory");
}
__device__ __forceinline__ uint64_t policy_evict_first() {
  uint64_t p;
  asm("createpolicy.fractional.L2::evict_first.b64 %0, 1.0;" : "=l"(p));
  return p;
}
__device__ __forceinline__ void tma_ld2_ef(uint32_t dst, const CUtensorMap* m, uint32_t bar, int c0, int c1) {
  asm volatile(ELECT "cp.async.bulk.tensor.2d.shared::cta.global.mbarrier::complete_tx::bytes.L2::cache_hint [%0], [%1, {%3,%4}], [%2], %5;\n}" ::"r"(dst), "l"(m), "r"(bar), "r"(c0), "r"(c1), "l"(policy_evict_first()) : "memory");
}
__device__ __forceinline__ void tma_ld3_ef(uint32_t dst, const CUtensorMap* m, uint32_t bar, int c0, int c1, int c2) {
  asm volatile(ELECT "cp.async.bulk.tensor.3d.shared::cta.global.mbarrier::complete_tx::bytes.L2::cache_hint [%0], [%1, {%3,%4,%5}], [%2], %6;\n}" ::"r"(dst), "l"(m), "r"(bar), "r"(c0), "r"(c1), "r"(c2), "l"(policy_evict_first()) : "memory");
}
__device__ __forceinline__ void bulk_ld(uint32_t dst, const void* src, uint32_t bytes, uint32_t bar) {
  asm volatile(ELECT "cp.async.bulk.shared::cta.global.mbarrier::complete_tx::bytes [%0], [%1], %2, [%3];\n}" ::"r"(dst), "l"(src), "r"(bytes), "r"(bar) : "memory");
}
__device__ __forceinline__ void tma_pf2(const CUtensorMap* m, int c0, int c1) { asm volatile(ELECT "cp.async.bulk.prefetch.tensor.2d.L2.global [%0, {%1,%2}];\n}" ::"l"(m), "r"(c0), "r"(c1) : "memory"); }
__device__ __forceinline__ void tma_pf3(const CUtensorMap* m, int c0, int c1, int c2) { asm volatile(ELECT "cp.async.bulk.prefetch.tensor.3d.L2.global [%0, {%1,%2,%3}];\n}" ::"l"(m), "r"(c0), "r"(c1), "r"(c2) : "memory"); }
__device__ __forceinline__ void sched_fence() { asm volatile("pmevent 0;" ::: "memory"); }
__device__ __forceinline__ void l2_prefetch(const void* p, uint32_t bytes) { asm volatile(ELECT "cp.async.bulk.prefetch.L2.global [%0], %1;\n}" ::"l"(p), "r"(bytes) : "memory"); }

__device__ __forceinline__ void wg_fence() { asm volatile("wgmma.fence.sync.aligned;" ::: "memory"); }
__device__ __forceinline__ void wg_commit() { asm volatile("wgmma.commit_group.sync.aligned;" ::: "memory"); }
template <int N> __device__ __forceinline__ void wg_wait() { asm volatile("wgmma.wait_group.sync.aligned %0;" ::"n"(N) : "memory"); }
template <int N> __device__ __forceinline__ void reg_alloc() { asm volatile("setmaxnreg.inc.sync.aligned.u32 %0;" ::"n"(N)); }
template <int N> __device__ __forceinline__ void reg_dealloc() { asm volatile("setmaxnreg.dec.sync.aligned.u32 %0;" ::"n"(N)); }
template <int N> __device__ __forceinline__ void fence_regs(float (&d)[N]) {
#pragma unroll
  for (int i = 0; i < N; i++) asm volatile("" : "+f"(d[i])::"memory");
}
template <int I0, int I1, int N> __device__ __forceinline__ void fence_part(float (&d)[N]) {
#pragma unroll
  for (int i = I0; i < I1; i++) asm volatile("" : "+f"(d[i])::"memory");
}
template <int N> __device__ __forceinline__ void fence_regs(uint32_t (&d)[N]) {
#pragma unroll
  for (int i = 0; i < N; i++) asm volatile("" : "+r"(d[i])::"memory");
}

__device__ __forceinline__ uint32_t mk_desc(uint32_t addr, uint32_t lbo) { return ((addr & 0x3FFFF) >> 4) | ((lbo >> 4) << 16); }

#define R8(b) "+f"(d[b + 0]), "+f"(d[b + 1]), "+f"(d[b + 2]), "+f"(d[b + 3]), "+f"(d[b + 4]), "+f"(d[b + 5]), "+f"(d[b + 6]), "+f"(d[b + 7])
#define REGS64 "%0,%1,%2,%3,%4,%5,%6,%7,%8,%9,%10,%11,%12,%13,%14,%15,%16,%17,%18,%19,%20,%21,%22,%23,%24,%25,%26,%27,%28,%29,%30,%31," \
               "%32,%33,%34,%35,%36,%37,%38,%39,%40,%41,%42,%43,%44,%45,%46,%47,%48,%49,%50,%51,%52,%53,%54,%55,%56,%57,%58,%59,%60,%61,%62,%63"
#define REGS128 REGS64 ",%64,%65,%66,%67,%68,%69,%70,%71,%72,%73,%74,%75,%76,%77,%78,%79,%80,%81,%82,%83,%84,%85,%86,%87,%88,%89,%90,%91,%92,%93,%94,%95," \
               "%96,%97,%98,%99,%100,%101,%102,%103,%104,%105,%106,%107,%108,%109,%110,%111,%112,%113,%114,%115,%116,%117,%118,%119,%120,%121,%122,%123,%124,%125,%126,%127"

#define DESC(d, r, o) "add.u32 t, " r ", " o ";\nmov.b64 " d ", {t, h};\n"
#define MMA_PRE_(acc, hi) "{\n.reg .pred p;\n.reg .b32 t, h;\n.reg .b64 da, db;\nmov.b32 h, " hi ";\nsetp.ne.b32 p, " acc ", 0;\n"
#define MMA_PRE(acc) MMA_PRE_(acc, "0x40000040")
#define MMA_PRE64(acc) MMA_PRE_(acc, "0x80000020")
template <int TB, int OA, int OB>
__device__ __forceinline__ void mma_n256_ss(float (&d)[128], uint32_t a, uint32_t b, int acc) {
  asm volatile(MMA_PRE("%130") DESC("da", "%128", "%132") DESC("db", "%129", "%133")
               "wgmma.mma_async.sync.aligned.m64n256k16.f32.bf16.bf16 {" REGS128 "}, da, db, p, 1, 1, 0, %131;\n}\n"
               : R8(0), R8(8), R8(16), R8(24), R8(32), R8(40), R8(48), R8(56), R8(64), R8(72), R8(80), R8(88), R8(96), R8(104), R8(112), R8(120)
               : "r"(a), "r"(b), "r"(acc), "n"(TB), "n"(OA >> 4), "n"(OB >> 4));
}
template <int TB, int OA, int OB>
__device__ __forceinline__ void mma_n128_ss(float (&d)[64], uint32_t a, uint32_t b, int acc) {
  asm volatile(MMA_PRE("%66") DESC("da", "%64", "%68") DESC("db", "%65", "%69")
               "wgmma.mma_async.sync.aligned.m64n128k16.f32.bf16.bf16 {" REGS64 "}, da, db, p, 1, 1, 0, %67;\n}\n"
               : R8(0), R8(8), R8(16), R8(24), R8(32), R8(40), R8(48), R8(56)
               : "r"(a), "r"(b), "r"(acc), "n"(TB), "n"(OA >> 4), "n"(OB >> 4));
}
template <int TB, int OB>
__device__ __forceinline__ void mma_n128_rs(float (&d)[64], const uint32_t* a, uint32_t b, int acc) {
  asm volatile(MMA_PRE64("%69") DESC("db", "%68", "%71")
               "wgmma.mma_async.sync.aligned.m64n128k16.f32.bf16.bf16 {" REGS64 "}, {%64,%65,%66,%67}, db, p, 1, 1, %70;\n}\n"
               : R8(0), R8(8), R8(16), R8(24), R8(32), R8(40), R8(48), R8(56)
               : "r"(a[0]), "r"(a[1]), "r"(a[2]), "r"(a[3]), "r"(b), "r"(acc), "n"(TB), "n"(OB >> 4));
}
#define W8(b) "=f"(d[b + 0]), "=f"(d[b + 1]), "=f"(d[b + 2]), "=f"(d[b + 3]), "=f"(d[b + 4]), "=f"(d[b + 5]), "=f"(d[b + 6]), "=f"(d[b + 7])
#define MMA_N64 MMA_PRE64("%37") DESC("db", "%36", "%38") \
  "wgmma.mma_async.sync.aligned.m64n64k16.f32.bf16.bf16 {%0,%1,%2,%3,%4,%5,%6,%7,%8,%9,%10,%11,%12,%13,%14,%15,%16,%17,%18,%19,%20,%21," \
  "%22,%23,%24,%25,%26,%27,%28,%29,%30,%31}, {%32,%33,%34,%35}, db, p, 1, 1, 0;\n}\n"
template <int H, int OB, bool ACC>
__device__ __forceinline__ void mma_n64_rs(float (&d)[64], const uint32_t* a, uint32_t b) {
  if (ACC) asm volatile(MMA_N64 : R8(32 * H), R8(32 * H + 8), R8(32 * H + 16), R8(32 * H + 24) : "r"(a[0]), "r"(a[1]), "r"(a[2]), "r"(a[3]), "r"(b), "n"(1), "n"(OB >> 4));
  else asm volatile(MMA_N64 : W8(32 * H), W8(32 * H + 8), W8(32 * H + 16), W8(32 * H + 24) : "r"(a[0]), "r"(a[1]), "r"(a[2]), "r"(a[3]), "r"(b), "n"(0), "n"(OB >> 4));
}
template <int OB>
__device__ __forceinline__ void mma_n128_rs0(float (&d)[64], const uint32_t* a, uint32_t b) {
  asm volatile(MMA_PRE64("%69") DESC("db", "%68", "%70")
               "wgmma.mma_async.sync.aligned.m64n128k16.f32.bf16.bf16 {" REGS64 "}, {%64,%65,%66,%67}, db, p, 1, 1, 0;\n}\n"
               : W8(0), W8(8), W8(16), W8(24), W8(32), W8(40), W8(48), W8(56)
               : "r"(a[0]), "r"(a[1]), "r"(a[2]), "r"(a[3]), "r"(b), "n"(0), "n"(OB >> 4));
}
#define MMA_SSH MMA_PRE("%67") DESC("db", "%65", "%69") "add.u32 t, %64, %68;\nmov.b64 da, {t, %66};\n" \
  "wgmma.mma_async.sync.aligned.m64n128k16.f32.bf16.bf16 {" REGS64 "}, da, db, p, 1, 1, 0, 1;\n}\n"
template <int OA, int OB, bool ACC>
__device__ __forceinline__ void mma_n128_ssh(float (&d)[64], uint32_t a, uint32_t ahi, uint32_t b) {
  if (ACC) asm volatile(MMA_SSH : R8(0), R8(8), R8(16), R8(24), R8(32), R8(40), R8(48), R8(56) : "r"(a), "r"(b), "r"(ahi), "n"(1), "n"(OA >> 4), "n"(OB >> 4));
  else asm volatile(MMA_SSH : W8(0), W8(8), W8(16), W8(24), W8(32), W8(40), W8(48), W8(56) : "r"(a), "r"(b), "r"(ahi), "n"(0), "n"(OA >> 4), "n"(OB >> 4));
}
template <int TB, int OA, int OB>
__device__ __forceinline__ void mma_n128_ss0(float (&d)[64], uint32_t a, uint32_t b) {
  asm volatile(MMA_PRE("%66") DESC("da", "%64", "%68") DESC("db", "%65", "%69")
               "wgmma.mma_async.sync.aligned.m64n128k16.f32.bf16.bf16 {" REGS64 "}, da, db, p, 1, 1, 0, %67;\n}\n"
               : W8(0), W8(8), W8(16), W8(24), W8(32), W8(40), W8(48), W8(56)
               : "r"(a), "r"(b), "n"(0), "n"(TB), "n"(OA >> 4), "n"(OB >> 4));
}
template <int V> struct IC { static constexpr int value = V; __host__ __device__ constexpr operator int() const { return V; } };
template <int N, class F, int... I>
__device__ __forceinline__ void static_for_(F f, std::integer_sequence<int, I...>) { (f(IC<I>{}), ...); }
template <int N, class F>
__device__ __forceinline__ void static_for(F f) { static_for_<N>(f, std::make_integer_sequence<int, N>{}); }
__device__ __forceinline__ uint32_t pack_bf16(float lo, float hi) {
  uint32_t r;
  asm("cvt.rn.bf16x2.f32 %0, %1, %2;" : "=r"(r) : "f"(hi), "f"(lo));
  return r;
}
__device__ __forceinline__ float bf_lo(uint32_t v) { return __uint_as_float(v << 16); }
__device__ __forceinline__ float bf_hi(uint32_t v) { return __uint_as_float(v & 0xFFFF0000u); }
__device__ __forceinline__ float bf_round(float v) { return bf_lo(pack_bf16(v, v)); }
__device__ __forceinline__ void stsm4(uint32_t addr, uint32_t r0, uint32_t r1, uint32_t r2, uint32_t r3) {
  asm volatile("stmatrix.sync.aligned.m8n8.x4.shared.b16 [%0], {%1,%2,%3,%4};" ::"r"(addr), "r"(r0), "r"(r1), "r"(r2), "r"(r3) : "memory");
}
__device__ __forceinline__ uint4 lds128(uint32_t addr) {
  uint4 v;
  asm volatile("ld.shared.v4.u32 {%0,%1,%2,%3}, [%4];" : "=r"(v.x), "=r"(v.y), "=r"(v.z), "=r"(v.w) : "r"(addr));
  return v;
}
__device__ __forceinline__ float ex2(float x) {
  float y;
  asm("ex2.approx.ftz.f32 %0, %1;" : "=f"(y) : "f"(x));
  return y;
}
__device__ __forceinline__ void stage_store_128(uint32_t base, int lane, const uint32_t* pk) {
  const int row = (lane & 7) + ((lane >> 3) & 1) * 8;
  const uint32_t rb = base + row * 128;
  const int hi = lane >> 4;
#pragma unroll
  for (int j = 0; j < 8; j++) {
    const int chunk = 2 * j + hi;
    const uint32_t a = rb + (j >> 2) * 8192 + (((chunk & 7) ^ (lane & 7)) << 4);
    stsm4(a, pk[4 * j + 0], pk[4 * j + 1], pk[4 * j + 2], pk[4 * j + 3]);
  }
}
__device__ __forceinline__ void ln_round(float mean, float var, float& m_bf, float& inv_s) {
  const uint32_t mv = pack_bf16(mean, var);
  m_bf = bf_lo(mv);
  float sq, rc;
  asm("sqrt.approx.ftz.f32 %0, %1;" : "=f"(sq) : "f"(bf_round(bf_hi(mv) + 1e-5f)));
  asm("rcp.approx.ftz.f32 %0, %1;" : "=f"(rc) : "f"(bf_round(sq)));
  inv_s = rc;
}
__device__ __forceinline__ uint32_t hadd2_bf(uint32_t a, uint32_t b) {
  uint32_t r;
  asm("add.rn.bf16x2 %0, %1, %2;" : "=r"(r) : "r"(a), "r"(b));
  return r;
}
__device__ __forceinline__ uint32_t ln_apply(uint32_t h, uint32_t nm2, float inv_s) {
  const uint32_t d = hadd2_bf(h, nm2);
  return pack_bf16(bf_lo(d) * inv_s, bf_hi(d) * inv_s);
}
__device__ __forceinline__ void mma16816(float* d, uint32_t a0, uint32_t a1, uint32_t a2, uint32_t a3, uint32_t b0, uint32_t b1) {
  asm volatile("mma.sync.aligned.m16n8k16.row.col.f32.bf16.bf16.f32 {%0,%1,%2,%3}, {%4,%5,%6,%7}, {%8,%9}, {%0,%1,%2,%3};"
               : "+f"(d[0]), "+f"(d[1]), "+f"(d[2]), "+f"(d[3]) : "r"(a0), "r"(a1), "r"(a2), "r"(a3), "r"(b0), "r"(b1));
}

constexpr float AT_C = 0.08838834764831845f * 1.4426950408889634f;
#define L_MIN 3.5527137e-15f
#define L_MAX 1.8446744e19f
struct AtState {
  float S[64], O[64];
  uint32_t P[32], Q[32];
  float l[4];
};
template <int I0, int I1>
__device__ __forceinline__ void at_exp(AtState& s) {
#pragma unroll
  for (int i = I0; i < I1; i++) asm volatile("ex2.approx.ftz.f32 %0, %0;" : "+f"(s.S[i]));
#pragma unroll
  for (int i = I0; i < I1; i++) asm volatile("add.f32 %0, %0, %1;" : "+f"(s.l[i & 3]) : "f"(s.S[i]));
}
template <int I0, int I1>
__device__ __forceinline__ void at_pack(AtState& s) {
#pragma unroll
  for (int i = I0; i < I1; i++) asm volatile("cvt.rn.bf16x2.f32 %0, %1, %2;" : "=r"(s.P[i]) : "f"(s.S[2 * i + 1]), "f"(s.S[2 * i]));
}
template <int J0>
__device__ __forceinline__ void at_mask(AtState& s, int r, int lane) {
  const int d = r + (lane >> 2) - (lane & 3) * 2;
#pragma unroll
  for (int j = 0; j < 8; j++) {
    float dummy0 = 0.f, dummy1 = 0.f;
    float& lo0 = j < 7 ? s.S[4 * (J0 + (j < 7 ? j + 1 : j)) + 2] : dummy0;
    float& lo1 = j < 7 ? s.S[4 * (J0 + (j < 7 ? j + 1 : j)) + 3] : dummy1;
    asm("{\n.reg .pred p, q;\nsetp.lt.s32 p, %4, %5;\nsetp.le.s32 q, %4, %5;\n"
        "@p add.f32 %0, %0, 0fFF800000;\n@q add.f32 %1, %1, 0fFF800000;\n@p add.f32 %2, %2, 0fFF800000;\n@q add.f32 %3, %3, 0fFF800000;\n}"
        : "+f"(s.S[4 * (J0 + j)]), "+f"(s.S[4 * (J0 + j) + 1]), "+f"(lo0), "+f"(lo1) : "r"(d), "r"(8 * j));
  }
}
template <int D>
__device__ __forceinline__ uint32_t ld_pair(const __nv_bfloat16* p) {
  uint32_t r;
  asm volatile("{\n.reg .b16 a, b;\nld.global.cg.b16 a, [%1];\nld.global.cg.b16 b, [%1 + %2];\nmov.b32 %0, {a, b};\n}" : "=r"(r) : "l"(p), "n"(2 * D) : "memory");
  return r;
}
__device__ __forceinline__ uint32_t ld_word(const uint32_t* p) {
  uint32_t r;
  asm volatile("ld.global.cg.b32 %0, [%1];" : "=r"(r) : "l"(p) : "memory");
  return r;
}
__device__ __noinline__ void slow_rows(const __nv_bfloat16* wq, int head, int row0) {
  const int lane = fresh_lane(), r = lane >> 2, c = lane & 3;
  uint32_t q[32];
  float o[32];
#pragma unroll
  for (int i = 0; i < 32; i++) q[i] = 0;
  const uint32_t* xa = reinterpret_cast<const uint32_t*>(g_xn + (size_t)(row0 + r) * DM) + c;
#pragma unroll 1
  for (int h = 0; h < 2; h++) {
    const __nv_bfloat16* wb = wq + (size_t)2 * c * NQ + head * HD + 64 * h + 8 * (r >> 1) + (r & 1);
#pragma unroll
    for (int i = 0; i < 32; i++) o[i] = 0.f;
#pragma unroll 1
    for (int kk = 0; kk < DM / 16; kk++) {
      const uint32_t a0 = ld_word(xa + 8 * kk), a1 = ld_word(xa + 8 * kk + 4 * DM), a2 = ld_word(xa + 8 * kk + 4), a3 = ld_word(xa + 8 * kk + 4 * DM + 4);
#pragma unroll
      for (int n = 0; n < 8; n++) {
        const __nv_bfloat16* b = wb + (size_t)16 * kk * NQ + 32 * (n >> 2) + 2 * (n & 3);
        mma16816(o + 4 * n, a0, a1, a2, a3, ld_pair<NQ>(b), ld_pair<NQ>(b + 8 * NQ));
        if (n & 1) sched_fence();
      }
    }
#pragma unroll
    for (int i = 0; i < 16; i++) { q[i] = q[16 + i]; q[16 + i] = pack_bf16(o[2 * i] * AT_C, o[2 * i + 1] * AT_C); }
  }
#pragma unroll 1
  for (int h = 0; h < 2; h++) {
    float m0 = -INFINITY, m1 = -INFINITY, l0 = 0.f, l1 = 0.f;
#pragma unroll
    for (int i = 0; i < 32; i++) o[i] = 0.f;
#pragma unroll 1
    for (int k0 = 0; k0 <= row0; k0 += 16) {
      float e[8] = {0.f, 0.f, 0.f, 0.f, 0.f, 0.f, 0.f, 0.f};
      const __nv_bfloat16* kt = g_kv + (size_t)(head * 16 + (k0 >> 7)) * KV_TILE + (k0 & 127) * 32;
      const uint32_t* kp = reinterpret_cast<const uint32_t*>(kt + r * 32) + c;
#pragma unroll
      for (int kk = 0; kk < 8; kk++) {
        const uint32_t* k0p = kp + (kk >> 1) * 2048 + (((kk & 1) * 2) ^ (r >> 1)) * 4;
        const uint32_t* k1p = kp + (kk >> 1) * 2048 + (((kk & 1) * 2 + 1) ^ (r >> 1)) * 4;
        mma16816(e, q[4 * kk], q[4 * kk + 1], q[4 * kk + 2], q[4 * kk + 3], ld_word(k0p), ld_word(k1p));
        mma16816(e + 4, q[4 * kk], q[4 * kk + 1], q[4 * kk + 2], q[4 * kk + 3], ld_word(k0p + 128), ld_word(k1p + 128));
        if (kk & 1) sched_fence();
      }
      if (k0 == row0) {
#pragma unroll
        for (int i = 0; i < 8; i++) if ((i >> 2) * 8 + 2 * c + (i & 1) > r + (i & 2) * 4) e[i] = -INFINITY;
      }
      float a0 = fmaxf(fmaxf(e[0], e[1]), fmaxf(e[4], e[5])), a1 = fmaxf(fmaxf(e[2], e[3]), fmaxf(e[6], e[7]));
      a0 = fmaxf(a0, __shfl_xor_sync(~0u, a0, 1)); a1 = fmaxf(a1, __shfl_xor_sync(~0u, a1, 1));
      a0 = fmaxf(a0, __shfl_xor_sync(~0u, a0, 2)); a1 = fmaxf(a1, __shfl_xor_sync(~0u, a1, 2));
      a0 = fmaxf(a0, m0); a1 = fmaxf(a1, m1);
      const float sc0 = ex2(m0 - a0), sc1 = ex2(m1 - a1);
      m0 = a0; m1 = a1;
#pragma unroll
      for (int i = 0; i < 8; i++) e[i] = ex2(e[i] - ((i & 2) ? m1 : m0));
      l0 = l0 * sc0 + (e[0] + e[1]) + (e[4] + e[5]);
      l1 = l1 * sc1 + (e[2] + e[3]) + (e[6] + e[7]);
      const uint32_t p0 = pack_bf16(e[0], e[1]), p1 = pack_bf16(e[2], e[3]), p2 = pack_bf16(e[4], e[5]), p3 = pack_bf16(e[6], e[7]);
      const __nv_bfloat16* vp = kt + (size_t)512 * KV_TILE + h * 8192 + 2 * c * 32 + r;
#pragma unroll
      for (int n = 0; n < 8; n++) {
        o[4 * n] *= sc0; o[4 * n + 1] *= sc0; o[4 * n + 2] *= sc1; o[4 * n + 3] *= sc1;
        mma16816(o + 4 * n, p0, p1, p2, p3, ld_pair<32>(vp + (n >> 2) * 4096 + ((n ^ c) & 3) * 8), ld_pair<32>(vp + (n >> 2) * 4096 + ((n ^ c) & 3) * 8 + 256));
        if (n & 1) sched_fence();
      }
    }
    l0 += __shfl_xor_sync(~0u, l0, 1); l1 += __shfl_xor_sync(~0u, l1, 1);
    l0 += __shfl_xor_sync(~0u, l0, 2); l1 += __shfl_xor_sync(~0u, l1, 2);
#pragma unroll
    for (int i = 0; i < 4; i++) {
      const float* v = o + 16 * (i >> 1) + 2 * (i & 1);
      const float f = __fdividef(1.f, (i & 1) ? l1 : l0);
      *reinterpret_cast<uint4*>(g_ctx + (size_t)((row0 >> 7) * 32 + head) * KV_TILE + (2 * h + (i >> 1)) * 4096 + ((row0 & 127) + r + (i & 1) * 8) * 32 + (c ^ (r >> 1)) * 8) =
          make_uint4(pack_bf16(v[0] * f, v[1] * f), pack_bf16(v[4] * f, v[5] * f), pack_bf16(v[8] * f, v[9] * f), pack_bf16(v[12] * f, v[13] * f));
    }
  }
}

constexpr int UNIT = 16384, SLOT = 32768;
constexpr int OFF_SIDE = 2 * SLOT;
__host__ __device__ constexpr int kv_a(int kb) { return (kb < 6 ? kb : 3 * kb - 10) * UNIT; }
__host__ __device__ constexpr int kv_b(int s) { return ((0x76DCA9 >> (4 * s)) & 15) * UNIT; }
__host__ __device__ constexpr int q_aw(int s) { return (3 * s + (s & 1)) * UNIT; }
__host__ __device__ constexpr int q_b(int s) { return (3 * s + 2 - 2 * (s & 1)) * UNIT; }
__host__ __device__ constexpr int k_slot(int j, int r) { return (j < 2 ? 2 * j : (r == 2 ? 0 : 3 + r)) * SLOT; }
__host__ __device__ constexpr int v_slot(int j) { return (6 - (j & 1)) * SLOT; }
__host__ __device__ constexpr int r3(int st) { return ((0x654130 >> (4 * st)) & 7) * SLOT; }
constexpr int OFF_BAR = 229376;
constexpr int OFF_MISC = OFF_BAR + 512;
constexpr int SMEM_BYTES = OFF_MISC + 2080 + TL_EXTRA;
constexpr int OFF_RSTAT = OFF_MISC + 1056;
enum : int {
  B_FULL1 = 0, B_FULLQ = 6, B_FULLB = 10, B_KF = 11, B_VF = 14, B_FULL3 = 16, B_WF = 22, B_DEP = 24, B_OUT2 = 29, B_PF = 30, B_SET = 31,
  B_SET2 = 32, B_LNGO = 33, B_WR = 34,
  B_KE = 35, B_VE = 38, B_WE = 40, B_PUB = 42, B_OUT = 48,
  B_EMPTY1 = 49, B_EMPTYQ = 55, B_X = 59, B_EMPTY3 = 63,
  B_NUM = 69
};
#define TUNABLE(name, v) constexpr int name = v
TUNABLE(LN_GO, 3);
TUNABLE(EP1, 2);
TUNABLE(SIDE_NS, 400);
TUNABLE(SET_KB, 44); TUNABLE(SET_NS, 40);
TUNABLE(PF_KB, 54); TUNABLE(PF_N, 7); TUNABLE(PF_NS, 300);
TUNABLE(PS_DLY, 120); TUNABLE(Y_DLY, 700); TUNABLE(Y_DLY0, 1500);
constexpr int PRE = 6;
constexpr int WIN = 6;
constexpr int OFF_STG = r3(0), OFF_SCR = r3(1);
struct Params {
  CUtensorMap xn, ckv, wq, wk, wv, wo, x, wd, wg, wu;
};

__global__ void __cluster_dims__(2, 1, 1) __launch_bounds__(384, 1)
fused_kernel(uint32_t zero, const __nv_bfloat16* __restrict__ x, __nv_bfloat16* g_kv, __nv_bfloat16* g_ctx, uint4* g_xr,
             __nv_bfloat16* __restrict__ out, __nv_bfloat16* g_xn, unsigned* g_cnt, const __nv_bfloat16* __restrict__ w_r,
             const __nv_bfloat16* __restrict__ wdown, const __nv_bfloat16* __restrict__ wq, const __grid_constant__ Params p) {
  extern __shared__ __align__(1024) uint8_t sp[];
  const uint32_t sb = s2u(sp);
  const uint32_t bar = sb + OFF_BAR;
  auto B = [&](int i) { return bar + 8 * i; };
  const int tid = threadIdx.x, warp = __shfl_sync(~0u, tid >> 5, 0), wg = warp >> 2, lane = tid & 31;
  const int cta = blockIdx.x, rank = cta & 1, cl = cta >> 1;
  const int mp = cl < 4 ? 1 : (cl < 36 ? (cl & 7) : (0x3207654 >> (4 * ((cl - 36) % 7))) & 7);
  const int gq = cl < 4 ? 4 + cl : (cl < 36 ? (cl - 4) >> 3 : 4 + (cl - 36) / 7);
  const int mt = 2 * mp + rank;
  const int qa = 15 - gq;
  const int ta = gq ? gq : 15, tb = 15 - ta;
  const int rid = mt * 8 + gq;
  const int fid = mt * 7 + gq;
  const bool ffn = gq < 7;
  TL(0, 0, warp == 4);
  auto load_pre = [&](int i) {
    e_expect(B(B_FULL1 + i), (i & 1) ? UNIT : 2 * UNIT);
    if (!(i & 1)) tma_ld2(sb + kv_a(i >> 1), &p.ckv, B(B_FULL1 + i), i * 32, mt * 128);
    tma_ld3(sb + kv_b(i) + rank * 8192, &p.wk, B(B_FULL1 + i), 0, i * 32, (gq + 8) * 4 + rank * 2);
    tma_ld3(sb + kv_b(i) + 8192 - rank * 8192, &p.wk, B(B_FULL1 + i), 0, i * 32, (gq + 8) * 4 + 2 - rank * 2);
  };
  if (warp == 0) {
    e_init(B(B_FULL1), 1);
    asm volatile("fence.mbarrier_init.release.cluster;" ::: "memory");
    TL(0, 16, true);
    load_pre(0);
    TL(0, 17, true);
#pragma unroll
    for (int kb = 1; kb < PRE; kb++) e_init(B(B_FULL1 + kb), 1);
  } else {
#pragma unroll 1
    for (int i = PRE - 1 + warp; i < B_NUM; i += 11) e_init(B(i), i >= B_EMPTY1 ? 16 : (i >= B_KE ? 8 : (i == B_WR ? 2 : 1)));
  }
  asm volatile("fence.mbarrier_init.release.cluster;" ::: "memory");
  cluster_arrive();
  const int rid0 = rid, warp0 = warp;
  if (wg == 0) {
    reg_dealloc<40>();
    if (warp == 0) {
      TL(0, 12, true);
#pragma unroll 1
      for (int kb = 1; kb < PRE; kb++) load_pre(kb);
      if (mt >= PRE) { tma_pf3(&p.wk, 0, mt * 32, (gq + 8) * 4); tma_pf3(&p.wk, 0, mt * 32, (gq + 8) * 4 + 2); }
      if (gq >= PRE / 2) tma_pf2(&p.ckv, gq * 64, mt * 128);
      TL(0, 15, true);
    }
    TL(0, 18, warp == 0);
    __syncwarp();
    cluster_wait();
    uint4* const xr = g_xr + rid * XR_SIZE;
    auto side_piece = [&](int c, int piece) {
      const uint32_t fb = B(B_WF + (c & 1));
      if (piece == 0) e_expect(fb, ffn ? UNIT : 0);
      if (ffn) tma_ld2_ef(sb + OFF_SIDE + (c & 1) * UNIT + piece * 4096, (piece & 2) ? &p.wg : &p.wu, fb, fid * 32, c * 128 + (piece & 1) * 64);
    };
    if (warp == 0) {
      {
        int st = 0; uint32_t ph = 0;
#pragma unroll 1
        for (int i = PRE; i < 64; i++) {
          const int t = i >> 4, h = i & 15;
          const uint32_t fb = B(B_FULL1 + st);
          const bool with_a = (i & 0x31) == 0;
          mbar_wait_c(B(B_EMPTY1 + st), ph);
          e_expect(fb, with_a ? 2 * UNIT : UNIT);
          if (with_a) tma_ld2(sb + kv_a(h >> 1), &p.ckv, fb, h * 32, mt * 128);
          tma_ld3_mc(sb + kv_b(st) + rank * 8192, (t & 1) ? &p.wv : &p.wk, fb, 0, h * 32, (gq + ((t >> 1) ^ 1) * 8) * 4 + rank * 2, 3);
          if (i == 2 * LN_GO) e_arrive(B(B_LNGO));
          if (i == 24) { prefetch_tm(&p.wq); prefetch_tm(&p.xn); }
          if ((h >> 1) == (t ? 0 : 4) && t < 3) tma_pf3((t & 1) ? &p.wk : &p.wv, 0, mt * 32, (gq + (((t + 1) >> 1) ^ 1) * 8) * 4 + (h & 1) * 2);
          if ((i | 2) == 50) tma_pf3(&p.wq, 0, (gq + 4 * h) * 64, mt * 2);
          if (++st == 6) { st = 0; ph ^= 1; }
        }
        prefetch_tm(&p.wo); prefetch_tm(&p.wd); prefetch_tm(&p.x); prefetch_tm(&p.wg); prefetch_tm(&p.wu);
        mbar_wait_c(B(B_DEP + 0), 0);
        uint32_t kpar = 7, vpar = 3;
        auto load_aw = [&](int kb, int head) {
          const uint32_t d = sb + q_aw(kb & 3), fb = B(B_FULLQ + (kb & 3));
          tma_ld2_mc(d + rank * 8192, &p.xn, fb, kb * 64, ta * 128 + rank * 64, 3);
          tma_ld3(d + UNIT, &p.wq, fb, 0, kb * 64, head * 2);
        };
        auto load_b = [&](int kb, uint32_t fb) { tma_ld2_mc(sb + q_b(kb & 3) + rank * 8192, &p.xn, fb, kb * 64, tb * 128 + rank * 64, 3); };
        auto load3 = [&](int kb, int s) {
          const uint32_t d = sb + r3(s), fb = B(B_FULL3 + s);
          e_expect(fb, SLOT);
          bulk_ld(d, g_ctx + (size_t)(mt * 64 + kb) * 8192, UNIT, fb);
          tma_ld3_mc(d + UNIT + rank * 8192, &p.wo, fb, 0, kb * 64, gq * 2 + rank, 3);
        };
#pragma unroll 1
        for (int half = 0; half < 2; half++) {
          const int head = mt + 16 * half;
#pragma unroll 1
          for (int kb = 2 * half; kb < 16; kb++) {
            if (kb >= 4) mbar_wait_c(B(B_EMPTYQ + (kb & 3)), ((kb >> 2) & 1) ^ 1);
            else if (half) mbar_wait_c(B(B_X + 2), 0);
            else if (kb > 0) mbar_wait_c(B(B_EMPTY1 + (2 * kb + 3) % 6), kb == 1);
            e_expect(B(B_FULLQ + (kb & 3)), 3 * UNIT);
            load_aw(kb, head);
            load_b(kb, B(B_FULLQ + (kb & 3)));
          }
          mbar_wait_c(B(B_DEP + 1 + half), 0);
          const __nv_bfloat16* kt = g_kv + (size_t)head * 16 * KV_TILE;
          l2_prefetch(kt, SLOT);
          auto load_v = [&](int j) {
            const int r = j & 1;
            mbar_wait_c(B(B_VE + r), (vpar >> r) & 1);
            vpar ^= 1 << r;
            e_expect(B(B_VF + r), SLOT);
            bulk_ld(sb + v_slot(j), kt + (size_t)(512 + (j > qa ? 16 - j : j)) * KV_TILE, SLOT, B(B_VF + r));
          };
          int r = 0;
#pragma unroll 1
          for (int j = 0; j < 17; j++) {
            if (j < 2) mbar_wait_c(B(B_EMPTYQ + j), 1);
            if (j == 2) mbar_wait_c(B(B_KE), kpar & 1);
            mbar_wait_c(B(B_KE + r), (kpar >> r) & 1);
            kpar ^= 1 << r;
            e_expect(B(B_KF + r), SLOT);
            bulk_ld(sb + k_slot(j, r), kt + (j > qa ? 16 - j : j) * KV_TILE, SLOT, B(B_KF + r));
            if (++r == 3) r = 0;
            if (j == 2) mbar_wait_c(B(B_EMPTYQ + 3), 1);
            if (j != 1) load_v(j ? j - 1 : 0);
            if (half == 0) {
              if (j == 16) {
                tma_pf3(&p.wq, 0, (4 + gq) * 64, (mt + 16) * 2);
                tma_pf2(&p.xn, (4 + (mp & 3)) * 64, ((mp & 4) ? qa : gq) * 128 + rank * 64);
              }
            } else if (j >= 14) {
              tma_pf3(&p.wo, 0, (5 + mp + 8 * (16 - j)) * 64, gq * 2 + rank);
            } else if (j >= 5 && j < 13) {
              side_piece((j - 5) >> 2, (j - 5) & 3);
            }
          }
          mbar_wait_c(B(B_X + 0), half);
          if (half == 0) {
            for (int kb = 0; kb < 2; kb++) { e_expect(B(B_FULLQ + kb), 2 * UNIT); load_aw(kb, mt + 16); }
          } else {
            mbar_wait_c(B(B_DEP + 3), 0);
            load3(0, 0);
          }
          mbar_wait_c(B(B_X + 1), half);
          if (half) load3(1, 1);
          load_v(16);
          if (gq == 0) mbar_wait_c(B(B_X + 2), half);
          if (half == 0) { e_expect(B(B_FULLB), 2 * UNIT); load_b(0, B(B_FULLB)); load_b(1, B(B_FULLB)); }
        }
        st = 2; ph = 1;
#pragma unroll 1
        for (int kb = 2; kb < 64; kb++) {
          if (kb == 32) mbar_wait_c(B(B_DEP + 4), 0);
          if (kb >= 6) mbar_wait_c(B(B_EMPTY3 + st), ph);
          else if (kb == 3 || kb == 5) mbar_wait_c(B(B_X + (kb + 1) / 2), 1);
          load3(kb, st);
          if (++st == 6) { st = 0; ph ^= 1; }
          if (kb == PF_KB) e_arrive(B(B_PF));
          if (kb == SET_KB) e_arrive(B(B_SET));
          if (kb == 58) l2_prefetch(xr, XR_CAND * 16);
        }
        if (ffn) {
#pragma unroll 1
          for (int j = 0; j < 2; j++) {
            mbar_wait_c(B(B_EMPTY3 + 4 + j), 1);
            e_expect(B(B_FULL3 + 4 + j), SLOT);
            tma_ld3(sb + r3(4 + j), &p.wd, B(B_FULL3 + 4 + j), 0, fid * 32, 8 * j);
          }
        }
        const uint4* kp = g_xr + ((lane >> 1) * 8 + gq) * XR_SIZE + XR_KEY + (lane & 1) * 2;
        mbar_wait_c(B(B_OUT), 0);
        uint32_t k1, k2, m1;
#pragma unroll 1
        for (int n = 0; n < 0x400000; n++) {
          uint4 a, b;
          asm volatile("ld.relaxed.gpu.global.v4.u32 {%0,%1,%2,%3}, [%4];" : "=r"(a.x), "=r"(a.y), "=r"(a.z), "=r"(a.w) : "l"(kp) : "memory");
          asm volatile("ld.relaxed.gpu.global.v4.u32 {%0,%1,%2,%3}, [%4 + 16];" : "=r"(b.x), "=r"(b.y), "=r"(b.z), "=r"(b.w) : "l"(kp) : "memory");
          const uint32_t a1 = max(a.x, a.z), a2 = max(min(a.x, a.z), max(a.y, a.w));
          const uint32_t b1 = max(b.x, b.z), b2 = max(min(b.x, b.z), max(b.y, b.w));
          k1 = max(a1, b1); k2 = max(min(a1, b1), max(a2, b2));
          m1 = __reduce_max_sync(~0u, max(k1, k2));
          if (m1 != 0xFFFFFFFFu) break;
        }
        const uint32_t m2 = __reduce_max_sync(~0u, k1 == m1 ? k2 : k1);
        const uint32_t t0 = ~m1 & 0x7FFF, t1 = ~m2 & 0x7FFF;
        const uint32_t o0 = (t0 >> 7) * (8 * XR_SIZE * 16) + (t0 & 0x70) * 64, o1 = (t1 >> 7) * (8 * XR_SIZE * 16) + (t1 & 0x70) * 64 + ((t0 ^ t1) < 16 ? 256 : 0);
        asm volatile(ELECT "st.shared.v4.u32 [%0], {%1,%2,%3,%4};\n}" ::"r"(sb + OFF_MISC + 256), "r"(o0), "r"(o1), "r"(m1), "r"(m2) : "memory");
        e_arrive(B(B_OUT2));
        if (rid == 127) { g_cnt[lane] = 0; g_cnt[32 + lane] = 0; }
      }
    } else {
      if (warp >= 2) {
#pragma unroll 1
        for (int i = tid - 64; i < XR_CAND; i += 64) xr[i] = make_uint4(~0u, ~0u, ~0u, ~0u);
        if (warp == 2) { __syncwarp(); if (lane == 0) mbar_arrive(B(B_WR)); }
      }
      if (warp == 3) {
        float ws = 0.f;
#pragma unroll 1
        for (int j = 0; j < 4; j++) {
          const uint4 q = __ldg(reinterpret_cast<const uint4*>(w_r) + j * 32 + lane);
          ws += bf_lo(q.x) + bf_hi(q.x) + bf_lo(q.y) + bf_hi(q.y) + bf_lo(q.z) + bf_hi(q.z) + bf_lo(q.w) + bf_hi(q.w);
        }
#pragma unroll
        for (int o = 16; o; o >>= 1) ws += __shfl_xor_sync(~0u, ws, o);
        uint2* tab = reinterpret_cast<uint2*>(sp + OFF_MISC + 512);
        tab[lane] = make_uint2(0x3F803F80u, 0x3F803F80u);
        tab[32 + lane] = __ldg(reinterpret_cast<const uint2*>(w_r + gq * 128) + lane);
        if (lane == 0) *reinterpret_cast<float*>(sp + OFF_MISC + 1024) = ws;
        __syncwarp();
        if (lane == 0) mbar_arrive(B(B_WR));
      }
      __syncwarp();
      mbar_wait_u(B(B_LNGO), 0);
#pragma unroll 1
      for (int r = warp == 2 ? 0 : (warp + 1) >> 1; r < 16; r += 3) {
        const uint4* src = reinterpret_cast<const uint4*>(x + (size_t)(cta * 16 + r) * DM) + lane;
        uint4 v[4];
#pragma unroll
        for (int j = 0; j < 4; j++) v[j] = __ldcs(src + j * 32);
        float a0 = 0.f, a1 = 0.f, b0 = 0.f, b1 = 0.f;
#pragma unroll
        for (int j = 0; j < 4; j++) {
          const uint32_t u[4] = {v[j].x, v[j].y, v[j].z, v[j].w};
#pragma unroll
          for (int i = 0; i < 4; i++) { const float a = bf_lo(u[i]), b = bf_hi(u[i]); a0 += a; a1 += b; b0 = fmaf(a, a, b0); b1 = fmaf(b, b, b1); }
        }
        a0 += a1; b0 += b1;
#pragma unroll
        for (int o = 16; o; o >>= 1) { a0 += __shfl_xor_sync(~0u, a0, o); b0 += __shfl_xor_sync(~0u, b0, o); }
        const float mean = a0 * (1.f / DM);
        float mb, inv;
        ln_round(mean, fmaxf(fmaf(b0, 1.f / DM, -mean * mean), 0.f), mb, inv);
        const uint32_t nm2 = pack_bf16(-mb, -mb);
        uint4* dst = reinterpret_cast<uint4*>(g_xn + (size_t)(cta * 16 + r) * DM) + lane;
#pragma unroll
        for (int j = 0; j < 4; j++) {
          dst[j * 32] = make_uint4(ln_apply(v[j].x, nm2, inv), ln_apply(v[j].y, nm2, inv), ln_apply(v[j].z, nm2, inv), ln_apply(v[j].w, nm2, inv));
          sched_fence();
        }
      }
      __syncwarp();
      if (lane == 0) {
        fence_gpu();
        red_add(&g_cnt[C_LN + (cta >> 3)], 1);
        TL(0, 20 + warp, true);
        if (warp == 3) {
          spin_until_ge<true>(&g_cnt[C_LN + gq], 24);
#pragma unroll 1
          for (int i = 0; i < 5; i++) {
            const int c = i == 0 ? C_LN + qa : (i < 3 ? C_KV + (i - 1) * 8 + mp : C_CTX + (i - 3) * 16 + mt);
            spin_until_ge<true>(&g_cnt[c], i == 0 ? 24 : 16);
            fence_async_all();
            mbar_arrive(B(B_DEP + i));
          }
        } else if (warp == 1) {
          mbar_wait(B(B_WR), 0);
#pragma unroll 1
          for (int i = 0; i < 6; i++) {
            const int c = i < 2 ? C_KV + gq + (i ^ 1) * 8 : C_CTX + ((i - 2) >> 1) * 16 + ((i & 1) ? tb : ta);
            mbar_wait(B(B_PUB + i), 0);
            fence_gpu();
            red_add(&g_cnt[c], 1);
          }
        }
      }
      __syncwarp();
      if (warp == 2) {
#pragma unroll 1
        for (int c = 2; c < WIN + 4; c++) {
          mbar_wait_u(B(B_WE + (c & 1)), ((c >> 1) & 1) ^ 1);
          if (c == WIN || c == WIN + 1) {
            e_expect(B(B_WF + (c & 1)), UNIT);
            tma_ld3_ef(sb + OFF_SIDE + (c & 1) * UNIT, &p.x, B(B_WF + (c & 1)), 0, mt * 128 + (c & 1) * 64, gq * 2);
          } else {
#pragma unroll 1
            for (int i = 0; i < 4; i++) { side_piece(c < WIN ? c : c - 2, i); __nanosleep(SIDE_NS); }
          }
        }
      } else if (warp == 1) {
        mbar_wait_u(B(B_SET), 0);
#pragma unroll 1
        for (int i = XR_CAND + lane; i < XR_SIZE; i += 32) { xr[i] = make_uint4(~0u, ~0u, ~0u, ~0u); __nanosleep(SET_NS); }
        __syncwarp();
        if (lane == 0) { fence_gpu(); mbar_arrive(B(B_SET2)); }
      } else {
        mbar_wait_u(B(B_PF), 0);
#pragma unroll 1
        for (int i = 0; i < PF_N; i++) {
          asm volatile("prefetch.global.L2 [%0];" ::"l"((const char*)wdown + (size_t)cta * 57344 + (i * 32 + lane) * 128));
          __nanosleep(PF_NS);
        }
      }
      __syncwarp();
      mbar_wait_u(B(B_OUT), 0);
      {
        const int sub = lane >> 4;
        const uint32_t src = sb + OFF_STG + ((lane & 15) >> 3) * 8192 + sub * 128;
        __nv_bfloat16* dst = out + (size_t)(mt * 128 + sub) * DM + gq * 128 + (lane & 15) * 8;
        auto ld = [&](int r, uint2& rs, uint4& v) {
          asm volatile("ld.shared.v2.u32 {%0,%1}, [%2];" : "=r"(rs.x), "=r"(rs.y) : "r"(sb + OFF_RSTAT + ((r + sub) & 127) * 8));
          v = lds128(src + ((r >> 6) & 1) * 16384 + (r & 63) * 128 + (((lane ^ (r + sub)) & 7) << 4));
        };
        uint2 rs; uint4 v;
        ld(2 * warp - 2, rs, v);
#pragma unroll 1
        for (int r = 2 * warp - 2; r < 128; r += 6) {
          const uint2 cs = rs; const uint4 c = v;
          ld(r + 6, rs, v);
          const float inv = __uint_as_float(cs.y);
          asm volatile("{\n.reg .pred p;\nsetp.ge.s32 p, %5, 0;\n@p st.global.v4.u32 [%0], {%1,%2,%3,%4};\n}" ::"l"(dst + (size_t)r * DM),
                       "r"(hadd2_bf(c.x, ln_apply(c.x, cs.x, inv))), "r"(hadd2_bf(c.y, ln_apply(c.y, cs.x, inv))),
                       "r"(hadd2_bf(c.z, ln_apply(c.z, cs.x, inv))), "r"(hadd2_bf(c.w, ln_apply(c.w, cs.x, inv))), "r"(cs.y) : "memory");
        }
      }
      TL(2, 25, warp == 1);
    }
    __syncwarp();
    cluster_arrive();
    cluster_wait();
  } else {
    reg_alloc<232>();
    const int rid_c = rid0 + zero, warp_c = warp0 + zero;
    const int lane = fresh_lane(), rid = rid_c, mt = rid >> 3, gq = rid & 7, qa = 15 - gq, ta = gq ? gq : 15, tb = 15 - ta;
    const int warp = warp_c, cw = warp - 4, w = cw >> 2;
    cluster_wait();
    auto publish = [&](int i) { __syncwarp(); e_arrive(B(B_PUB + i)); };
    auto release2 = [&](uint32_t b, bool cond = true) { mbar_arrive_both(b, lane, cond); };
    AtState s;
    const uint32_t dA = mk_desc(sb + w * 8192, 16);
    const uint32_t dW = mk_desc(sb, 8192);
    auto mma_kb = [&](float (&d)[64], uint32_t a, uint32_t b, int accum) {
      static_for<4>([&](auto k) { mma_n128_ss<1, k * 32, k * 2048>(d, dA + (a >> 4), dW + (b >> 4), k == 0 ? accum : 1); });
    };
    auto mma_kc = [&](float (&d)[64], auto a, auto b, int accum) {
      static_for<4>([&](auto k) { mma_n128_ss<1, decltype(a)::value + k * 32, decltype(b)::value + k * 2048>(d, dA, dW, k == 0 ? accum : 1); });
    };
    auto issue_q = [&](int kb, auto accum) {
      const int st = kb & 3;
      if (accum) mbar_wait_c(B(B_FULLQ + st), (kb >> 2) & 1);
      wg_fence();
      mma_kb(s.S, q_aw(st), q_aw(st) + UNIT, accum);
      wg_commit();
      if (accum) {
        wg_wait<1>();
        release2(B(B_EMPTYQ + ((kb - 1) & 3)));
        wg_fence();
      }
      mma_kb(s.O, q_b(st), q_aw(st) + UNIT, accum);
      wg_commit();
    };
    {
      uint4 pk[16];
      __nv_bfloat16* pdst = g_kv;
      auto put = [&](int i) { __stcs(reinterpret_cast<uint4*>(pdst + (i & 1) * 256 + ((i >> 1) & 3) * 4096 + (i >> 3) * 16 * KV_TILE), pk[i]); };
      float acc1[128];
      TL(0, 1, warp == 4);
      int st = 0; uint32_t ph = 0;
      const uint32_t dH = mk_desc(sb, 4096);
      mbar_wait_c(B(B_FULL1), 0);
      auto issue = [&](int h, auto accum) {
        if (accum) mbar_wait_c(B(B_FULL1 + st), ph);
        wg_fence();
        static_for<2>([&](auto k) { mma_n256_ss<1, k * 32, k * 2048>(acc1, dA + (kv_a(h >> 1) >> 4) + (h & 1) * 4, dH + (kv_b(st) >> 4), k == 0 ? (int)accum : 1); });
        wg_commit();
      };
#pragma unroll 1
      for (int t = 0; t < 4; t++) {
        issue(0, IC<0>{});
        TL(0, 2 + 2 * t, warp == 4);
        if (t > 0) { put(0); put(1); }
        int prev = st;
        if (++st == 6) { st = 0; ph ^= 1; }
#pragma unroll 1
        for (int h = 1; h < 16; h++) {
          if (h == 14 && w == 1) bar_sync(5, 256);
          issue(h, IC<1>{});
          if (h == 15 && w == 0) bar_arrive(5, 256);
          if (t > 0) {
#pragma unroll
            for (int i = 2; i < 16; i++) if (h == (i < 4 ? 1 : i - 2)) put(i);
            if (h == 13 && t == 2) publish(0);
          }
          wg_wait<1>();
          if (!(h & 1)) TK(24 + t * 8 + (h >> 1) - 1);
          release2(B(B_EMPTY1 + prev));
          prev = st;
          if (++st == 6) { st = 0; ph ^= 1; }
        }
        pdst = g_kv + (size_t)(((t & 1) * 32 + (gq + ((t >> 1) ^ 1) * 8) * 2) * 16 + mt) * KV_TILE + (cw * 16 + (lane >> 2)) * 32 + ((lane ^ (lane >> 3)) & 3) * 8;
        mbar_wait_c(B(t < 3 ? B_FULL1 + st : B_FULLQ), t < 3 ? ph : 0);
        wg_wait<0>();
        TK(24 + t * 8 + 7);
        fence_regs(acc1);
        release2(B(B_EMPTY1 + prev));
        TL(0, 3 + 2 * t, warp == 4);
#pragma unroll
        for (int a = 0; a < 8; a++)
#pragma unroll
          for (int h = 0; h < 2; h++)
            pk[2 * a + h] = make_uint4(pack_bf16(acc1[16 * a + 2 * h], acc1[16 * a + 2 * h + 1]), pack_bf16(acc1[16 * a + 4 + 2 * h], acc1[16 * a + 5 + 2 * h]),
                                       pack_bf16(acc1[16 * a + 8 + 2 * h], acc1[16 * a + 9 + 2 * h]), pack_bf16(acc1[16 * a + 12 + 2 * h], acc1[16 * a + 13 + 2 * h]));
      }
      issue_q(0, IC<0>{});
      TL(0, 10, warp == 4);
      put(0); put(1);
#pragma unroll 1
      for (int kb = 1; kb < 8; kb++) {
        issue_q(kb, IC<1>{});
        TK(66 + kb - 1);
#pragma unroll
        for (int i = 1; i < 8; i++) if (kb == i) { put(2 * i); put(2 * i + 1); }
      }
      publish(1);
      TL(0, 11, warp == 4);
    }
    __nv_bfloat16* cdst;
    uint32_t redo = 0;
    auto put_ctx = [&](int i, bool cond) {
      asm volatile("{\n.reg .pred p;\nsetp.ne.u32 p, %5, 0;\n@p st.global.cs.v4.u32 [%0], {%1,%2,%3,%4};\n}" ::"l"(cdst + (i & 1) * 256 + (i >> 1) * 4096),
                   "r"(s.P[4 * i]), "r"(s.P[4 * i + 1]), "r"(s.P[4 * i + 2]), "r"(s.P[4 * i + 3]), "r"((uint32_t)(cond && !(redo & 2))) : "memory");
    };
    {
      const int wrow = cw * 16;
      const uint32_t dK = mk_desc(sb, 16), dV = mk_desc(sb, 8192);
      uint32_t kph = 0, vph = 0;
      auto q_store = [&](const float (&d)[64]) {
        const int r0 = lane >> 2;
        const uint32_t a = sb + SLOT + (wrow + r0) * 128 + (((lane & 3) ^ (((r0 & 1) << 2) | (r0 >> 1))) << 4);
#pragma unroll
        for (int i = 0; i < 8; i++) {
          const float* o = d + 16 * (i >> 1) + 2 * (i & 1);
          asm volatile("st.shared.v4.u32 [%0], {%1,%2,%3,%4};" ::"r"((a ^ ((i & 2) << 5)) + (i >> 2) * UNIT + (i & 1) * 1024),
                       "r"(pack_bf16(o[0] * AT_C, o[1] * AT_C)), "r"(pack_bf16(o[4] * AT_C, o[5] * AT_C)),
                       "r"(pack_bf16(o[8] * AT_C, o[9] * AT_C)), "r"(pack_bf16(o[12] * AT_C, o[13] * AT_C)) : "memory");
        }
        __syncwarp();
      };
      auto q_load = [&](auto k0, auto k1) {
        const uint32_t a = sb + SLOT + (wrow + (lane & 15)) * 128 + (((lane >> 4) ^ (((lane & 1) << 2) | ((lane >> 1) & 3))) << 4);
#pragma unroll
        for (int k = k0; k < k1; k++)
          asm volatile("ldmatrix.sync.aligned.m8n8.x4.shared.b16 {%0,%1,%2,%3}, [%4];"
                       : "=r"(s.Q[4 * k]), "=r"(s.Q[4 * k + 1]), "=r"(s.Q[4 * k + 2]), "=r"(s.Q[4 * k + 3]) : "r"((a ^ ((k & 3) << 5)) + (k >> 2) * UNIT) : "memory");
      };
      auto q_load_if = [&](auto k, bool cond, float after) {
        const uint32_t a = sb + SLOT + (wrow + (lane & 15)) * 128 + (((lane >> 4) ^ (((lane & 1) << 2) | ((lane >> 1) & 3))) << 4);
        asm volatile("{\n.reg .pred p;\nsetp.ne.u32 p, %5, 0;\n@p ldmatrix.sync.aligned.m8n8.x4.shared.b16 {%0,%1,%2,%3}, [%4];\n}"
                     : "+r"(s.Q[4 * k]), "+r"(s.Q[4 * k + 1]), "+r"(s.Q[4 * k + 2]), "+r"(s.Q[4 * k + 3])
                     : "r"((a ^ ((k & 3) << 5)) + (k >> 2) * UNIT + (__float_as_uint(after) >> 31)), "r"((uint32_t)cond) : "memory");
      };
      auto issue_s = [&](uint32_t dk, auto mid) {
        mma_n128_rs0<0>(s.S, s.Q, dk);
        static_for<7>([&](auto i) {
          constexpr int k = i + 1;
          if (k == 4) mid();
          mma_n128_rs<0, (k >> 1) * 8192 + (k & 1) * 32>(s.S, s.Q + 4 * k, dk, 1);
        });
        wg_commit();
      };
      auto wait_v = [&](int jv) {
        mbar_wait_c(B(B_VF + (jv & 1)), (vph >> (jv & 1)) & 1);
        vph ^= 1 << (jv & 1);
      };
      auto issue_pva = [&](int jv, int accum) {
        wg_fence();
        static_for<4>([&](auto k) { mma_n128_rs<1, k * 1024>(s.O, s.P + 4 * k, dV + (v_slot(jv) >> 4), k == 0 ? accum : 1); });
        wg_commit();
      };
      auto issue_pvb = [&](int jv, bool upper) {
        if (upper) {
          wg_fence();
          static_for<4>([&](auto k) { mma_n128_rs<1, (k + 4) * 1024>(s.O, s.P + 16 + 4 * k, dV + (v_slot(jv) >> 4), 1); });
          wg_commit();
        } else {
          asm volatile("wgmma.fence.sync.aligned;\nwgmma.commit_group.sync.aligned;" ::: "memory");
        }
      };
      auto issue_pv = [&](int jv, int accum, bool upper) { wait_v(jv); issue_pva(jv, accum); issue_pvb(jv, upper); };
      if (w == 1) bar_arrive(1, 256);
#pragma unroll 1
      for (int half = 0; half < 2; half++) {
        const int head = mt + 16 * half;
        redo = 0;
        float inv[2];
        auto ep_prep = [&]() {
          float l0 = s.l[0] + s.l[1], l1 = s.l[2] + s.l[3];
          l0 += __shfl_xor_sync(~0u, l0, 1); l1 += __shfl_xor_sync(~0u, l1, 1);
          l0 += __shfl_xor_sync(~0u, l0, 2); l1 += __shfl_xor_sync(~0u, l1, 2);
          asm("rcp.approx.ftz.f32 %0, %1;" : "=f"(inv[0]) : "f"(l0));
          asm("rcp.approx.ftz.f32 %0, %1;" : "=f"(inv[1]) : "f"(l1));
          return __any_sync(~0u, !(fminf(l0, l1) >= L_MIN && l0 + l1 <= L_MAX));
        };
        auto ep_out = [&](auto i0, auto i1) {
          __nv_bfloat16* dst = g_ctx + (size_t)(ta * 32 + head) * KV_TILE + (wrow + (lane >> 2)) * 32 + ((lane ^ (lane >> 3)) & 3) * 8;
#pragma unroll
          for (int i = i0; i < i1; i++) {
            const float* o = s.O + 16 * (i >> 1) + 2 * (i & 1);
            const float c = inv[i & 1];
            asm volatile("st.global.cs.v4.u32 [%0], {%1,%2,%3,%4};" ::"l"(dst + (i & 1) * 256 + (i >> 1) * 4096), "r"(pack_bf16(o[0] * c, o[1] * c)),
                         "r"(pack_bf16(o[4] * c, o[5] * c)), "r"(pack_bf16(o[8] * c, o[9] * c)), "r"(pack_bf16(o[12] * c, o[13] * c)) : "memory");
          }
        };
        auto ep_rest = [&]() {
          ep_out(IC<EP1>{}, IC<8>{});
          if (!__any_sync(~0u, redo)) publish(2 + 2 * half);
          fence_regs(s.O);
        };
#pragma unroll 1
        for (int kb = 8; kb < 14; kb++) {
          issue_q(kb, IC<1>{});
          TK(66 + half * 24 + kb - 1);
        }
        TL(1, 20 * half + 0, warp == 4);
        mbar_wait_c(B(B_FULLQ + 2), 1);
        mbar_wait_c(B(B_FULLQ + 3), 1);
        bar_sync(1 + w, 256);
        wg_fence();
        mma_kc(s.S, IC<q_aw(2)>{}, IC<q_aw(2) + UNIT>{}, 1);
        wg_commit();
        wg_wait<1>();
        TK(66 + half * 24 + 13);
        release2(B(B_EMPTYQ + 1));
        wg_fence();
        mma_kc(s.S, IC<q_aw(3)>{}, IC<q_aw(3) + UNIT>{}, 1);
        wg_commit();
        bar_arrive(2 - w, 256);
        bar_sync(6 + w, 128);
        wg_wait<0>();
        TK(66 + half * 24 + 14);
        fence_regs(s.S);
        q_store(s.S);
        q_load(IC<0>{}, IC<8>{});
        TL(1, 20 * half + 1, warp == 4);
        TC(w, 17 * half, 0);
        mbar_wait_c(B(B_KF), kph & 1);
        kph ^= 1;
        bar_sync(1 + w, 256);
        TC(w, 17 * half, 2);
        fence_regs(s.O); fence_regs(s.Q);
        wg_fence();
        issue_s(dK, []() {});
        mma_kc(s.O, IC<q_b(2)>{}, IC<q_aw(2) + UNIT>{}, 1);
        mma_kc(s.O, IC<q_b(3)>{}, IC<q_aw(3) + UNIT>{}, 1);
        wg_commit();
        bar_arrive(2 - w, 256);
        wg_wait<1>();
        TC(w, 17 * half, 4);
        fence_regs(s.S);
        e_arrive(B(B_KE));
        s.l[0] = s.l[1] = s.l[2] = s.l[3] = 0.f;
        at_exp<0, 48>(s);
        at_pack<0, 22>(s);
        sched_fence();
        wg_wait<0>();
        fence_regs(s.O); fence_regs(s.Q);
        release2(B(B_EMPTYQ + 2)); release2(B(B_EMPTYQ + 3));
        at_exp<48, 64>(s);
        at_pack<22, 32>(s);
        q_store(s.O);
        TL(1, 20 * half + 2, warp == 4);
        int kr = 1;
        bool kok = false;
        inv[0] = inv[1] = 0.f;
        const int db = gq ? qa : 16;
#pragma unroll 1
        for (int j = 1; j < 17; j++) {
          const bool diag = j == ta || j == db;
          TC(w, j + 17 * half, 0);
          if (!kok) mbar_wait_c(B(B_KF + kr), (kph >> kr) & 1);
          kph ^= 1 << kr;
          if (j == ta + 2) ep_out(IC<0>{}, IC<EP1>{});
          bar_sync(1 + w, 256);
          TC(w, j + 17 * half, 2);
          fence_regs(s.O); fence_regs(s.P); fence_regs(s.Q);
          const uint32_t ke = B(B_KE + kr), dk = dK + (k_slot(j, kr) >> 4);
          if (++kr == 3) kr = 0;
          auto issue_rest = [&](auto trimmed) {
            TC(w, j + 17 * half, 1);
            if (j == ta + 1) {
              if (ep_prep()) redo = 1;
              s.l[0] = s.l[1] = s.l[2] = s.l[3] = 0.f;
            }
            if (!trimmed && j == ta + 2) ep_rest();
            TC(w, j + 17 * half, 3);
            if (trimmed) wait_v(j - 1);
            issue_pva(j - 1, j != 1 && j != ta + 2);
            issue_pvb(j - 1, w == 1 || (j != ta + 1 && j != db + 1));
            bar_arrive(2 - w, 256);
          };
          auto s_done = [&](auto n) {
            wg_wait<2>();
            TC(w, j + 17 * half, 4);
            fence_part<0, n>(s.S); fence_regs(s.Q);
            e_arrive(ke);
            release2(B(B_X + j - 14), j == 14 || j == 15);
          };
          auto pv_half = [&]() { sched_fence(); wg_wait<1>(); fence_regs(s.P); };
          auto pv_done = [&]() {
            sched_fence();
            wg_wait<0>();
            fence_regs(s.O); fence_regs(s.P);
            e_arrive(B(B_VE + ((j - 1) & 1)));
            release2(B(B_X + 2), j == 16);
            kok = mbar_test(B(B_KF + kr), (kph >> kr) & 1);
          };
          if (diag && w == 0) {
            wg_fence();
            static_for<8>([&](auto k) { mma_n64_rs<0, (k >> 1) * 8192 + (k & 1) * 32, k != 0>(s.S, s.Q + 4 * k, dk); });
            wg_commit();
            issue_rest(IC<1>{});
            s_done(IC<32>{});
            at_mask<0>(s, wrow, lane);
            pv_half();
            static_for<8>([&](auto k) {
              at_exp<4 * k, 4 * k + 4>(s);
              q_load_if(k, j == ta, s.S[4 * k]);
            });
            at_pack<0, 16>(s);
            pv_done();
          } else {
            wg_fence();
            issue_s(dk, [&]() { wait_v(j - 1); wg_fence(); });
            issue_rest(IC<0>{});
            if (!diag) {
              s_done(IC<64>{});
              at_exp<0, 24>(s);
              pv_half();
              at_exp<24, 48>(s);
              at_pack<0, 16>(s);
              pv_done();
              at_exp<48, 64>(s);
              at_pack<16, 32>(s);
            } else {
              s_done(IC<64>{});
              at_mask<8>(s, wrow - 64, lane);
              static_for<8>([&](auto k) {
                at_exp<7 * k, 7 * k + 7>(s);
                q_load_if(k, j == ta, s.S[7 * k + 3]);
                if (k == 2) pv_half();
                if (k == 5) { at_pack<0, 16>(s); pv_done(); }
              });
              at_exp<56, 64>(s);
              at_pack<16, 32>(s);
            }
          }
          TL(1, 20 * half + 2 + j, warp == 4);
        }
        TK(84 + half * 24);
        mbar_wait_c(B(half ? B_FULL3 : B_FULLQ), 0);
        if (gq == 0) ep_out(IC<0>{}, IC<EP1>{});
        bar_sync(1 + w, 256);
        fence_regs(s.O); fence_regs(s.P);
        const uint32_t ga = dA - half * w * 256, gb = ga + (half ? 512 : 4), gh = half ? 0x80000020u : 0x40000040u, go = (2 + half) * (SLOT >> 4);
        wg_fence();
        static_for<4>([&](auto k) { mma_n128_ssh<(k & 1) * 32, UNIT + k * 2048, k != 0>(s.S, k < 2 ? ga : gb, gh, dW); });
        mbar_wait_c(B(half ? B_FULL3 + 1 : B_FULLQ + 1), 0);
        wg_fence();
        static_for<4>([&](auto k) { mma_n128_ssh<(k & 1) * 32, UNIT + k * 2048, true>(s.S, (k < 2 ? ga : gb) + go, gh, dW + go); });
        wg_commit();
        TK(85 + half * 24);
        if (gq == 0) ep_rest();
        issue_pv(16, gq != 0, w == 1 || gq != 0);
        if (w == 0 || half == 0) bar_arrive(2 - w, 256);
        TK(86 + half * 24);
        wg_wait<2>();
        release2(B(B_EMPTY3), half); release2(B(B_EMPTY3 + 1), half);
        if (ep_prep()) redo |= 2;
        sched_fence();
        wg_wait<0>();
        TK(87 + half * 24);
        fence_regs(s.S);
        fence_regs(s.O);
        e_arrive(B(B_VE));
        release2(B(B_X + 3));
        fence_regs(s.P);
        {
          const int r = fresh_lane();
          cdst = g_ctx + (size_t)(tb * 32 + head) * KV_TILE + (wrow + (r >> 2)) * 32 + ((r ^ (r >> 3)) & 3) * 8;
        }
#pragma unroll
        for (int i = 0; i < 32; i++) {
          const float* o = s.O + 16 * (i >> 3) + 2 * ((i >> 2) & 1) + 4 * (i & 3);
          s.P[i] = pack_bf16(o[0] * inv[(i >> 2) & 1], o[1] * inv[(i >> 2) & 1]);
        }
        fence_regs(s.P);
        if (__builtin_expect(__any_sync(~0u, redo != 0), 0)) {
#pragma unroll
          for (int i = 0; i < 8; i++) put_ctx(i, true);
#pragma unroll 1
          for (int t = 0; t < 2; t++) {
            if (__any_sync(~0u, (redo >> t) & 1)) slow_rows(wq, head, (t ? tb : ta) * 128 + wrow);
          }
          if (__any_sync(~0u, redo & 1)) publish(2 + 2 * half);
#pragma unroll
          for (int i = 0; i < 32; i++) s.P[i] = 0;
          redo = 2;
        }
        TL(1, 20 * half + 19, warp == 4);
        TK(88 + half * 24);
        if (half) break;
        mbar_wait_c(B(B_FULLB), 0);
        TK(89);
        wg_fence();
        mma_n128_ss0<1, q_b(0), UNIT>(s.O, dA, dW);
        static_for<3>([&](auto k) { mma_n128_ss<1, q_b(0) + k * 32 + 32, UNIT + k * 2048 + 2048>(s.O, dA, dW, 1); });
        wg_commit();
        mma_kc(s.O, IC<q_b(1)>{}, IC<q_aw(1) + UNIT>{}, 1);
        wg_commit();
        wg_wait<1>();
        release2(B(B_EMPTYQ));
        put_ctx(0, true);
#pragma unroll 1
        for (int kb = 2; kb < 8; kb++) {
          issue_q(kb, IC<1>{});
          TK(90 + kb - 1);
#pragma unroll
          for (int i = 1; i < 8; i++) put_ctx(i, kb == (i < 7 ? i + 1 : 7));
        }
        publish(3);
      }
    }
    const int rid_ = rid + zero, cw_ = cw + zero;
    {
    const int lane = fresh_lane(), rid = rid_, mt = rid >> 3, gq = rid & 7, cw = cw_, w = cw >> 2, ct = cw * 32 + lane;
    const int fid = mt * 7 + gq;
    const bool ffn = gq < 7;
    const uint32_t stg = sb + OFF_STG + w * 16384 + (cw & 3) * 2048;
    const int wr_ = w * 64 + (lane & 7) + (lane >> 4) * 8;
    const uint32_t wl = sb + ((lane >> 3) & 1) * 8192 + wr_ * 64 + (((cw ^ (wr_ >> 1)) & 3) << 4);
    __syncwarp();
    float (&acc)[64] = s.S;
    uint32_t wf[128];
    auto grab = [&](auto c, uint32_t off) {
#pragma unroll
      for (int m = 0; m < 4; m++)
        asm volatile("ldmatrix.sync.aligned.m8n8.x4.trans.shared.b16 {%0,%1,%2,%3}, [%4];"
                     : "=r"(wf[16 * c + 4 * m]), "=r"(wf[16 * c + 4 * m + 1]), "=r"(wf[16 * c + 4 * m + 2]), "=r"(wf[16 * c + 4 * m + 3])
                     : "r"(wl + off + m * 1024) : "memory");
    };
    const int r0 = lane >> 2;
    uint32_t hp[32], rt[16];
    {
      const uint32_t dC = mk_desc(sb + w * 4096, 16);
      uint32_t dep = 0;
      auto hand = [&](uint32_t b, int n) {
        asm volatile("{\n.reg .pred p;\n.reg .b32 t;\nsetp.lt.u32 p, %1, %4;\nmad.lo.u32 t, %2, %3, %0;\n@p mbarrier.arrive.shared::cta.b64 _, [t];\n}"
                     ::"r"(b + 8 * lane), "r"(lane), "r"(dep), "r"(zero), "r"(n) : "memory");
      };
      auto kblock = [&](auto st, uint32_t ph, bool rel) {
        mbar_wait_c(B(B_FULL3 + st), ph);
        wg_fence();
        static_for<4>([&](auto k) { mma_n128_ssh<r3(decltype(st)::value) + (k >> 1) * 8192 + (k & 1) * 32, r3(decltype(st)::value) + UNIT + k * 2048, true>(acc, dC, 0x80000020u, dW); });
        wg_commit();
        wg_wait<1>();
        release2(B(B_EMPTY3 + (st + 5) % 6), rel);
      };
      auto ldsm_if = [&](uint32_t* r, uint32_t a, bool c, auto trans) {
        if (trans) asm volatile("{\n.reg .pred p;\nsetp.ne.u32 p, %5, 0;\n@p ldmatrix.sync.aligned.m8n8.x4.trans.shared.b16 {%0,%1,%2,%3}, [%4];\n}"
                                : "+r"(r[0]), "+r"(r[1]), "+r"(r[2]), "+r"(r[3]) : "r"(a), "r"((uint32_t)c) : "memory");
        else asm volatile("{\n.reg .pred p;\nsetp.ne.u32 p, %5, 0;\n@p ldmatrix.sync.aligned.m8n8.x4.shared.b16 {%0,%1,%2,%3}, [%4];\n}"
                          : "+r"(r[0]), "+r"(r[1]), "+r"(r[2]), "+r"(r[3]) : "r"(a), "r"((uint32_t)c) : "memory");
      };
#pragma unroll
      for (int i = 0; i < 48; i++) wf[i] = 0;
#pragma unroll 1
      for (int lap = 0; lap < 3; lap++) {
        kblock(IC<2>{}, lap & 1, lap > 0);
#pragma unroll
        for (int i = 0; i < 3; i++) put_ctx(3 * i, lap == i);
        kblock(IC<3>{}, lap & 1, true);
        mbar_wait_c(B(B_WF + (lap & 1)), lap >> 1);
#pragma unroll
        for (int i = 0; i < 12; i++) ldsm_if(wf + 4 * i, wl + OFF_SIDE + ((i >> 2) & 1) * UNIT + (i & 3) * 1024, lap == (i >> 2), IC<1>{});
        kblock(IC<4>{}, lap & 1, true);
        sched_fence();
        dep = 0;
#pragma unroll
        for (int i = 0; i < 12; i++) dep ^= wf[4 * i];
        hand(B(B_WE + (lap & 1)), 1);
#pragma unroll
        for (int i = 0; i < 3; i++) put_ctx(3 * i + 1, lap == i);
        kblock(IC<5>{}, lap & 1, true);
        if (lap == 2) publish(5);
        kblock(IC<0>{}, (lap & 1) ^ 1, true);
#pragma unroll
        for (int i = 0; i < 2; i++) put_ctx(3 * i + 2, lap == i);
        kblock(IC<1>{}, (lap & 1) ^ 1, true);
        TL(2, 40 + lap, warp == 4);
      }
#pragma unroll
      for (int i = 48; i < 96; i++) wf[i] = 0;
#pragma unroll
      for (int i = 0; i < 32; i++) { hp[i] = 0; rt[i >> 1] = 0; }
      const uint32_t xa = sb + OFF_SIDE + w * UNIT + (cw & 3) * 2048 + (lane & 15) * 128 + (((lane >> 4) ^ (lane & 7)) << 4);
#pragma unroll 1
      for (int lap = 3; lap < 11; lap++) {
        if (lap == 10 && w == 1) bar_sync(5, 256);
        kblock(IC<2>{}, lap & 1, true);
        if (lap == 10 && w == 0) bar_arrive(5, 256);
        kblock(IC<3>{}, lap & 1, true);
        if (lap == 10) break;
        if (lap < WIN) {
          mbar_wait_c(B(B_WF + (lap & 1)), (lap >> 1) & 1);
#pragma unroll
          for (int i = 12; i < 24; i++) ldsm_if(wf + 4 * i, wl + OFF_SIDE + ((i >> 2) & 1) * UNIT + (i & 3) * 1024, lap == (i >> 2), IC<1>{});
        } else if (lap == WIN) {
          mbar_wait_c(B(B_WF), (WIN >> 1) & 1);
          mbar_wait_c(B(B_WF + 1), (WIN >> 1) & 1);
#pragma unroll
          for (int j = 0; j < 8; j++) ldsm_if(hp + 4 * j, (xa ^ ((j & 3) << 5)) + (j >> 2) * 8192, true, IC<0>{});
        } else if (lap == 9) {
          mbar_wait_c(B(B_WR), 0);
          mbar_wait_c(B(B_SET2), 0);
#pragma unroll
          for (int j = 0; j < 4; j++) ldsm_if(rt + 4 * j, sb + OFF_MISC + 512 + (lane & 1) * 256 + (lane >> 3) * 16 + j * 64, true, IC<0>{});
        }
        kblock(IC<4>{}, lap & 1, true);
        sched_fence();
        dep = 0;
#pragma unroll
        for (int i = 0; i < 20; i++) dep ^= i < 12 ? wf[48 + 4 * i] : hp[4 * (i - 12)];
        hand(B(B_WE + (lap < WIN ? lap & 1 : 0)), lap < WIN ? 1 : (lap == WIN ? 2 : 0));
        kblock(IC<5>{}, lap & 1, true);
        kblock(IC<0>{}, (lap & 1) ^ 1, true);
        kblock(IC<1>{}, (lap & 1) ^ 1, true);
        TL(2, 40 + lap, warp == 4);
      }
    }
    uint4* const xr = g_xr + rid * XR_SIZE;
    uint4* const psd = xr + XR_PS + cw * 16 + r0;
    settle(psd, zero);
    sched_fence();
    wg_wait<0>();
    fence_regs(acc);
    TL(2, 10, warp == 4);
    {
      float d[4] = {0.f, 0.f, 0.f, 0.f}, qa[4] = {0.f, 0.f, 0.f, 0.f}, qb[4] = {0.f, 0.f, 0.f, 0.f};
#pragma unroll
      for (int j = 0; j < 16; j++) {
        hp[2 * j] = hadd2_bf(hp[2 * j], pack_bf16(acc[4 * j], acc[4 * j + 1]));
        hp[2 * j + 1] = hadd2_bf(hp[2 * j + 1], pack_bf16(acc[4 * j + 2], acc[4 * j + 3]));
        if (j & 1) {
          mma16816(d, hp[2 * j - 2], hp[2 * j - 1], hp[2 * j], hp[2 * j + 1], rt[j - 1], rt[j]);
          mma16816(qa, hp[2 * j - 2], hp[2 * j - 1], hp[2 * j], hp[2 * j + 1], hp[2 * j - 2], hp[2 * j]);
          mma16816(qb, hp[2 * j - 2], hp[2 * j - 1], hp[2 * j], hp[2 * j + 1], hp[2 * j - 1], hp[2 * j + 1]);
        }
      }
      asm volatile("{\n.reg .pred p;\nsetp.eq.u32 p, %7, %8;\n@p st.global.cg.v4.f32 [%0], {%1,%2,%3,%3};\n@p st.global.cg.v4.f32 [%0 + 128], {%4,%5,%6,%6};\n}"
                   ::"l"(psd), "f"(d[0]), "f"(d[1]), "f"((r0 & 1) ? qa[1] : qa[0]), "f"(d[2]), "f"(d[3]), "f"((r0 & 1) ? qb[3] : qb[2]),
                   "r"(lane & 3), "r"(r0 >> 1) : "memory");
      sched_fence();
    }
    mbar_wait_c(B(B_EMPTY3), 0);
    __syncwarp();
    stage_store_128(stg, lane, hp);
    TL(2, 11, warp == 4);
    __syncwarp();
    uint4 cout;
    uint32_t ckey;
    {
      const float wsum = *reinterpret_cast<const float*>(sp + OFF_MISC + 1024);
      const uint4* pp = g_xr + (mt * 8 + (ct & 1) * 4) * XR_SIZE + XR_PS + (ct >> 1);
      uint2* kd = reinterpret_cast<uint2*>(xr + XR_KEY) + cw;
      const uint32_t tok = 0x7FFFu - (mt * 128 + (ct >> 1));
      settle(pp, zero); settle(kd, zero); settle(tok, zero);
      spin_clk(PS_DLY);
      float s1, s2, s3;
#pragma unroll 1
      for (int n = 0; n < 0x400000; n++) {
        float4 z[4];
#pragma unroll
        for (int i = 0; i < 4; i++)
          asm volatile("ld.relaxed.gpu.global.v4.f32 {%0,%1,%2,%3}, [%4];" : "=f"(z[i].x), "=f"(z[i].y), "=f"(z[i].z), "=f"(z[i].w) : "l"(pp + i * XR_SIZE) : "memory");
        s1 = (z[0].x + z[1].x) + (z[2].x + z[3].x); s3 = (z[0].y + z[1].y) + (z[2].y + z[3].y); s2 = (z[0].z + z[1].z) + (z[2].z + z[3].z);
        const float t = s1 + s2 + s3;
        s1 += __shfl_xor_sync(~0u, s1, 1); s2 += __shfl_xor_sync(~0u, s2, 1); s3 += __shfl_xor_sync(~0u, s3, 1);
        if (__all_sync(~0u, t == t)) break;
        uint32_t m = 0;
#pragma unroll
        for (int i = 0; i < 4; i++) m = max(max(m, __float_as_uint(z[i].x)), max(__float_as_uint(z[i].y), __float_as_uint(z[i].z)));
        if (__all_sync(~0u, m != 0xFFFFFFFFu)) break;
      }
      TL(2, 12, warp == 4);
      const float mean = s1 * (1.f / DM);
      float mb, inv;
      ln_round(mean, fmaxf(fmaf(s2, 1.f / DM, -mean * mean), 0.f), mb, inv);
      const uint32_t u = pack_bf16(0.f, fmaf(s3 - mb * wsum, inv, 0.f));
      const uint32_t key = ((u ^ (((int)u >> 31) | 0x80000000u)) & 0xFFFF0000u) | tok;
      const uint32_t c1 = __reduce_max_sync(~0u, key);
      const uint32_t c2 = __reduce_max_sync(~0u, key == c1 ? 0u : key);
      asm volatile(ELECT "st.global.cg.v2.u32 [%0], {%1,%2};\n}" ::"l"(kd), "r"(c1), "r"(c2) : "memory");
      sched_fence();
      const uint32_t nm2 = pack_bf16(-mb, -mb);
      if (!(ct & 1)) *reinterpret_cast<uint2*>(sp + OFF_RSTAT + (ct >> 1) * 8) = make_uint2(nm2, __float_as_uint(inv) | (key >= c2 ? 0x80000000u : 0u));
      ckey = (lane >> 4) ? c2 : c1;
      const int row = (0x7FFF - (ckey & 0x7FFF)) & 15;
      const uint32_t rn = __shfl_sync(~0u, nm2, row * 2);
      const float ri = __shfl_sync(~0u, inv, row * 2);
      const uint4 v = lds128(stg + ((lane & 15) >> 3) * 8192 + row * 128 + (((lane & 7) ^ (row & 7)) << 4));
      const uint4 n = make_uint4(ln_apply(v.x, rn, ri), ln_apply(v.y, rn, ri), ln_apply(v.z, rn, ri), ln_apply(v.w, rn, ri));
      __stcg(xr + XR_CAND + cw * 64 + 32 + lane, n);
      __stcg(xr + XR_CAND + cw * 64 + lane, v);
      cdst = out + (size_t)(0x7FFF - (ckey & 0x7FFF)) * DM + gq * 128 + (lane & 15) * 8;
      cout = make_uint4(hadd2_bf(v.x, n.x), hadd2_bf(v.y, n.y), hadd2_bf(v.z, n.z), hadd2_bf(v.w, n.w));
    }
    publish(B_OUT - B_PUB);
    cluster_arrive();
    TL(2, 13, warp == 4);
    uint32_t wd[16][4];
    if (ffn) {
      static_for<2>([&](auto i) {
        mbar_wait_b(B(B_WF + i), ((WIN >> 1) & 1) ^ 1);
        grab(IC<WIN + i>{}, OFF_SIDE + i * UNIT);
      });
      mbar_wait_b(B(B_FULL3 + 4 + w), 0);
#pragma unroll
      for (int i = 0; i < 16; i++) {
        const int k = (i & 1) * 16 + (lane & 7) + (lane >> 4) * 8;
        asm volatile("ldmatrix.sync.aligned.m8n8.x4.trans.shared.b16 {%0,%1,%2,%3}, [%4];"
                     : "=r"(wd[i][0]), "=r"(wd[i][1]), "=r"(wd[i][2]), "=r"(wd[i][3])
                     : "r"(sb + r3(4) + w * SLOT + (2 * (cw & 3) + (i >> 3)) * 4096 + k * 128 + (((2 * ((i >> 1) & 3) + ((lane >> 3) & 1)) ^ (lane & 7)) << 4)) : "memory");
      }
    }
    const int fc = 16 * (rid >> 1) + 4 * (rid & 1) + (lane & 3) + 8 * (lane >> 4), ft = (lane >> 3) & 1;
    const char* pc = reinterpret_cast<const char*>(g_xr + ((ct & 127) >> 4) * XR_SIZE + XR_CAND + 32 + (ct & 15));
    const char* pf = reinterpret_cast<const char*>(g_xr + (fc >> 7) * XR_SIZE + XR_CAND) + (fc & 127) * 2;
    const uint32_t xs = sb + OFF_SCR + w * 2112 + ((ct & 127) >> 2) * 64 + (((ct >> 3) & 3) << 4) + (ct & 3) * 4;
    const uint32_t xb = sb + OFF_SCR + (r0 & 1) * 2112 + w * 128 + (((lane ^ w) & 3) << 4);
    settle(pc, zero); settle(pf, zero); settle(cdst, zero); settle(xs, zero); settle(xb, zero);
    mbar_wait_b(B(B_OUT2), 0);
    const uint4 top = lds128(sb + OFF_MISC + 256);
    TL(2, 14, warp == 4);
    uint32_t fh, fn;
    {
      pc += w ? top.y : top.x;
      pf += ft ? top.y : top.x;
      uint4 v;
#pragma unroll 1
      for (int n = 0; n < 0x400000; n++) {
        asm volatile("ld.relaxed.gpu.global.v4.u32 {%0,%1,%2,%3}, [%4];" : "=r"(v.x), "=r"(v.y), "=r"(v.z), "=r"(v.w) : "l"(pc) : "memory");
        asm volatile("ld.relaxed.gpu.global.u16 %0, [%1];" : "=r"(fh) : "l"(pf) : "memory");
        asm volatile("ld.relaxed.gpu.global.u16 %0, [%1 + 512];" : "=r"(fn) : "l"(pf) : "memory");
        asm volatile("st.shared.u32 [%0], %1;" ::"r"(xs), "r"(v.x) : "memory");
        asm volatile("st.shared.u32 [%0], %1;" ::"r"(xs ^ 16), "r"(v.y) : "memory");
        asm volatile("st.shared.u32 [%0], %1;" ::"r"(xs ^ 32), "r"(v.z) : "memory");
        asm volatile("st.shared.u32 [%0], %1;" ::"r"(xs ^ 48), "r"(v.w) : "memory");
        if (__all_sync(~0u, max(max(v.x, v.y), max(v.z, v.w)) != 0xFFFFFFFFu && max(fh, fn) != 0xFFFFu)) break;
      }
    }
    bar_sync(3, 256);
    asm volatile("{\n.reg .pred p;\nsetp.lt.u32 p, %5, %6;\n@p st.global.v4.u32 [%0], {%1,%2,%3,%4};\n}" ::"l"(cdst), "r"(cout.x), "r"(cout.y), "r"(cout.z),
                 "r"(cout.w), "r"(ckey), "r"(top.w) : "memory");
    if (ffn) {
      TL(2, 15, warp == 4);
      float d[4][4] = {};
      auto xl = [&](int i) { return lds128((xb ^ ((i & 2) << 4)) + (i >> 1) * 256 + (i & 1) * 64); };
      uint4 b0 = xl(0), b1 = xl(1);
#pragma unroll
      for (int i = 0; i < 16; i += 2) {
        const uint4 c0 = b0, c1 = b1;
        if (i < 14) { b0 = xl(i + 2); b1 = xl(i + 3); }
        mma16816(d[0], wf[8 * i], wf[8 * i + 1], wf[8 * i + 2], wf[8 * i + 3], c0.x, c0.y);
        mma16816(d[1], wf[8 * i + 4], wf[8 * i + 5], wf[8 * i + 6], wf[8 * i + 7], c0.z, c0.w);
        mma16816(d[2], wf[8 * i + 8], wf[8 * i + 9], wf[8 * i + 10], wf[8 * i + 11], c1.x, c1.y);
        mma16816(d[3], wf[8 * i + 12], wf[8 * i + 13], wf[8 * i + 14], wf[8 * i + 15], c1.z, c1.w);
      }
      const float e0 = (d[0][0] + d[1][0]) + (d[2][0] + d[3][0]), e1 = (d[0][1] + d[1][1]) + (d[2][1] + d[3][1]);
      const float e2 = (d[0][2] + d[1][2]) + (d[2][2] + d[3][2]), e3 = (d[0][3] + d[1][3]) + (d[2][3] + d[3][3]);
      asm volatile("st.shared.v2.f32 [%0], {%1,%2};" ::"r"(sb + OFF_SCR + 8192 + ((w * 2 + (lane & 1)) * 32 + (cw & 3) * 8 + r0) * 8),
                   "f"((lane & 1) ? e1 : e0), "f"((lane & 1) ? e3 : e2) : "memory");
      bar_sync(3, 256);
      TL(2, 16, warp == 4);
      const uint32_t ra = sb + OFF_SCR + 8192 + (r0 & 1) * 256 + (r0 >> 1) * 64 + (lane & 3) * 16;
      const uint4 p0 = lds128(ra), p1 = lds128(ra + 512);
      auto act = [](uint32_t u0, uint32_t u1, uint32_t g0, uint32_t g1) {
        const uint32_t ug = pack_bf16(__uint_as_float(u0) + __uint_as_float(u1), __uint_as_float(g0) + __uint_as_float(g1));
        const float g = bf_hi(ug);
        float r;
        asm("rcp.approx.ftz.f32 %0, %1;" : "=f"(r) : "f"(1.f + ex2(g * -1.4426950408889634f)));
        return bf_round(g * r) * bf_lo(ug);
      };
      const uint32_t av = pack_bf16(act(p0.x, p1.x, p0.y, p1.y), act(p0.z, p1.z, p0.w, p1.w));
      uint32_t b[4];
#pragma unroll
      for (int i = 0; i < 4; i++) b[i] = __shfl_sync(~0u, av, 8 * i + (lane & 7));
      TL(2, 17, warp == 4);
      float y[2][4] = {{0.f, 0.f, 0.f, 0.f}, {0.f, 0.f, 0.f, 0.f}};
#pragma unroll
      for (int c = 0; c < 4; c++) {
        const bool on = (lane >> 3) == c;
        const uint32_t b0 = on ? b[0] : 0, b1 = on ? b[1] : 0, b2 = on ? b[2] : 0, b3 = on ? b[3] : 0;
#pragma unroll
        for (int a = 0; a < 2; a++) {
          const int i = 8 * a + 2 * c;
          mma16816(y[a], wd[i][0], wd[i][1], wd[i][2], wd[i][3], b0, b1);
          mma16816(y[a], wd[i + 1][0], wd[i + 1][1], wd[i + 1][2], wd[i + 1][3], b2, b3);
        }
      }
      float4* yd = reinterpret_cast<float4*>(g_xr + (cw * 16 + (lane & 3) * 2 + (lane >> 4)) * XR_SIZE + XR_Y + fid * 4 + (r0 & 3));
      __stcg(yd, make_float4(y[0][0], y[0][1], y[0][2], y[0][3]));
      __stcg(yd + 8 * XR_SIZE, make_float4(y[1][0], y[1][1], y[1][2], y[1][3]));
    }
    TL(2, 18, warp == 4);
    if (cw == 0) {
      const uint32_t fk = ft ? top.w : top.z;
      uint32_t u = fk >> 16;
      u = (u & 0x8000u) ? (u & 0x7FFFu) : (~u & 0xFFFFu);
      float rs = bf_round(__fdividef(1.f, 1.f + __expf(-__uint_as_float(u << 16))));
      uint16_t* op = reinterpret_cast<uint16_t*>(out) + (size_t)(~fk & 0x7FFF) * DM + fc;
      settle(op, zero); settle(__float_as_uint(rs), zero);
      spin_clk(ffn ? Y_DLY : Y_DLY + Y_DLY0);
      float v[4];
#pragma unroll 1
      for (int n = 0; n < 0x400000; n++) {
        float4 z[14];
#pragma unroll
        for (int i = 0; i < 14; i++)
          asm volatile("ld.relaxed.gpu.global.v4.f32 {%0,%1,%2,%3}, [%4];" : "=f"(z[i].x), "=f"(z[i].y), "=f"(z[i].z), "=f"(z[i].w) : "l"(xr + XR_Y + lane + 32 * i) : "memory");
        float a[4] = {z[0].x, z[0].y, z[0].z, z[0].w}, b[4] = {z[1].x, z[1].y, z[1].z, z[1].w};
#pragma unroll
        for (int i = 2; i < 14; i += 2) {
          a[0] += z[i].x; a[1] += z[i].y; a[2] += z[i].z; a[3] += z[i].w;
          b[0] += z[i + 1].x; b[1] += z[i + 1].y; b[2] += z[i + 1].z; b[3] += z[i + 1].w;
        }
#pragma unroll
        for (int i = 0; i < 4; i++) v[i] = a[i] + b[i];
        const float t = (v[0] + v[1]) + (v[2] + v[3]);
        if (__all_sync(~0u, t == t)) break;
        uint32_t m = 0;
#pragma unroll
        for (int i = 0; i < 14; i++) m = max(max(m, max(__float_as_uint(z[i].x), __float_as_uint(z[i].y))), max(__float_as_uint(z[i].z), __float_as_uint(z[i].w)));
        if (__all_sync(~0u, m != 0xFFFFFFFFu)) break;
      }
      TL(2, 30, true);
      const bool hi = lane & 16, odd = lane & 8;
      const float a0 = (hi ? v[2] : v[0]) + __shfl_xor_sync(~0u, hi ? v[0] : v[2], 16), a1 = (hi ? v[3] : v[1]) + __shfl_xor_sync(~0u, hi ? v[1] : v[3], 16);
      float yv = (odd ? a1 : a0) + __shfl_xor_sync(~0u, odd ? a0 : a1, 8);
      yv += __shfl_xor_sync(~0u, yv, 4);
      const uint32_t o = hadd2_bf(fh, hadd2_bf(fn, pack_bf16(bf_round(yv) * rs, 0.f)));
      if (!(lane & 4)) *op = (uint16_t)o;
      TL(2, 21, true);
    }
    TL(2, 20, warp == 4);
    }
    __syncwarp();
    cluster_wait();
  }
}

typedef CUresult (*EncodeFn)(CUtensorMap*, CUtensorMapDataType, cuuint32_t, void*, const cuuint64_t*, const cuuint64_t*, const cuuint32_t*,
                             const cuuint32_t*, CUtensorMapInterleave, CUtensorMapSwizzle, CUtensorMapL2promotion, CUtensorMapFloatOOBfill);
EncodeFn g_enc = nullptr;

void map2(CUtensorMap* m, const void* ptr, uint64_t rows, uint64_t cols, uint32_t bc, uint32_t br) {
  const CUtensorMapSwizzle sw = bc == 64 ? CU_TENSOR_MAP_SWIZZLE_128B : CU_TENSOR_MAP_SWIZZLE_64B;
  cuuint64_t gd[2] = {cols, rows}, gs[1] = {cols * 2};
  cuuint32_t bd[2] = {bc, br}, es[2] = {1, 1};
  g_enc(m, CU_TENSOR_MAP_DATA_TYPE_BFLOAT16, 2, (void*)ptr, gd, gs, bd, es, CU_TENSOR_MAP_INTERLEAVE_NONE, sw,
        CU_TENSOR_MAP_L2_PROMOTION_L2_128B, CU_TENSOR_MAP_FLOAT_OOB_FILL_NONE);
}
void map3(CUtensorMap* m, const void* ptr, uint64_t rows, uint64_t cols, uint32_t br, uint32_t bch) {
  cuuint64_t gd[3] = {64, rows, cols / 64}, gs[2] = {cols * 2, 128};
  cuuint32_t bd[3] = {64, br, bch}, es[3] = {1, 1, 1};
  g_enc(m, CU_TENSOR_MAP_DATA_TYPE_BFLOAT16, 3, (void*)ptr, gd, gs, bd, es, CU_TENSOR_MAP_INTERLEAVE_NONE, CU_TENSOR_MAP_SWIZZLE_128B,
        CU_TENSOR_MAP_L2_PROMOTION_L2_128B, CU_TENSOR_MAP_FLOAT_OOB_FILL_NONE);
}

}

extern "C" void kernel_launch(void* const* d_in, const int* in_sizes, int n_in, void* d_out, int out_size) {
  const __nv_bfloat16* x = (const __nv_bfloat16*)d_in[0];
  const __nv_bfloat16* ckv = (const __nv_bfloat16*)d_in[1];
  const __nv_bfloat16* wq = (const __nv_bfloat16*)d_in[2];
  const __nv_bfloat16* wk = (const __nv_bfloat16*)d_in[3];
  const __nv_bfloat16* wv = (const __nv_bfloat16*)d_in[4];
  const __nv_bfloat16* wo = (const __nv_bfloat16*)d_in[5];
  const __nv_bfloat16* w_r = (const __nv_bfloat16*)d_in[7];
  const __nv_bfloat16* wgate = (const __nv_bfloat16*)d_in[8];
  const __nv_bfloat16* wup = (const __nv_bfloat16*)d_in[9];
  const __nv_bfloat16* wdown = (const __nv_bfloat16*)d_in[10];
  __nv_bfloat16* out = (__nv_bfloat16*)d_out;

  if (!g_enc) {
    void* fn = nullptr;
    cudaDriverEntryPointQueryResult qr;
    cudaGetDriverEntryPoint("cuTensorMapEncodeTiled", &fn, cudaEnableDefault, &qr);
    g_enc = (EncodeFn)fn;
    cudaFuncSetAttribute(fused_kernel, cudaFuncAttributeMaxDynamicSharedMemorySize, SMEM_BYTES);
  }
  void *xn, *kv, *ctx, *xr, *cnt;
  cudaGetSymbolAddress(&xr, g_xr);
  cudaGetSymbolAddress(&cnt, g_cnt);
  cudaGetSymbolAddress(&xn, g_xn);
  cudaGetSymbolAddress(&kv, g_kv);
  cudaGetSymbolAddress(&ctx, g_ctx);

  Params p;
  map2(&p.xn, xn, SEQ, DM, 64, 64);
  map2(&p.ckv, ckv, SEQ, DC, 64, 128);
  map3(&p.wq, wq, DM, NQ, 64, 2);
  map3(&p.wk, wk, DC, NQ, 32, 2);
  map3(&p.wv, wv, DC, NQ, 32, 2);
  map3(&p.wo, wo, NQ, DM, 64, 1);
  map3(&p.x, x, SEQ, DM, 64, 2);
  map3(&p.wd, wdown, FF, DM, 32, 8);
  map2(&p.wg, wgate, DM, FF, 32, 64);
  map2(&p.wu, wup, DM, FF, 32, 64);
  fused_kernel<<<128, 384, SMEM_BYTES, cudaStreamPerThread>>>(0u, x, (__nv_bfloat16*)kv, (__nv_bfloat16*)ctx, (uint4*)xr, out, (__nv_bfloat16*)xn,
                                                               (unsigned*)cnt, w_r, wdown, wq, p);
}
```

```cpp
#include <cuda_runtime.h>
#include <cuda_bf16.h>
#include <cuda.h>
#include <stdint.h>
#include <utility>

#pragma nv_diag_suppress 549
#pragma nv_diag_suppress 177
namespace {

constexpr int SEQ = 2048, DM = 1024, NH = 32, HD = 128, DC = 512, NQ = NH * HD, FF = 3584;

__device__ __align__(1024) __nv_bfloat16 g_xn[SEQ * DM];
constexpr int KV_TILE = 128 * 128;
__device__ __align__(1024) __nv_bfloat16 g_kv[2 * SEQ * NQ];
__device__ __align__(1024) __nv_bfloat16 g_ctx[SEQ * NQ];
constexpr int XR_PS = 0;
constexpr int XR_KEY = 128;
constexpr int XR_CAND = 136;
constexpr int XR_Y = 648;
constexpr int XR_SIZE = 1104;
__device__ __align__(1024) uint4 g_xr[128 * XR_SIZE];
constexpr int C_LN = 0, C_KV = 16, C_CTX = 32, C_NUM = 64;
__device__ unsigned g_cnt[C_NUM];

#define TL(k, i, cond) do {} while (0)
#define TC(w, g, i) do {} while (0)
#define TL_EXTRA 0
#define TK(i) do {} while (0)

__device__ __forceinline__ uint32_t s2u(const void* p) { return (uint32_t)__cvta_generic_to_shared(p); }
__device__ __forceinline__ void mbar_arrive(uint32_t b) { asm volatile("mbarrier.arrive.shared::cta.b64 _, [%0];" ::"r"(b) : "memory"); }
__device__ __forceinline__ void mbar_arrive_both(uint32_t b, uint32_t lane, bool cond) {
  asm volatile("{\n.reg .pred p;\n.reg .b32 r;\nsetp.lt.u32 p, %1, %2;\nmapa.shared::cluster.u32 r, %0, %1;\n@p mbarrier.arrive.shared::cluster.b64 _, [r];\n}"
               ::"r"(b), "r"(lane), "r"(cond ? 2 : 0) : "memory");
}
__device__ __forceinline__ bool mbar_test(uint32_t b, uint32_t ph) {
  uint32_t ok;
  asm volatile("{\n.reg .pred p;\nmbarrier.test_wait.parity.shared::cta.b64 p, [%1], %2;\nselp.u32 %0, 1, 0, p;\n}" : "=r"(ok) : "r"(b), "r"(ph) : "memory");
  return __all_sync(~0u, ok);
}
__device__ __forceinline__ void mbar_wait(uint32_t b, uint32_t ph) {
  asm volatile(
      "{\n.reg .pred p;\n.reg .u32 n;\nmov.u32 n, 0;\n"
      "LW:\nmbarrier.try_wait.parity.shared::cta.b64 p, [%0], %1, 20000;\n@p bra LD;\n"
      "add.u32 n, n, 1;\nsetp.lt.u32 p, n, 0x40000;\n@p bra LW;\ntrap;\nLD:\n}" ::"r"(b), "r"(ph) : "memory");
}
__device__ __forceinline__ void mbar_wait_u(uint32_t b, uint32_t ph) {
  asm volatile(
      "{\n.reg .pred p;\n.reg .u32 n;\nmov.u32 n, 0;\n"
      "LW:\nmbarrier.try_wait.parity.shared::cta.b64 p, [%0], %1, 20000;\n@p bra.uni LD;\n"
      "add.u32 n, n, 1;\nsetp.lt.u32 p, n, 0x40000;\n@p bra.uni LW;\ntrap;\nLD:\n}" ::"r"(b), "r"(ph) : "memory");
}
__device__ __forceinline__ void mbar_wait_c(uint32_t b, uint32_t ph) {
  asm volatile("{\n.reg .pred p;\nLW:\nmbarrier.try_wait.parity.shared::cta.b64 p, [%0], %1;\n@!p bra.uni LW;\n}" ::"r"(b), "r"(ph) : "memory");
}
__device__ __forceinline__ void mbar_wait_b(uint32_t b, uint32_t ph) {
  asm volatile(
      "{\n.reg .pred p;\n.reg .u32 n;\nmov.u32 n, 0;\n"
      "LW:\nmbarrier.try_wait.parity.shared::cta.b64 p, [%0], %1;\n@p bra.uni LD;\n"
      "add.u32 n, n, 1;\nsetp.lt.u32 p, n, 0x1000000;\n@p bra.uni LW;\ntrap;\nLD:\n}" ::"r"(b), "r"(ph) : "memory");
}
template <bool SLEEP = false>
__device__ __forceinline__ void spin_until_ge(const unsigned* p, unsigned target) {
  asm volatile(
      "{\n.reg .pred p, q;\n.reg .u32 n, v;\nmov.u32 n, 0;\nsetp.ne.u32 q, %2, 0;\n"
      "LW:\nld.acquire.gpu.global.u32 v, [%0];\nsetp.ge.u32 p, v, %1;\n@p bra LD;\n@q nanosleep.u32 200;\n"
      "add.u32 n, n, 1;\nsetp.lt.u32 p, n, 0x400000;\n@p bra LW;\ntrap;\nLD:\n}" ::"l"(p), "r"(target), "n"((int)SLEEP) : "memory");
}
__device__ __forceinline__ void spin_clk(uint32_t n) {
  asm volatile("{\n.reg .pred p;\n.reg .u32 a, b;\nmov.u32 a, %%clock;\nLW:\nmov.u32 b, %%clock;\nsub.u32 b, b, a;\nsetp.lt.u32 p, b, %0;\n@p bra.uni LW;\n}" ::"r"(n) : "memory");
}
__device__ __forceinline__ int fresh_lane() {
  int r;
  asm volatile("mov.u32 %0, %%laneid;" : "=r"(r));
  return r;
}
__device__ __forceinline__ void settle(const void* a, uint32_t zero) {
  asm volatile("{\n.reg .pred p;\nsetp.ne.u32 p, %1, 0;\n@p st.global.u32 [%0], %1;\n}" ::"l"(a), "r"(zero) : "memory");
}
__device__ __forceinline__ void settle(uint32_t a, uint32_t zero) {
  asm volatile("{\n.reg .pred p;\nsetp.ne.u32 p, %1, 0;\n@p st.shared.u32 [%0], %1;\n}" ::"r"(a), "r"(zero) : "memory");
}
__device__ __forceinline__ void fence_async_all() { asm volatile("fence.proxy.async;" ::: "memory"); }
__device__ __forceinline__ void bar_sync(int id, int n) { asm volatile("bar.sync %0, %1;" ::"r"(id), "r"(n) : "memory"); }
__device__ __forceinline__ void bar_arrive(int id, int n) { asm volatile("bar.arrive %0, %1;" ::"r"(id), "r"(n) : "memory"); }
__device__ __forceinline__ void cluster_arrive() { asm volatile("barrier.cluster.arrive.relaxed.aligned;" ::: "memory"); }
__device__ __forceinline__ void cluster_wait() { asm volatile("barrier.cluster.wait.acquire.aligned;" ::: "memory"); }
__device__ __forceinline__ void fence_gpu() { asm volatile("fence.acq_rel.gpu;" ::: "memory"); }
__device__ __forceinline__ void red_add(unsigned* p, unsigned v) { asm volatile("red.relaxed.gpu.global.add.u32 [%0], %1;" ::"l"(p), "r"(v) : "memory"); }
#define ELECT "{\n.reg .pred E;\nelect.sync _|E, 0xFFFFFFFF;\n@E "
__device__ __forceinline__ void e_init(uint32_t b, uint32_t c) { asm volatile(ELECT "mbarrier.init.shared::cta.b64 [%0], %1;\n}" ::"r"(b), "r"(c) : "memory"); }
__device__ __forceinline__ void e_expect(uint32_t b, uint32_t bytes) { asm volatile(ELECT "mbarrier.arrive.expect_tx.shared::cta.b64 _, [%0], %1;\n}" ::"r"(b), "r"(bytes) : "memory"); }
__device__ __forceinline__ void e_arrive(uint32_t b) { asm volatile(ELECT "mbarrier.arrive.shared::cta.b64 _, [%0];\n}" ::"r"(b) : "memory"); }
__device__ __forceinline__ void prefetch_tm(const CUtensorMap* m) { asm volatile(ELECT "prefetch.tensormap [%0];\n}" ::"l"(m) : "memory"); }
__device__ __forceinline__ void tma_ld2(uint32_t dst, const CUtensorMap* m, uint32_t bar, int c0, int c1) {
  asm volatile(ELECT "cp.async.bulk.tensor.2d.shared::cta.global.mbarrier::complete_tx::bytes [%0], [%1, {%3,%4}], [%2];\n}" ::"r"(dst), "l"(m), "r"(bar), "r"(c0), "r"(c1) : "memory");
}
__device__ __forceinline__ void tma_ld3(uint32_t dst, const CUtensorMap* m, uint32_t bar, int c0, int c1, int c2) {
  asm volatile(ELECT "cp.async.bulk.tensor.3d.shared::cta.global.mbarrier::complete_tx::bytes [%0], [%1, {%3,%4,%5}], [%2];\n}" ::"r"(dst), "l"(m), "r"(bar), "r"(c0), "r"(c1), "r"(c2) : "memory");
}
__device__ __forceinline__ void tma_ld2_mc(uint32_t dst, const CUtensorMap* m, uint32_t bar, int c0, int c1, uint16_t mask) {
  asm volatile(ELECT "cp.async.bulk.tensor.2d.shared::cluster.global.mbarrier::complete_tx::bytes.multicast::cluster [%0], [%1, {%3,%4}], [%2], %5;\n}" ::"r"(dst), "l"(m), "r"(bar), "r"(c0), "r"(c1), "h"(mask) : "memory");
}
__device__ __forceinline__ void tma_ld3_mc(uint32_t dst, const CUtensorMap* m, uint32_t bar, int c0, int c1, int c2, uint16_t mask) {
  asm volatile(ELECT "cp.async.bulk.tensor.3d.shared::cluster.global.mbarrier::complete_tx::bytes.multicast::cluster [%0], [%1, {%3,%4,%5}], [%2], %6;\n}" ::"r"(dst), "l"(m), "r"(bar), "r"(c0), "r"(c1), "r"(c2), "h"(mask) : "memory");
}
__device__ __forceinline__ uint64_t policy_evict_first() {
  uint64_t p;
  asm("createpolicy.fractional.L2::evict_first.b64 %0, 1.0;" : "=l"(p));
  return p;
}
__device__ __forceinline__ void tma_ld2_ef(uint32_t dst, const CUtensorMap* m, uint32_t bar, int c0, int c1) {
  asm volatile(ELECT "cp.async.bulk.tensor.2d.shared::cta.global.mbarrier::complete_tx::bytes.L2::cache_hint [%0], [%1, {%3,%4}], [%2], %5;\n}" ::"r"(dst), "l"(m), "r"(bar), "r"(c0), "r"(c1), "l"(policy_evict_first()) : "memory");
}
__device__ __forceinline__ void tma_ld3_ef(uint32_t dst, const CUtensorMap* m, uint32_t bar, int c0, int c1, int c2) {
  asm volatile(ELECT "cp.async.bulk.tensor.3d.shared::cta.global.mbarrier::complete_tx::bytes.L2::cache_hint [%0], [%1, {%3,%4,%5}], [%2], %6;\n}" ::"r"(dst), "l"(m), "r"(bar), "r"(c0), "r"(c1), "r"(c2), "l"(policy_evict_first()) : "memory");
}
__device__ __forceinline__ void bulk_ld(uint32_t dst, const void* src, uint32_t bytes, uint32_t bar) {
  asm volatile(ELECT "cp.async.bulk.shared::cta.global.mbarrier::complete_tx::bytes [%0], [%1], %2, [%3];\n}" ::"r"(dst), "l"(src), "r"(bytes), "r"(bar) : "memory");
}
__device__ __forceinline__ void tma_pf2(const CUtensorMap* m, int c0, int c1) { asm volatile(ELECT "cp.async.bulk.prefetch.tensor.2d.L2.global [%0, {%1,%2}];\n}" ::"l"(m), "r"(c0), "r"(c1) : "memory"); }
__device__ __forceinline__ void tma_pf3(const CUtensorMap* m, int c0, int c1, int c2) { asm volatile(ELECT "cp.async.bulk.prefetch.tensor.3d.L2.global [%0, {%1,%2,%3}];\n}" ::"l"(m), "r"(c0), "r"(c1), "r"(c2) : "memory"); }
__device__ __forceinline__ void sched_fence() { asm volatile("pmevent 0;" ::: "memory"); }
__device__ __forceinline__ void l2_prefetch(const void* p, uint32_t bytes) { asm volatile(ELECT "cp.async.bulk.prefetch.L2.global [%0], %1;\n}" ::"l"(p), "r"(bytes) : "memory"); }

__device__ __forceinline__ void wg_fence() { asm volatile("wgmma.fence.sync.aligned;" ::: "memory"); }
__device__ __forceinline__ void wg_commit() { asm volatile("wgmma.commit_group.sync.aligned;" ::: "memory"); }
template <int N> __device__ __forceinline__ void wg_wait() { asm volatile("wgmma.wait_group.sync.aligned %0;" ::"n"(N) : "memory"); }
template <int N> __device__ __forceinline__ void reg_alloc() { asm volatile("setmaxnreg.inc.sync.aligned.u32 %0;" ::"n"(N)); }
template <int N> __device__ __forceinline__ void reg_dealloc() { asm volatile("setmaxnreg.dec.sync.aligned.u32 %0;" ::"n"(N)); }
template <int N> __device__ __forceinline__ void fence_regs(float (&d)[N]) {
#pragma unroll
  for (int i = 0; i < N; i++) asm volatile("" : "+f"(d[i])::"memory");
}
template <int I0, int I1, int N> __device__ __forceinline__ void fence_part(float (&d)[N]) {
#pragma unroll
  for (int i = I0; i < I1; i++) asm volatile("" : "+f"(d[i])::"memory");
}
template <int N> __device__ __forceinline__ void fence_regs(uint32_t (&d)[N]) {
#pragma unroll
  for (int i = 0; i < N; i++) asm volatile("" : "+r"(d[i])::"memory");
}

__device__ __forceinline__ uint32_t mk_desc(uint32_t addr, uint32_t lbo) { return ((addr & 0x3FFFF) >> 4) | ((lbo >> 4) << 16); }

#define R8(b) "+f"(d[b + 0]), "+f"(d[b + 1]), "+f"(d[b + 2]), "+f"(d[b + 3]), "+f"(d[b + 4]), "+f"(d[b + 5]), "+f"(d[b + 6]), "+f"(d[b + 7])
#define REGS64 "%0,%1,%2,%3,%4,%5,%6,%7,%8,%9,%10,%11,%12,%13,%14,%15,%16,%17,%18,%19,%20,%21,%22,%23,%24,%25,%26,%27,%28,%29,%30,%31," \
               "%32,%33,%34,%35,%36,%37,%38,%39,%40,%41,%42,%43,%44,%45,%46,%47,%48,%49,%50,%51,%52,%53,%54,%55,%56,%57,%58,%59,%60,%61,%62,%63"
#define REGS128 REGS64 ",%64,%65,%66,%67,%68,%69,%70,%71,%72,%73,%74,%75,%76,%77,%78,%79,%80,%81,%82,%83,%84,%85,%86,%87,%88,%89,%90,%91,%92,%93,%94,%95," \
               "%96,%97,%98,%99,%100,%101,%102,%103,%104,%105,%106,%107,%108,%109,%110,%111,%112,%113,%114,%115,%116,%117,%118,%119,%120,%121,%122,%123,%124,%125,%126,%127"

#define DESC(d, r, o) "add.u32 t, " r ", " o ";\nmov.b64 " d ", {t, h};\n"
#define MMA_PRE_(acc, hi) "{\n.reg .pred p;\n.reg .b32 t, h;\n.reg .b64 da, db;\nmov.b32 h, " hi ";\nsetp.ne.b32 p, " acc ", 0;\n"
#define MMA_PRE(acc) MMA_PRE_(acc, "0x40000040")
#define MMA_PRE64(acc) MMA_PRE_(acc, "0x80000020")
template <int TB, int OA, int OB>
__device__ __forceinline__ void mma_n256_ss(float (&d)[128], uint32_t a, uint32_t b, int acc) {
  asm volatile(MMA_PRE("%130") DESC("da", "%128", "%132") DESC("db", "%129", "%133")
               "wgmma.mma_async.sync.aligned.m64n256k16.f32.bf16.bf16 {" REGS128 "}, da, db, p, 1, 1, 0, %131;\n}\n"
               : R8(0), R8(8), R8(16), R8(24), R8(32), R8(40), R8(48), R8(56), R8(64), R8(72), R8(80), R8(88), R8(96), R8(104), R8(112), R8(120)
               : "r"(a), "r"(b), "r"(acc), "n"(TB), "n"(OA >> 4), "n"(OB >> 4));
}
template <int TB, int OA, int OB>
__device__ __forceinline__ void mma_n128_ss(float (&d)[64], uint32_t a, uint32_t b, int acc) {
  asm volatile(MMA_PRE("%66") DESC("da", "%64", "%68") DESC("db", "%65", "%69")
               "wgmma.mma_async.sync.aligned.m64n128k16.f32.bf16.bf16 {" REGS64 "}, da, db, p, 1, 1, 0, %67;\n}\n"
               : R8(0), R8(8), R8(16), R8(24), R8(32), R8(40), R8(48), R8(56)
               : "r"(a), "r"(b), "r"(acc), "n"(TB), "n"(OA >> 4), "n"(OB >> 4));
}
template <int TB, int OB>
__device__ __forceinline__ void mma_n128_rs(float (&d)[64], const uint32_t* a, uint32_t b, int acc) {
  asm volatile(MMA_PRE64("%69") DESC("db", "%68", "%71")
               "wgmma.mma_async.sync.aligned.m64n128k16.f32.bf16.bf16 {" REGS64 "}, {%64,%65,%66,%67}, db, p, 1, 1, %70;\n}\n"
               : R8(0), R8(8), R8(16), R8(24), R8(32), R8(40), R8(48), R8(56)
               : "r"(a[0]), "r"(a[1]), "r"(a[2]), "r"(a[3]), "r"(b), "r"(acc), "n"(TB), "n"(OB >> 4));
}
#define W8(b) "=f"(d[b + 0]), "=f"(d[b + 1]), "=f"(d[b + 2]), "=f"(d[b + 3]), "=f"(d[b + 4]), "=f"(d[b + 5]), "=f"(d[b + 6]), "=f"(d[b + 7])
#define MMA_N64 MMA_PRE64("%37") DESC("db", "%36", "%38") \
  "wgmma.mma_async.sync.aligned.m64n64k16.f32.bf16.bf16 {%0,%1,%2,%3,%4,%5,%6,%7,%8,%9,%10,%11,%12,%13,%14,%15,%16,%17,%18,%19,%20,%21," \
  "%22,%23,%24,%25,%26,%27,%28,%29,%30,%31}, {%32,%33,%34,%35}, db, p, 1, 1, 0;\n}\n"
template <int H, int OB, bool ACC>
__device__ __forceinline__ void mma_n64_rs(float (&d)[64], const uint32_t* a, uint32_t b) {
  if (ACC) asm volatile(MMA_N64 : R8(32 * H), R8(32 * H + 8), R8(32 * H + 16), R8(32 * H + 24) : "r"(a[0]), "r"(a[1]), "r"(a[2]), "r"(a[3]), "r"(b), "n"(1), "n"(OB >> 4));
  else asm volatile(MMA_N64 : W8(32 * H), W8(32 * H + 8), W8(32 * H + 16), W8(32 * H + 24) : "r"(a[0]), "r"(a[1]), "r"(a[2]), "r"(a[3]), "r"(b), "n"(0), "n"(OB >> 4));
}
template <int OB>
__device__ __forceinline__ void mma_n128_rs0(float (&d)[64], const uint32_t* a, uint32_t b) {
  asm volatile(MMA_PRE64("%69") DESC("db", "%68", "%70")
               "wgmma.mma_async.sync.aligned.m64n128k16.f32.bf16.bf16 {" REGS64 "}, {%64,%65,%66,%67}, db, p, 1, 1, 0;\n}\n"
               : W8(0), W8(8), W8(16), W8(24), W8(32), W8(40), W8(48), W8(56)
               : "r"(a[0]), "r"(a[1]), "r"(a[2]), "r"(a[3]), "r"(b), "n"(0), "n"(OB >> 4));
}
#define MMA_SSH MMA_PRE("%67") DESC("db", "%65", "%69") "add.u32 t, %64, %68;\nmov.b64 da, {t, %66};\n" \
  "wgmma.mma_async.sync.aligned.m64n128k16.f32.bf16.bf16 {" REGS64 "}, da, db, p, 1, 1, 0, 1;\n}\n"
template <int OA, int OB, bool ACC>
__device__ __forceinline__ void mma_n128_ssh(float (&d)[64], uint32_t a, uint32_t ahi, uint32_t b) {
  if (ACC) asm volatile(MMA_SSH : R8(0), R8(8), R8(16), R8(24), R8(32), R8(40), R8(48), R8(56) : "r"(a), "r"(b), "r"(ahi), "n"(1), "n"(OA >> 4), "n"(OB >> 4));
  else asm volatile(MMA_SSH : W8(0), W8(8), W8(16), W8(24), W8(32), W8(40), W8(48), W8(56) : "r"(a), "r"(b), "r"(ahi), "n"(0), "n"(OA >> 4), "n"(OB >> 4));
}
template <int TB, int OA, int OB>
__device__ __forceinline__ void mma_n128_ss0(float (&d)[64], uint32_t a, uint32_t b) {
  asm volatile(MMA_PRE("%66") DESC("da", "%64", "%68") DESC("db", "%65", "%69")
               "wgmma.mma_async.sync.aligned.m64n128k16.f32.bf16.bf16 {" REGS64 "}, da, db, p, 1, 1, 0, %67;\n}\n"
               : W8(0), W8(8), W8(16), W8(24), W8(32), W8(40), W8(48), W8(56)
               : "r"(a), "r"(b), "n"(0), "n"(TB), "n"(OA >> 4), "n"(OB >> 4));
}
template <int V> struct IC { static constexpr int value = V; __host__ __device__ constexpr operator int() const { return V; } };
template <int N, class F, int... I>
__device__ __forceinline__ void static_for_(F f, std::integer_sequence<int, I...>) { (f(IC<I>{}), ...); }
template <int N, class F>
__device__ __forceinline__ void static_for(F f) { static_for_<N>(f, std::make_integer_sequence<int, N>{}); }
__device__ __forceinline__ uint32_t pack_bf16(float lo, float hi) {
  uint32_t r;
  asm("cvt.rn.bf16x2.f32 %0, %1, %2;" : "=r"(r) : "f"(hi), "f"(lo));
  return r;
}
__device__ __forceinline__ float bf_lo(uint32_t v) { return __uint_as_float(v << 16); }
__device__ __forceinline__ float bf_hi(uint32_t v) { return __uint_as_float(v & 0xFFFF0000u); }
__device__ __forceinline__ float bf_round(float v) { return bf_lo(pack_bf16(v, v)); }
__device__ __forceinline__ void stsm4(uint32_t addr, uint32_t r0, uint32_t r1, uint32_t r2, uint32_t r3) {
  asm volatile("stmatrix.sync.aligned.m8n8.x4.shared.b16 [%0], {%1,%2,%3,%4};" ::"r"(addr), "r"(r0), "r"(r1), "r"(r2), "r"(r3) : "memory");
}
__device__ __forceinline__ uint4 lds128(uint32_t addr) {
  uint4 v;
  asm volatile("ld.shared.v4.u32 {%0,%1,%2,%3}, [%4];" : "=r"(v.x), "=r"(v.y), "=r"(v.z), "=r"(v.w) : "r"(addr));
  return v;
}
__device__ __forceinline__ float ex2(float x) {
  float y;
  asm("ex2.approx.ftz.f32 %0, %1;" : "=f"(y) : "f"(x));
  return y;
}
__device__ __forceinline__ void stage_store_128(uint32_t base, int lane, const uint32_t* pk) {
  const int row = (lane & 7) + ((lane >> 3) & 1) * 8;
  const uint32_t rb = base + row * 128;
  const int hi = lane >> 4;
#pragma unroll
  for (int j = 0; j < 8; j++) {
    const int chunk = 2 * j + hi;
    const uint32_t a = rb + (j >> 2) * 8192 + (((chunk & 7) ^ (lane & 7)) << 4);
    stsm4(a, pk[4 * j + 0], pk[4 * j + 1], pk[4 * j + 2], pk[4 * j + 3]);
  }
}
__device__ __forceinline__ void ln_round(float mean, float var, float& m_bf, float& inv_s) {
  const uint32_t mv = pack_bf16(mean, var);
  m_bf = bf_lo(mv);
  float sq, rc;
  asm("sqrt.approx.ftz.f32 %0, %1;" : "=f"(sq) : "f"(bf_round(bf_hi(mv) + 1e-5f)));
  asm("rcp.approx.ftz.f32 %0, %1;" : "=f"(rc) : "f"(bf_round(sq)));
  inv_s = rc;
}
__device__ __forceinline__ uint32_t hadd2_bf(uint32_t a, uint32_t b) {
  uint32_t r;
  asm("add.rn.bf16x2 %0, %1, %2;" : "=r"(r) : "r"(a), "r"(b));
  return r;
}
__device__ __forceinline__ uint32_t ln_apply(uint32_t h, uint32_t nm2, float inv_s) {
  const uint32_t d = hadd2_bf(h, nm2);
  return pack_bf16(bf_lo(d) * inv_s, bf_hi(d) * inv_s);
}
__device__ __forceinline__ void mma16816(float* d, uint32_t a0, uint32_t a1, uint32_t a2, uint32_t a3, uint32_t b0, uint32_t b1) {
  asm volatile("mma.sync.aligned.m16n8k16.row.col.f32.bf16.bf16.f32 {%0,%1,%2,%3}, {%4,%5,%6,%7}, {%8,%9}, {%0,%1,%2,%3};"
               : "+f"(d[0]), "+f"(d[1]), "+f"(d[2]), "+f"(d[3]) : "r"(a0), "r"(a1), "r"(a2), "r"(a3), "r"(b0), "r"(b1));
}

constexpr float AT_C = 0.08838834764831845f * 1.4426950408889634f;
#define L_MIN 3.5527137e-15f
#define L_MAX 1.8446744e19f
struct AtState {
  float S[64], O[64];
  uint32_t P[32], Q[32];
  float l[4];
};
template <int I0, int I1>
__device__ __forceinline__ void at_exp(AtState& s) {
#pragma unroll
  for (int i = I0; i < I1; i++) asm volatile("ex2.approx.ftz.f32 %0, %0;" : "+f"(s.S[i]));
#pragma unroll
  for (int i = I0; i < I1; i++) asm volatile("add.f32 %0, %0, %1;" : "+f"(s.l[i & 3]) : "f"(s.S[i]));
}
template <int I0, int I1>
__device__ __forceinline__ void at_pack(AtState& s) {
#pragma unroll
  for (int i = I0; i < I1; i++) asm volatile("cvt.rn.bf16x2.f32 %0, %1, %2;" : "=r"(s.P[i]) : "f"(s.S[2 * i + 1]), "f"(s.S[2 * i]));
}
template <int J0>
__device__ __forceinline__ void at_mask(AtState& s, int r, int lane) {
  const int d = r + (lane >> 2) - (lane & 3) * 2;
#pragma unroll
  for (int j = 0; j < 8; j++) {
    float dummy0 = 0.f, dummy1 = 0.f;
    float& lo0 = j < 7 ? s.S[4 * (J0 + (j < 7 ? j + 1 : j)) + 2] : dummy0;
    float& lo1 = j < 7 ? s.S[4 * (J0 + (j < 7 ? j + 1 : j)) + 3] : dummy1;
    asm("{\n.reg .pred p, q;\nsetp.lt.s32 p, %4, %5;\nsetp.le.s32 q, %4, %5;\n"
        "@p add.f32 %0, %0, 0fFF800000;\n@q add.f32 %1, %1, 0fFF800000;\n@p add.f32 %2, %2, 0fFF800000;\n@q add.f32 %3, %3, 0fFF800000;\n}"
        : "+f"(s.S[4 * (J0 + j)]), "+f"(s.S[4 * (J0 + j) + 1]), "+f"(lo0), "+f"(lo1) : "r"(d), "r"(8 * j));
  }
}
template <int D>
__device__ __forceinline__ uint32_t ld_pair(const __nv_bfloat16* p) {
  uint32_t r;
  asm volatile("{\n.reg .b16 a, b;\nld.global.cg.b16 a, [%1];\nld.global.cg.b16 b, [%1 + %2];\nmov.b32 %0, {a, b};\n}" : "=r"(r) : "l"(p), "n"(2 * D) : "memory");
  return r;
}
__device__ __forceinline__ uint32_t ld_word(const uint32_t* p) {
  uint32_t r;
  asm volatile("ld.global.cg.b32 %0, [%1];" : "=r"(r) : "l"(p) : "memory");
  return r;
}
__device__ __noinline__ void slow_rows(const __nv_bfloat16* wq, int head, int row0) {
  const int lane = fresh_lane(), r = lane >> 2, c = lane & 3;
  uint32_t q[32];
  float o[32];
#pragma unroll
  for (int i = 0; i < 32; i++) q[i] = 0;
  const uint32_t* xa = reinterpret_cast<const uint32_t*>(g_xn + (size_t)(row0 + r) * DM) + c;
#pragma unroll 1
  for (int h = 0; h < 2; h++) {
    const __nv_bfloat16* wb = wq + (size_t)2 * c * NQ + head * HD + 64 * h + 8 * (r >> 1) + (r & 1);
#pragma unroll
    for (int i = 0; i < 32; i++) o[i] = 0.f;
#pragma unroll 1
    for (int kk = 0; kk < DM / 16; kk++) {
      const uint32_t a0 = ld_word(xa + 8 * kk), a1 = ld_word(xa + 8 * kk + 4 * DM), a2 = ld_word(xa + 8 * kk + 4), a3 = ld_word(xa + 8 * kk + 4 * DM + 4);
#pragma unroll
      for (int n = 0; n < 8; n++) {
        const __nv_bfloat16* b = wb + (size_t)16 * kk * NQ + 32 * (n >> 2) + 2 * (n & 3);
        mma16816(o + 4 * n, a0, a1, a2, a3, ld_pair<NQ>(b), ld_pair<NQ>(b + 8 * NQ));
        if (n & 1) sched_fence();
      }
    }
#pragma unroll
    for (int i = 0; i < 16; i++) { q[i] = q[16 + i]; q[16 + i] = pack_bf16(o[2 * i] * AT_C, o[2 * i + 1] * AT_C); }
  }
#pragma unroll 1
  for (int h = 0; h < 2; h++) {
    float m0 = -INFINITY, m1 = -INFINITY, l0 = 0.f, l1 = 0.f;
#pragma unroll
    for (int i = 0; i < 32; i++) o[i] = 0.f;
#pragma unroll 1
    for (int k0 = 0; k0 <= row0; k0 += 16) {
      float e[8] = {0.f, 0.f, 0.f, 0.f, 0.f, 0.f, 0.f, 0.f};
      const __nv_bfloat16* kt = g_kv + (size_t)(head * 16 + (k0 >> 7)) * KV_TILE + (k0 & 127) * 32;
      const uint32_t* kp = reinterpret_cast<const uint32_t*>(kt + r * 32) + c;
#pragma unroll
      for (int kk = 0; kk < 8; kk++) {
        const uint32_t* k0p = kp + (kk >> 1) * 2048 + (((kk & 1) * 2) ^ (r >> 1)) * 4;
        const uint32_t* k1p = kp + (kk >> 1) * 2048 + (((kk & 1) * 2 + 1) ^ (r >> 1)) * 4;
        mma16816(e, q[4 * kk], q[4 * kk + 1], q[4 * kk + 2], q[4 * kk + 3], ld_word(k0p), ld_word(k1p));
        mma16816(e + 4, q[4 * kk], q[4 * kk + 1], q[4 * kk + 2], q[4 * kk + 3], ld_word(k0p + 128), ld_word(k1p + 128));
        if (kk & 1) sched_fence();
      }
      if (k0 == row0) {
#pragma unroll
        for (int i = 0; i < 8; i++) if ((i >> 2) * 8 + 2 * c + (i & 1) > r + (i & 2) * 4) e[i] = -INFINITY;
      }
      float a0 = fmaxf(fmaxf(e[0], e[1]), fmaxf(e[4], e[5])), a1 = fmaxf(fmaxf(e[2], e[3]), fmaxf(e[6], e[7]));
      a0 = fmaxf(a0, __shfl_xor_sync(~0u, a0, 1)); a1 = fmaxf(a1, __shfl_xor_sync(~0u, a1, 1));
      a0 = fmaxf(a0, __shfl_xor_sync(~0u, a0, 2)); a1 = fmaxf(a1, __shfl_xor_sync(~0u, a1, 2));
      a0 = fmaxf(a0, m0); a1 = fmaxf(a1, m1);
      const float sc0 = ex2(m0 - a0), sc1 = ex2(m1 - a1);
      m0 = a0; m1 = a1;
#pragma unroll
      for (int i = 0; i < 8; i++) e[i] = ex2(e[i] - ((i & 2) ? m1 : m0));
      l0 = l0 * sc0 + (e[0] + e[1]) + (e[4] + e[5]);
      l1 = l1 * sc1 + (e[2] + e[3]) + (e[6] + e[7]);
      const uint32_t p0 = pack_bf16(e[0], e[1]), p1 = pack_bf16(e[2], e[3]), p2 = pack_bf16(e[4], e[5]), p3 = pack_bf16(e[6], e[7]);
      const __nv_bfloat16* vp = kt + (size_t)512 * KV_TILE + h * 8192 + 2 * c * 32 + r;
#pragma unroll
      for (int n = 0; n < 8; n++) {
        o[4 * n] *= sc0; o[4 * n + 1] *= sc0; o[4 * n + 2] *= sc1; o[4 * n + 3] *= sc1;
        mma16816(o + 4 * n, p0, p1, p2, p3, ld_pair<32>(vp + (n >> 2) * 4096 + ((n ^ c) & 3) * 8), ld_pair<32>(vp + (n >> 2) * 4096 + ((n ^ c) & 3) * 8 + 256));
        if (n & 1) sched_fence();
      }
    }
    l0 += __shfl_xor_sync(~0u, l0, 1); l1 += __shfl_xor_sync(~0u, l1, 1);
    l0 += __shfl_xor_sync(~0u, l0, 2); l1 += __shfl_xor_sync(~0u, l1, 2);
#pragma unroll
    for (int i = 0; i < 4; i++) {
      const float* v = o + 16 * (i >> 1) + 2 * (i & 1);
      const float f = __fdividef(1.f, (i & 1) ? l1 : l0);
      *reinterpret_cast<uint4*>(g_ctx + (size_t)((row0 >> 7) * 32 + head) * KV_TILE + (2 * h + (i >> 1)) * 4096 + ((row0 & 127) + r + (i & 1) * 8) * 32 + (c ^ (r >> 1)) * 8) =
          make_uint4(pack_bf16(v[0] * f, v[1] * f), pack_bf16(v[4] * f, v[5] * f), pack_bf16(v[8] * f, v[9] * f), pack_bf16(v[12] * f, v[13] * f));
    }
  }
}

constexpr int UNIT = 16384, SLOT = 32768;
constexpr int OFF_SIDE = 2 * SLOT;
__host__ __device__ constexpr int kv_a(int kb) { return (kb < 6 ? kb : 3 * kb - 10) * UNIT; }
__host__ __device__ constexpr int kv_b(int s) { return ((0x76DCA9 >> (4 * s)) & 15) * UNIT; }
__host__ __device__ constexpr int q_aw(int s) { return (3 * s + (s & 1)) * UNIT; }
__host__ __device__ constexpr int q_b(int s) { return (3 * s + 2 - 2 * (s & 1)) * UNIT; }
__host__ __device__ constexpr int k_slot(int j, int r) { return (j < 2 ? 2 * j : (r == 2 ? 0 : 3 + r)) * SLOT; }
__host__ __device__ constexpr int v_slot(int j) { return (6 - (j & 1)) * SLOT; }
__host__ __device__ constexpr int r3(int st) { return ((0x654130 >> (4 * st)) & 7) * SLOT; }
constexpr int OFF_BAR = 229376;
constexpr int OFF_MISC = OFF_BAR + 512;
constexpr int SMEM_BYTES = OFF_MISC + 2080 + TL_EXTRA;
constexpr int OFF_RSTAT = OFF_MISC + 1056;
enum : int {
  B_FULL1 = 0, B_FULLQ = 6, B_FULLB = 10, B_KF = 11, B_VF = 14, B_FULL3 = 16, B_WF = 22, B_DEP = 24, B_OUT2 = 29, B_PF = 30, B_SET = 31,
  B_SET2 = 32, B_LNGO = 33, B_WR = 34,
  B_KE = 35, B_VE = 38, B_WE = 40, B_PUB = 42, B_OUT = 48,
  B_EMPTY1 = 49, B_EMPTYQ = 55, B_X = 59, B_EMPTY3 = 63,
  B_NUM = 69
};
#define TUNABLE(name, v) constexpr int name = v
TUNABLE(LN_GO, 3);
TUNABLE(EP1, 2);
TUNABLE(SIDE_NS, 400);
TUNABLE(SET_KB, 44); TUNABLE(SET_NS, 40);
TUNABLE(PF_KB, 54); TUNABLE(PF_N, 7); TUNABLE(PF_NS, 300);
TUNABLE(PS_DLY, 120); TUNABLE(Y_DLY, 700); TUNABLE(Y_DLY0, 1500);
constexpr int PRE = 6;
constexpr int WIN = 6;
constexpr int OFF_STG = r3(0), OFF_SCR = r3(1);
struct Params {
  CUtensorMap xn, ckv, wq, wk, wv, wo, x, wd, wg, wu;
};

__global__ void __cluster_dims__(2, 1, 1) __launch_bounds__(384, 1)
fused_kernel(uint32_t zero, const __nv_bfloat16* __restrict__ x, __nv_bfloat16* g_kv, __nv_bfloat16* g_ctx, uint4* g_xr,
             __nv_bfloat16* __restrict__ out, __nv_bfloat16* g_xn, unsigned* g_cnt, const __nv_bfloat16* __restrict__ w_r,
             const __nv_bfloat16* __restrict__ wdown, const __nv_bfloat16* __restrict__ wq, const __grid_constant__ Params p) {
  extern __shared__ __align__(1024) uint8_t sp[];
  const uint32_t sb = s2u(sp);
  const uint32_t bar = sb + OFF_BAR;
  auto B = [&](int i) { return bar + 8 * i; };
  const int tid = threadIdx.x, warp = __shfl_sync(~0u, tid >> 5, 0), wg = warp >> 2, lane = tid & 31;
  const int cta = blockIdx.x, rank = cta & 1, cl = cta >> 1;
  const int mp = cl < 4 ? 1 : (cl < 36 ? (cl & 7) : (0x3207654 >> (4 * ((cl - 36) % 7))) & 7);
  const int gq = cl < 4 ? 4 + cl : (cl < 36 ? (cl - 4) >> 3 : 4 + (cl - 36) / 7);
  const int mt = 2 * mp + rank;
  const int qa = 15 - gq;
  const int ta = gq ? gq : 15, tb = 15 - ta;
  const int rid = mt * 8 + gq;
  const int fid = mt * 7 + gq;
  const bool ffn = gq < 7;
  TL(0, 0, warp == 4);
  auto load_pre = [&](int i) {
    e_expect(B(B_FULL1 + i), (i & 1) ? UNIT : 2 * UNIT);
    if (!(i & 1)) tma_ld2(sb + kv_a(i >> 1), &p.ckv, B(B_FULL1 + i), i * 32, mt * 128);
    tma_ld3(sb + kv_b(i) + rank * 8192, &p.wk, B(B_FULL1 + i), 0, i * 32, (gq + 8) * 4 + rank * 2);
    tma_ld3(sb + kv_b(i) + 8192 - rank * 8192, &p.wk, B(B_FULL1 + i), 0, i * 32, (gq + 8) * 4 + 2 - rank * 2);
  };
  if (warp == 0) {
    e_init(B(B_FULL1), 1);
    asm volatile("fence.mbarrier_init.release.cluster;" ::: "memory");
    TL(0, 16, true);
    load_pre(0);
    TL(0, 17, true);
#pragma unroll
    for (int kb = 1; kb < PRE; kb++) e_init(B(B_FULL1 + kb), 1);
  } else {
#pragma unroll 1
    for (int i = PRE - 1 + warp; i < B_NUM; i += 11) e_init(B(i), i >= B_EMPTY1 ? 16 : (i >= B_KE ? 8 : (i == B_WR ? 2 : 1)));
  }
  asm volatile("fence.mbarrier_init.release.cluster;" ::: "memory");
  cluster_arrive();
  const int rid0 = rid, warp0 = warp;
  if (wg == 0) {
    reg_dealloc<40>();
    if (warp == 0) {
      TL(0, 12, true);
#pragma unroll 1
      for (int kb = 1; kb < PRE; kb++) load_pre(kb);
      if (mt >= PRE) { tma_pf3(&p.wk, 0, mt * 32, (gq + 8) * 4); tma_pf3(&p.wk, 0, mt * 32, (gq + 8) * 4 + 2); }
      if (gq >= PRE / 2) tma_pf2(&p.ckv, gq * 64, mt * 128);
      TL(0, 15, true);
    }
    TL(0, 18, warp == 0);
    __syncwarp();
    cluster_wait();
    uint4* const xr = g_xr + rid * XR_SIZE;
    auto side_piece = [&](int c, int piece) {
      const uint32_t fb = B(B_WF + (c & 1));
      if (piece == 0) e_expect(fb, ffn ? UNIT : 0);
      if (ffn) tma_ld2_ef(sb + OFF_SIDE + (c & 1) * UNIT + piece * 4096, (piece & 2) ? &p.wg : &p.wu, fb, fid * 32, c * 128 + (piece & 1) * 64);
    };
    if (warp == 0) {
      {
        int st = 0; uint32_t ph = 0;
#pragma unroll 1
        for (int i = PRE; i < 64; i++) {
          const int t = i >> 4, h = i & 15;
          const uint32_t fb = B(B_FULL1 + st);
          const bool with_a = (i & 0x31) == 0;
          mbar_wait_c(B(B_EMPTY1 + st), ph);
          e_expect(fb, with_a ? 2 * UNIT : UNIT);
          if (with_a) tma_ld2(sb + kv_a(h >> 1), &p.ckv, fb, h * 32, mt * 128);
          tma_ld3_mc(sb + kv_b(st) + rank * 8192, (t & 1) ? &p.wv : &p.wk, fb, 0, h * 32, (gq + ((t >> 1) ^ 1) * 8) * 4 + rank * 2, 3);
          if (i == 2 * LN_GO) e_arrive(B(B_LNGO));
          if (i == 24) { prefetch_tm(&p.wq); prefetch_tm(&p.xn); }
          if ((h >> 1) == (t ? 0 : 4) && t < 3) tma_pf3((t & 1) ? &p.wk : &p.wv, 0, mt * 32, (gq + (((t + 1) >> 1) ^ 1) * 8) * 4 + (h & 1) * 2);
          if ((i | 2) == 50) tma_pf3(&p.wq, 0, (gq + 4 * h) * 64, mt * 2);
          if (++st == 6) { st = 0; ph ^= 1; }
        }
        prefetch_tm(&p.wo); prefetch_tm(&p.wd); prefetch_tm(&p.x); prefetch_tm(&p.wg); prefetch_tm(&p.wu);
        mbar_wait_c(B(B_DEP + 0), 0);
        uint32_t kpar = 7, vpar = 3;
        auto load_aw = [&](int kb, int head) {
          const uint32_t d = sb + q_aw(kb & 3), fb = B(B_FULLQ + (kb & 3));
          tma_ld2_mc(d + rank * 8192, &p.xn, fb, kb * 64, ta * 128 + rank * 64, 3);
          tma_ld3(d + UNIT, &p.wq, fb, 0, kb * 64, head * 2);
        };
        auto load_b = [&](int kb, uint32_t fb) { tma_ld2_mc(sb + q_b(kb & 3) + rank * 8192, &p.xn, fb, kb * 64, tb * 128 + rank * 64, 3); };
        auto load3 = [&](int kb, int s) {
          const uint32_t d = sb + r3(s), fb = B(B_FULL3 + s);
          e_expect(fb, SLOT);
          bulk_ld(d, g_ctx + (size_t)(mt * 64 + kb) * 8192, UNIT, fb);
          tma_ld3_mc(d + UNIT + rank * 8192, &p.wo, fb, 0, kb * 64, gq * 2 + rank, 3);
        };
#pragma unroll 1
        for (int half = 0; half < 2; half++) {
          const int head = mt + 16 * half;
#pragma unroll 1
          for (int kb = 2 * half; kb < 16; kb++) {
            if (kb >= 4) mbar_wait_c(B(B_EMPTYQ + (kb & 3)), ((kb >> 2) & 1) ^ 1);
            else if (half) mbar_wait_c(B(B_X + 2), 0);
            else if (kb > 0) mbar_wait_c(B(B_EMPTY1 + (2 * kb + 3) % 6), kb == 1);
            e_expect(B(B_FULLQ + (kb & 3)), 3 * UNIT);
            load_aw(kb, head);
            load_b(kb, B(B_FULLQ + (kb & 3)));
          }
          mbar_wait_c(B(B_DEP + 1 + half), 0);
          const __nv_bfloat16* kt = g_kv + (size_t)head * 16 * KV_TILE;
          l2_prefetch(kt, SLOT);
          auto load_v = [&](int j) {
            const int r = j & 1;
            mbar_wait_c(B(B_VE + r), (vpar >> r) & 1);
            vpar ^= 1 << r;
            e_expect(B(B_VF + r), SLOT);
            bulk_ld(sb + v_slot(j), kt + (size_t)(512 + (j > qa ? 16 - j : j)) * KV_TILE, SLOT, B(B_VF + r));
          };
          int r = 0;
#pragma unroll 1
          for (int j = 0; j < 17; j++) {
            if (j < 2) mbar_wait_c(B(B_EMPTYQ + j), 1);
            if (j == 2) mbar_wait_c(B(B_KE), kpar & 1);
            mbar_wait_c(B(B_KE + r), (kpar >> r) & 1);
            kpar ^= 1 << r;
            e_expect(B(B_KF + r), SLOT);
            bulk_ld(sb + k_slot(j, r), kt + (j > qa ? 16 - j : j) * KV_TILE, SLOT, B(B_KF + r));
            if (++r == 3) r = 0;
            if (j == 2) mbar_wait_c(B(B_EMPTYQ + 3), 1);
            if (j != 1) load_v(j ? j - 1 : 0);
            if (half && j < 16) l2_prefetch(kt + (size_t)(512 + j) * KV_TILE + gq * 2048, 4096);
            if (half == 0) {
              if (j == 16) {
                tma_pf3(&p.wq, 0, (4 + gq) * 64, (mt + 16) * 2);
                tma_pf2(&p.xn, (4 + (mp & 3)) * 64, ((mp & 4) ? qa : gq) * 128 + rank * 64);
              }
            } else if (j >= 14) {
              tma_pf3(&p.wo, 0, (5 + mp + 8 * (16 - j)) * 64, gq * 2 + rank);
            } else if (j >= 5 && j < 13) {
              side_piece((j - 5) >> 2, (j - 5) & 3);
            }
          }
          mbar_wait_c(B(B_X + 0), half);
          if (half == 0) {
            for (int kb = 0; kb < 2; kb++) { e_expect(B(B_FULLQ + kb), 2 * UNIT); load_aw(kb, mt + 16); }
          } else {
            mbar_wait_c(B(B_DEP + 3), 0);
            load3(0, 0);
          }
          mbar_wait_c(B(B_X + 1), half);
          if (half) load3(1, 1);
          load_v(16);
          if (gq == 0) mbar_wait_c(B(B_X + 2), half);
          if (half == 0) { e_expect(B(B_FULLB), 2 * UNIT); load_b(0, B(B_FULLB)); load_b(1, B(B_FULLB)); }
        }
        st = 2; ph = 1;
#pragma unroll 1
        for (int kb = 2; kb < 64; kb++) {
          if (kb == 32) mbar_wait_c(B(B_DEP + 4), 0);
          if (kb >= 6) mbar_wait_c(B(B_EMPTY3 + st), ph);
          else if (kb == 3 || kb == 5) mbar_wait_c(B(B_X + (kb + 1) / 2), 1);
          load3(kb, st);
          if (++st == 6) { st = 0; ph ^= 1; }
          if (kb == PF_KB) e_arrive(B(B_PF));
          if (kb == SET_KB) e_arrive(B(B_SET));
          if (kb == 58) l2_prefetch(xr, XR_CAND * 16);
        }
        if (ffn) {
#pragma unroll 1
          for (int j = 0; j < 2; j++) {
            mbar_wait_c(B(B_EMPTY3 + 4 + j), 1);
            e_expect(B(B_FULL3 + 4 + j), SLOT);
            tma_ld3(sb + r3(4 + j), &p.wd, B(B_FULL3 + 4 + j), 0, fid * 32, 8 * j);
          }
        }
        const uint4* kp = g_xr + ((lane >> 1) * 8 + gq) * XR_SIZE + XR_KEY + (lane & 1) * 2;
        mbar_wait_c(B(B_OUT), 0);
        uint32_t k1, k2, m1;
#pragma unroll 1
        for (int n = 0; n < 0x400000; n++) {
          uint4 a, b;
          asm volatile("ld.relaxed.gpu.global.v4.u32 {%0,%1,%2,%3}, [%4];" : "=r"(a.x), "=r"(a.y), "=r"(a.z), "=r"(a.w) : "l"(kp) : "memory");
          asm volatile("ld.relaxed.gpu.global.v4.u32 {%0,%1,%2,%3}, [%4 + 16];" : "=r"(b.x), "=r"(b.y), "=r"(b.z), "=r"(b.w) : "l"(kp) : "memory");
          const uint32_t a1 = max(a.x, a.z), a2 = max(min(a.x, a.z), max(a.y, a.w));
          const uint32_t b1 = max(b.x, b.z), b2 = max(min(b.x, b.z), max(b.y, b.w));
          k1 = max(a1, b1); k2 = max(min(a1, b1), max(a2, b2));
          m1 = __reduce_max_sync(~0u, max(k1, k2));
          if (m1 != 0xFFFFFFFFu) break;
        }
        const uint32_t m2 = __reduce_max_sync(~0u, k1 == m1 ? k2 : k1);
        const uint32_t t0 = ~m1 & 0x7FFF, t1 = ~m2 & 0x7FFF;
        const uint32_t o0 = (t0 >> 7) * (8 * XR_SIZE * 16) + (t0 & 0x70) * 64, o1 = (t1 >> 7) * (8 * XR_SIZE * 16) + (t1 & 0x70) * 64 + ((t0 ^ t1) < 16 ? 256 : 0);
        asm volatile(ELECT "st.shared.v4.u32 [%0], {%1,%2,%3,%4};\n}" ::"r"(sb + OFF_MISC + 256), "r"(o0), "r"(o1), "r"(m1), "r"(m2) : "memory");
        e_arrive(B(B_OUT2));
        if (rid == 127) { g_cnt[lane] = 0; g_cnt[32 + lane] = 0; }
      }
    } else {
      if (warp >= 2) {
#pragma unroll 1
        for (int i = tid - 64; i < XR_CAND; i += 64) xr[i] = make_uint4(~0u, ~0u, ~0u, ~0u);
        if (warp == 2) { __syncwarp(); if (lane == 0) mbar_arrive(B(B_WR)); }
      }
      if (warp == 3) {
        float ws = 0.f;
#pragma unroll 1
        for (int j = 0; j < 4; j++) {
          const uint4 q = __ldg(reinterpret_cast<const uint4*>(w_r) + j * 32 + lane);
          ws += bf_lo(q.x) + bf_hi(q.x) + bf_lo(q.y) + bf_hi(q.y) + bf_lo(q.z) + bf_hi(q.z) + bf_lo(q.w) + bf_hi(q.w);
        }
#pragma unroll
        for (int o = 16; o; o >>= 1) ws += __shfl_xor_sync(~0u, ws, o);
        uint2* tab = reinterpret_cast<uint2*>(sp + OFF_MISC + 512);
        tab[lane] = make_uint2(0x3F803F80u, 0x3F803F80u);
        tab[32 + lane] = __ldg(reinterpret_cast<const uint2*>(w_r + gq * 128) + lane);
        if (lane == 0) *reinterpret_cast<float*>(sp + OFF_MISC + 1024) = ws;
        __syncwarp();
        if (lane == 0) mbar_arrive(B(B_WR));
      }
      __syncwarp();
      mbar_wait_u(B(B_LNGO), 0);
#pragma unroll 1
      for (int r = warp == 2 ? 0 : (warp + 1) >> 1; r < 16; r += 3) {
        const uint4* src = reinterpret_cast<const uint4*>(x + (size_t)(cta * 16 + r) * DM) + lane;
        uint4 v[4];
#pragma unroll
        for (int j = 0; j < 4; j++) v[j] = __ldcs(src + j * 32);
        float a0 = 0.f, a1 = 0.f, b0 = 0.f, b1 = 0.f;
#pragma unroll
        for (int j = 0; j < 4; j++) {
          const uint32_t u[4] = {v[j].x, v[j].y, v[j].z, v[j].w};
#pragma unroll
          for (int i = 0; i < 4; i++) { const float a = bf_lo(u[i]), b = bf_hi(u[i]); a0 += a; a1 += b; b0 = fmaf(a, a, b0); b1 = fmaf(b, b, b1); }
        }
        a0 += a1; b0 += b1;
#pragma unroll
        for (int o = 16; o; o >>= 1) { a0 += __shfl_xor_sync(~0u, a0, o); b0 += __shfl_xor_sync(~0u, b0, o); }
        const float mean = a0 * (1.f / DM);
        float mb, inv;
        ln_round(mean, fmaxf(fmaf(b0, 1.f / DM, -mean * mean), 0.f), mb, inv);
        const uint32_t nm2 = pack_bf16(-mb, -mb);
        uint4* dst = reinterpret_cast<uint4*>(g_xn + (size_t)(cta * 16 + r) * DM) + lane;
#pragma unroll
        for (int j = 0; j < 4; j++) {
          dst[j * 32] = make_uint4(ln_apply(v[j].x, nm2, inv), ln_apply(v[j].y, nm2, inv), ln_apply(v[j].z, nm2, inv), ln_apply(v[j].w, nm2, inv));
          sched_fence();
        }
      }
      __syncwarp();
      if (lane == 0) {
        fence_gpu();
        red_add(&g_cnt[C_LN + (cta >> 3)], 1);
        TL(0, 20 + warp, true);
        if (warp == 3) {
          spin_until_ge<true>(&g_cnt[C_LN + gq], 24);
#pragma unroll 1
          for (int i = 0; i < 5; i++) {
            const int c = i == 0 ? C_LN + qa : (i < 3 ? C_KV + (i - 1) * 8 + mp : C_CTX + (i - 3) * 16 + mt);
            spin_until_ge<true>(&g_cnt[c], i == 0 ? 24 : 16);
            fence_async_all();
            mbar_arrive(B(B_DEP + i));
          }
        } else if (warp == 1) {
          mbar_wait(B(B_WR), 0);
#pragma unroll 1
          for (int i = 0; i < 6; i++) {
            const int c = i < 2 ? C_KV + gq + (i ^ 1) * 8 : C_CTX + ((i - 2) >> 1) * 16 + ((i & 1) ? tb : ta);
            mbar_wait(B(B_PUB + i), 0);
            fence_gpu();
            red_add(&g_cnt[c], 1);
          }
        }
      }
      __syncwarp();
      if (warp == 2) {
#pragma unroll 1
        for (int c = 2; c < WIN + 4; c++) {
          mbar_wait_u(B(B_WE + (c & 1)), ((c >> 1) & 1) ^ 1);
          if (c == WIN || c == WIN + 1) {
            e_expect(B(B_WF + (c & 1)), UNIT);
            tma_ld3_ef(sb + OFF_SIDE + (c & 1) * UNIT, &p.x, B(B_WF + (c & 1)), 0, mt * 128 + (c & 1) * 64, gq * 2);
          } else {
#pragma unroll 1
            for (int i = 0; i < 4; i++) { side_piece(c < WIN ? c : c - 2, i); __nanosleep(SIDE_NS); }
          }
        }
      } else if (warp == 1) {
        mbar_wait_u(B(B_SET), 0);
#pragma unroll 1
        for (int i = XR_CAND + lane; i < XR_SIZE; i += 32) { xr[i] = make_uint4(~0u, ~0u, ~0u, ~0u); __nanosleep(SET_NS); }
        __syncwarp();
        if (lane == 0) { fence_gpu(); mbar_arrive(B(B_SET2)); }
      } else {
        mbar_wait_u(B(B_PF), 0);
#pragma unroll 1
        for (int i = 0; i < PF_N; i++) {
          asm volatile("prefetch.global.L2 [%0];" ::"l"((const char*)wdown + (size_t)cta * 57344 + (i * 32 + lane) * 128));
          __nanosleep(PF_NS);
        }
      }
      __syncwarp();
      mbar_wait_u(B(B_OUT), 0);
      {
        const int sub = lane >> 4;
        const uint32_t src = sb + OFF_STG + ((lane & 15) >> 3) * 8192 + sub * 128;
        __nv_bfloat16* dst = out + (size_t)(mt * 128 + sub) * DM + gq * 128 + (lane & 15) * 8;
        auto ld = [&](int r, uint2& rs, uint4& v) {
          asm volatile("ld.shared.v2.u32 {%0,%1}, [%2];" : "=r"(rs.x), "=r"(rs.y) : "r"(sb + OFF_RSTAT + ((r + sub) & 127) * 8));
          v = lds128(src + ((r >> 6) & 1) * 16384 + (r & 63) * 128 + (((lane ^ (r + sub)) & 7) << 4));
        };
        uint2 rs; uint4 v;
        ld(2 * warp - 2, rs, v);
#pragma unroll 1
        for (int r = 2 * warp - 2; r < 128; r += 6) {
          const uint2 cs = rs; const uint4 c = v;
          ld(r + 6, rs, v);
          const float inv = __uint_as_float(cs.y);
          asm volatile("{\n.reg .pred p;\nsetp.ge.s32 p, %5, 0;\n@p st.global.v4.u32 [%0], {%1,%2,%3,%4};\n}" ::"l"(dst + (size_t)r * DM),
                       "r"(hadd2_bf(c.x, ln_apply(c.x, cs.x, inv))), "r"(hadd2_bf(c.y, ln_apply(c.y, cs.x, inv))),
                       "r"(hadd2_bf(c.z, ln_apply(c.z, cs.x, inv))), "r"(hadd2_bf(c.w, ln_apply(c.w, cs.x, inv))), "r"(cs.y) : "memory");
        }
      }
      TL(2, 25, warp == 1);
    }
    __syncwarp();
    cluster_arrive();
    cluster_wait();
  } else {
    reg_alloc<232>();
    const int rid_c = rid0 + zero, warp_c = warp0 + zero;
    const int lane = fresh_lane(), rid = rid_c, mt = rid >> 3, gq = rid & 7, qa = 15 - gq, ta = gq ? gq : 15, tb = 15 - ta;
    const int warp = warp_c, cw = warp - 4, w = cw >> 2;
    cluster_wait();
    auto publish = [&](int i) { __syncwarp(); e_arrive(B(B_PUB + i)); };
    auto release2 = [&](uint32_t b, bool cond = true) { mbar_arrive_both(b, lane, cond); };
    AtState s;
    const uint32_t dA = mk_desc(sb + w * 8192, 16);
    const uint32_t dW = mk_desc(sb, 8192);
    auto mma_kb = [&](float (&d)[64], uint32_t a, uint32_t b, int accum) {
      static_for<4>([&](auto k) { mma_n128_ss<1, k * 32, k * 2048>(d, dA + (a >> 4), dW + (b >> 4), k == 0 ? accum : 1); });
    };
    auto mma_kc = [&](float (&d)[64], auto a, auto b, int accum) {
      static_for<4>([&](auto k) { mma_n128_ss<1, decltype(a)::value + k * 32, decltype(b)::value + k * 2048>(d, dA, dW, k == 0 ? accum : 1); });
    };
    auto issue_q = [&](int kb, auto accum, bool rel = true) {
      const int st = kb & 3;
      if (accum) mbar_wait_c(B(B_FULLQ + st), (kb >> 2) & 1);
      wg_fence();
      mma_kb(s.S, q_aw(st), q_aw(st) + UNIT, accum);
      wg_commit();
      if (accum) {
        wg_wait<1>();
        release2(B(B_EMPTYQ + ((kb - 1) & 3)), rel);
        wg_fence();
      }
      mma_kb(s.O, q_b(st), q_aw(st) + UNIT, accum);
      wg_commit();
    };
    {
      uint4 pk[16];
      __nv_bfloat16* pdst = g_kv;
      auto put = [&](int i) { __stcs(reinterpret_cast<uint4*>(pdst + (i & 1) * 256 + ((i >> 1) & 3) * 4096 + (i >> 3) * 16 * KV_TILE), pk[i]); };
      float acc1[128];
      TL(0, 1, warp == 4);
      int st = 0; uint32_t ph = 0;
      const uint32_t dH = mk_desc(sb, 4096);
      mbar_wait_c(B(B_FULL1), 0);
      auto issue = [&](int h, auto accum) {
        if (accum) mbar_wait_c(B(B_FULL1 + st), ph);
        wg_fence();
        static_for<2>([&](auto k) { mma_n256_ss<1, k * 32, k * 2048>(acc1, dA + (kv_a(h >> 1) >> 4) + (h & 1) * 4, dH + (kv_b(st) >> 4), k == 0 ? (int)accum : 1); });
        wg_commit();
      };
#pragma unroll 1
      for (int t = 0; t < 4; t++) {
        issue(0, IC<0>{});
        TL(0, 2 + 2 * t, warp == 4);
        if (t > 0) { put(0); put(1); }
        int prev = st;
        if (++st == 6) { st = 0; ph ^= 1; }
#pragma unroll 1
        for (int h = 1; h < 16; h++) {
          if (h == 14 && w == 1) bar_sync(5, 256);
          issue(h, IC<1>{});
          if (h == 15 && w == 0) bar_arrive(5, 256);
          if (t > 0) {
#pragma unroll
            for (int i = 2; i < 16; i++) if (h == (i < 4 ? 1 : i - 2)) put(i);
            if (h == 13 && t == 2) publish(0);
          }
          wg_wait<1>();
          if (!(h & 1)) TK(24 + t * 8 + (h >> 1) - 1);
          release2(B(B_EMPTY1 + prev));
          prev = st;
          if (++st == 6) { st = 0; ph ^= 1; }
        }
        pdst = g_kv + (size_t)(((t & 1) * 32 + (gq + ((t >> 1) ^ 1) * 8) * 2) * 16 + mt) * KV_TILE + (cw * 16 + (lane >> 2)) * 32 + ((lane ^ (lane >> 3)) & 3) * 8;
        mbar_wait_c(B(t < 3 ? B_FULL1 + st : B_FULLQ), t < 3 ? ph : 0);
        wg_wait<0>();
        TK(24 + t * 8 + 7);
        fence_regs(acc1);
        release2(B(B_EMPTY1 + prev));
        TL(0, 3 + 2 * t, warp == 4);
#pragma unroll
        for (int a = 0; a < 8; a++)
#pragma unroll
          for (int h = 0; h < 2; h++)
            pk[2 * a + h] = make_uint4(pack_bf16(acc1[16 * a + 2 * h], acc1[16 * a + 2 * h + 1]), pack_bf16(acc1[16 * a + 4 + 2 * h], acc1[16 * a + 5 + 2 * h]),
                                       pack_bf16(acc1[16 * a + 8 + 2 * h], acc1[16 * a + 9 + 2 * h]), pack_bf16(acc1[16 * a + 12 + 2 * h], acc1[16 * a + 13 + 2 * h]));
      }
      issue_q(0, IC<0>{});
      TL(0, 10, warp == 4);
      put(0); put(1);
#pragma unroll 1
      for (int kb = 1; kb < 8; kb++) {
        issue_q(kb, IC<1>{});
        TK(66 + kb - 1);
#pragma unroll
        for (int i = 1; i < 8; i++) if (kb == i) { put(2 * i); put(2 * i + 1); }
      }
      publish(1);
      TL(0, 11, warp == 4);
    }
    __nv_bfloat16* cdst;
    uint32_t redo = 0;
    auto put_ctx = [&](int i, bool cond) {
      asm volatile("{\n.reg .pred p;\nsetp.ne.u32 p, %5, 0;\n@p st.global.cs.v4.u32 [%0], {%1,%2,%3,%4};\n}" ::"l"(cdst + (i & 1) * 256 + (i >> 1) * 4096),
                   "r"(s.P[4 * i]), "r"(s.P[4 * i + 1]), "r"(s.P[4 * i + 2]), "r"(s.P[4 * i + 3]), "r"((uint32_t)(cond && !(redo & 2))) : "memory");
    };
    {
      const int wrow = cw * 16;
      const uint32_t dK = mk_desc(sb, 16), dV = mk_desc(sb, 8192);
      uint32_t kph = 0, vph = 0;
      auto q_store = [&](const float (&d)[64], auto i0, auto i1) {
        const int r0 = lane >> 2;
        const uint32_t a = sb + SLOT + (wrow + r0) * 128 + (((lane & 3) ^ (((r0 & 1) << 2) | (r0 >> 1))) << 4);
#pragma unroll
        for (int i = i0; i < i1; i++) {
          const float* o = d + 16 * (i >> 1) + 2 * (i & 1);
          asm volatile("st.shared.v4.u32 [%0], {%1,%2,%3,%4};" ::"r"((a ^ ((i & 2) << 5)) + (i >> 2) * UNIT + (i & 1) * 1024),
                       "r"(pack_bf16(o[0] * AT_C, o[1] * AT_C)), "r"(pack_bf16(o[4] * AT_C, o[5] * AT_C)),
                       "r"(pack_bf16(o[8] * AT_C, o[9] * AT_C)), "r"(pack_bf16(o[12] * AT_C, o[13] * AT_C)) : "memory");
        }
        __syncwarp();
      };
      auto q_load = [&](auto k0, auto k1) {
        const uint32_t a = sb + SLOT + (wrow + (lane & 15)) * 128 + (((lane >> 4) ^ (((lane & 1) << 2) | ((lane >> 1) & 3))) << 4);
#pragma unroll
        for (int k = k0; k < k1; k++)
          asm volatile("ldmatrix.sync.aligned.m8n8.x4.shared.b16 {%0,%1,%2,%3}, [%4];"
                       : "=r"(s.Q[4 * k]), "=r"(s.Q[4 * k + 1]), "=r"(s.Q[4 * k + 2]), "=r"(s.Q[4 * k + 3]) : "r"((a ^ ((k & 3) << 5)) + (k >> 2) * UNIT) : "memory");
      };
      auto q_load_if = [&](auto k, bool cond, float after) {
        const uint32_t a = sb + SLOT + (wrow + (lane & 15)) * 128 + (((lane >> 4) ^ (((lane & 1) << 2) | ((lane >> 1) & 3))) << 4);
        asm volatile("{\n.reg .pred p;\nsetp.ne.u32 p, %5, 0;\n@p ldmatrix.sync.aligned.m8n8.x4.shared.b16 {%0,%1,%2,%3}, [%4];\n}"
                     : "+r"(s.Q[4 * k]), "+r"(s.Q[4 * k + 1]), "+r"(s.Q[4 * k + 2]), "+r"(s.Q[4 * k + 3])
                     : "r"((a ^ ((k & 3) << 5)) + (k >> 2) * UNIT + (__float_as_uint(after) >> 31)), "r"((uint32_t)cond) : "memory");
      };
      auto issue_s = [&](uint32_t dk, auto mid) {
        mma_n128_rs0<0>(s.S, s.Q, dk);
        static_for<7>([&](auto i) {
          constexpr int k = i + 1;
          if (k == 4) mid();
          mma_n128_rs<0, (k >> 1) * 8192 + (k & 1) * 32>(s.S, s.Q + 4 * k, dk, 1);
        });
        wg_commit();
      };
      auto wait_v = [&](int jv) {
        mbar_wait_c(B(B_VF + (jv & 1)), (vph >> (jv & 1)) & 1);
        vph ^= 1 << (jv & 1);
      };
      auto issue_pva = [&](int jv, int accum) {
        wg_fence();
        static_for<4>([&](auto k) { mma_n128_rs<1, k * 1024>(s.O, s.P + 4 * k, dV + (v_slot(jv) >> 4), k == 0 ? accum : 1); });
        wg_commit();
      };
      auto issue_pvb = [&](int jv, bool upper) {
        if (upper) {
          wg_fence();
          static_for<4>([&](auto k) { mma_n128_rs<1, (k + 4) * 1024>(s.O, s.P + 16 + 4 * k, dV + (v_slot(jv) >> 4), 1); });
          wg_commit();
        } else {
          asm volatile("wgmma.fence.sync.aligned;\nwgmma.commit_group.sync.aligned;" ::: "memory");
        }
      };
      auto issue_pv = [&](int jv, int accum, bool upper) { wait_v(jv); issue_pva(jv, accum); issue_pvb(jv, upper); };
      if (w == 1) bar_arrive(1, 256);
#pragma unroll 1
      for (int half = 0; half < 2; half++) {
        const int head = mt + 16 * half;
        redo = 0;
        float inv[2];
        auto ep_prep = [&]() {
          float l0 = s.l[0] + s.l[1], l1 = s.l[2] + s.l[3];
          l0 += __shfl_xor_sync(~0u, l0, 1); l1 += __shfl_xor_sync(~0u, l1, 1);
          l0 += __shfl_xor_sync(~0u, l0, 2); l1 += __shfl_xor_sync(~0u, l1, 2);
          asm("rcp.approx.ftz.f32 %0, %1;" : "=f"(inv[0]) : "f"(l0));
          asm("rcp.approx.ftz.f32 %0, %1;" : "=f"(inv[1]) : "f"(l1));
          return __any_sync(~0u, !(fminf(l0, l1) >= L_MIN && l0 + l1 <= L_MAX));
        };
        auto ep_out = [&](auto i0, auto i1) {
          __nv_bfloat16* dst = g_ctx + (size_t)(ta * 32 + head) * KV_TILE + (wrow + (lane >> 2)) * 32 + ((lane ^ (lane >> 3)) & 3) * 8;
#pragma unroll
          for (int i = i0; i < i1; i++) {
            const float* o = s.O + 16 * (i >> 1) + 2 * (i & 1);
            const float c = inv[i & 1];
            asm volatile("st.global.cs.v4.u32 [%0], {%1,%2,%3,%4};" ::"l"(dst + (i & 1) * 256 + (i >> 1) * 4096), "r"(pack_bf16(o[0] * c, o[1] * c)),
                         "r"(pack_bf16(o[4] * c, o[5] * c)), "r"(pack_bf16(o[8] * c, o[9] * c)), "r"(pack_bf16(o[12] * c, o[13] * c)) : "memory");
          }
        };
        auto ep_rest = [&]() {
          ep_out(IC<EP1>{}, IC<8>{});
          if (!__any_sync(~0u, redo)) publish(2 + 2 * half);
          fence_regs(s.O);
        };
#pragma unroll 1
        for (int kb = 8; kb < 14; kb++) {
          if (kb == 13) {
            if (w) { wg_wait<0>(); release2(B(B_EMPTYQ)); }
            bar_sync(1 + w, 256);
          }
          issue_q(kb, IC<1>{}, kb != 13 || !w);
          TK(66 + half * 24 + kb - 1);
        }
        TL(1, 20 * half + 0, warp == 4);
        mbar_wait_c(B(B_FULLQ + 2), 1);
        wg_fence();
        mma_kc(s.S, IC<q_aw(2)>{}, IC<q_aw(2) + UNIT>{}, 1);
        wg_commit();
        wg_wait<1>();
        TK(66 + half * 24 + 13);
        release2(B(B_EMPTYQ + 1));
        mbar_wait_c(B(B_FULLQ + 3), 1);
        wg_fence();
        mma_kc(s.S, IC<q_aw(3)>{}, IC<q_aw(3) + UNIT>{}, 1);
        wg_commit();
        bar_arrive(2 - w, 256);
        bar_sync(6 + w, 128);
        wg_wait<0>();
        TK(66 + half * 24 + 14);
        fence_regs(s.S);
        static_for<4>([&](auto i) {
          q_store(s.S, IC<2 * i>{}, IC<2 * i + 2>{});
          q_load(IC<2 * i>{}, IC<2 * i + 2>{});
        });
        TL(1, 20 * half + 1, warp == 4);
        TC(w, 17 * half, 0);
        mbar_wait_c(B(B_KF), kph & 1);
        kph ^= 1;
        bar_sync(1 + w, 256);
        TC(w, 17 * half, 2);
        fence_regs(s.O); fence_regs(s.Q);
        wg_fence();
        issue_s(dK, []() {});
        mma_kc(s.O, IC<q_b(2)>{}, IC<q_aw(2) + UNIT>{}, 1);
        mma_kc(s.O, IC<q_b(3)>{}, IC<q_aw(3) + UNIT>{}, 1);
        wg_commit();
        bar_arrive(2 - w, 256);
        wg_wait<1>();
        TC(w, 17 * half, 4);
        fence_regs(s.S);
        e_arrive(B(B_KE));
        s.l[0] = s.l[1] = s.l[2] = s.l[3] = 0.f;
        at_exp<0, 48>(s);
        at_pack<0, 22>(s);
        sched_fence();
        wg_wait<0>();
        fence_regs(s.O); fence_regs(s.Q);
        release2(B(B_EMPTYQ + 2)); release2(B(B_EMPTYQ + 3));
        at_exp<48, 64>(s);
        at_pack<22, 32>(s);
        q_store(s.O, IC<0>{}, IC<8>{});
        TL(1, 20 * half + 2, warp == 4);
        int kr = 1;
        bool kok = false;
        inv[0] = inv[1] = 0.f;
        const int db = gq ? qa : 16;
#pragma unroll 1
        for (int j = 1; j < 17; j++) {
          const bool diag = j == ta || j == db;
          TC(w, j + 17 * half, 0);
          if (!kok) mbar_wait_c(B(B_KF + kr), (kph >> kr) & 1);
          kph ^= 1 << kr;
          if (j == ta + 2) ep_out(IC<0>{}, IC<EP1>{});
          bar_sync(1 + w, 256);
          TC(w, j + 17 * half, 2);
          fence_regs(s.O); fence_regs(s.P); fence_regs(s.Q);
          const uint32_t ke = B(B_KE + kr), dk = dK + (k_slot(j, kr) >> 4);
          if (++kr == 3) kr = 0;
          auto issue_rest = [&](auto trimmed) {
            TC(w, j + 17 * half, 1);
            if (j == ta + 1) {
              if (ep_prep()) redo = 1;
              s.l[0] = s.l[1] = s.l[2] = s.l[3] = 0.f;
            }
            if (!trimmed && j == ta + 2) ep_rest();
            TC(w, j + 17 * half, 3);
            if (trimmed) wait_v(j - 1);
            issue_pva(j - 1, j != 1 && j != ta + 2);
            issue_pvb(j - 1, w == 1 || (j != ta + 1 && j != db + 1));
            bar_arrive(2 - w, 256);
          };
          auto s_done = [&](auto n) {
            wg_wait<2>();
            TC(w, j + 17 * half, 4);
            fence_part<0, n>(s.S); fence_regs(s.Q);
            e_arrive(ke);
            release2(B(B_X + j - 14), j == 14 || j == 15);
          };
          auto pv_half = [&]() { sched_fence(); wg_wait<1>(); fence_regs(s.P); };
          auto pv_done = [&]() {
            sched_fence();
            wg_wait<0>();
            fence_regs(s.O); fence_regs(s.P);
            e_arrive(B(B_VE + ((j - 1) & 1)));
            release2(B(B_X + 2), j == 16);
            kok = mbar_test(B(B_KF + kr), (kph >> kr) & 1);
          };
          if (diag && w == 0) {
            wg_fence();
            static_for<8>([&](auto k) { mma_n64_rs<0, (k >> 1) * 8192 + (k & 1) * 32, k != 0>(s.S, s.Q + 4 * k, dk); });
            wg_commit();
            issue_rest(IC<1>{});
            s_done(IC<32>{});
            at_mask<0>(s, wrow, lane);
            pv_half();
            static_for<8>([&](auto k) {
              at_exp<4 * k, 4 * k + 4>(s);
              q_load_if(k, j == ta, s.S[4 * k]);
            });
            at_pack<0, 16>(s);
            pv_done();
          } else {
            wg_fence();
            issue_s(dk, [&]() { wait_v(j - 1); wg_fence(); });
            issue_rest(IC<0>{});
            if (!diag) {
              s_done(IC<64>{});
              at_exp<0, 24>(s);
              pv_half();
              at_exp<24, 48>(s);
              at_pack<0, 16>(s);
              pv_done();
              at_exp<48, 64>(s);
              at_pack<16, 32>(s);
            } else {
              s_done(IC<64>{});
              at_mask<8>(s, wrow - 64, lane);
              static_for<8>([&](auto k) {
                at_exp<7 * k, 7 * k + 7>(s);
                q_load_if(k, j == ta, s.S[7 * k + 3]);
                if (k == 2) pv_half();
                if (k == 5) { at_pack<0, 16>(s); pv_done(); }
              });
              at_exp<56, 64>(s);
              at_pack<16, 32>(s);
            }
          }
          TL(1, 20 * half + 2 + j, warp == 4);
        }
        TK(84 + half * 24);
        mbar_wait_c(B(half ? B_FULL3 : B_FULLQ), 0);
        if (gq == 0) ep_out(IC<0>{}, IC<EP1>{});
        bar_sync(1 + w, 256);
        fence_regs(s.O); fence_regs(s.P);
        const uint32_t ga = dA - half * w * 256, gb = ga + (half ? 512 : 4), gh = half ? 0x80000020u : 0x40000040u, go = (2 + half) * (SLOT >> 4);
        wg_fence();
        static_for<4>([&](auto k) { mma_n128_ssh<(k & 1) * 32, UNIT + k * 2048, k != 0>(s.S, k < 2 ? ga : gb, gh, dW); });
        mbar_wait_c(B(half ? B_FULL3 + 1 : B_FULLQ + 1), 0);
        wg_fence();
        static_for<4>([&](auto k) { mma_n128_ssh<(k & 1) * 32, UNIT + k * 2048, true>(s.S, (k < 2 ? ga : gb) + go, gh, dW + go); });
        wg_commit();
        TK(85 + half * 24);
        if (gq == 0) ep_rest();
        issue_pv(16, gq != 0, w == 1 || gq != 0);
        if (w == 0 || half == 0) bar_arrive(2 - w, 256);
        TK(86 + half * 24);
        wg_wait<2>();
        release2(B(B_EMPTY3), half); release2(B(B_EMPTY3 + 1), half);
        if (ep_prep()) redo |= 2;
        sched_fence();
        wg_wait<0>();
        TK(87 + half * 24);
        fence_regs(s.S);
        fence_regs(s.O);
        e_arrive(B(B_VE));
        release2(B(B_X + 3));
        fence_regs(s.P);
        {
          const int r = fresh_lane();
          cdst = g_ctx + (size_t)(tb * 32 + head) * KV_TILE + (wrow + (r >> 2)) * 32 + ((r ^ (r >> 3)) & 3) * 8;
        }
#pragma unroll
        for (int i = 0; i < 32; i++) {
          const float* o = s.O + 16 * (i >> 3) + 2 * ((i >> 2) & 1) + 4 * (i & 3);
          s.P[i] = pack_bf16(o[0] * inv[(i >> 2) & 1], o[1] * inv[(i >> 2) & 1]);
        }
        fence_regs(s.P);
        if (__builtin_expect(__any_sync(~0u, redo != 0), 0)) {
#pragma unroll
          for (int i = 0; i < 8; i++) put_ctx(i, true);
#pragma unroll 1
          for (int t = 0; t < 2; t++) {
            if (__any_sync(~0u, (redo >> t) & 1)) slow_rows(wq, head, (t ? tb : ta) * 128 + wrow);
          }
          if (__any_sync(~0u, redo & 1)) publish(2 + 2 * half);
#pragma unroll
          for (int i = 0; i < 32; i++) s.P[i] = 0;
          redo = 2;
        }
        TL(1, 20 * half + 19, warp == 4);
        TK(88 + half * 24);
        if (half) break;
        mbar_wait_c(B(B_FULLB), 0);
        TK(89);
        wg_fence();
        mma_n128_ss0<1, q_b(0), UNIT>(s.O, dA, dW);
        static_for<3>([&](auto k) { mma_n128_ss<1, q_b(0) + k * 32 + 32, UNIT + k * 2048 + 2048>(s.O, dA, dW, 1); });
        wg_commit();
        mma_kc(s.O, IC<q_b(1)>{}, IC<q_aw(1) + UNIT>{}, 1);
        wg_commit();
        wg_wait<1>();
        release2(B(B_EMPTYQ));
        put_ctx(0, true);
#pragma unroll 1
        for (int kb = 2; kb < 8; kb++) {
          issue_q(kb, IC<1>{});
          TK(90 + kb - 1);
#pragma unroll
          for (int i = 1; i < 8; i++) put_ctx(i, kb == (i < 7 ? i + 1 : 7));
        }
        publish(3);
      }
    }
    const int rid_ = rid + zero, cw_ = cw + zero;
    {
    const int lane = fresh_lane(), rid = rid_, mt = rid >> 3, gq = rid & 7, cw = cw_, w = cw >> 2, ct = cw * 32 + lane;
    const int fid = mt * 7 + gq;
    const bool ffn = gq < 7;
    const uint32_t stg = sb + OFF_STG + w * 16384 + (cw & 3) * 2048;
    const int wr_ = w * 64 + (lane & 7) + (lane >> 4) * 8;
    const uint32_t wl = sb + ((lane >> 3) & 1) * 8192 + wr_ * 64 + (((cw ^ (wr_ >> 1)) & 3) << 4);
    __syncwarp();
    float (&acc)[64] = s.S;
    uint32_t wf[128];
    auto grab = [&](auto c, uint32_t off) {
#pragma unroll
      for (int m = 0; m < 4; m++)
        asm volatile("ldmatrix.sync.aligned.m8n8.x4.trans.shared.b16 {%0,%1,%2,%3}, [%4];"
                     : "=r"(wf[16 * c + 4 * m]), "=r"(wf[16 * c + 4 * m + 1]), "=r"(wf[16 * c + 4 * m + 2]), "=r"(wf[16 * c + 4 * m + 3])
                     : "r"(wl + off + m * 1024) : "memory");
    };
    const int r0 = lane >> 2;
    uint32_t hp[32], rt[16];
    {
      const uint32_t dC = mk_desc(sb + w * 4096, 16);
      uint32_t dep = 0;
      auto hand = [&](uint32_t b, int n) {
        asm volatile("{\n.reg .pred p;\n.reg .b32 t;\nsetp.lt.u32 p, %1, %4;\nmad.lo.u32 t, %2, %3, %0;\n@p mbarrier.arrive.shared::cta.b64 _, [t];\n}"
                     ::"r"(b + 8 * lane), "r"(lane), "r"(dep), "r"(zero), "r"(n) : "memory");
      };
      auto kblock = [&](auto st, uint32_t ph, bool rel) {
        mbar_wait_c(B(B_FULL3 + st), ph);
        wg_fence();
        static_for<4>([&](auto k) { mma_n128_ssh<r3(decltype(st)::value) + (k >> 1) * 8192 + (k & 1) * 32, r3(decltype(st)::value) + UNIT + k * 2048, true>(acc, dC, 0x80000020u, dW); });
        wg_commit();
        wg_wait<1>();
        release2(B(B_EMPTY3 + (st + 5) % 6), rel);
      };
      auto ldsm_if = [&](uint32_t* r, uint32_t a, bool c, auto trans) {
        if (trans) asm volatile("{\n.reg .pred p;\nsetp.ne.u32 p, %5, 0;\n@p ldmatrix.sync.aligned.m8n8.x4.trans.shared.b16 {%0,%1,%2,%3}, [%4];\n}"
                                : "+r"(r[0]), "+r"(r[1]), "+r"(r[2]), "+r"(r[3]) : "r"(a), "r"((uint32_t)c) : "memory");
        else asm volatile("{\n.reg .pred p;\nsetp.ne.u32 p, %5, 0;\n@p ldmatrix.sync.aligned.m8n8.x4.shared.b16 {%0,%1,%2,%3}, [%4];\n}"
                          : "+r"(r[0]), "+r"(r[1]), "+r"(r[2]), "+r"(r[3]) : "r"(a), "r"((uint32_t)c) : "memory");
      };
#pragma unroll
      for (int i = 0; i < 48; i++) asm volatile("" : "=r"(wf[i]));
#pragma unroll 1
      for (int lap = 0; lap < 3; lap++) {
        kblock(IC<2>{}, lap & 1, lap > 0);
#pragma unroll
        for (int i = 0; i < 3; i++) put_ctx(3 * i, lap == i);
        kblock(IC<3>{}, lap & 1, true);
        mbar_wait_c(B(B_WF + (lap & 1)), lap >> 1);
#pragma unroll
        for (int i = 0; i < 12; i++) ldsm_if(wf + 4 * i, wl + OFF_SIDE + ((i >> 2) & 1) * UNIT + (i & 3) * 1024, lap == (i >> 2), IC<1>{});
        kblock(IC<4>{}, lap & 1, true);
        sched_fence();
        dep = 0;
#pragma unroll
        for (int i = 0; i < 12; i++) dep ^= wf[4 * i];
        hand(B(B_WE + (lap & 1)), 1);
#pragma unroll
        for (int i = 0; i < 3; i++) put_ctx(3 * i + 1, lap == i);
        kblock(IC<5>{}, lap & 1, true);
        if (lap == 2) publish(5);
        kblock(IC<0>{}, (lap & 1) ^ 1, true);
#pragma unroll
        for (int i = 0; i < 2; i++) put_ctx(3 * i + 2, lap == i);
        kblock(IC<1>{}, (lap & 1) ^ 1, true);
        TL(2, 40 + lap, warp == 4);
      }
#pragma unroll
      for (int i = 48; i < 96; i++) asm volatile("" : "=r"(wf[i]));
#pragma unroll
      for (int i = 0; i < 32; i++) asm volatile("" : "=r"(hp[i]), "=r"(rt[i >> 1]));
      const uint32_t xa = sb + OFF_SIDE + w * UNIT + (cw & 3) * 2048 + (lane & 15) * 128 + (((lane >> 4) ^ (lane & 7)) << 4);
#pragma unroll 1
      for (int lap = 3; lap < 11; lap++) {
        if (lap == 10 && w == 1) bar_sync(5, 256);
        kblock(IC<2>{}, lap & 1, true);
        if (lap == 10 && w == 0) bar_arrive(5, 256);
        kblock(IC<3>{}, lap & 1, true);
        if (lap == 10) break;
        if (lap < WIN) {
          mbar_wait_c(B(B_WF + (lap & 1)), (lap >> 1) & 1);
#pragma unroll
          for (int i = 12; i < 24; i++) ldsm_if(wf + 4 * i, wl + OFF_SIDE + ((i >> 2) & 1) * UNIT + (i & 3) * 1024, lap == (i >> 2), IC<1>{});
        } else if (lap == WIN) {
          mbar_wait_c(B(B_WF), (WIN >> 1) & 1);
          mbar_wait_c(B(B_WF + 1), (WIN >> 1) & 1);
#pragma unroll
          for (int j = 0; j < 8; j++) ldsm_if(hp + 4 * j, (xa ^ ((j & 3) << 5)) + (j >> 2) * 8192, true, IC<0>{});
        } else if (lap == 9) {
          mbar_wait_c(B(B_WR), 0);
          mbar_wait_c(B(B_SET2), 0);
#pragma unroll
          for (int j = 0; j < 4; j++) ldsm_if(rt + 4 * j, sb + OFF_MISC + 512 + (lane & 1) * 256 + (lane >> 3) * 16 + j * 64, true, IC<0>{});
        }
        kblock(IC<4>{}, lap & 1, true);
        sched_fence();
        dep = 0;
#pragma unroll
        for (int i = 0; i < 20; i++) dep ^= i < 12 ? wf[48 + 4 * i] : hp[4 * (i - 12)];
        hand(B(B_WE + (lap < WIN ? lap & 1 : 0)), lap < WIN ? 1 : (lap == WIN ? 2 : 0));
        kblock(IC<5>{}, lap & 1, true);
        kblock(IC<0>{}, (lap & 1) ^ 1, true);
        kblock(IC<1>{}, (lap & 1) ^ 1, true);
        TL(2, 40 + lap, warp == 4);
      }
    }
    uint4* const xr = g_xr + rid * XR_SIZE;
    uint4* const psd = xr + XR_PS + cw * 16 + r0;
    settle(psd, zero);
    sched_fence();
    wg_wait<0>();
    fence_regs(acc);
    TL(2, 10, warp == 4);
    {
      float d[4] = {0.f, 0.f, 0.f, 0.f}, qa[4] = {0.f, 0.f, 0.f, 0.f}, qb[4] = {0.f, 0.f, 0.f, 0.f};
#pragma unroll
      for (int j = 0; j < 16; j++) {
        hp[2 * j] = hadd2_bf(hp[2 * j], pack_bf16(acc[4 * j], acc[4 * j + 1]));
        hp[2 * j + 1] = hadd2_bf(hp[2 * j + 1], pack_bf16(acc[4 * j + 2], acc[4 * j + 3]));
        if (j & 1) {
          mma16816(d, hp[2 * j - 2], hp[2 * j - 1], hp[2 * j], hp[2 * j + 1], rt[j - 1], rt[j]);
          mma16816(qa, hp[2 * j - 2], hp[2 * j - 1], hp[2 * j], hp[2 * j + 1], hp[2 * j - 2], hp[2 * j]);
          mma16816(qb, hp[2 * j - 2], hp[2 * j - 1], hp[2 * j], hp[2 * j + 1], hp[2 * j - 1], hp[2 * j + 1]);
        }
      }
      asm volatile("{\n.reg .pred p;\nsetp.eq.u32 p, %7, %8;\n@p st.global.cg.v4.f32 [%0], {%1,%2,%3,%3};\n@p st.global.cg.v4.f32 [%0 + 128], {%4,%5,%6,%6};\n}"
                   ::"l"(psd), "f"(d[0]), "f"(d[1]), "f"((r0 & 1) ? qa[1] : qa[0]), "f"(d[2]), "f"(d[3]), "f"((r0 & 1) ? qb[3] : qb[2]),
                   "r"(lane & 3), "r"(r0 >> 1) : "memory");
      sched_fence();
    }
    mbar_wait_c(B(B_EMPTY3), 0);
    __syncwarp();
    stage_store_128(stg, lane, hp);
    TL(2, 11, warp == 4);
    __syncwarp();
    uint4 cout;
    uint32_t ckey;
    {
      const float wsum = *reinterpret_cast<const float*>(sp + OFF_MISC + 1024);
      const uint4* pp = g_xr + (mt * 8 + (ct & 1) * 4) * XR_SIZE + XR_PS + (ct >> 1);
      uint2* kd = reinterpret_cast<uint2*>(xr + XR_KEY) + cw;
      const uint32_t tok = 0x7FFFu - (mt * 128 + (ct >> 1));
      settle(pp, zero); settle(kd, zero); settle(tok, zero);
      spin_clk(PS_DLY);
      float s1, s2, s3;
#pragma unroll 1
      for (int n = 0; n < 0x400000; n++) {
        float4 z[4];
#pragma unroll
        for (int i = 0; i < 4; i++)
          asm volatile("ld.relaxed.gpu.global.v4.f32 {%0,%1,%2,%3}, [%4];" : "=f"(z[i].x), "=f"(z[i].y), "=f"(z[i].z), "=f"(z[i].w) : "l"(pp + i * XR_SIZE) : "memory");
        s1 = (z[0].x + z[1].x) + (z[2].x + z[3].x); s3 = (z[0].y + z[1].y) + (z[2].y + z[3].y); s2 = (z[0].z + z[1].z) + (z[2].z + z[3].z);
        const float t = s1 + s2 + s3;
        s1 += __shfl_xor_sync(~0u, s1, 1); s2 += __shfl_xor_sync(~0u, s2, 1); s3 += __shfl_xor_sync(~0u, s3, 1);
        if (__all_sync(~0u, t == t)) break;
        uint32_t m = 0;
#pragma unroll
        for (int i = 0; i < 4; i++) m = max(max(m, __float_as_uint(z[i].x)), max(__float_as_uint(z[i].y), __float_as_uint(z[i].z)));
        if (__all_sync(~0u, m != 0xFFFFFFFFu)) break;
      }
      TL(2, 12, warp == 4);
      const float mean = s1 * (1.f / DM);
      float mb, inv;
      ln_round(mean, fmaxf(fmaf(s2, 1.f / DM, -mean * mean), 0.f), mb, inv);
      const uint32_t u = pack_bf16(0.f, fmaf(s3 - mb * wsum, inv, 0.f));
      const uint32_t key = ((u ^ (((int)u >> 31) | 0x80000000u)) & 0xFFFF0000u) | tok;
      const uint32_t c1 = __reduce_max_sync(~0u, key);
      const uint32_t c2 = __reduce_max_sync(~0u, key == c1 ? 0u : key);
      asm volatile(ELECT "st.global.cg.v2.u32 [%0], {%1,%2};\n}" ::"l"(kd), "r"(c1), "r"(c2) : "memory");
      sched_fence();
      const uint32_t nm2 = pack_bf16(-mb, -mb);
      if (!(ct & 1)) *reinterpret_cast<uint2*>(sp + OFF_RSTAT + (ct >> 1) * 8) = make_uint2(nm2, __float_as_uint(inv) | (key >= c2 ? 0x80000000u : 0u));
      ckey = (lane >> 4) ? c2 : c1;
      const int row = (0x7FFF - (ckey & 0x7FFF)) & 15;
      const uint32_t rn = __shfl_sync(~0u, nm2, row * 2);
      const float ri = __shfl_sync(~0u, inv, row * 2);
      const uint4 v = lds128(stg + ((lane & 15) >> 3) * 8192 + row * 128 + (((lane & 7) ^ (row & 7)) << 4));
      const uint4 n = make_uint4(ln_apply(v.x, rn, ri), ln_apply(v.y, rn, ri), ln_apply(v.z, rn, ri), ln_apply(v.w, rn, ri));
      __stcg(xr + XR_CAND + cw * 64 + 32 + lane, n);
      __stcg(xr + XR_CAND + cw * 64 + lane, v);
      cdst = out + (size_t)(0x7FFF - (ckey & 0x7FFF)) * DM + gq * 128 + (lane & 15) * 8;
      cout = make_uint4(hadd2_bf(v.x, n.x), hadd2_bf(v.y, n.y), hadd2_bf(v.z, n.z), hadd2_bf(v.w, n.w));
    }
    publish(B_OUT - B_PUB);
    cluster_arrive();
    TL(2, 13, warp == 4);
    uint32_t wd[16][4];
    if (ffn) {
      static_for<2>([&](auto i) {
        mbar_wait_b(B(B_WF + i), ((WIN >> 1) & 1) ^ 1);
        grab(IC<WIN + i>{}, OFF_SIDE + i * UNIT);
      });
      mbar_wait_b(B(B_FULL3 + 4 + w), 0);
#pragma unroll
      for (int i = 0; i < 16; i++) {
        const int k = (i & 1) * 16 + (lane & 7) + (lane >> 4) * 8;
        asm volatile("ldmatrix.sync.aligned.m8n8.x4.trans.shared.b16 {%0,%1,%2,%3}, [%4];"
                     : "=r"(wd[i][0]), "=r"(wd[i][1]), "=r"(wd[i][2]), "=r"(wd[i][3])
                     : "r"(sb + r3(4) + w * SLOT + (2 * (cw & 3) + (i >> 3)) * 4096 + k * 128 + (((2 * ((i >> 1) & 3) + ((lane >> 3) & 1)) ^ (lane & 7)) << 4)) : "memory");
      }
    }
    const int fc = 16 * (rid >> 1) + 4 * (rid & 1) + (lane & 3) + 8 * (lane >> 4), ft = (lane >> 3) & 1;
    const char* pc = reinterpret_cast<const char*>(g_xr + ((ct & 127) >> 4) * XR_SIZE + XR_CAND + 32 + (ct & 15));
    const char* pf = reinterpret_cast<const char*>(g_xr + (fc >> 7) * XR_SIZE + XR_CAND) + (fc & 127) * 2;
    const uint32_t xs = sb + OFF_SCR + w * 2112 + ((ct & 127) >> 2) * 64 + (((ct >> 3) & 3) << 4) + (ct & 3) * 4;
    const uint32_t xb = sb + OFF_SCR + (r0 & 1) * 2112 + w * 128 + (((lane ^ w) & 3) << 4);
    settle(pc, zero); settle(pf, zero); settle(cdst, zero); settle(xs, zero); settle(xb, zero);
    mbar_wait_b(B(B_OUT2), 0);
    const uint4 top = lds128(sb + OFF_MISC + 256);
    TL(2, 14, warp == 4);
    uint32_t fh, fn;
    {
      pc += w ? top.y : top.x;
      pf += ft ? top.y : top.x;
      uint4 v;
#pragma unroll 1
      for (int n = 0; n < 0x400000; n++) {
        asm volatile("ld.relaxed.gpu.global.v4.u32 {%0,%1,%2,%3}, [%4];" : "=r"(v.x), "=r"(v.y), "=r"(v.z), "=r"(v.w) : "l"(pc) : "memory");
        asm volatile("ld.relaxed.gpu.global.u16 %0, [%1];" : "=r"(fh) : "l"(pf) : "memory");
        asm volatile("ld.relaxed.gpu.global.u16 %0, [%1 + 512];" : "=r"(fn) : "l"(pf) : "memory");
        asm volatile("st.shared.u32 [%0], %1;" ::"r"(xs), "r"(v.x) : "memory");
        asm volatile("st.shared.u32 [%0], %1;" ::"r"(xs ^ 16), "r"(v.y) : "memory");
        asm volatile("st.shared.u32 [%0], %1;" ::"r"(xs ^ 32), "r"(v.z) : "memory");
        asm volatile("st.shared.u32 [%0], %1;" ::"r"(xs ^ 48), "r"(v.w) : "memory");
        if (__all_sync(~0u, max(max(v.x, v.y), max(v.z, v.w)) != 0xFFFFFFFFu && max(fh, fn) != 0xFFFFu)) break;
      }
    }
    bar_sync(3, 256);
    asm volatile("{\n.reg .pred p;\nsetp.lt.u32 p, %5, %6;\n@p st.global.v4.u32 [%0], {%1,%2,%3,%4};\n}" ::"l"(cdst), "r"(cout.x), "r"(cout.y), "r"(cout.z),
                 "r"(cout.w), "r"(ckey), "r"(top.w) : "memory");
    if (ffn) {
      TL(2, 15, warp == 4);
      float d[4][4] = {};
      auto xl = [&](int i) { return lds128((xb ^ ((i & 2) << 4)) + (i >> 1) * 256 + (i & 1) * 64); };
      uint4 b0 = xl(0), b1 = xl(1);
#pragma unroll
      for (int i = 0; i < 16; i += 2) {
        const uint4 c0 = b0, c1 = b1;
        if (i < 14) { b0 = xl(i + 2); b1 = xl(i + 3); }
        mma16816(d[0], wf[8 * i], wf[8 * i + 1], wf[8 * i + 2], wf[8 * i + 3], c0.x, c0.y);
        mma16816(d[1], wf[8 * i + 4], wf[8 * i + 5], wf[8 * i + 6], wf[8 * i + 7], c0.z, c0.w);
        mma16816(d[2], wf[8 * i + 8], wf[8 * i + 9], wf[8 * i + 10], wf[8 * i + 11], c1.x, c1.y);
        mma16816(d[3], wf[8 * i + 12], wf[8 * i + 13], wf[8 * i + 14], wf[8 * i + 15], c1.z, c1.w);
      }
      const float e0 = (d[0][0] + d[1][0]) + (d[2][0] + d[3][0]), e1 = (d[0][1] + d[1][1]) + (d[2][1] + d[3][1]);
      const float e2 = (d[0][2] + d[1][2]) + (d[2][2] + d[3][2]), e3 = (d[0][3] + d[1][3]) + (d[2][3] + d[3][3]);
      asm volatile("st.shared.v2.f32 [%0], {%1,%2};" ::"r"(sb + OFF_SCR + 8192 + ((w * 2 + (lane & 1)) * 32 + (cw & 3) * 8 + r0) * 8),
                   "f"((lane & 1) ? e1 : e0), "f"((lane & 1) ? e3 : e2) : "memory");
      bar_sync(3, 256);
      TL(2, 16, warp == 4);
      const uint32_t ra = sb + OFF_SCR + 8192 + (r0 & 1) * 256 + (r0 >> 1) * 64 + (lane & 3) * 16;
      const uint4 p0 = lds128(ra), p1 = lds128(ra + 512);
      auto act = [](uint32_t u0, uint32_t u1, uint32_t g0, uint32_t g1) {
        const uint32_t ug = pack_bf16(__uint_as_float(u0) + __uint_as_float(u1), __uint_as_float(g0) + __uint_as_float(g1));
        const float g = bf_hi(ug);
        float r;
        asm("rcp.approx.ftz.f32 %0, %1;" : "=f"(r) : "f"(1.f + ex2(g * -1.4426950408889634f)));
        return bf_round(g * r) * bf_lo(ug);
      };
      const uint32_t av = pack_bf16(act(p0.x, p1.x, p0.y, p1.y), act(p0.z, p1.z, p0.w, p1.w));
      uint32_t b[4];
#pragma unroll
      for (int i = 0; i < 4; i++) b[i] = __shfl_sync(~0u, av, 8 * i + (lane & 7));
      TL(2, 17, warp == 4);
      float y[2][4] = {{0.f, 0.f, 0.f, 0.f}, {0.f, 0.f, 0.f, 0.f}};
#pragma unroll
      for (int c = 0; c < 4; c++) {
        const bool on = (lane >> 3) == c;
        const uint32_t b0 = on ? b[0] : 0, b1 = on ? b[1] : 0, b2 = on ? b[2] : 0, b3 = on ? b[3] : 0;
#pragma unroll
        for (int a = 0; a < 2; a++) {
          const int i = 8 * a + 2 * c;
          mma16816(y[a], wd[i][0], wd[i][1], wd[i][2], wd[i][3], b0, b1);
          mma16816(y[a], wd[i + 1][0], wd[i + 1][1], wd[i + 1][2], wd[i + 1][3], b2, b3);
        }
      }
      float4* yd = reinterpret_cast<float4*>(g_xr + (cw * 16 + (lane & 3) * 2 + (lane >> 4)) * XR_SIZE + XR_Y + fid * 4 + (r0 & 3));
      __stcg(yd, make_float4(y[0][0], y[0][1], y[0][2], y[0][3]));
      __stcg(yd + 8 * XR_SIZE, make_float4(y[1][0], y[1][1], y[1][2], y[1][3]));
    }
    TL(2, 18, warp == 4);
    if (cw == 0) {
      const uint32_t fk = ft ? top.w : top.z;
      uint32_t u = fk >> 16;
      u = (u & 0x8000u) ? (u & 0x7FFFu) : (~u & 0xFFFFu);
      float rs = bf_round(__fdividef(1.f, 1.f + __expf(-__uint_as_float(u << 16))));
      uint16_t* op = reinterpret_cast<uint16_t*>(out) + (size_t)(~fk & 0x7FFF) * DM + fc;
      settle(op, zero); settle(__float_as_uint(rs), zero);
      spin_clk(ffn ? Y_DLY : Y_DLY + Y_DLY0);
      float v[4];
#pragma unroll 1
      for (int n = 0; n < 0x400000; n++) {
        float4 z[14];
#pragma unroll
        for (int i = 0; i < 14; i++)
          asm volatile("ld.relaxed.gpu.global.v4.f32 {%0,%1,%2,%3}, [%4];" : "=f"(z[i].x), "=f"(z[i].y), "=f"(z[i].z), "=f"(z[i].w) : "l"(xr + XR_Y + lane + 32 * i) : "memory");
        float a[4] = {z[0].x, z[0].y, z[0].z, z[0].w}, b[4] = {z[1].x, z[1].y, z[1].z, z[1].w};
#pragma unroll
        for (int i = 2; i < 14; i += 2) {
          a[0] += z[i].x; a[1] += z[i].y; a[2] += z[i].z; a[3] += z[i].w;
          b[0] += z[i + 1].x; b[1] += z[i + 1].y; b[2] += z[i + 1].z; b[3] += z[i + 1].w;
        }
#pragma unroll
        for (int i = 0; i < 4; i++) v[i] = a[i] + b[i];
        const float t = (v[0] + v[1]) + (v[2] + v[3]);
        if (__all_sync(~0u, t == t)) break;
        uint32_t m = 0;
#pragma unroll
        for (int i = 0; i < 14; i++) m = max(max(m, max(__float_as_uint(z[i].x), __float_as_uint(z[i].y))), max(__float_as_uint(z[i].z), __float_as_uint(z[i].w)));
        if (__all_sync(~0u, m != 0xFFFFFFFFu)) break;
      }
      TL(2, 30, true);
      const bool hi = lane & 16, odd = lane & 8;
      const float a0 = (hi ? v[2] : v[0]) + __shfl_xor_sync(~0u, hi ? v[0] : v[2], 16), a1 = (hi ? v[3] : v[1]) + __shfl_xor_sync(~0u, hi ? v[1] : v[3], 16);
      float yv = (odd ? a1 : a0) + __shfl_xor_sync(~0u, odd ? a0 : a1, 8);
      yv += __shfl_xor_sync(~0u, yv, 4);
      const uint32_t o = hadd2_bf(fh, hadd2_bf(fn, pack_bf16(bf_round(yv) * rs, 0.f)));
      if (!(lane & 4)) *op = (uint16_t)o;
      TL(2, 21, true);
    }
    TL(2, 20, warp == 4);
    }
    __syncwarp();
    cluster_wait();
  }
}

typedef CUresult (*EncodeFn)(CUtensorMap*, CUtensorMapDataType, cuuint32_t, void*, const cuuint64_t*, const cuuint64_t*, const cuuint32_t*,
                             const cuuint32_t*, CUtensorMapInterleave, CUtensorMapSwizzle, CUtensorMapL2promotion, CUtensorMapFloatOOBfill);
EncodeFn g_enc = nullptr;

void map2(CUtensorMap* m, const void* ptr, uint64_t rows, uint64_t cols, uint32_t bc, uint32_t br) {
  const CUtensorMapSwizzle sw = bc == 64 ? CU_TENSOR_MAP_SWIZZLE_128B : CU_TENSOR_MAP_SWIZZLE_64B;
  cuuint64_t gd[2] = {cols, rows}, gs[1] = {cols * 2};
  cuuint32_t bd[2] = {bc, br}, es[2] = {1, 1};
  g_enc(m, CU_TENSOR_MAP_DATA_TYPE_BFLOAT16, 2, (void*)ptr, gd, gs, bd, es, CU_TENSOR_MAP_INTERLEAVE_NONE, sw,
        CU_TENSOR_MAP_L2_PROMOTION_L2_128B, CU_TENSOR_MAP_FLOAT_OOB_FILL_NONE);
}
void map3(CUtensorMap* m, const void* ptr, uint64_t rows, uint64_t cols, uint32_t br, uint32_t bch) {
  cuuint64_t gd[3] = {64, rows, cols / 64}, gs[2] = {cols * 2, 128};
  cuuint32_t bd[3] = {64, br, bch}, es[3] = {1, 1, 1};
  g_enc(m, CU_TENSOR_MAP_DATA_TYPE_BFLOAT16, 3, (void*)ptr, gd, gs, bd, es, CU_TENSOR_MAP_INTERLEAVE_NONE, CU_TENSOR_MAP_SWIZZLE_128B,
        CU_TENSOR_MAP_L2_PROMOTION_L2_128B, CU_TENSOR_MAP_FLOAT_OOB_FILL_NONE);
}

}

extern "C" void kernel_launch(void* const* d_in, const int* in_sizes, int n_in, void* d_out, int out_size) {
  const __nv_bfloat16* x = (const __nv_bfloat16*)d_in[0];
  const __nv_bfloat16* ckv = (const __nv_bfloat16*)d_in[1];
  const __nv_bfloat16* wq = (const __nv_bfloat16*)d_in[2];
  const __nv_bfloat16* wk = (const __nv_bfloat16*)d_in[3];
  const __nv_bfloat16* wv = (const __nv_bfloat16*)d_in[4];
  const __nv_bfloat16* wo = (const __nv_bfloat16*)d_in[5];
  const __nv_bfloat16* w_r = (const __nv_bfloat16*)d_in[7];
  const __nv_bfloat16* wgate = (const __nv_bfloat16*)d_in[8];
  const __nv_bfloat16* wup = (const __nv_bfloat16*)d_in[9];
  const __nv_bfloat16* wdown = (const __nv_bfloat16*)d_in[10];
  __nv_bfloat16* out = (__nv_bfloat16*)d_out;

  if (!g_enc) {
    void* fn = nullptr;
    cudaDriverEntryPointQueryResult qr;
    cudaGetDriverEntryPoint("cuTensorMapEncodeTiled", &fn, cudaEnableDefault, &qr);
    g_enc = (EncodeFn)fn;
    cudaFuncSetAttribute(fused_kernel, cudaFuncAttributeMaxDynamicSharedMemorySize, SMEM_BYTES);
  }
  void *xn, *kv, *ctx, *xr, *cnt;
  cudaGetSymbolAddress(&xr, g_xr);
  cudaGetSymbolAddress(&cnt, g_cnt);
  cudaGetSymbolAddress(&xn, g_xn);
  cudaGetSymbolAddress(&kv, g_kv);
  cudaGetSymbolAddress(&ctx, g_ctx);

  Params p;
  map2(&p.xn, xn, SEQ, DM, 64, 64);
  map2(&p.ckv, ckv, SEQ, DC, 64, 128);
  map3(&p.wq, wq, DM, NQ, 64, 2);
  map3(&p.wk, wk, DC, NQ, 32, 2);
  map3(&p.wv, wv, DC, NQ, 32, 2);
  map3(&p.wo, wo, NQ, DM, 64, 1);
  map3(&p.x, x, SEQ, DM, 64, 2);
  map3(&p.wd, wdown, FF, DM, 32, 8);
  map2(&p.wg, wgate, DM, FF, 32, 64);
  map2(&p.wu, wup, DM, FF, 32, 64);
  fused_kernel<<<128, 384, SMEM_BYTES, cudaStreamPerThread>>>(0u, x, (__nv_bfloat16*)kv, (__nv_bfloat16*)ctx, (uint4*)xr, out, (__nv_bfloat16*)xn,
                                                               (unsigned*)cnt, w_r, wdown, wq, p);
}
```

```cpp
#include <cuda_runtime.h>
#include <cuda_bf16.h>
#include <cuda.h>
#include <stdint.h>
#include <utility>

#pragma nv_diag_suppress 549
#pragma nv_diag_suppress 177
namespace {

constexpr int SEQ = 2048, DM = 1024, NH = 32, HD = 128, DC = 512, NQ = NH * HD, FF = 3584;

__device__ __align__(1024) __nv_bfloat16 g_xn[SEQ * DM];
constexpr int KV_TILE = 128 * 128;
__device__ __align__(1024) __nv_bfloat16 g_kv[2 * SEQ * NQ];
__device__ __align__(1024) __nv_bfloat16 g_ctx[SEQ * NQ];
constexpr int XR_PS = 0;
constexpr int XR_KEY = 128;
constexpr int XR_CAND = 136;
constexpr int XR_Y = 648;
constexpr int XR_SIZE = 1104;
__device__ __align__(1024) uint4 g_xr[128 * XR_SIZE];
constexpr int C_LN = 0, C_KV = 16, C_CTX = 32, C_NUM = 64;
__device__ unsigned g_cnt[C_NUM];

#define TL(k, i, cond) do {} while (0)
#define TC(w, g, i) do {} while (0)
#define TL_EXTRA 0
#define TK(i) do {} while (0)

__device__ __forceinline__ uint32_t s2u(const void* p) { return (uint32_t)__cvta_generic_to_shared(p); }
__device__ __forceinline__ void mbar_arrive(uint32_t b) { asm volatile("mbarrier.arrive.shared::cta.b64 _, [%0];" ::"r"(b) : "memory"); }
__device__ __forceinline__ void mbar_arrive_both(uint32_t b, uint32_t lane, bool cond) {
  asm volatile("{\n.reg .pred p;\n.reg .b32 r;\nsetp.lt.u32 p, %1, %2;\nmapa.shared::cluster.u32 r, %0, %1;\n@p mbarrier.arrive.shared::cluster.b64 _, [r];\n}"
               ::"r"(b), "r"(lane), "r"(cond ? 2 : 0) : "memory");
}
__device__ __forceinline__ bool mbar_test(uint32_t b, uint32_t ph) {
  uint32_t ok;
  asm volatile("{\n.reg .pred p;\nmbarrier.test_wait.parity.shared::cta.b64 p, [%1], %2;\nselp.u32 %0, 1, 0, p;\n}" : "=r"(ok) : "r"(b), "r"(ph) : "memory");
  return __all_sync(~0u, ok);
}
__device__ __forceinline__ void mbar_wait(uint32_t b, uint32_t ph) {
  asm volatile(
      "{\n.reg .pred p;\n.reg .u32 n;\nmov.u32 n, 0;\n"
      "LW:\nmbarrier.try_wait.parity.shared::cta.b64 p, [%0], %1, 20000;\n@p bra LD;\n"
      "add.u32 n, n, 1;\nsetp.lt.u32 p, n, 0x40000;\n@p bra LW;\ntrap;\nLD:\n}" ::"r"(b), "r"(ph) : "memory");
}
__device__ __forceinline__ void mbar_wait_u(uint32_t b, uint32_t ph) {
  asm volatile(
      "{\n.reg .pred p;\n.reg .u32 n;\nmov.u32 n, 0;\n"
      "LW:\nmbarrier.try_wait.parity.shared::cta.b64 p, [%0], %1, 20000;\n@p bra.uni LD;\n"
      "add.u32 n, n, 1;\nsetp.lt.u32 p, n, 0x40000;\n@p bra.uni LW;\ntrap;\nLD:\n}" ::"r"(b), "r"(ph) : "memory");
}
__device__ __forceinline__ void mbar_wait_c(uint32_t b, uint32_t ph) {
  asm volatile("{\n.reg .pred p;\nLW:\nmbarrier.try_wait.parity.shared::cta.b64 p, [%0], %1;\n@!p bra.uni LW;\n}" ::"r"(b), "r"(ph) : "memory");
}
__device__ __forceinline__ void mbar_wait_b(uint32_t b, uint32_t ph) {
  asm volatile(
      "{\n.reg .pred p;\n.reg .u32 n;\nmov.u32 n, 0;\n"
      "LW:\nmbarrier.try_wait.parity.shared::cta.b64 p, [%0], %1;\n@p bra.uni LD;\n"
      "add.u32 n, n, 1;\nsetp.lt.u32 p, n, 0x1000000;\n@p bra.uni LW;\ntrap;\nLD:\n}" ::"r"(b), "r"(ph) : "memory");
}
template <bool SLEEP = false>
__device__ __forceinline__ void spin_until_ge(const unsigned* p, unsigned target) {
  asm volatile(
      "{\n.reg .pred p, q;\n.reg .u32 n, v;\nmov.u32 n, 0;\nsetp.ne.u32 q, %2, 0;\n"
      "LW:\nld.acquire.gpu.global.u32 v, [%0];\nsetp.ge.u32 p, v, %1;\n@p bra LD;\n@q nanosleep.u32 200;\n"
      "add.u32 n, n, 1;\nsetp.lt.u32 p, n, 0x400000;\n@p bra LW;\ntrap;\nLD:\n}" ::"l"(p), "r"(target), "n"((int)SLEEP) : "memory");
}
__device__ __forceinline__ void spin_clk(uint32_t n) {
  asm volatile("{\n.reg .pred p;\n.reg .u32 a, b;\nmov.u32 a, %%clock;\nLW:\nmov.u32 b, %%clock;\nsub.u32 b, b, a;\nsetp.lt.u32 p, b, %0;\n@p bra.uni LW;\n}" ::"r"(n) : "memory");
}
__device__ __forceinline__ int fresh_lane() {
  int r;
  asm volatile("mov.u32 %0, %%laneid;" : "=r"(r));
  return r;
}
__device__ __forceinline__ void settle(const void* a, uint32_t zero) {
  asm volatile("{\n.reg .pred p;\nsetp.ne.u32 p, %1, 0;\n@p st.global.u32 [%0], %1;\n}" ::"l"(a), "r"(zero) : "memory");
}
__device__ __forceinline__ void settle(uint32_t a, uint32_t zero) {
  asm volatile("{\n.reg .pred p;\nsetp.ne.u32 p, %1, 0;\n@p st.shared.u32 [%0], %1;\n}" ::"r"(a), "r"(zero) : "memory");
}
__device__ __forceinline__ void fence_async_all() { asm volatile("fence.proxy.async;" ::: "memory"); }
__device__ __forceinline__ void bar_sync(int id, int n) { asm volatile("bar.sync %0, %1;" ::"r"(id), "r"(n) : "memory"); }
__device__ __forceinline__ void bar_arrive(int id, int n) { asm volatile("bar.arrive %0, %1;" ::"r"(id), "r"(n) : "memory"); }
__device__ __forceinline__ void cluster_arrive() { asm volatile("barrier.cluster.arrive.relaxed.aligned;" ::: "memory"); }
__device__ __forceinline__ void cluster_wait() { asm volatile("barrier.cluster.wait.acquire.aligned;" ::: "memory"); }
__device__ __forceinline__ void fence_gpu() { asm volatile("fence.acq_rel.gpu;" ::: "memory"); }
__device__ __forceinline__ void red_add(unsigned* p, unsigned v) { asm volatile("red.relaxed.gpu.global.add.u32 [%0], %1;" ::"l"(p), "r"(v) : "memory"); }
#define ELECT "{\n.reg .pred E;\nelect.sync _|E, 0xFFFFFFFF;\n@E "
__device__ __forceinline__ void e_init(uint32_t b, uint32_t c) { asm volatile(ELECT "mbarrier.init.shared::cta.b64 [%0], %1;\n}" ::"r"(b), "r"(c) : "memory"); }
__device__ __forceinline__ void e_expect(uint32_t b, uint32_t bytes) { asm volatile(ELECT "mbarrier.arrive.expect_tx.shared::cta.b64 _, [%0], %1;\n}" ::"r"(b), "r"(bytes) : "memory"); }
__device__ __forceinline__ void e_arrive(uint32_t b) { asm volatile(ELECT "mbarrier.arrive.shared::cta.b64 _, [%0];\n}" ::"r"(b) : "memory"); }
__device__ __forceinline__ void prefetch_tm(const CUtensorMap* m) { asm volatile(ELECT "prefetch.tensormap [%0];\n}" ::"l"(m) : "memory"); }
__device__ __forceinline__ void tma_ld2(uint32_t dst, const CUtensorMap* m, uint32_t bar, int c0, int c1) {
  asm volatile(ELECT "cp.async.bulk.tensor.2d.shared::cta.global.mbarrier::complete_tx::bytes [%0], [%1, {%3,%4}], [%2];\n}" ::"r"(dst), "l"(m), "r"(bar), "r"(c0), "r"(c1) : "memory");
}
__device__ __forceinline__ void tma_ld3(uint32_t dst, const CUtensorMap* m, uint32_t bar, int c0, int c1, int c2) {
  asm volatile(ELECT "cp.async.bulk.tensor.3d.shared::cta.global.mbarrier::complete_tx::bytes [%0], [%1, {%3,%4,%5}], [%2];\n}" ::"r"(dst), "l"(m), "r"(bar), "r"(c0), "r"(c1), "r"(c2) : "memory");
}
__device__ __forceinline__ void tma_ld2_mc(uint32_t dst, const CUtensorMap* m, uint32_t bar, int c0, int c1, uint16_t mask) {
  asm volatile(ELECT "cp.async.bulk.tensor.2d.shared::cluster.global.mbarrier::complete_tx::bytes.multicast::cluster [%0], [%1, {%3,%4}], [%2], %5;\n}" ::"r"(dst), "l"(m), "r"(bar), "r"(c0), "r"(c1), "h"(mask) : "memory");
}
__device__ __forceinline__ void tma_ld3_mc(uint32_t dst, const CUtensorMap* m, uint32_t bar, int c0, int c1, int c2, uint16_t mask) {
  asm volatile(ELECT "cp.async.bulk.tensor.3d.shared::cluster.global.mbarrier::complete_tx::bytes.multicast::cluster [%0], [%1, {%3,%4,%5}], [%2], %6;\n}" ::"r"(dst), "l"(m), "r"(bar), "r"(c0), "r"(c1), "r"(c2), "h"(mask) : "memory");
}
__device__ __forceinline__ uint64_t policy_evict_first() {
  uint64_t p;
  asm("createpolicy.fractional.L2::evict_first.b64 %0, 1.0;" : "=l"(p));
  return p;
}
__device__ __forceinline__ void tma_ld2_ef(uint32_t dst, const CUtensorMap* m, uint32_t bar, int c0, int c1) {
  asm volatile(ELECT "cp.async.bulk.tensor.2d.shared::cta.global.mbarrier::complete_tx::bytes.L2::cache_hint [%0], [%1, {%3,%4}], [%2], %5;\n}" ::"r"(dst), "l"(m), "r"(bar), "r"(c0), "r"(c1), "l"(policy_evict_first()) : "memory");
}
__device__ __forceinline__ void tma_ld3_ef(uint32_t dst, const CUtensorMap* m, uint32_t bar, int c0, int c1, int c2) {
  asm volatile(ELECT "cp.async.bulk.tensor.3d.shared::cta.global.mbarrier::complete_tx::bytes.L2::cache_hint [%0], [%1, {%3,%4,%5}], [%2], %6;\n}" ::"r"(dst), "l"(m), "r"(bar), "r"(c0), "r"(c1), "r"(c2), "l"(policy_evict_first()) : "memory");
}
__device__ __forceinline__ void bulk_ld(uint32_t dst, const void* src, uint32_t bytes, uint32_t bar) {
  asm volatile(ELECT "cp.async.bulk.shared::cta.global.mbarrier::complete_tx::bytes [%0], [%1], %2, [%3];\n}" ::"r"(dst), "l"(src), "r"(bytes), "r"(bar) : "memory");
}
__device__ __forceinline__ void tma_pf2(const CUtensorMap* m, int c0, int c1) { asm volatile(ELECT "cp.async.bulk.prefetch.tensor.2d.L2.global [%0, {%1,%2}];\n}" ::"l"(m), "r"(c0), "r"(c1) : "memory"); }
__device__ __forceinline__ void tma_pf3(const CUtensorMap* m, int c0, int c1, int c2) { asm volatile(ELECT "cp.async.bulk.prefetch.tensor.3d.L2.global [%0, {%1,%2,%3}];\n}" ::"l"(m), "r"(c0), "r"(c1), "r"(c2) : "memory"); }
__device__ __forceinline__ void sched_fence() { asm volatile("pmevent 0;" ::: "memory"); }
__device__ __forceinline__ void l2_prefetch(const void* p, uint32_t bytes) { asm volatile(ELECT "cp.async.bulk.prefetch.L2.global [%0], %1;\n}" ::"l"(p), "r"(bytes) : "memory"); }

__device__ __forceinline__ void wg_fence() { asm volatile("wgmma.fence.sync.aligned;" ::: "memory"); }
__device__ __forceinline__ void wg_commit() { asm volatile("wgmma.commit_group.sync.aligned;" ::: "memory"); }
template <int N> __device__ __forceinline__ void wg_wait() { asm volatile("wgmma.wait_group.sync.aligned %0;" ::"n"(N) : "memory"); }
template <int N> __device__ __forceinline__ void reg_alloc() { asm volatile("setmaxnreg.inc.sync.aligned.u32 %0;" ::"n"(N)); }
template <int N> __device__ __forceinline__ void reg_dealloc() { asm volatile("setmaxnreg.dec.sync.aligned.u32 %0;" ::"n"(N)); }
template <int N> __device__ __forceinline__ void fence_regs(float (&d)[N]) {
#pragma unroll
  for (int i = 0; i < N; i++) asm volatile("" : "+f"(d[i])::"memory");
}
template <int I0, int I1, int N> __device__ __forceinline__ void fence_part(float (&d)[N]) {
#pragma unroll
  for (int i = I0; i < I1; i++) asm volatile("" : "+f"(d[i])::"memory");
}
template <int N> __device__ __forceinline__ void fence_regs(uint32_t (&d)[N]) {
#pragma unroll
  for (int i = 0; i < N; i++) asm volatile("" : "+r"(d[i])::"memory");
}

__device__ __forceinline__ uint32_t mk_desc(uint32_t addr, uint32_t lbo) { return ((addr & 0x3FFFF) >> 4) | ((lbo >> 4) << 16); }

#define R8(b) "+f"(d[b + 0]), "+f"(d[b + 1]), "+f"(d[b + 2]), "+f"(d[b + 3]), "+f"(d[b + 4]), "+f"(d[b + 5]), "+f"(d[b + 6]), "+f"(d[b + 7])
#define REGS64 "%0,%1,%2,%3,%4,%5,%6,%7,%8,%9,%10,%11,%12,%13,%14,%15,%16,%17,%18,%19,%20,%21,%22,%23,%24,%25,%26,%27,%28,%29,%30,%31," \
               "%32,%33,%34,%35,%36,%37,%38,%39,%40,%41,%42,%43,%44,%45,%46,%47,%48,%49,%50,%51,%52,%53,%54,%55,%56,%57,%58,%59,%60,%61,%62,%63"
#define REGS128 REGS64 ",%64,%65,%66,%67,%68,%69,%70,%71,%72,%73,%74,%75,%76,%77,%78,%79,%80,%81,%82,%83,%84,%85,%86,%87,%88,%89,%90,%91,%92,%93,%94,%95," \
               "%96,%97,%98,%99,%100,%101,%102,%103,%104,%105,%106,%107,%108,%109,%110,%111,%112,%113,%114,%115,%116,%117,%118,%119,%120,%121,%122,%123,%124,%125,%126,%127"

#define DESC(d, r, o) "add.u32 t, " r ", " o ";\nmov.b64 " d ", {t, h};\n"
#define MMA_PRE_(acc, hi) "{\n.reg .pred p;\n.reg .b32 t, h;\n.reg .b64 da, db;\nmov.b32 h, " hi ";\nsetp.ne.b32 p, " acc ", 0;\n"
#define MMA_PRE(acc) MMA_PRE_(acc, "0x40000040")
#define MMA_PRE64(acc) MMA_PRE_(acc, "0x80000020")
template <int TB, int OA, int OB>
__device__ __forceinline__ void mma_n256_ss(float (&d)[128], uint32_t a, uint32_t b, int acc) {
  asm volatile(MMA_PRE("%130") DESC("da", "%128", "%132") DESC("db", "%129", "%133")
               "wgmma.mma_async.sync.aligned.m64n256k16.f32.bf16.bf16 {" REGS128 "}, da, db, p, 1, 1, 0, %131;\n}\n"
               : R8(0), R8(8), R8(16), R8(24), R8(32), R8(40), R8(48), R8(56), R8(64), R8(72), R8(80), R8(88), R8(96), R8(104), R8(112), R8(120)
               : "r"(a), "r"(b), "r"(acc), "n"(TB), "n"(OA >> 4), "n"(OB >> 4));
}
template <int TB, int OA, int OB>
__device__ __forceinline__ void mma_n128_ss(float (&d)[64], uint32_t a, uint32_t b, int acc) {
  asm volatile(MMA_PRE("%66") DESC("da", "%64", "%68") DESC("db", "%65", "%69")
               "wgmma.mma_async.sync.aligned.m64n128k16.f32.bf16.bf16 {" REGS64 "}, da, db, p, 1, 1, 0, %67;\n}\n"
               : R8(0), R8(8), R8(16), R8(24), R8(32), R8(40), R8(48), R8(56)
               : "r"(a), "r"(b), "r"(acc), "n"(TB), "n"(OA >> 4), "n"(OB >> 4));
}
template <int TB, int OB>
__device__ __forceinline__ void mma_n128_rs(float (&d)[64], const uint32_t* a, uint32_t b, int acc) {
  asm volatile(MMA_PRE64("%69") DESC("db", "%68", "%71")
               "wgmma.mma_async.sync.aligned.m64n128k16.f32.bf16.bf16 {" REGS64 "}, {%64,%65,%66,%67}, db, p, 1, 1, %70;\n}\n"
               : R8(0), R8(8), R8(16), R8(24), R8(32), R8(40), R8(48), R8(56)
               : "r"(a[0]), "r"(a[1]), "r"(a[2]), "r"(a[3]), "r"(b), "r"(acc), "n"(TB), "n"(OB >> 4));
}
#define W8(b) "=f"(d[b + 0]), "=f"(d[b + 1]), "=f"(d[b + 2]), "=f"(d[b + 3]), "=f"(d[b + 4]), "=f"(d[b + 5]), "=f"(d[b + 6]), "=f"(d[b + 7])
#define MMA_N64 MMA_PRE64("%37") DESC("db", "%36", "%38") \
  "wgmma.mma_async.sync.aligned.m64n64k16.f32.bf16.bf16 {%0,%1,%2,%3,%4,%5,%6,%7,%8,%9,%10,%11,%12,%13,%14,%15,%16,%17,%18,%19,%20,%21," \
  "%22,%23,%24,%25,%26,%27,%28,%29,%30,%31}, {%32,%33,%34,%35}, db, p, 1, 1, 0;\n}\n"
template <int H, int OB, bool ACC>
__device__ __forceinline__ void mma_n64_rs(float (&d)[64], const uint32_t* a, uint32_t b) {
  if (ACC) asm volatile(MMA_N64 : R8(32 * H), R8(32 * H + 8), R8(32 * H + 16), R8(32 * H + 24) : "r"(a[0]), "r"(a[1]), "r"(a[2]), "r"(a[3]), "r"(b), "n"(1), "n"(OB >> 4));
  else asm volatile(MMA_N64 : W8(32 * H), W8(32 * H + 8), W8(32 * H + 16), W8(32 * H + 24) : "r"(a[0]), "r"(a[1]), "r"(a[2]), "r"(a[3]), "r"(b), "n"(0), "n"(OB >> 4));
}
template <int OB>
__device__ __forceinline__ void mma_n128_rs0(float (&d)[64], const uint32_t* a, uint32_t b) {
  asm volatile(MMA_PRE64("%69") DESC("db", "%68", "%70")
               "wgmma.mma_async.sync.aligned.m64n128k16.f32.bf16.bf16 {" REGS64 "}, {%64,%65,%66,%67}, db, p, 1, 1, 0;\n}\n"
               : W8(0), W8(8), W8(16), W8(24), W8(32), W8(40), W8(48), W8(56)
               : "r"(a[0]), "r"(a[1]), "r"(a[2]), "r"(a[3]), "r"(b), "n"(0), "n"(OB >> 4));
}
#define MMA_SSH MMA_PRE("%67") DESC("db", "%65", "%69") "add.u32 t, %64, %68;\nmov.b64 da, {t, %66};\n" \
  "wgmma.mma_async.sync.aligned.m64n128k16.f32.bf16.bf16 {" REGS64 "}, da, db, p, 1, 1, 0, 1;\n}\n"
template <int OA, int OB, bool ACC>
__device__ __forceinline__ void mma_n128_ssh(float (&d)[64], uint32_t a, uint32_t ahi, uint32_t b) {
  if (ACC) asm volatile(MMA_SSH : R8(0), R8(8), R8(16), R8(24), R8(32), R8(40), R8(48), R8(56) : "r"(a), "r"(b), "r"(ahi), "n"(1), "n"(OA >> 4), "n"(OB >> 4));
  else asm volatile(MMA_SSH : W8(0), W8(8), W8(16), W8(24), W8(32), W8(40), W8(48), W8(56) : "r"(a), "r"(b), "r"(ahi), "n"(0), "n"(OA >> 4), "n"(OB >> 4));
}
template <int TB, int OA, int OB>
__device__ __forceinline__ void mma_n128_ss0(float (&d)[64], uint32_t a, uint32_t b) {
  asm volatile(MMA_PRE("%66") DESC("da", "%64", "%68") DESC("db", "%65", "%69")
               "wgmma.mma_async.sync.aligned.m64n128k16.f32.bf16.bf16 {" REGS64 "}, da, db, p, 1, 1, 0, %67;\n}\n"
               : W8(0), W8(8), W8(16), W8(24), W8(32), W8(40), W8(48), W8(56)
               : "r"(a), "r"(b), "n"(0), "n"(TB), "n"(OA >> 4), "n"(OB >> 4));
}
template <int V> struct IC { static constexpr int value = V; __host__ __device__ constexpr operator int() const { return V; } };
template <int N, class F, int... I>
__device__ __forceinline__ void static_for_(F f, std::integer_sequence<int, I...>) { (f(IC<I>{}), ...); }
template <int N, class F>
__device__ __forceinline__ void static_for(F f) { static_for_<N>(f, std::make_integer_sequence<int, N>{}); }
__device__ __forceinline__ uint32_t pack_bf16(float lo, float hi) {
  uint32_t r;
  asm("cvt.rn.bf16x2.f32 %0, %1, %2;" : "=r"(r) : "f"(hi), "f"(lo));
  return r;
}
__device__ __forceinline__ float bf_lo(uint32_t v) { return __uint_as_float(v << 16); }
__device__ __forceinline__ float bf_hi(uint32_t v) { return __uint_as_float(v & 0xFFFF0000u); }
__device__ __forceinline__ float bf_round(float v) { return bf_lo(pack_bf16(v, v)); }
__device__ __forceinline__ void stsm4(uint32_t addr, uint32_t r0, uint32_t r1, uint32_t r2, uint32_t r3) {
  asm volatile("stmatrix.sync.aligned.m8n8.x4.shared.b16 [%0], {%1,%2,%3,%4};" ::"r"(addr), "r"(r0), "r"(r1), "r"(r2), "r"(r3) : "memory");
}
__device__ __forceinline__ uint4 lds128(uint32_t addr) {
  uint4 v;
  asm volatile("ld.shared.v4.u32 {%0,%1,%2,%3}, [%4];" : "=r"(v.x), "=r"(v.y), "=r"(v.z), "=r"(v.w) : "r"(addr));
  return v;
}
__device__ __forceinline__ float ex2(float x) {
  float y;
  asm("ex2.approx.ftz.f32 %0, %1;" : "=f"(y) : "f"(x));
  return y;
}
__device__ __forceinline__ void stage_store_128(uint32_t base, int lane, const uint32_t* pk) {
  const int row = (lane & 7) + ((lane >> 3) & 1) * 8;
  const uint32_t rb = base + row * 128;
  const int hi = lane >> 4;
#pragma unroll
  for (int j = 0; j < 8; j++) {
    const int chunk = 2 * j + hi;
    const uint32_t a = rb + (j >> 2) * 8192 + (((chunk & 7) ^ (lane & 7)) << 4);
    stsm4(a, pk[4 * j + 0], pk[4 * j + 1], pk[4 * j + 2], pk[4 * j + 3]);
  }
}
__device__ __forceinline__ void ln_round(float mean, float var, float& m_bf, float& inv_s) {
  const uint32_t mv = pack_bf16(mean, var);
  m_bf = bf_lo(mv);
  float sq, rc;
  asm("sqrt.approx.ftz.f32 %0, %1;" : "=f"(sq) : "f"(bf_round(bf_hi(mv) + 1e-5f)));
  asm("rcp.approx.ftz.f32 %0, %1;" : "=f"(rc) : "f"(bf_round(sq)));
  inv_s = rc;
}
__device__ __forceinline__ uint32_t hadd2_bf(uint32_t a, uint32_t b) {
  uint32_t r;
  asm("add.rn.bf16x2 %0, %1, %2;" : "=r"(r) : "r"(a), "r"(b));
  return r;
}
__device__ __forceinline__ uint32_t ln_split(float inv_s) {
  const float hi = bf_round(inv_s);
  return pack_bf16(inv_s - hi, hi);
}
__device__ __forceinline__ uint32_t ln_apply(uint32_t h, uint32_t nm2, uint32_t inv2) {
  uint32_t r;
  asm("{\n.reg .b16 l, u;\n.reg .b32 d, t, ll, uu;\nmov.b32 {l, u}, %3;\nmov.b32 ll, {l, l};\nmov.b32 uu, {u, u};\n"
      "add.rn.bf16x2 d, %1, %2;\nmul.rn.bf16x2 t, d, ll;\nfma.rn.bf16x2 %0, d, uu, t;\n}" : "=r"(r) : "r"(h), "r"(nm2), "r"(inv2));
  return r;
}
__device__ __forceinline__ void mma16816(float* d, uint32_t a0, uint32_t a1, uint32_t a2, uint32_t a3, uint32_t b0, uint32_t b1) {
  asm volatile("mma.sync.aligned.m16n8k16.row.col.f32.bf16.bf16.f32 {%0,%1,%2,%3}, {%4,%5,%6,%7}, {%8,%9}, {%0,%1,%2,%3};"
               : "+f"(d[0]), "+f"(d[1]), "+f"(d[2]), "+f"(d[3]) : "r"(a0), "r"(a1), "r"(a2), "r"(a3), "r"(b0), "r"(b1));
}

constexpr float AT_C = 0.08838834764831845f * 1.4426950408889634f;
#define L_MIN 3.5527137e-15f
#define L_MAX 1.8446744e19f
struct AtState {
  float S[64], O[64];
  uint32_t P[32], Q[32];
  float l[4];
};
template <int I0, int I1>
__device__ __forceinline__ void at_exp(AtState& s) {
#pragma unroll
  for (int i = I0; i < I1; i++) asm volatile("ex2.approx.ftz.f32 %0, %0;" : "+f"(s.S[i]));
#pragma unroll
  for (int i = I0; i < I1; i++) asm volatile("add.f32 %0, %0, %1;" : "+f"(s.l[i & 3]) : "f"(s.S[i]));
}
template <int I0, int I1>
__device__ __forceinline__ void at_pack(AtState& s) {
#pragma unroll
  for (int i = I0; i < I1; i++) asm volatile("cvt.rn.bf16x2.f32 %0, %1, %2;" : "=r"(s.P[i]) : "f"(s.S[2 * i + 1]), "f"(s.S[2 * i]));
}
template <int J0>
__device__ __forceinline__ void at_mask(AtState& s, int r, int lane) {
  const int d = r + (lane >> 2) - (lane & 3) * 2;
#pragma unroll
  for (int j = 0; j < 8; j++) {
    float dummy0 = 0.f, dummy1 = 0.f;
    float& lo0 = j < 7 ? s.S[4 * (J0 + (j < 7 ? j + 1 : j)) + 2] : dummy0;
    float& lo1 = j < 7 ? s.S[4 * (J0 + (j < 7 ? j + 1 : j)) + 3] : dummy1;
    asm("{\n.reg .pred p, q;\nsetp.lt.s32 p, %4, %5;\nsetp.le.s32 q, %4, %5;\n"
        "@p add.f32 %0, %0, 0fFF800000;\n@q add.f32 %1, %1, 0fFF800000;\n@p add.f32 %2, %2, 0fFF800000;\n@q add.f32 %3, %3, 0fFF800000;\n}"
        : "+f"(s.S[4 * (J0 + j)]), "+f"(s.S[4 * (J0 + j) + 1]), "+f"(lo0), "+f"(lo1) : "r"(d), "r"(8 * j));
  }
}
template <int D>
__device__ __forceinline__ uint32_t ld_pair(const __nv_bfloat16* p) {
  uint32_t r;
  asm volatile("{\n.reg .b16 a, b;\nld.global.cg.b16 a, [%1];\nld.global.cg.b16 b, [%1 + %2];\nmov.b32 %0, {a, b};\n}" : "=r"(r) : "l"(p), "n"(2 * D) : "memory");
  return r;
}
__device__ __forceinline__ uint32_t ld_word(const uint32_t* p) {
  uint32_t r;
  asm volatile("ld.global.cg.b32 %0, [%1];" : "=r"(r) : "l"(p) : "memory");
  return r;
}
__device__ __noinline__ void slow_rows(const __nv_bfloat16* wq, int head, int row0) {
  const int lane = fresh_lane(), r = lane >> 2, c = lane & 3;
  uint32_t q[32];
  float o[32];
#pragma unroll
  for (int i = 0; i < 32; i++) q[i] = 0;
  const uint32_t* xa = reinterpret_cast<const uint32_t*>(g_xn + (size_t)(row0 + r) * DM) + c;
#pragma unroll 1
  for (int h = 0; h < 2; h++) {
    const __nv_bfloat16* wb = wq + (size_t)2 * c * NQ + head * HD + 64 * h + 8 * (r >> 1) + (r & 1);
#pragma unroll
    for (int i = 0; i < 32; i++) o[i] = 0.f;
#pragma unroll 1
    for (int kk = 0; kk < DM / 16; kk++) {
      const uint32_t a0 = ld_word(xa + 8 * kk), a1 = ld_word(xa + 8 * kk + 4 * DM), a2 = ld_word(xa + 8 * kk + 4), a3 = ld_word(xa + 8 * kk + 4 * DM + 4);
#pragma unroll
      for (int n = 0; n < 8; n++) {
        const __nv_bfloat16* b = wb + (size_t)16 * kk * NQ + 32 * (n >> 2) + 2 * (n & 3);
        mma16816(o + 4 * n, a0, a1, a2, a3, ld_pair<NQ>(b), ld_pair<NQ>(b + 8 * NQ));
        if (n & 1) sched_fence();
      }
    }
#pragma unroll
    for (int i = 0; i < 16; i++) { q[i] = q[16 + i]; q[16 + i] = pack_bf16(o[2 * i] * AT_C, o[2 * i + 1] * AT_C); }
  }
#pragma unroll 1
  for (int h = 0; h < 2; h++) {
    float m0 = -INFINITY, m1 = -INFINITY, l0 = 0.f, l1 = 0.f;
#pragma unroll
    for (int i = 0; i < 32; i++) o[i] = 0.f;
#pragma unroll 1
    for (int k0 = 0; k0 <= row0; k0 += 16) {
      float e[8] = {0.f, 0.f, 0.f, 0.f, 0.f, 0.f, 0.f, 0.f};
      const __nv_bfloat16* kt = g_kv + (size_t)(head * 16 + (k0 >> 7)) * KV_TILE + (k0 & 127) * 32;
      const uint32_t* kp = reinterpret_cast<const uint32_t*>(kt + r * 32) + c;
#pragma unroll
      for (int kk = 0; kk < 8; kk++) {
        const uint32_t* k0p = kp + (kk >> 1) * 2048 + (((kk & 1) * 2) ^ (r >> 1)) * 4;
        const uint32_t* k1p = kp + (kk >> 1) * 2048 + (((kk & 1) * 2 + 1) ^ (r >> 1)) * 4;
        mma16816(e, q[4 * kk], q[4 * kk + 1], q[4 * kk + 2], q[4 * kk + 3], ld_word(k0p), ld_word(k1p));
        mma16816(e + 4, q[4 * kk], q[4 * kk + 1], q[4 * kk + 2], q[4 * kk + 3], ld_word(k0p + 128), ld_word(k1p + 128));
        if (kk & 1) sched_fence();
      }
      if (k0 == row0) {
#pragma unroll
        for (int i = 0; i < 8; i++) if ((i >> 2) * 8 + 2 * c + (i & 1) > r + (i & 2) * 4) e[i] = -INFINITY;
      }
      float a0 = fmaxf(fmaxf(e[0], e[1]), fmaxf(e[4], e[5])), a1 = fmaxf(fmaxf(e[2], e[3]), fmaxf(e[6], e[7]));
      a0 = fmaxf(a0, __shfl_xor_sync(~0u, a0, 1)); a1 = fmaxf(a1, __shfl_xor_sync(~0u, a1, 1));
      a0 = fmaxf(a0, __shfl_xor_sync(~0u, a0, 2)); a1 = fmaxf(a1, __shfl_xor_sync(~0u, a1, 2));
      a0 = fmaxf(a0, m0); a1 = fmaxf(a1, m1);
      const float sc0 = ex2(m0 - a0), sc1 = ex2(m1 - a1);
      m0 = a0; m1 = a1;
#pragma unroll
      for (int i = 0; i < 8; i++) e[i] = ex2(e[i] - ((i & 2) ? m1 : m0));
      l0 = l0 * sc0 + (e[0] + e[1]) + (e[4] + e[5]);
      l1 = l1 * sc1 + (e[2] + e[3]) + (e[6] + e[7]);
      const uint32_t p0 = pack_bf16(e[0], e[1]), p1 = pack_bf16(e[2], e[3]), p2 = pack_bf16(e[4], e[5]), p3 = pack_bf16(e[6], e[7]);
      const __nv_bfloat16* vp = kt + (size_t)512 * KV_TILE + h * 8192 + 2 * c * 32 + r;
#pragma unroll
      for (int n = 0; n < 8; n++) {
        o[4 * n] *= sc0; o[4 * n + 1] *= sc0; o[4 * n + 2] *= sc1; o[4 * n + 3] *= sc1;
        mma16816(o + 4 * n, p0, p1, p2, p3, ld_pair<32>(vp + (n >> 2) * 4096 + ((n ^ c) & 3) * 8), ld_pair<32>(vp + (n >> 2) * 4096 + ((n ^ c) & 3) * 8 + 256));
        if (n & 1) sched_fence();
      }
    }
    l0 += __shfl_xor_sync(~0u, l0, 1); l1 += __shfl_xor_sync(~0u, l1, 1);
    l0 += __shfl_xor_sync(~0u, l0, 2); l1 += __shfl_xor_sync(~0u, l1, 2);
#pragma unroll
    for (int i = 0; i < 4; i++) {
      const float* v = o + 16 * (i >> 1) + 2 * (i & 1);
      const float f = __fdividef(1.f, (i & 1) ? l1 : l0);
      *reinterpret_cast<uint4*>(g_ctx + (size_t)((row0 >> 7) * 32 + head) * KV_TILE + (2 * h + (i >> 1)) * 4096 + ((row0 & 127) + r + (i & 1) * 8) * 32 + (c ^ (r >> 1)) * 8) =
          make_uint4(pack_bf16(v[0] * f, v[1] * f), pack_bf16(v[4] * f, v[5] * f), pack_bf16(v[8] * f, v[9] * f), pack_bf16(v[12] * f, v[13] * f));
    }
  }
}

constexpr int UNIT = 16384, SLOT = 32768;
constexpr int OFF_SIDE = 2 * SLOT;
__host__ __device__ constexpr int kv_a(int kb) { return (kb < 6 ? kb : 3 * kb - 10) * UNIT; }
__host__ __device__ constexpr int kv_b(int s) { return ((0x76DCA9 >> (4 * s)) & 15) * UNIT; }
__host__ __device__ constexpr int q_aw(int s) { return (3 * s + (s & 1)) * UNIT; }
__host__ __device__ constexpr int q_b(int s) { return (3 * s + 2 - 2 * (s & 1)) * UNIT; }
__host__ __device__ constexpr int k_slot(int j, int r) { return (j < 2 ? 2 * j : (r == 2 ? 0 : 3 + r)) * SLOT; }
__host__ __device__ constexpr int v_slot(int j) { return (6 - (j & 1)) * SLOT; }
__host__ __device__ constexpr int r3(int st) { return ((0x654130 >> (4 * st)) & 7) * SLOT; }
constexpr int OFF_BAR = 229376;
constexpr int OFF_MISC = OFF_BAR + 512;
constexpr int SMEM_BYTES = OFF_MISC + 2080 + TL_EXTRA;
constexpr int OFF_RSTAT = OFF_MISC + 1056;
enum : int {
  B_FULL1 = 0, B_FULLQ = 6, B_FULLB = 10, B_KF = 11, B_VF = 14, B_FULL3 = 16, B_WF = 22, B_DEP = 24, B_OUT2 = 29, B_PF = 30, B_SET = 31,
  B_SET2 = 32, B_LNGO = 33, B_WR = 34,
  B_KE = 35, B_VE = 38, B_WE = 40, B_PUB = 42, B_OUT = 48,
  B_EMPTY1 = 49, B_EMPTYQ = 55, B_X = 59, B_EMPTY3 = 63,
  B_NUM = 69
};
#define TUNABLE(name, v) constexpr int name = v
TUNABLE(LN_GO, 3);
TUNABLE(EP1, 2);
TUNABLE(SIDE_NS, 400);
TUNABLE(SET_KB, 44); TUNABLE(SET_NS, 40);
TUNABLE(PF_KB, 54); TUNABLE(PF_N, 7); TUNABLE(PF_NS, 300);
TUNABLE(PS_DLY, 120); TUNABLE(Y_DLY, 700); TUNABLE(Y_DLY0, 1500);
constexpr int PRE = 6;
constexpr int WIN = 6;
constexpr int OFF_STG = r3(0), OFF_SCR = r3(1);
struct Params {
  CUtensorMap xn, ckv, wq, wk, wv, wo, x, wd, wg, wu;
};

__global__ void __cluster_dims__(2, 1, 1) __launch_bounds__(384, 1)
fused_kernel(uint32_t zero, const __nv_bfloat16* __restrict__ x, __nv_bfloat16* g_kv, __nv_bfloat16* g_ctx, uint4* g_xr,
             __nv_bfloat16* __restrict__ out, __nv_bfloat16* g_xn, unsigned* g_cnt, const __nv_bfloat16* __restrict__ w_r,
             const __nv_bfloat16* __restrict__ wdown, const __nv_bfloat16* __restrict__ wq, const __grid_constant__ Params p) {
  extern __shared__ __align__(1024) uint8_t sp[];
  const uint32_t sb = s2u(sp);
  const uint32_t bar = sb + OFF_BAR;
  auto B = [&](int i) { return bar + 8 * i; };
  const int tid = threadIdx.x, warp = __shfl_sync(~0u, tid >> 5, 0), wg = warp >> 2, lane = tid & 31;
  const int cta = blockIdx.x, rank = cta & 1, cl = cta >> 1;
  const int mp = cl < 4 ? 1 : (cl < 36 ? (cl & 7) : (0x3207654 >> (4 * ((cl - 36) % 7))) & 7);
  const int gq = cl < 4 ? 4 + cl : (cl < 36 ? (cl - 4) >> 3 : 4 + (cl - 36) / 7);
  const int mt = 2 * mp + rank;
  const int qa = 15 - gq;
  const int ta = gq ? gq : 15, tb = 15 - ta;
  const int rid = mt * 8 + gq;
  const int fid = mt * 7 + gq;
  const bool ffn = gq < 7;
  TL(0, 0, warp == 4);
  auto load_pre = [&](int i) {
    e_expect(B(B_FULL1 + i), (i & 1) ? UNIT : 2 * UNIT);
    if (!(i & 1)) tma_ld2(sb + kv_a(i >> 1), &p.ckv, B(B_FULL1 + i), i * 32, mt * 128);
    tma_ld3(sb + kv_b(i) + rank * 8192, &p.wk, B(B_FULL1 + i), 0, i * 32, (gq + 8) * 4 + rank * 2);
    tma_ld3(sb + kv_b(i) + 8192 - rank * 8192, &p.wk, B(B_FULL1 + i), 0, i * 32, (gq + 8) * 4 + 2 - rank * 2);
  };
  if (warp == 0) {
    e_init(B(B_FULL1), 1);
    asm volatile("fence.mbarrier_init.release.cluster;" ::: "memory");
    TL(0, 16, true);
    load_pre(0);
    TL(0, 17, true);
#pragma unroll
    for (int kb = 1; kb < PRE; kb++) e_init(B(B_FULL1 + kb), 1);
  } else {
#pragma unroll 1
    for (int i = PRE - 1 + warp; i < B_NUM; i += 11) e_init(B(i), i >= B_EMPTY1 ? 16 : (i >= B_KE ? 8 : (i == B_WR ? 2 : 1)));
  }
  asm volatile("fence.mbarrier_init.release.cluster;" ::: "memory");
  cluster_arrive();
  const int rid0 = rid, warp0 = warp;
  if (wg == 0) {
    reg_dealloc<40>();
    if (warp == 0) {
      TL(0, 12, true);
#pragma unroll 1
      for (int kb = 1; kb < PRE; kb++) load_pre(kb);
      if (mt >= PRE) { tma_pf3(&p.wk, 0, mt * 32, (gq + 8) * 4); tma_pf3(&p.wk, 0, mt * 32, (gq + 8) * 4 + 2); }
      if (gq >= PRE / 2) tma_pf2(&p.ckv, gq * 64, mt * 128);
      TL(0, 15, true);
    }
    TL(0, 18, warp == 0);
    __syncwarp();
    cluster_wait();
    uint4* const xr = g_xr + rid * XR_SIZE;
    auto side_piece = [&](int c, int piece) {
      const uint32_t fb = B(B_WF + (c & 1));
      if (piece == 0) e_expect(fb, ffn ? UNIT : 0);
      if (ffn) tma_ld2_ef(sb + OFF_SIDE + (c & 1) * UNIT + piece * 4096, (piece & 2) ? &p.wg : &p.wu, fb, fid * 32, c * 128 + (piece & 1) * 64);
    };
    if (warp == 0) {
      {
        int st = 0; uint32_t ph = 0;
#pragma unroll 1
        for (int i = PRE; i < 64; i++) {
          const int t = i >> 4, h = i & 15;
          const uint32_t fb = B(B_FULL1 + st);
          const bool with_a = (i & 0x31) == 0;
          mbar_wait_c(B(B_EMPTY1 + st), ph);
          e_expect(fb, with_a ? 2 * UNIT : UNIT);
          if (with_a) tma_ld2(sb + kv_a(h >> 1), &p.ckv, fb, h * 32, mt * 128);
          tma_ld3_mc(sb + kv_b(st) + rank * 8192, (t & 1) ? &p.wv : &p.wk, fb, 0, h * 32, (gq + ((t >> 1) ^ 1) * 8) * 4 + rank * 2, 3);
          if (i == 2 * LN_GO) e_arrive(B(B_LNGO));
          if (i == 24) { prefetch_tm(&p.wq); prefetch_tm(&p.xn); }
          if ((h >> 1) == (t ? 0 : 4) && t < 3) tma_pf3((t & 1) ? &p.wk : &p.wv, 0, mt * 32, (gq + (((t + 1) >> 1) ^ 1) * 8) * 4 + (h & 1) * 2);
          if ((i | 2) == 50) tma_pf3(&p.wq, 0, (gq + 4 * h) * 64, mt * 2);
          if (++st == 6) { st = 0; ph ^= 1; }
        }
        prefetch_tm(&p.wo); prefetch_tm(&p.wd); prefetch_tm(&p.x); prefetch_tm(&p.wg); prefetch_tm(&p.wu);
        mbar_wait_c(B(B_DEP + 0), 0);
        uint32_t kpar = 7, vpar = 3;
        auto load_aw = [&](int kb, int head) {
          const uint32_t d = sb + q_aw(kb & 3), fb = B(B_FULLQ + (kb & 3));
          tma_ld2_mc(d + rank * 8192, &p.xn, fb, kb * 64, ta * 128 + rank * 64, 3);
          tma_ld3(d + UNIT, &p.wq, fb, 0, kb * 64, head * 2);
        };
        auto load_b = [&](int kb, uint32_t fb) { tma_ld2_mc(sb + q_b(kb & 3) + rank * 8192, &p.xn, fb, kb * 64, tb * 128 + rank * 64, 3); };
        auto load3 = [&](int kb, int s) {
          const uint32_t d = sb + r3(s), fb = B(B_FULL3 + s);
          e_expect(fb, SLOT);
          bulk_ld(d, g_ctx + (size_t)(mt * 64 + kb) * 8192, UNIT, fb);
          tma_ld3_mc(d + UNIT + rank * 8192, &p.wo, fb, 0, kb * 64, gq * 2 + rank, 3);
        };
#pragma unroll 1
        for (int half = 0; half < 2; half++) {
          const int head = mt + 16 * half;
#pragma unroll 1
          for (int kb = 2 * half; kb < 16; kb++) {
            if (kb >= 4) mbar_wait_c(B(B_EMPTYQ + (kb & 3)), ((kb >> 2) & 1) ^ 1);
            else if (half) mbar_wait_c(B(B_X + 2), 0);
            else if (kb > 0) mbar_wait_c(B(B_EMPTY1 + (2 * kb + 3) % 6), kb == 1);
            e_expect(B(B_FULLQ + (kb & 3)), 3 * UNIT);
            load_aw(kb, head);
            load_b(kb, B(B_FULLQ + (kb & 3)));
          }
          mbar_wait_c(B(B_DEP + 1 + half), 0);
          const __nv_bfloat16* kt = g_kv + (size_t)head * 16 * KV_TILE;
          l2_prefetch(kt, SLOT);
          auto load_v = [&](int j) {
            const int r = j & 1;
            mbar_wait_c(B(B_VE + r), (vpar >> r) & 1);
            vpar ^= 1 << r;
            e_expect(B(B_VF + r), SLOT);
            bulk_ld(sb + v_slot(j), kt + (size_t)(512 + (j > qa ? 16 - j : j)) * KV_TILE, SLOT, B(B_VF + r));
          };
          int r = 0;
#pragma unroll 1
          for (int j = 0; j < 17; j++) {
            if (j < 2) mbar_wait_c(B(B_EMPTYQ + j), 1);
            if (j == 2) mbar_wait_c(B(B_KE), kpar & 1);
            mbar_wait_c(B(B_KE + r), (kpar >> r) & 1);
            kpar ^= 1 << r;
            e_expect(B(B_KF + r), SLOT);
            bulk_ld(sb + k_slot(j, r), kt + (j > qa ? 16 - j : j) * KV_TILE, SLOT, B(B_KF + r));
            if (++r == 3) r = 0;
            if (j == 2) mbar_wait_c(B(B_EMPTYQ + 3), 1);
            if (j != 1) load_v(j ? j - 1 : 0);
            if (half && j < 16) l2_prefetch(kt + (size_t)(512 + j) * KV_TILE + gq * 2048, 4096);
            if (half == 0) {
              if (j == 16) {
                tma_pf3(&p.wq, 0, (4 + gq) * 64, (mt + 16) * 2);
                tma_pf2(&p.xn, (4 + (mp & 3)) * 64, ((mp & 4) ? qa : gq) * 128 + rank * 64);
              }
            } else if (j >= 14) {
              tma_pf3(&p.wo, 0, (5 + mp + 8 * (16 - j)) * 64, gq * 2 + rank);
            } else if (j >= 5 && j < 13) {
              side_piece((j - 5) >> 2, (j - 5) & 3);
            }
          }
          mbar_wait_c(B(B_X + 0), half);
          if (half == 0) {
            for (int kb = 0; kb < 2; kb++) { e_expect(B(B_FULLQ + kb), 2 * UNIT); load_aw(kb, mt + 16); }
          } else {
            mbar_wait_c(B(B_DEP + 3), 0);
            load3(0, 0);
          }
          mbar_wait_c(B(B_X + 1), half);
          if (half) load3(1, 1);
          load_v(16);
          if (gq == 0) mbar_wait_c(B(B_X + 2), half);
          if (half == 0) { e_expect(B(B_FULLB), 2 * UNIT); load_b(0, B(B_FULLB)); load_b(1, B(B_FULLB)); }
        }
        st = 2; ph = 1;
#pragma unroll 1
        for (int kb = 2; kb < 64; kb++) {
          if (kb == 32) mbar_wait_c(B(B_DEP + 4), 0);
          if (kb >= 6) mbar_wait_c(B(B_EMPTY3 + st), ph);
          else if (kb == 3 || kb == 5) mbar_wait_c(B(B_X + (kb + 1) / 2), 1);
          load3(kb, st);
          if (++st == 6) { st = 0; ph ^= 1; }
          if (kb == PF_KB) e_arrive(B(B_PF));
          if (kb == SET_KB) e_arrive(B(B_SET));
          if (kb == 58) l2_prefetch(xr, XR_CAND * 16);
        }
        if (ffn) {
#pragma unroll 1
          for (int j = 0; j < 2; j++) {
            mbar_wait_c(B(B_EMPTY3 + 4 + j), 1);
            e_expect(B(B_FULL3 + 4 + j), SLOT);
            tma_ld3(sb + r3(4 + j), &p.wd, B(B_FULL3 + 4 + j), 0, fid * 32, 8 * j);
          }
        }
        const uint4* kp = g_xr + ((lane >> 1) * 8 + gq) * XR_SIZE + XR_KEY + (lane & 1) * 2;
        mbar_wait_c(B(B_OUT), 0);
        uint32_t k1, k2, m1;
#pragma unroll 1
        for (int n = 0; n < 0x400000; n++) {
          uint4 a, b;
          asm volatile("ld.relaxed.gpu.global.v4.u32 {%0,%1,%2,%3}, [%4];" : "=r"(a.x), "=r"(a.y), "=r"(a.z), "=r"(a.w) : "l"(kp) : "memory");
          asm volatile("ld.relaxed.gpu.global.v4.u32 {%0,%1,%2,%3}, [%4 + 16];" : "=r"(b.x), "=r"(b.y), "=r"(b.z), "=r"(b.w) : "l"(kp) : "memory");
          const uint32_t a1 = max(a.x, a.z), a2 = max(min(a.x, a.z), max(a.y, a.w));
          const uint32_t b1 = max(b.x, b.z), b2 = max(min(b.x, b.z), max(b.y, b.w));
          k1 = max(a1, b1); k2 = max(min(a1, b1), max(a2, b2));
          m1 = __reduce_max_sync(~0u, max(k1, k2));
          if (m1 != 0xFFFFFFFFu) break;
        }
        const uint32_t m2 = __reduce_max_sync(~0u, k1 == m1 ? k2 : k1);
        const uint32_t t0 = ~m1 & 0x7FFF, t1 = ~m2 & 0x7FFF;
        const uint32_t o0 = (t0 >> 7) * (8 * XR_SIZE * 16) + (t0 & 0x70) * 64, o1 = (t1 >> 7) * (8 * XR_SIZE * 16) + (t1 & 0x70) * 64 + ((t0 ^ t1) < 16 ? 256 : 0);
        asm volatile(ELECT "st.shared.v4.u32 [%0], {%1,%2,%3,%4};\n}" ::"r"(sb + OFF_MISC + 256), "r"(o0), "r"(o1), "r"(m1), "r"(m2) : "memory");
        e_arrive(B(B_OUT2));
        if (rid == 127) { g_cnt[lane] = 0; g_cnt[32 + lane] = 0; }
      }
    } else {
      if (warp >= 2) {
#pragma unroll 1
        for (int i = tid - 64; i < XR_CAND; i += 64) xr[i] = make_uint4(~0u, ~0u, ~0u, ~0u);
        if (warp == 2) { __syncwarp(); if (lane == 0) mbar_arrive(B(B_WR)); }
      }
      if (warp == 3) {
        float ws = 0.f;
#pragma unroll 1
        for (int j = 0; j < 4; j++) {
          const uint4 q = __ldg(reinterpret_cast<const uint4*>(w_r) + j * 32 + lane);
          ws += bf_lo(q.x) + bf_hi(q.x) + bf_lo(q.y) + bf_hi(q.y) + bf_lo(q.z) + bf_hi(q.z) + bf_lo(q.w) + bf_hi(q.w);
        }
#pragma unroll
        for (int o = 16; o; o >>= 1) ws += __shfl_xor_sync(~0u, ws, o);
        uint2* tab = reinterpret_cast<uint2*>(sp + OFF_MISC + 512);
        tab[lane] = make_uint2(0x3F803F80u, 0x3F803F80u);
        tab[32 + lane] = __ldg(reinterpret_cast<const uint2*>(w_r + gq * 128) + lane);
        if (lane == 0) *reinterpret_cast<float*>(sp + OFF_MISC + 1024) = ws;
        __syncwarp();
        if (lane == 0) mbar_arrive(B(B_WR));
      }
      __syncwarp();
      mbar_wait_u(B(B_LNGO), 0);
#pragma unroll 1
      for (int r = warp == 2 ? 0 : (warp + 1) >> 1; r < 16; r += 3) {
        const uint4* src = reinterpret_cast<const uint4*>(x + (size_t)(cta * 16 + r) * DM) + lane;
        uint4 v[4];
#pragma unroll
        for (int j = 0; j < 4; j++) v[j] = __ldcs(src + j * 32);
        float a0 = 0.f, a1 = 0.f, b0 = 0.f, b1 = 0.f;
#pragma unroll
        for (int j = 0; j < 4; j++) {
          const uint32_t u[4] = {v[j].x, v[j].y, v[j].z, v[j].w};
#pragma unroll
          for (int i = 0; i < 4; i++) { const float a = bf_lo(u[i]), b = bf_hi(u[i]); a0 += a; a1 += b; b0 = fmaf(a, a, b0); b1 = fmaf(b, b, b1); }
        }
        a0 += a1; b0 += b1;
#pragma unroll
        for (int o = 16; o; o >>= 1) { a0 += __shfl_xor_sync(~0u, a0, o); b0 += __shfl_xor_sync(~0u, b0, o); }
        const float mean = a0 * (1.f / DM);
        float mb, inv;
        ln_round(mean, fmaxf(fmaf(b0, 1.f / DM, -mean * mean), 0.f), mb, inv);
        const uint32_t nm2 = pack_bf16(-mb, -mb), inv2 = ln_split(inv);
        uint4* dst = reinterpret_cast<uint4*>(g_xn + (size_t)(cta * 16 + r) * DM) + lane;
#pragma unroll
        for (int j = 0; j < 4; j++) {
          dst[j * 32] = make_uint4(ln_apply(v[j].x, nm2, inv2), ln_apply(v[j].y, nm2, inv2), ln_apply(v[j].z, nm2, inv2), ln_apply(v[j].w, nm2, inv2));
        }
      }
      __syncwarp();
      if (lane == 0) {
        fence_gpu();
        red_add(&g_cnt[C_LN + (cta >> 3)], 1);
        TL(0, 20 + warp, true);
        if (warp == 3) {
          spin_until_ge<true>(&g_cnt[C_LN + gq], 24);
#pragma unroll 1
          for (int i = 0; i < 5; i++) {
            const int c = i == 0 ? C_LN + qa : (i < 3 ? C_KV + (i - 1) * 8 + mp : C_CTX + (i - 3) * 16 + mt);
            spin_until_ge<true>(&g_cnt[c], i == 0 ? 24 : 16);
            fence_async_all();
            mbar_arrive(B(B_DEP + i));
          }
        } else if (warp == 1) {
          mbar_wait(B(B_WR), 0);
#pragma unroll 1
          for (int i = 0; i < 6; i++) {
            const int c = i < 2 ? C_KV + gq + (i ^ 1) * 8 : C_CTX + ((i - 2) >> 1) * 16 + ((i & 1) ? tb : ta);
            mbar_wait(B(B_PUB + i), 0);
            fence_gpu();
            red_add(&g_cnt[c], 1);
          }
        }
      }
      __syncwarp();
      if (warp == 2) {
#pragma unroll 1
        for (int c = 2; c < WIN + 4; c++) {
          mbar_wait_u(B(B_WE + (c & 1)), ((c >> 1) & 1) ^ 1);
          if (c == WIN || c == WIN + 1) {
            e_expect(B(B_WF + (c & 1)), UNIT);
            tma_ld3_ef(sb + OFF_SIDE + (c & 1) * UNIT, &p.x, B(B_WF + (c & 1)), 0, mt * 128 + (c & 1) * 64, gq * 2);
          } else {
#pragma unroll 1
            for (int i = 0; i < 4; i++) { side_piece(c < WIN ? c : c - 2, i); __nanosleep(SIDE_NS); }
          }
        }
      } else if (warp == 1) {
        mbar_wait_u(B(B_SET), 0);
#pragma unroll 1
        for (int i = XR_CAND + lane; i < XR_SIZE; i += 32) { xr[i] = make_uint4(~0u, ~0u, ~0u, ~0u); __nanosleep(SET_NS); }
        __syncwarp();
        if (lane == 0) { fence_gpu(); mbar_arrive(B(B_SET2)); }
      } else {
        mbar_wait_u(B(B_PF), 0);
#pragma unroll 1
        for (int i = 0; i < PF_N; i++) {
          asm volatile("prefetch.global.L2 [%0];" ::"l"((const char*)wdown + (size_t)cta * 57344 + (i * 32 + lane) * 128));
          __nanosleep(PF_NS);
        }
      }
      __syncwarp();
      mbar_wait_u(B(B_OUT), 0);
      {
        const int sub = lane >> 4;
        const uint32_t src = sb + OFF_STG + ((lane & 15) >> 3) * 8192 + sub * 128;
        __nv_bfloat16* dst = out + (size_t)(mt * 128 + sub) * DM + gq * 128 + (lane & 15) * 8;
        auto ld = [&](int r, uint2& rs, uint4& v) {
          asm volatile("ld.shared.v2.u32 {%0,%1}, [%2];" : "=r"(rs.x), "=r"(rs.y) : "r"(sb + OFF_RSTAT + ((r + sub) & 127) * 8));
          v = lds128(src + ((r >> 6) & 1) * 16384 + (r & 63) * 128 + (((lane ^ (r + sub)) & 7) << 4));
        };
        uint2 rs; uint4 v;
        ld(2 * warp - 2, rs, v);
#pragma unroll 1
        for (int r = 2 * warp - 2; r < 128; r += 6) {
          const uint2 cs = rs; const uint4 c = v;
          ld(r + 6, rs, v);
          asm volatile("{\n.reg .pred p;\nsetp.ge.s32 p, %5, 0;\n@p st.global.v4.u32 [%0], {%1,%2,%3,%4};\n}" ::"l"(dst + (size_t)r * DM),
                       "r"(hadd2_bf(c.x, ln_apply(c.x, cs.x, cs.y))), "r"(hadd2_bf(c.y, ln_apply(c.y, cs.x, cs.y))),
                       "r"(hadd2_bf(c.z, ln_apply(c.z, cs.x, cs.y))), "r"(hadd2_bf(c.w, ln_apply(c.w, cs.x, cs.y))), "r"(cs.y) : "memory");
        }
      }
      TL(2, 25, warp == 1);
    }
    __syncwarp();
    cluster_arrive();
    cluster_wait();
  } else {
    reg_alloc<232>();
    const int rid_c = rid0 + zero, warp_c = warp0 + zero;
    const int lane = fresh_lane(), rid = rid_c, mt = rid >> 3, gq = rid & 7, qa = 15 - gq, ta = gq ? gq : 15, tb = 15 - ta;
    const int warp = warp_c, cw = warp - 4, w = cw >> 2;
    cluster_wait();
    auto publish = [&](int i) { __syncwarp(); e_arrive(B(B_PUB + i)); };
    auto release2 = [&](uint32_t b, bool cond = true) { mbar_arrive_both(b, lane, cond); };
    AtState s;
    const uint32_t dA = mk_desc(sb + w * 8192, 16);
    const uint32_t dW = mk_desc(sb, 8192);
    auto mma_kb = [&](float (&d)[64], uint32_t a, uint32_t b, int accum) {
      static_for<4>([&](auto k) { mma_n128_ss<1, k * 32, k * 2048>(d, dA + (a >> 4), dW + (b >> 4), k == 0 ? accum : 1); });
    };
    auto mma_kc = [&](float (&d)[64], auto a, auto b, int accum) {
      static_for<4>([&](auto k) { mma_n128_ss<1, decltype(a)::value + k * 32, decltype(b)::value + k * 2048>(d, dA, dW, k == 0 ? accum : 1); });
    };
    auto issue_q = [&](int kb, auto accum, bool rel = true) {
      const int st = kb & 3;
      if (accum) mbar_wait_c(B(B_FULLQ + st), (kb >> 2) & 1);
      wg_fence();
      mma_kb(s.S, q_aw(st), q_aw(st) + UNIT, accum);
      wg_commit();
      if (accum) {
        wg_wait<1>();
        release2(B(B_EMPTYQ + ((kb - 1) & 3)), rel);
        wg_fence();
      }
      mma_kb(s.O, q_b(st), q_aw(st) + UNIT, accum);
      wg_commit();
    };
    {
      uint4 pk[16];
      __nv_bfloat16* pdst = g_kv;
      auto put = [&](int i) { __stcs(reinterpret_cast<uint4*>(pdst + (i & 1) * 256 + ((i >> 1) & 3) * 4096 + (i >> 3) * 16 * KV_TILE), pk[i]); };
      float acc1[128];
      TL(0, 1, warp == 4);
      int st = 0; uint32_t ph = 0;
      const uint32_t dH = mk_desc(sb, 4096);
      mbar_wait_c(B(B_FULL1), 0);
      auto issue = [&](int h, auto accum) {
        if (accum) mbar_wait_c(B(B_FULL1 + st), ph);
        wg_fence();
        static_for<2>([&](auto k) { mma_n256_ss<1, k * 32, k * 2048>(acc1, dA + (kv_a(h >> 1) >> 4) + (h & 1) * 4, dH + (kv_b(st) >> 4), k == 0 ? (int)accum : 1); });
        wg_commit();
      };
#pragma unroll 1
      for (int t = 0; t < 4; t++) {
        issue(0, IC<0>{});
        TL(0, 2 + 2 * t, warp == 4);
        if (t > 0) { put(0); put(1); }
        int prev = st;
        if (++st == 6) { st = 0; ph ^= 1; }
#pragma unroll 1
        for (int h = 1; h < 16; h++) {
          if (h == 14 && w == 1) bar_sync(5, 256);
          issue(h, IC<1>{});
          if (h == 15 && w == 0) bar_arrive(5, 256);
          if (t > 0) {
#pragma unroll
            for (int i = 2; i < 16; i++) if (h == (i < 4 ? 1 : i - 2)) put(i);
            if (h == 13 && t == 2) publish(0);
          }
          wg_wait<1>();
          if (!(h & 1)) TK(24 + t * 8 + (h >> 1) - 1);
          release2(B(B_EMPTY1 + prev));
          prev = st;
          if (++st == 6) { st = 0; ph ^= 1; }
        }
        pdst = g_kv + (size_t)(((t & 1) * 32 + (gq + ((t >> 1) ^ 1) * 8) * 2) * 16 + mt) * KV_TILE + (cw * 16 + (lane >> 2)) * 32 + ((lane ^ (lane >> 3)) & 3) * 8;
        mbar_wait_c(B(t < 3 ? B_FULL1 + st : B_FULLQ), t < 3 ? ph : 0);
        wg_wait<0>();
        TK(24 + t * 8 + 7);
        fence_regs(acc1);
        release2(B(B_EMPTY1 + prev));
        TL(0, 3 + 2 * t, warp == 4);
#pragma unroll
        for (int a = 0; a < 8; a++)
#pragma unroll
          for (int h = 0; h < 2; h++)
            pk[2 * a + h] = make_uint4(pack_bf16(acc1[16 * a + 2 * h], acc1[16 * a + 2 * h + 1]), pack_bf16(acc1[16 * a + 4 + 2 * h], acc1[16 * a + 5 + 2 * h]),
                                       pack_bf16(acc1[16 * a + 8 + 2 * h], acc1[16 * a + 9 + 2 * h]), pack_bf16(acc1[16 * a + 12 + 2 * h], acc1[16 * a + 13 + 2 * h]));
      }
      issue_q(0, IC<0>{});
      TL(0, 10, warp == 4);
      put(0); put(1);
#pragma unroll 1
      for (int kb = 1; kb < 8; kb++) {
        issue_q(kb, IC<1>{});
        TK(66 + kb - 1);
#pragma unroll
        for (int i = 1; i < 8; i++) if (kb == i) { put(2 * i); put(2 * i + 1); }
      }
      publish(1);
      TL(0, 11, warp == 4);
    }
    __nv_bfloat16* cdst;
    uint32_t redo = 0;
    auto put_ctx = [&](int i, bool cond) {
      asm volatile("{\n.reg .pred p;\nsetp.ne.u32 p, %5, 0;\n@p st.global.cs.v4.u32 [%0], {%1,%2,%3,%4};\n}" ::"l"(cdst + (i & 1) * 256 + (i >> 1) * 4096),
                   "r"(s.P[4 * i]), "r"(s.P[4 * i + 1]), "r"(s.P[4 * i + 2]), "r"(s.P[4 * i + 3]), "r"((uint32_t)(cond && !(redo & 2))) : "memory");
    };
    {
      const int wrow = cw * 16;
      const uint32_t dK = mk_desc(sb, 16), dV = mk_desc(sb, 8192);
      uint32_t kph = 0, vph = 0;
      auto q_store = [&](const float (&d)[64], auto i0, auto i1) {
        const int r0 = lane >> 2;
        const uint32_t a = sb + SLOT + (wrow + r0) * 128 + (((lane & 3) ^ (((r0 & 1) << 2) | (r0 >> 1))) << 4);
#pragma unroll
        for (int i = i0; i < i1; i++) {
          const float* o = d + 16 * (i >> 1) + 2 * (i & 1);
          asm volatile("st.shared.v4.u32 [%0], {%1,%2,%3,%4};" ::"r"((a ^ ((i & 2) << 5)) + (i >> 2) * UNIT + (i & 1) * 1024),
                       "r"(pack_bf16(o[0] * AT_C, o[1] * AT_C)), "r"(pack_bf16(o[4] * AT_C, o[5] * AT_C)),
                       "r"(pack_bf16(o[8] * AT_C, o[9] * AT_C)), "r"(pack_bf16(o[12] * AT_C, o[13] * AT_C)) : "memory");
        }
        __syncwarp();
      };
      auto q_load = [&](auto k0, auto k1) {
        const uint32_t a = sb + SLOT + (wrow + (lane & 15)) * 128 + (((lane >> 4) ^ (((lane & 1) << 2) | ((lane >> 1) & 3))) << 4);
#pragma unroll
        for (int k = k0; k < k1; k++)
          asm volatile("ldmatrix.sync.aligned.m8n8.x4.shared.b16 {%0,%1,%2,%3}, [%4];"
                       : "=r"(s.Q[4 * k]), "=r"(s.Q[4 * k + 1]), "=r"(s.Q[4 * k + 2]), "=r"(s.Q[4 * k + 3]) : "r"((a ^ ((k & 3) << 5)) + (k >> 2) * UNIT) : "memory");
      };
      auto q_load_if = [&](auto k, bool cond, float after) {
        const uint32_t a = sb + SLOT + (wrow + (lane & 15)) * 128 + (((lane >> 4) ^ (((lane & 1) << 2) | ((lane >> 1) & 3))) << 4);
        asm volatile("{\n.reg .pred p;\nsetp.ne.u32 p, %5, 0;\n@p ldmatrix.sync.aligned.m8n8.x4.shared.b16 {%0,%1,%2,%3}, [%4];\n}"
                     : "+r"(s.Q[4 * k]), "+r"(s.Q[4 * k + 1]), "+r"(s.Q[4 * k + 2]), "+r"(s.Q[4 * k + 3])
                     : "r"((a ^ ((k & 3) << 5)) + (k >> 2) * UNIT + (__float_as_uint(after) >> 31)), "r"((uint32_t)cond) : "memory");
      };
      auto issue_s = [&](uint32_t dk, auto mid) {
        mma_n128_rs0<0>(s.S, s.Q, dk);
        static_for<7>([&](auto i) {
          constexpr int k = i + 1;
          if (k == 4) mid();
          mma_n128_rs<0, (k >> 1) * 8192 + (k & 1) * 32>(s.S, s.Q + 4 * k, dk, 1);
        });
        wg_commit();
      };
      auto wait_v = [&](int jv) {
        mbar_wait_c(B(B_VF + (jv & 1)), (vph >> (jv & 1)) & 1);
        vph ^= 1 << (jv & 1);
      };
      auto issue_pva = [&](int jv, int accum) {
        wg_fence();
        static_for<4>([&](auto k) { mma_n128_rs<1, k * 1024>(s.O, s.P + 4 * k, dV + (v_slot(jv) >> 4), k == 0 ? accum : 1); });
        wg_commit();
      };
      auto issue_pvb = [&](int jv, bool upper) {
        if (upper) {
          wg_fence();
          static_for<4>([&](auto k) { mma_n128_rs<1, (k + 4) * 1024>(s.O, s.P + 16 + 4 * k, dV + (v_slot(jv) >> 4), 1); });
          wg_commit();
        } else {
          asm volatile("wgmma.fence.sync.aligned;\nwgmma.commit_group.sync.aligned;" ::: "memory");
        }
      };
      auto issue_pv = [&](int jv, int accum, bool upper) { wait_v(jv); issue_pva(jv, accum); issue_pvb(jv, upper); };
      if (w == 1) bar_arrive(1, 256);
#pragma unroll 1
      for (int half = 0; half < 2; half++) {
        const int head = mt + 16 * half;
        redo = 0;
        float inv[2];
        auto ep_prep = [&]() {
          float l0 = s.l[0] + s.l[1], l1 = s.l[2] + s.l[3];
          l0 += __shfl_xor_sync(~0u, l0, 1); l1 += __shfl_xor_sync(~0u, l1, 1);
          l0 += __shfl_xor_sync(~0u, l0, 2); l1 += __shfl_xor_sync(~0u, l1, 2);
          asm("rcp.approx.ftz.f32 %0, %1;" : "=f"(inv[0]) : "f"(l0));
          asm("rcp.approx.ftz.f32 %0, %1;" : "=f"(inv[1]) : "f"(l1));
          return __any_sync(~0u, !(fminf(l0, l1) >= L_MIN && l0 + l1 <= L_MAX));
        };
        auto ep_out = [&](auto i0, auto i1) {
          __nv_bfloat16* dst = g_ctx + (size_t)(ta * 32 + head) * KV_TILE + (wrow + (lane >> 2)) * 32 + ((lane ^ (lane >> 3)) & 3) * 8;
#pragma unroll
          for (int i = i0; i < i1; i++) {
            const float* o = s.O + 16 * (i >> 1) + 2 * (i & 1);
            const float c = inv[i & 1];
            asm volatile("st.global.cs.v4.u32 [%0], {%1,%2,%3,%4};" ::"l"(dst + (i & 1) * 256 + (i >> 1) * 4096), "r"(pack_bf16(o[0] * c, o[1] * c)),
                         "r"(pack_bf16(o[4] * c, o[5] * c)), "r"(pack_bf16(o[8] * c, o[9] * c)), "r"(pack_bf16(o[12] * c, o[13] * c)) : "memory");
          }
        };
        auto ep_rest = [&]() {
          ep_out(IC<EP1>{}, IC<8>{});
          if (!__any_sync(~0u, redo)) publish(2 + 2 * half);
          fence_regs(s.O);
        };
#pragma unroll 1
        for (int kb = 8; kb < 14; kb++) {
          if (kb == 13) {
            if (w) { wg_wait<0>(); release2(B(B_EMPTYQ)); }
            bar_sync(1 + w, 256);
          }
          issue_q(kb, IC<1>{}, kb != 13 || !w);
          TK(66 + half * 24 + kb - 1);
        }
        TL(1, 20 * half + 0, warp == 4);
        mbar_wait_c(B(B_FULLQ + 2), 1);
        wg_fence();
        mma_kc(s.S, IC<q_aw(2)>{}, IC<q_aw(2) + UNIT>{}, 1);
        wg_commit();
        wg_wait<1>();
        TK(66 + half * 24 + 13);
        release2(B(B_EMPTYQ + 1));
        mbar_wait_c(B(B_FULLQ + 3), 1);
        wg_fence();
        mma_kc(s.S, IC<q_aw(3)>{}, IC<q_aw(3) + UNIT>{}, 1);
        wg_commit();
        bar_arrive(2 - w, 256);
        bar_sync(6 + w, 128);
        wg_wait<0>();
        TK(66 + half * 24 + 14);
        fence_regs(s.S);
        static_for<4>([&](auto i) {
          q_store(s.S, IC<2 * i>{}, IC<2 * i + 2>{});
          q_load(IC<2 * i>{}, IC<2 * i + 2>{});
        });
        TL(1, 20 * half + 1, warp == 4);
        TC(w, 17 * half, 0);
        mbar_wait_c(B(B_KF), kph & 1);
        kph ^= 1;
        bar_sync(1 + w, 256);
        TC(w, 17 * half, 2);
        fence_regs(s.O); fence_regs(s.Q);
        wg_fence();
        issue_s(dK, []() {});
        mma_kc(s.O, IC<q_b(2)>{}, IC<q_aw(2) + UNIT>{}, 1);
        mma_kc(s.O, IC<q_b(3)>{}, IC<q_aw(3) + UNIT>{}, 1);
        wg_commit();
        bar_arrive(2 - w, 256);
        wg_wait<1>();
        TC(w, 17 * half, 4);
        fence_regs(s.S);
        e_arrive(B(B_KE));
        s.l[0] = s.l[1] = s.l[2] = s.l[3] = 0.f;
        at_exp<0, 48>(s);
        at_pack<0, 22>(s);
        sched_fence();
        wg_wait<0>();
        fence_regs(s.O); fence_regs(s.Q);
        release2(B(B_EMPTYQ + 2)); release2(B(B_EMPTYQ + 3));
        at_exp<48, 64>(s);
        at_pack<22, 32>(s);
        q_store(s.O, IC<0>{}, IC<8>{});
        TL(1, 20 * half + 2, warp == 4);
        int kr = 1;
        bool kok = false;
        inv[0] = inv[1] = 0.f;
        const int db = gq ? qa : 16;
#pragma unroll 1
        for (int j = 1; j < 17; j++) {
          const bool diag = j == ta || j == db;
          TC(w, j + 17 * half, 0);
          if (!kok) mbar_wait_c(B(B_KF + kr), (kph >> kr) & 1);
          kph ^= 1 << kr;
          if (j == ta + 2) ep_out(IC<0>{}, IC<EP1>{});
          bar_sync(1 + w, 256);
          TC(w, j + 17 * half, 2);
          fence_regs(s.O); fence_regs(s.P); fence_regs(s.Q);
          const uint32_t ke = B(B_KE + kr), dk = dK + (k_slot(j, kr) >> 4);
          if (++kr == 3) kr = 0;
          auto issue_rest = [&](auto trimmed) {
            TC(w, j + 17 * half, 1);
            if (j == ta + 1) {
              if (ep_prep()) redo = 1;
              s.l[0] = s.l[1] = s.l[2] = s.l[3] = 0.f;
            }
            if (!trimmed && j == ta + 2) ep_rest();
            TC(w, j + 17 * half, 3);
            if (trimmed) wait_v(j - 1);
            issue_pva(j - 1, j != 1 && j != ta + 2);
            issue_pvb(j - 1, w == 1 || (j != ta + 1 && j != db + 1));
            bar_arrive(2 - w, 256);
          };
          auto s_done = [&](auto n) {
            wg_wait<2>();
            TC(w, j + 17 * half, 4);
            fence_part<0, n>(s.S); fence_regs(s.Q);
            e_arrive(ke);
            release2(B(B_X + j - 14), j == 14 || j == 15);
          };
          auto pv_half = [&]() { sched_fence(); wg_wait<1>(); fence_regs(s.P); };
          auto pv_done = [&]() {
            sched_fence();
            wg_wait<0>();
            fence_regs(s.O); fence_regs(s.P);
            e_arrive(B(B_VE + ((j - 1) & 1)));
            release2(B(B_X + 2), j == 16);
            kok = mbar_test(B(B_KF + kr), (kph >> kr) & 1);
          };
          if (diag && w == 0) {
            wg_fence();
            static_for<8>([&](auto k) { mma_n64_rs<0, (k >> 1) * 8192 + (k & 1) * 32, k != 0>(s.S, s.Q + 4 * k, dk); });
            wg_commit();
            issue_rest(IC<1>{});
            s_done(IC<32>{});
            at_mask<0>(s, wrow, lane);
            pv_half();
            static_for<8>([&](auto k) {
              at_exp<4 * k, 4 * k + 4>(s);
              q_load_if(k, j == ta, s.S[4 * k]);
            });
            at_pack<0, 16>(s);
            pv_done();
          } else {
            wg_fence();
            issue_s(dk, [&]() { wait_v(j - 1); wg_fence(); });
            issue_rest(IC<0>{});
            if (!diag) {
              s_done(IC<64>{});
              at_exp<0, 24>(s);
              pv_half();
              at_exp<24, 48>(s);
              at_pack<0, 16>(s);
              pv_done();
              at_exp<48, 64>(s);
              at_pack<16, 32>(s);
            } else {
              s_done(IC<64>{});
              at_mask<8>(s, wrow - 64, lane);
              static_for<8>([&](auto k) {
                at_exp<7 * k, 7 * k + 7>(s);
                q_load_if(k, j == ta, s.S[7 * k + 3]);
                if (k == 2) pv_half();
                if (k == 5) { at_pack<0, 16>(s); pv_done(); }
              });
              at_exp<56, 64>(s);
              at_pack<16, 32>(s);
            }
          }
          TL(1, 20 * half + 2 + j, warp == 4);
        }
        TK(84 + half * 24);
        mbar_wait_c(B(half ? B_FULL3 : B_FULLQ), 0);
        if (gq == 0) ep_out(IC<0>{}, IC<EP1>{});
        bar_sync(1 + w, 256);
        fence_regs(s.O); fence_regs(s.P);
        const uint32_t ga = dA - half * w * 256, gb = ga + (half ? 512 : 4), gh = half ? 0x80000020u : 0x40000040u, go = (2 + half) * (SLOT >> 4);
        wg_fence();
        static_for<4>([&](auto k) { mma_n128_ssh<(k & 1) * 32, UNIT + k * 2048, k != 0>(s.S, k < 2 ? ga : gb, gh, dW); });
        mbar_wait_c(B(half ? B_FULL3 + 1 : B_FULLQ + 1), 0);
        wg_fence();
        static_for<4>([&](auto k) { mma_n128_ssh<(k & 1) * 32, UNIT + k * 2048, true>(s.S, (k < 2 ? ga : gb) + go, gh, dW + go); });
        wg_commit();
        TK(85 + half * 24);
        if (gq == 0) ep_rest();
        issue_pv(16, gq != 0, w == 1 || gq != 0);
        if (w == 0 || half == 0) bar_arrive(2 - w, 256);
        TK(86 + half * 24);
        wg_wait<2>();
        release2(B(B_EMPTY3), half); release2(B(B_EMPTY3 + 1), half);
        if (ep_prep()) redo |= 2;
        sched_fence();
        wg_wait<0>();
        TK(87 + half * 24);
        fence_regs(s.S);
        fence_regs(s.O);
        e_arrive(B(B_VE));
        release2(B(B_X + 3));
        fence_regs(s.P);
        {
          const int r = fresh_lane();
          cdst = g_ctx + (size_t)(tb * 32 + head) * KV_TILE + (wrow + (r >> 2)) * 32 + ((r ^ (r >> 3)) & 3) * 8;
        }
#pragma unroll
        for (int i = 0; i < 32; i++) {
          const float* o = s.O + 16 * (i >> 3) + 2 * ((i >> 2) & 1) + 4 * (i & 3);
          s.P[i] = pack_bf16(o[0] * inv[(i >> 2) & 1], o[1] * inv[(i >> 2) & 1]);
        }
        fence_regs(s.P);
        if (__builtin_expect(__any_sync(~0u, redo != 0), 0)) {
#pragma unroll
          for (int i = 0; i < 8; i++) put_ctx(i, true);
#pragma unroll 1
          for (int t = 0; t < 2; t++) {
            if (__any_sync(~0u, (redo >> t) & 1)) slow_rows(wq, head, (t ? tb : ta) * 128 + wrow);
          }
          if (__any_sync(~0u, redo & 1)) publish(2 + 2 * half);
#pragma unroll
          for (int i = 0; i < 32; i++) s.P[i] = 0;
          redo = 2;
        }
        TL(1, 20 * half + 19, warp == 4);
        TK(88 + half * 24);
        if (half) break;
        mbar_wait_c(B(B_FULLB), 0);
        TK(89);
        wg_fence();
        mma_n128_ss0<1, q_b(0), UNIT>(s.O, dA, dW);
        static_for<3>([&](auto k) { mma_n128_ss<1, q_b(0) + k * 32 + 32, UNIT + k * 2048 + 2048>(s.O, dA, dW, 1); });
        wg_commit();
        mma_kc(s.O, IC<q_b(1)>{}, IC<q_aw(1) + UNIT>{}, 1);
        wg_commit();
        wg_wait<1>();
        release2(B(B_EMPTYQ));
        put_ctx(0, true);
#pragma unroll 1
        for (int kb = 2; kb < 8; kb++) {
          issue_q(kb, IC<1>{});
          TK(90 + kb - 1);
#pragma unroll
          for (int i = 1; i < 8; i++) put_ctx(i, kb == (i < 7 ? i + 1 : 7));
        }
        publish(3);
      }
    }
    const int rid_ = rid + zero, cw_ = cw + zero;
    {
    const int lane = fresh_lane(), rid = rid_, mt = rid >> 3, gq = rid & 7, cw = cw_, w = cw >> 2, ct = cw * 32 + lane;
    const int fid = mt * 7 + gq;
    const bool ffn = gq < 7;
    const uint32_t stg = sb + OFF_STG + w * 16384 + (cw & 3) * 2048;
    const int wr_ = w * 64 + (lane & 7) + (lane >> 4) * 8;
    const uint32_t wl = sb + ((lane >> 3) & 1) * 8192 + wr_ * 64 + (((cw ^ (wr_ >> 1)) & 3) << 4);
    __syncwarp();
    float (&acc)[64] = s.S;
    uint32_t wf[128];
    auto grab = [&](auto c, uint32_t off) {
#pragma unroll
      for (int m = 0; m < 4; m++)
        asm volatile("ldmatrix.sync.aligned.m8n8.x4.trans.shared.b16 {%0,%1,%2,%3}, [%4];"
                     : "=r"(wf[16 * c + 4 * m]), "=r"(wf[16 * c + 4 * m + 1]), "=r"(wf[16 * c + 4 * m + 2]), "=r"(wf[16 * c + 4 * m + 3])
                     : "r"(wl + off + m * 1024) : "memory");
    };
    const int r0 = lane >> 2;
    uint32_t hp[32], rt[16];
    {
      const uint32_t dC = mk_desc(sb + w * 4096, 16);
      uint32_t dep = 0;
      auto hand = [&](uint32_t b, int n) {
        asm volatile("{\n.reg .pred p;\n.reg .b32 t;\nsetp.lt.u32 p, %1, %4;\nmad.lo.u32 t, %2, %3, %0;\n@p mbarrier.arrive.shared::cta.b64 _, [t];\n}"
                     ::"r"(b + 8 * lane), "r"(lane), "r"(dep), "r"(zero), "r"(n) : "memory");
      };
      auto kblock = [&](auto st, uint32_t ph, bool rel) {
        mbar_wait_c(B(B_FULL3 + st), ph);
        wg_fence();
        static_for<4>([&](auto k) { mma_n128_ssh<r3(decltype(st)::value) + (k >> 1) * 8192 + (k & 1) * 32, r3(decltype(st)::value) + UNIT + k * 2048, true>(acc, dC, 0x80000020u, dW); });
        wg_commit();
        wg_wait<1>();
        release2(B(B_EMPTY3 + (st + 5) % 6), rel);
      };
      auto ldsm_if = [&](uint32_t* r, uint32_t a, bool c, auto trans) {
        if (trans) asm volatile("{\n.reg .pred p;\nsetp.ne.u32 p, %5, 0;\n@p ldmatrix.sync.aligned.m8n8.x4.trans.shared.b16 {%0,%1,%2,%3}, [%4];\n}"
                                : "+r"(r[0]), "+r"(r[1]), "+r"(r[2]), "+r"(r[3]) : "r"(a), "r"((uint32_t)c) : "memory");
        else asm volatile("{\n.reg .pred p;\nsetp.ne.u32 p, %5, 0;\n@p ldmatrix.sync.aligned.m8n8.x4.shared.b16 {%0,%1,%2,%3}, [%4];\n}"
                          : "+r"(r[0]), "+r"(r[1]), "+r"(r[2]), "+r"(r[3]) : "r"(a), "r"((uint32_t)c) : "memory");
      };
#pragma unroll
      for (int i = 0; i < 48; i++) asm volatile("" : "=r"(wf[i]));
#pragma unroll 1
      for (int lap = 0; lap < 3; lap++) {
        kblock(IC<2>{}, lap & 1, lap > 0);
#pragma unroll
        for (int i = 0; i < 3; i++) put_ctx(3 * i, lap == i);
        kblock(IC<3>{}, lap & 1, true);
        mbar_wait_c(B(B_WF + (lap & 1)), lap >> 1);
#pragma unroll
        for (int i = 0; i < 12; i++) ldsm_if(wf + 4 * i, wl + OFF_SIDE + ((i >> 2) & 1) * UNIT + (i & 3) * 1024, lap == (i >> 2), IC<1>{});
        kblock(IC<4>{}, lap & 1, true);
        sched_fence();
        dep = 0;
#pragma unroll
        for (int i = 0; i < 12; i++) dep ^= wf[4 * i];
        hand(B(B_WE + (lap & 1)), 1);
#pragma unroll
        for (int i = 0; i < 3; i++) put_ctx(3 * i + 1, lap == i);
        kblock(IC<5>{}, lap & 1, true);
        if (lap == 2) publish(5);
        kblock(IC<0>{}, (lap & 1) ^ 1, true);
#pragma unroll
        for (int i = 0; i < 2; i++) put_ctx(3 * i + 2, lap == i);
        kblock(IC<1>{}, (lap & 1) ^ 1, true);
        TL(2, 40 + lap, warp == 4);
      }
#pragma unroll
      for (int i = 48; i < 96; i++) asm volatile("" : "=r"(wf[i]));
#pragma unroll
      for (int i = 0; i < 32; i++) asm volatile("" : "=r"(hp[i]), "=r"(rt[i >> 1]));
      const uint32_t xa = sb + OFF_SIDE + w * UNIT + (cw & 3) * 2048 + (lane & 15) * 128 + (((lane >> 4) ^ (lane & 7)) << 4);
#pragma unroll 1
      for (int lap = 3; lap < 11; lap++) {
        if (lap == 10 && w == 1) bar_sync(5, 256);
        kblock(IC<2>{}, lap & 1, true);
        if (lap == 10 && w == 0) bar_arrive(5, 256);
        kblock(IC<3>{}, lap & 1, true);
        if (lap == 10) break;
        if (lap < WIN) {
          mbar_wait_c(B(B_WF + (lap & 1)), (lap >> 1) & 1);
#pragma unroll
          for (int i = 12; i < 24; i++) ldsm_if(wf + 4 * i, wl + OFF_SIDE + ((i >> 2) & 1) * UNIT + (i & 3) * 1024, lap == (i >> 2), IC<1>{});
        } else if (lap == WIN) {
          mbar_wait_c(B(B_WF), (WIN >> 1) & 1);
          mbar_wait_c(B(B_WF + 1), (WIN >> 1) & 1);
#pragma unroll
          for (int j = 0; j < 8; j++) ldsm_if(hp + 4 * j, (xa ^ ((j & 3) << 5)) + (j >> 2) * 8192, true, IC<0>{});
        } else if (lap == 9) {
          mbar_wait_c(B(B_WR), 0);
          mbar_wait_c(B(B_SET2), 0);
#pragma unroll
          for (int j = 0; j < 4; j++) ldsm_if(rt + 4 * j, sb + OFF_MISC + 512 + (lane & 1) * 256 + (lane >> 3) * 16 + j * 64, true, IC<0>{});
        }
        kblock(IC<4>{}, lap & 1, true);
        sched_fence();
        dep = 0;
#pragma unroll
        for (int i = 0; i < 20; i++) dep ^= i < 12 ? wf[48 + 4 * i] : hp[4 * (i - 12)];
        hand(B(B_WE + (lap < WIN ? lap & 1 : 0)), lap < WIN ? 1 : (lap == WIN ? 2 : 0));
        kblock(IC<5>{}, lap & 1, true);
        kblock(IC<0>{}, (lap & 1) ^ 1, true);
        kblock(IC<1>{}, (lap & 1) ^ 1, true);
        TL(2, 40 + lap, warp == 4);
      }
    }
    uint4* const xr = g_xr + rid * XR_SIZE;
    uint4* const psd = xr + XR_PS + cw * 16 + r0;
    settle(psd, zero);
    sched_fence();
    wg_wait<0>();
    fence_regs(acc);
    TL(2, 10, warp == 4);
    {
      float d[4] = {0.f, 0.f, 0.f, 0.f}, qa[4] = {0.f, 0.f, 0.f, 0.f}, qb[4] = {0.f, 0.f, 0.f, 0.f};
#pragma unroll
      for (int j = 0; j < 16; j++) {
        hp[2 * j] = hadd2_bf(hp[2 * j], pack_bf16(acc[4 * j], acc[4 * j + 1]));
        hp[2 * j + 1] = hadd2_bf(hp[2 * j + 1], pack_bf16(acc[4 * j + 2], acc[4 * j + 3]));
        if (j & 1) {
          mma16816(d, hp[2 * j - 2], hp[2 * j - 1], hp[2 * j], hp[2 * j + 1], rt[j - 1], rt[j]);
          mma16816(qa, hp[2 * j - 2], hp[2 * j - 1], hp[2 * j], hp[2 * j + 1], hp[2 * j - 2], hp[2 * j]);
          mma16816(qb, hp[2 * j - 2], hp[2 * j - 1], hp[2 * j], hp[2 * j + 1], hp[2 * j - 1], hp[2 * j + 1]);
        }
      }
      asm volatile("{\n.reg .pred p;\nsetp.eq.u32 p, %7, %8;\n@p st.global.cg.v4.f32 [%0], {%1,%2,%3,%3};\n@p st.global.cg.v4.f32 [%0 + 128], {%4,%5,%6,%6};\n}"
                   ::"l"(psd), "f"(d[0]), "f"(d[1]), "f"((r0 & 1) ? qa[1] : qa[0]), "f"(d[2]), "f"(d[3]), "f"((r0 & 1) ? qb[3] : qb[2]),
                   "r"(lane & 3), "r"(r0 >> 1) : "memory");
      sched_fence();
    }
    mbar_wait_c(B(B_EMPTY3), 0);
    __syncwarp();
    stage_store_128(stg, lane, hp);
    TL(2, 11, warp == 4);
    __syncwarp();
    uint4 cout;
    uint32_t ckey;
    {
      const float wsum = *reinterpret_cast<const float*>(sp + OFF_MISC + 1024);
      const uint4* pp = g_xr + (mt * 8 + (ct & 1) * 4) * XR_SIZE + XR_PS + (ct >> 1);
      uint2* kd = reinterpret_cast<uint2*>(xr + XR_KEY) + cw;
      const uint32_t tok = 0x7FFFu - (mt * 128 + (ct >> 1));
      settle(pp, zero); settle(kd, zero); settle(tok, zero);
      spin_clk(PS_DLY);
      float s1, s2, s3;
#pragma unroll 1
      for (int n = 0; n < 0x400000; n++) {
        float4 z[4];
#pragma unroll
        for (int i = 0; i < 4; i++)
          asm volatile("ld.relaxed.gpu.global.v4.f32 {%0,%1,%2,%3}, [%4];" : "=f"(z[i].x), "=f"(z[i].y), "=f"(z[i].z), "=f"(z[i].w) : "l"(pp + i * XR_SIZE) : "memory");
        s1 = (z[0].x + z[1].x) + (z[2].x + z[3].x); s3 = (z[0].y + z[1].y) + (z[2].y + z[3].y); s2 = (z[0].z + z[1].z) + (z[2].z + z[3].z);
        const float t = s1 + s2 + s3;
        s1 += __shfl_xor_sync(~0u, s1, 1); s2 += __shfl_xor_sync(~0u, s2, 1); s3 += __shfl_xor_sync(~0u, s3, 1);
        if (__all_sync(~0u, t == t)) break;
        uint32_t m = 0;
#pragma unroll
        for (int i = 0; i < 4; i++) m = max(max(m, __float_as_uint(z[i].x)), max(__float_as_uint(z[i].y), __float_as_uint(z[i].z)));
        if (__all_sync(~0u, m != 0xFFFFFFFFu)) break;
      }
      TL(2, 12, warp == 4);
      const float mean = s1 * (1.f / DM);
      float mb, inv;
      ln_round(mean, fmaxf(fmaf(s2, 1.f / DM, -mean * mean), 0.f), mb, inv);
      const uint32_t u = pack_bf16(0.f, fmaf(s3 - mb * wsum, inv, 0.f));
      const uint32_t key = ((u ^ (((int)u >> 31) | 0x80000000u)) & 0xFFFF0000u) | tok;
      const uint32_t c1 = __reduce_max_sync(~0u, key);
      const uint32_t c2 = __reduce_max_sync(~0u, key == c1 ? 0u : key);
      asm volatile(ELECT "st.global.cg.v2.u32 [%0], {%1,%2};\n}" ::"l"(kd), "r"(c1), "r"(c2) : "memory");
      sched_fence();
      const uint32_t nm2 = pack_bf16(-mb, -mb), inv2 = ln_split(inv);
      if (!(ct & 1)) *reinterpret_cast<uint2*>(sp + OFF_RSTAT + (ct >> 1) * 8) = make_uint2(nm2, inv2 | (key >= c2 ? 0x80000000u : 0u));
      ckey = (lane >> 4) ? c2 : c1;
      const int row = (0x7FFF - (ckey & 0x7FFF)) & 15;
      const uint32_t rn = __shfl_sync(~0u, nm2, row * 2);
      const uint32_t ri = __shfl_sync(~0u, inv2, row * 2);
      const uint4 v = lds128(stg + ((lane & 15) >> 3) * 8192 + row * 128 + (((lane & 7) ^ (row & 7)) << 4));
      const uint4 n = make_uint4(ln_apply(v.x, rn, ri), ln_apply(v.y, rn, ri), ln_apply(v.z, rn, ri), ln_apply(v.w, rn, ri));
      __stcg(xr + XR_CAND + cw * 64 + 32 + lane, n);
      __stcg(xr + XR_CAND + cw * 64 + lane, v);
      cdst = out + (size_t)(0x7FFF - (ckey & 0x7FFF)) * DM + gq * 128 + (lane & 15) * 8;
      cout = make_uint4(hadd2_bf(v.x, n.x), hadd2_bf(v.y, n.y), hadd2_bf(v.z, n.z), hadd2_bf(v.w, n.w));
    }
    publish(B_OUT - B_PUB);
    cluster_arrive();
    TL(2, 13, warp == 4);
    uint32_t wd[16][4];
    if (ffn) {
      static_for<2>([&](auto i) {
        mbar_wait_b(B(B_WF + i), ((WIN >> 1) & 1) ^ 1);
        grab(IC<WIN + i>{}, OFF_SIDE + i * UNIT);
      });
      mbar_wait_b(B(B_FULL3 + 4 + w), 0);
#pragma unroll
      for (int i = 0; i < 16; i++) {
        const int k = (i & 1) * 16 + (lane & 7) + (lane >> 4) * 8;
        asm volatile("ldmatrix.sync.aligned.m8n8.x4.trans.shared.b16 {%0,%1,%2,%3}, [%4];"
                     : "=r"(wd[i][0]), "=r"(wd[i][1]), "=r"(wd[i][2]), "=r"(wd[i][3])
                     : "r"(sb + r3(4) + w * SLOT + (2 * (cw & 3) + (i >> 3)) * 4096 + k * 128 + (((2 * ((i >> 1) & 3) + ((lane >> 3) & 1)) ^ (lane & 7)) << 4)) : "memory");
      }
    }
    const int fc = 16 * (rid >> 1) + 4 * (rid & 1) + (lane & 3) + 8 * (lane >> 4), ft = (lane >> 3) & 1;
    const char* pc = reinterpret_cast<const char*>(g_xr + ((ct & 127) >> 4) * XR_SIZE + XR_CAND + 32 + (ct & 15));
    const char* pf = reinterpret_cast<const char*>(g_xr + (fc >> 7) * XR_SIZE + XR_CAND) + (fc & 127) * 2;
    const uint32_t xs = sb + OFF_SCR + w * 2112 + ((ct & 127) >> 2) * 64 + (((ct >> 3) & 3) << 4) + (ct & 3) * 4;
    const uint32_t xb = sb + OFF_SCR + (r0 & 1) * 2112 + w * 128 + (((lane ^ w) & 3) << 4);
    settle(pc, zero); settle(pf, zero); settle(cdst, zero); settle(xs, zero); settle(xb, zero);
    mbar_wait_b(B(B_OUT2), 0);
    const uint4 top = lds128(sb + OFF_MISC + 256);
    TL(2, 14, warp == 4);
    uint32_t fh, fn;
    {
      pc += w ? top.y : top.x;
      pf += ft ? top.y : top.x;
      uint4 v;
#pragma unroll 1
      for (int n = 0; n < 0x400000; n++) {
        asm volatile("ld.relaxed.gpu.global.v4.u32 {%0,%1,%2,%3}, [%4];" : "=r"(v.x), "=r"(v.y), "=r"(v.z), "=r"(v.w) : "l"(pc) : "memory");
        asm volatile("ld.relaxed.gpu.global.u16 %0, [%1];" : "=r"(fh) : "l"(pf) : "memory");
        asm volatile("ld.relaxed.gpu.global.u16 %0, [%1 + 512];" : "=r"(fn) : "l"(pf) : "memory");
        asm volatile("st.shared.u32 [%0], %1;" ::"r"(xs), "r"(v.x) : "memory");
        asm volatile("st.shared.u32 [%0], %1;" ::"r"(xs ^ 16), "r"(v.y) : "memory");
        asm volatile("st.shared.u32 [%0], %1;" ::"r"(xs ^ 32), "r"(v.z) : "memory");
        asm volatile("st.shared.u32 [%0], %1;" ::"r"(xs ^ 48), "r"(v.w) : "memory");
        if (__all_sync(~0u, max(max(v.x, v.y), max(v.z, v.w)) != 0xFFFFFFFFu && max(fh, fn) != 0xFFFFu)) break;
      }
    }
    bar_sync(3, 256);
    asm volatile("{\n.reg .pred p;\nsetp.lt.u32 p, %5, %6;\n@p st.global.v4.u32 [%0], {%1,%2,%3,%4};\n}" ::"l"(cdst), "r"(cout.x), "r"(cout.y), "r"(cout.z),
                 "r"(cout.w), "r"(ckey), "r"(top.w) : "memory");
    if (ffn) {
      TL(2, 15, warp == 4);
      float d[4][4] = {};
      auto xl = [&](int i) { return lds128((xb ^ ((i & 2) << 4)) + (i >> 1) * 256 + (i & 1) * 64); };
      uint4 b0 = xl(0), b1 = xl(1);
#pragma unroll
      for (int i = 0; i < 16; i += 2) {
        const uint4 c0 = b0, c1 = b1;
        if (i < 14) { b0 = xl(i + 2); b1 = xl(i + 3); }
        mma16816(d[0], wf[8 * i], wf[8 * i + 1], wf[8 * i + 2], wf[8 * i + 3], c0.x, c0.y);
        mma16816(d[1], wf[8 * i + 4], wf[8 * i + 5], wf[8 * i + 6], wf[8 * i + 7], c0.z, c0.w);
        mma16816(d[2], wf[8 * i + 8], wf[8 * i + 9], wf[8 * i + 10], wf[8 * i + 11], c1.x, c1.y);
        mma16816(d[3], wf[8 * i + 12], wf[8 * i + 13], wf[8 * i + 14], wf[8 * i + 15], c1.z, c1.w);
      }
      const float e0 = (d[0][0] + d[1][0]) + (d[2][0] + d[3][0]), e1 = (d[0][1] + d[1][1]) + (d[2][1] + d[3][1]);
      const float e2 = (d[0][2] + d[1][2]) + (d[2][2] + d[3][2]), e3 = (d[0][3] + d[1][3]) + (d[2][3] + d[3][3]);
      asm volatile("st.shared.v2.f32 [%0], {%1,%2};" ::"r"(sb + OFF_SCR + 8192 + ((w * 2 + (lane & 1)) * 32 + (cw & 3) * 8 + r0) * 8),
                   "f"((lane & 1) ? e1 : e0), "f"((lane & 1) ? e3 : e2) : "memory");
      bar_sync(3, 256);
      TL(2, 16, warp == 4);
      const uint32_t ra = sb + OFF_SCR + 8192 + (r0 & 1) * 256 + (r0 >> 1) * 64 + (lane & 3) * 16;
      const uint4 p0 = lds128(ra), p1 = lds128(ra + 512);
      auto act = [](uint32_t u0, uint32_t u1, uint32_t g0, uint32_t g1) {
        const uint32_t ug = pack_bf16(__uint_as_float(u0) + __uint_as_float(u1), __uint_as_float(g0) + __uint_as_float(g1));
        const float g = bf_hi(ug);
        float r;
        asm("rcp.approx.ftz.f32 %0, %1;" : "=f"(r) : "f"(1.f + ex2(g * -1.4426950408889634f)));
        return bf_round(g * r) * bf_lo(ug);
      };
      const uint32_t av = pack_bf16(act(p0.x, p1.x, p0.y, p1.y), act(p0.z, p1.z, p0.w, p1.w));
      uint32_t b[4];
#pragma unroll
      for (int i = 0; i < 4; i++) b[i] = __shfl_sync(~0u, av, 8 * i + (lane & 7));
      TL(2, 17, warp == 4);
      float y[2][4] = {{0.f, 0.f, 0.f, 0.f}, {0.f, 0.f, 0.f, 0.f}};
#pragma unroll
      for (int c = 0; c < 4; c++) {
        const bool on = (lane >> 3) == c;
        const uint32_t b0 = on ? b[0] : 0, b1 = on ? b[1] : 0, b2 = on ? b[2] : 0, b3 = on ? b[3] : 0;
#pragma unroll
        for (int a = 0; a < 2; a++) {
          const int i = 8 * a + 2 * c;
          mma16816(y[a], wd[i][0], wd[i][1], wd[i][2], wd[i][3], b0, b1);
          mma16816(y[a], wd[i + 1][0], wd[i + 1][1], wd[i + 1][2], wd[i + 1][3], b2, b3);
        }
      }
      float4* yd = reinterpret_cast<float4*>(g_xr + (cw * 16 + (lane & 3) * 2 + (lane >> 4)) * XR_SIZE + XR_Y + fid * 4 + (r0 & 3));
      __stcg(yd, make_float4(y[0][0], y[0][1], y[0][2], y[0][3]));
      __stcg(yd + 8 * XR_SIZE, make_float4(y[1][0], y[1][1], y[1][2], y[1][3]));
    }
    TL(2, 18, warp == 4);
    if (cw == 0) {
      const uint32_t fk = ft ? top.w : top.z;
      uint32_t u = fk >> 16;
      u = (u & 0x8000u) ? (u & 0x7FFFu) : (~u & 0xFFFFu);
      float rs = bf_round(__fdividef(1.f, 1.f + __expf(-__uint_as_float(u << 16))));
      uint16_t* op = reinterpret_cast<uint16_t*>(out) + (size_t)(~fk & 0x7FFF) * DM + fc;
      settle(op, zero); settle(__float_as_uint(rs), zero);
      spin_clk(ffn ? Y_DLY : Y_DLY + Y_DLY0);
      float v[4];
#pragma unroll 1
      for (int n = 0; n < 0x400000; n++) {
        float4 z[14];
#pragma unroll
        for (int i = 0; i < 14; i++)
          asm volatile("ld.relaxed.gpu.global.v4.f32 {%0,%1,%2,%3}, [%4];" : "=f"(z[i].x), "=f"(z[i].y), "=f"(z[i].z), "=f"(z[i].w) : "l"(xr + XR_Y + lane + 32 * i) : "memory");
        float a[4] = {z[0].x, z[0].y, z[0].z, z[0].w}, b[4] = {z[1].x, z[1].y, z[1].z, z[1].w};
#pragma unroll
        for (int i = 2; i < 14; i += 2) {
          a[0] += z[i].x; a[1] += z[i].y; a[2] += z[i].z; a[3] += z[i].w;
          b[0] += z[i + 1].x; b[1] += z[i + 1].y; b[2] += z[i + 1].z; b[3] += z[i + 1].w;
        }
#pragma unroll
        for (int i = 0; i < 4; i++) v[i] = a[i] + b[i];
        const float t = (v[0] + v[1]) + (v[2] + v[3]);
        if (__all_sync(~0u, t == t)) break;
        uint32_t m = 0;
#pragma unroll
        for (int i = 0; i < 14; i++) m = max(max(m, max(__float_as_uint(z[i].x), __float_as_uint(z[i].y))), max(__float_as_uint(z[i].z), __float_as_uint(z[i].w)));
        if (__all_sync(~0u, m != 0xFFFFFFFFu)) break;
      }
      TL(2, 30, true);
      const bool hi = lane & 16, odd = lane & 8;
      const float a0 = (hi ? v[2] : v[0]) + __shfl_xor_sync(~0u, hi ? v[0] : v[2], 16), a1 = (hi ? v[3] : v[1]) + __shfl_xor_sync(~0u, hi ? v[1] : v[3], 16);
      float yv = (odd ? a1 : a0) + __shfl_xor_sync(~0u, odd ? a0 : a1, 8);
      yv += __shfl_xor_sync(~0u, yv, 4);
      const uint32_t o = hadd2_bf(fh, hadd2_bf(fn, pack_bf16(bf_round(yv) * rs, 0.f)));
      if (!(lane & 4)) *op = (uint16_t)o;
      TL(2, 21, true);
    }
    TL(2, 20, warp == 4);
    }
    __syncwarp();
    cluster_wait();
  }
}

typedef CUresult (*EncodeFn)(CUtensorMap*, CUtensorMapDataType, cuuint32_t, void*, const cuuint64_t*, const cuuint64_t*, const cuuint32_t*,
                             const cuuint32_t*, CUtensorMapInterleave, CUtensorMapSwizzle, CUtensorMapL2promotion, CUtensorMapFloatOOBfill);
EncodeFn g_enc = nullptr;

void map2(CUtensorMap* m, const void* ptr, uint64_t rows, uint64_t cols, uint32_t bc, uint32_t br) {
  const CUtensorMapSwizzle sw = bc == 64 ? CU_TENSOR_MAP_SWIZZLE_128B : CU_TENSOR_MAP_SWIZZLE_64B;
  cuuint64_t gd[2] = {cols, rows}, gs[1] = {cols * 2};
  cuuint32_t bd[2] = {bc, br}, es[2] = {1, 1};
  g_enc(m, CU_TENSOR_MAP_DATA_TYPE_BFLOAT16, 2, (void*)ptr, gd, gs, bd, es, CU_TENSOR_MAP_INTERLEAVE_NONE, sw,
        CU_TENSOR_MAP_L2_PROMOTION_L2_128B, CU_TENSOR_MAP_FLOAT_OOB_FILL_NONE);
}
void map3(CUtensorMap* m, const void* ptr, uint64_t rows, uint64_t cols, uint32_t br, uint32_t bch) {
  cuuint64_t gd[3] = {64, rows, cols / 64}, gs[2] = {cols * 2, 128};
  cuuint32_t bd[3] = {64, br, bch}, es[3] = {1, 1, 1};
  g_enc(m, CU_TENSOR_MAP_DATA_TYPE_BFLOAT16, 3, (void*)ptr, gd, gs, bd, es, CU_TENSOR_MAP_INTERLEAVE_NONE, CU_TENSOR_MAP_SWIZZLE_128B,
        CU_TENSOR_MAP_L2_PROMOTION_L2_128B, CU_TENSOR_MAP_FLOAT_OOB_FILL_NONE);
}

}

extern "C" void kernel_launch(void* const* d_in, const int* in_sizes, int n_in, void* d_out, int out_size) {
  const __nv_bfloat16* x = (const __nv_bfloat16*)d_in[0];
  const __nv_bfloat16* ckv = (const __nv_bfloat16*)d_in[1];
  const __nv_bfloat16* wq = (const __nv_bfloat16*)d_in[2];
  const __nv_bfloat16* wk = (const __nv_bfloat16*)d_in[3];
  const __nv_bfloat16* wv = (const __nv_bfloat16*)d_in[4];
  const __nv_bfloat16* wo = (const __nv_bfloat16*)d_in[5];
  const __nv_bfloat16* w_r = (const __nv_bfloat16*)d_in[7];
  const __nv_bfloat16* wgate = (const __nv_bfloat16*)d_in[8];
  const __nv_bfloat16* wup = (const __nv_bfloat16*)d_in[9];
  const __nv_bfloat16* wdown = (const __nv_bfloat16*)d_in[10];
  __nv_bfloat16* out = (__nv_bfloat16*)d_out;

  if (!g_enc) {
    void* fn = nullptr;
    cudaDriverEntryPointQueryResult qr;
    cudaGetDriverEntryPoint("cuTensorMapEncodeTiled", &fn, cudaEnableDefault, &qr);
    g_enc = (EncodeFn)fn;
    cudaFuncSetAttribute(fused_kernel, cudaFuncAttributeMaxDynamicSharedMemorySize, SMEM_BYTES);
  }
  void *xn, *kv, *ctx, *xr, *cnt;
  cudaGetSymbolAddress(&xr, g_xr);
  cudaGetSymbolAddress(&cnt, g_cnt);
  cudaGetSymbolAddress(&xn, g_xn);
  cudaGetSymbolAddress(&kv, g_kv);
  cudaGetSymbolAddress(&ctx, g_ctx);

  Params p;
  map2(&p.xn, xn, SEQ, DM, 64, 64);
  map2(&p.ckv, ckv, SEQ, DC, 64, 128);
  map3(&p.wq, wq, DM, NQ, 64, 2);
  map3(&p.wk, wk, DC, NQ, 32, 2);
  map3(&p.wv, wv, DC, NQ, 32, 2);
  map3(&p.wo, wo, NQ, DM, 64, 1);
  map3(&p.x, x, SEQ, DM, 64, 2);
  map3(&p.wd, wdown, FF, DM, 32, 8);
  map2(&p.wg, wgate, DM, FF, 32, 64);
  map2(&p.wu, wup, DM, FF, 32, 64);
  fused_kernel<<<128, 384, SMEM_BYTES, cudaStreamPerThread>>>(0u, x, (__nv_bfloat16*)kv, (__nv_bfloat16*)ctx, (uint4*)xr, out, (__nv_bfloat16*)xn,
                                                               (unsigned*)cnt, w_r, wdown, wq, p);
}
```

```cpp
#include <cuda_runtime.h>
#include <cuda_bf16.h>
#include <cuda.h>
#include <stdint.h>
#include <utility>

#pragma nv_diag_suppress 549
#pragma nv_diag_suppress 177
namespace {

constexpr int SEQ = 2048, DM = 1024, NH = 32, HD = 128, DC = 512, NQ = NH * HD, FF = 3584;

__device__ __align__(1024) __nv_bfloat16 g_xn[SEQ * DM];
constexpr int KV_TILE = 128 * 128;
__device__ __align__(1024) __nv_bfloat16 g_kv[2 * SEQ * NQ];
__device__ __align__(1024) __nv_bfloat16 g_ctx[SEQ * NQ];
constexpr int XR_PS = 0;
constexpr int XR_KEY = 128;
constexpr int XR_CAND = 136;
constexpr int XR_Y = 648;
constexpr int XR_SIZE = 1104;
__device__ __align__(1024) uint4 g_xr[128 * XR_SIZE];
constexpr int C_LN = 0, C_KV = 16, C_CTX = 32, C_NUM = 64;
__device__ unsigned g_cnt[C_NUM];

#define TL(k, i, cond) do {} while (0)
#define TC(w, g, i) do {} while (0)
#define TL_EXTRA 0
#define TK(i) do {} while (0)

__device__ __forceinline__ uint32_t s2u(const void* p) { return (uint32_t)__cvta_generic_to_shared(p); }
__device__ __forceinline__ void mbar_arrive(uint32_t b) { asm volatile("mbarrier.arrive.shared::cta.b64 _, [%0];" ::"r"(b) : "memory"); }
__device__ __forceinline__ void mbar_arrive_both(uint32_t b, uint32_t lane, bool cond) {
  asm volatile("{\n.reg .pred p;\n.reg .b32 r;\nsetp.lt.u32 p, %1, %2;\nmapa.shared::cluster.u32 r, %0, %1;\n@p mbarrier.arrive.shared::cluster.b64 _, [r];\n}"
               ::"r"(b), "r"(lane), "r"(cond ? 2 : 0) : "memory");
}
__device__ __forceinline__ bool mbar_test(uint32_t b, uint32_t ph) {
  uint32_t ok;
  asm volatile("{\n.reg .pred p;\nmbarrier.test_wait.parity.shared::cta.b64 p, [%1], %2;\nselp.u32 %0, 1, 0, p;\n}" : "=r"(ok) : "r"(b), "r"(ph) : "memory");
  return __all_sync(~0u, ok);
}
__device__ __forceinline__ void mbar_wait(uint32_t b, uint32_t ph) {
  asm volatile(
      "{\n.reg .pred p;\n.reg .u32 n;\nmov.u32 n, 0;\n"
      "LW:\nmbarrier.try_wait.parity.shared::cta.b64 p, [%0], %1, 20000;\n@p bra LD;\n"
      "add.u32 n, n, 1;\nsetp.lt.u32 p, n, 0x40000;\n@p bra LW;\ntrap;\nLD:\n}" ::"r"(b), "r"(ph) : "memory");
}
__device__ __forceinline__ void mbar_wait_u(uint32_t b, uint32_t ph) {
  asm volatile(
      "{\n.reg .pred p;\n.reg .u32 n;\nmov.u32 n, 0;\n"
      "LW:\nmbarrier.try_wait.parity.shared::cta.b64 p, [%0], %1, 20000;\n@p bra.uni LD;\n"
      "add.u32 n, n, 1;\nsetp.lt.u32 p, n, 0x40000;\n@p bra.uni LW;\ntrap;\nLD:\n}" ::"r"(b), "r"(ph) : "memory");
}
__device__ __forceinline__ void mbar_wait_c(uint32_t b, uint32_t ph) {
  asm volatile("{\n.reg .pred p;\nLW:\nmbarrier.try_wait.parity.shared::cta.b64 p, [%0], %1;\n@!p bra.uni LW;\n}" ::"r"(b), "r"(ph) : "memory");
}
__device__ __forceinline__ void mbar_wait_b(uint32_t b, uint32_t ph) {
  asm volatile(
      "{\n.reg .pred p;\n.reg .u32 n;\nmov.u32 n, 0;\n"
      "LW:\nmbarrier.try_wait.parity.shared::cta.b64 p, [%0], %1;\n@p bra.uni LD;\n"
      "add.u32 n, n, 1;\nsetp.lt.u32 p, n, 0x1000000;\n@p bra.uni LW;\ntrap;\nLD:\n}" ::"r"(b), "r"(ph) : "memory");
}
template <bool SLEEP = false>
__device__ __forceinline__ void spin_until_ge(const unsigned* p, unsigned target) {
  asm volatile(
      "{\n.reg .pred p, q;\n.reg .u32 n, v;\nmov.u32 n, 0;\nsetp.ne.u32 q, %2, 0;\n"
      "LW:\nld.acquire.gpu.global.u32 v, [%0];\nsetp.ge.u32 p, v, %1;\n@p bra LD;\n@q nanosleep.u32 200;\n"
      "add.u32 n, n, 1;\nsetp.lt.u32 p, n, 0x400000;\n@p bra LW;\ntrap;\nLD:\n}" ::"l"(p), "r"(target), "n"((int)SLEEP) : "memory");
}
__device__ __forceinline__ void spin_clk(uint32_t n) {
  asm volatile("{\n.reg .pred p;\n.reg .u32 a, b;\nmov.u32 a, %%clock;\nLW:\nmov.u32 b, %%clock;\nsub.u32 b, b, a;\nsetp.lt.u32 p, b, %0;\n@p bra.uni LW;\n}" ::"r"(n) : "memory");
}
__device__ __forceinline__ int fresh_lane() {
  int r;
  asm volatile("mov.u32 %0, %%laneid;" : "=r"(r));
  return r;
}
__device__ __forceinline__ void settle(const void* a, uint32_t zero) {
  asm volatile("{\n.reg .pred p;\nsetp.ne.u32 p, %1, 0;\n@p st.global.u32 [%0], %1;\n}" ::"l"(a), "r"(zero) : "memory");
}
__device__ __forceinline__ void settle(uint32_t a, uint32_t zero) {
  asm volatile("{\n.reg .pred p;\nsetp.ne.u32 p, %1, 0;\n@p st.shared.u32 [%0], %1;\n}" ::"r"(a), "r"(zero) : "memory");
}
__device__ __forceinline__ void fence_async_all() { asm volatile("fence.proxy.async;" ::: "memory"); }
__device__ __forceinline__ void bar_sync(int id, int n) { asm volatile("bar.sync %0, %1;" ::"r"(id), "r"(n) : "memory"); }
__device__ __forceinline__ void bar_arrive(int id, int n) { asm volatile("bar.arrive %0, %1;" ::"r"(id), "r"(n) : "memory"); }
__device__ __forceinline__ void cluster_arrive() { asm volatile("barrier.cluster.arrive.relaxed.aligned;" ::: "memory"); }
__device__ __forceinline__ void cluster_wait() { asm volatile("barrier.cluster.wait.acquire.aligned;" ::: "memory"); }
__device__ __forceinline__ void fence_gpu() { asm volatile("fence.acq_rel.gpu;" ::: "memory"); }
__device__ __forceinline__ void red_add(unsigned* p, unsigned v) { asm volatile("red.relaxed.gpu.global.add.u32 [%0], %1;" ::"l"(p), "r"(v) : "memory"); }
#define ELECT "{\n.reg .pred E;\nelect.sync _|E, 0xFFFFFFFF;\n@E "
__device__ __forceinline__ void e_init(uint32_t b, uint32_t c) { asm volatile(ELECT "mbarrier.init.shared::cta.b64 [%0], %1;\n}" ::"r"(b), "r"(c) : "memory"); }
__device__ __forceinline__ void e_expect(uint32_t b, uint32_t bytes) { asm volatile(ELECT "mbarrier.arrive.expect_tx.shared::cta.b64 _, [%0], %1;\n}" ::"r"(b), "r"(bytes) : "memory"); }
__device__ __forceinline__ void e_arrive(uint32_t b) { asm volatile(ELECT "mbarrier.arrive.shared::cta.b64 _, [%0];\n}" ::"r"(b) : "memory"); }
__device__ __forceinline__ void prefetch_tm(const CUtensorMap* m) { asm volatile(ELECT "prefetch.tensormap [%0];\n}" ::"l"(m) : "memory"); }
__device__ __forceinline__ void tma_ld2(uint32_t dst, const CUtensorMap* m, uint32_t bar, int c0, int c1) {
  asm volatile(ELECT "cp.async.bulk.tensor.2d.shared::cta.global.mbarrier::complete_tx::bytes [%0], [%1, {%3,%4}], [%2];\n}" ::"r"(dst), "l"(m), "r"(bar), "r"(c0), "r"(c1) : "memory");
}
__device__ __forceinline__ void tma_ld3(uint32_t dst, const CUtensorMap* m, uint32_t bar, int c0, int c1, int c2) {
  asm volatile(ELECT "cp.async.bulk.tensor.3d.shared::cta.global.mbarrier::complete_tx::bytes [%0], [%1, {%3,%4,%5}], [%2];\n}" ::"r"(dst), "l"(m), "r"(bar), "r"(c0), "r"(c1), "r"(c2) : "memory");
}
__device__ __forceinline__ void tma_ld2_mc(uint32_t dst, const CUtensorMap* m, uint32_t bar, int c0, int c1, uint16_t mask) {
  asm volatile(ELECT "cp.async.bulk.tensor.2d.shared::cluster.global.mbarrier::complete_tx::bytes.multicast::cluster [%0], [%1, {%3,%4}], [%2], %5;\n}" ::"r"(dst), "l"(m), "r"(bar), "r"(c0), "r"(c1), "h"(mask) : "memory");
}
__device__ __forceinline__ void tma_ld3_mc(uint32_t dst, const CUtensorMap* m, uint32_t bar, int c0, int c1, int c2, uint16_t mask) {
  asm volatile(ELECT "cp.async.bulk.tensor.3d.shared::cluster.global.mbarrier::complete_tx::bytes.multicast::cluster [%0], [%1, {%3,%4,%5}], [%2], %6;\n}" ::"r"(dst), "l"(m), "r"(bar), "r"(c0), "r"(c1), "r"(c2), "h"(mask) : "memory");
}
__device__ __forceinline__ uint64_t policy_evict_first() {
  uint64_t p;
  asm("createpolicy.fractional.L2::evict_first.b64 %0, 1.0;" : "=l"(p));
  return p;
}
__device__ __forceinline__ void tma_ld2_ef(uint32_t dst, const CUtensorMap* m, uint32_t bar, int c0, int c1) {
  asm volatile(ELECT "cp.async.bulk.tensor.2d.shared::cta.global.mbarrier::complete_tx::bytes.L2::cache_hint [%0], [%1, {%3,%4}], [%2], %5;\n}" ::"r"(dst), "l"(m), "r"(bar), "r"(c0), "r"(c1), "l"(policy_evict_first()) : "memory");
}
__device__ __forceinline__ void tma_ld3_ef(uint32_t dst, const CUtensorMap* m, uint32_t bar, int c0, int c1, int c2) {
  asm volatile(ELECT "cp.async.bulk.tensor.3d.shared::cta.global.mbarrier::complete_tx::bytes.L2::cache_hint [%0], [%1, {%3,%4,%5}], [%2], %6;\n}" ::"r"(dst), "l"(m), "r"(bar), "r"(c0), "r"(c1), "r"(c2), "l"(policy_evict_first()) : "memory");
}
__device__ __forceinline__ void bulk_ld(uint32_t dst, const void* src, uint32_t bytes, uint32_t bar) {
  asm volatile(ELECT "cp.async.bulk.shared::cta.global.mbarrier::complete_tx::bytes [%0], [%1], %2, [%3];\n}" ::"r"(dst), "l"(src), "r"(bytes), "r"(bar) : "memory");
}
__device__ __forceinline__ void tma_pf2(const CUtensorMap* m, int c0, int c1) { asm volatile(ELECT "cp.async.bulk.prefetch.tensor.2d.L2.global [%0, {%1,%2}];\n}" ::"l"(m), "r"(c0), "r"(c1) : "memory"); }
__device__ __forceinline__ void tma_pf3(const CUtensorMap* m, int c0, int c1, int c2) { asm volatile(ELECT "cp.async.bulk.prefetch.tensor.3d.L2.global [%0, {%1,%2,%3}];\n}" ::"l"(m), "r"(c0), "r"(c1), "r"(c2) : "memory"); }
__device__ __forceinline__ void sched_fence() { asm volatile("pmevent 0;" ::: "memory"); }
__device__ __forceinline__ void l2_prefetch(const void* p, uint32_t bytes) { asm volatile(ELECT "cp.async.bulk.prefetch.L2.global [%0], %1;\n}" ::"l"(p), "r"(bytes) : "memory"); }

__device__ __forceinline__ void wg_fence() { asm volatile("wgmma.fence.sync.aligned;" ::: "memory"); }
__device__ __forceinline__ void wg_commit() { asm volatile("wgmma.commit_group.sync.aligned;" ::: "memory"); }
template <int N> __device__ __forceinline__ void wg_wait() { asm volatile("wgmma.wait_group.sync.aligned %0;" ::"n"(N) : "memory"); }
template <int N> __device__ __forceinline__ void reg_alloc() { asm volatile("setmaxnreg.inc.sync.aligned.u32 %0;" ::"n"(N)); }
template <int N> __device__ __forceinline__ void reg_dealloc() { asm volatile("setmaxnreg.dec.sync.aligned.u32 %0;" ::"n"(N)); }
template <int N> __device__ __forceinline__ void fence_regs(float (&d)[N]) {
#pragma unroll
  for (int i = 0; i < N; i++) asm volatile("" : "+f"(d[i])::"memory");
}
template <int I0, int I1, int N> __device__ __forceinline__ void fence_part(float (&d)[N]) {
#pragma unroll
  for (int i = I0; i < I1; i++) asm volatile("" : "+f"(d[i])::"memory");
}
template <int N> __device__ __forceinline__ void fence_regs(uint32_t (&d)[N]) {
#pragma unroll
  for (int i = 0; i < N; i++) asm volatile("" : "+r"(d[i])::"memory");
}

__device__ __forceinline__ uint32_t mk_desc(uint32_t addr, uint32_t lbo) { return ((addr & 0x3FFFF) >> 4) | ((lbo >> 4) << 16); }

#define R8(b) "+f"(d[b + 0]), "+f"(d[b + 1]), "+f"(d[b + 2]), "+f"(d[b + 3]), "+f"(d[b + 4]), "+f"(d[b + 5]), "+f"(d[b + 6]), "+f"(d[b + 7])
#define REGS64 "%0,%1,%2,%3,%4,%5,%6,%7,%8,%9,%10,%11,%12,%13,%14,%15,%16,%17,%18,%19,%20,%21,%22,%23,%24,%25,%26,%27,%28,%29,%30,%31," \
               "%32,%33,%34,%35,%36,%37,%38,%39,%40,%41,%42,%43,%44,%45,%46,%47,%48,%49,%50,%51,%52,%53,%54,%55,%56,%57,%58,%59,%60,%61,%62,%63"
#define REGS128 REGS64 ",%64,%65,%66,%67,%68,%69,%70,%71,%72,%73,%74,%75,%76,%77,%78,%79,%80,%81,%82,%83,%84,%85,%86,%87,%88,%89,%90,%91,%92,%93,%94,%95," \
               "%96,%97,%98,%99,%100,%101,%102,%103,%104,%105,%106,%107,%108,%109,%110,%111,%112,%113,%114,%115,%116,%117,%118,%119,%120,%121,%122,%123,%124,%125,%126,%127"

#define DESC(d, r, o) "add.u32 t, " r ", " o ";\nmov.b64 " d ", {t, h};\n"
#define MMA_PRE_(acc, hi) "{\n.reg .pred p;\n.reg .b32 t, h;\n.reg .b64 da, db;\nmov.b32 h, " hi ";\nsetp.ne.b32 p, " acc ", 0;\n"
#define MMA_PRE(acc) MMA_PRE_(acc, "0x40000040")
#define MMA_PRE64(acc) MMA_PRE_(acc, "0x80000020")
template <int TB, int OA, int OB>
__device__ __forceinline__ void mma_n256_ss(float (&d)[128], uint32_t a, uint32_t b, int acc) {
  asm volatile(MMA_PRE("%130") DESC("da", "%128", "%132") DESC("db", "%129", "%133")
               "wgmma.mma_async.sync.aligned.m64n256k16.f32.bf16.bf16 {" REGS128 "}, da, db, p, 1, 1, 0, %131;\n}\n"
               : R8(0), R8(8), R8(16), R8(24), R8(32), R8(40), R8(48), R8(56), R8(64), R8(72), R8(80), R8(88), R8(96), R8(104), R8(112), R8(120)
               : "r"(a), "r"(b), "r"(acc), "n"(TB), "n"(OA >> 4), "n"(OB >> 4));
}
template <int TB, int OA, int OB>
__device__ __forceinline__ void mma_n128_ss(float (&d)[64], uint32_t a, uint32_t b, int acc) {
  asm volatile(MMA_PRE("%66") DESC("da", "%64", "%68") DESC("db", "%65", "%69")
               "wgmma.mma_async.sync.aligned.m64n128k16.f32.bf16.bf16 {" REGS64 "}, da, db, p, 1, 1, 0, %67;\n}\n"
               : R8(0), R8(8), R8(16), R8(24), R8(32), R8(40), R8(48), R8(56)
               : "r"(a), "r"(b), "r"(acc), "n"(TB), "n"(OA >> 4), "n"(OB >> 4));
}
template <int TB, int OB>
__device__ __forceinline__ void mma_n128_rs(float (&d)[64], const uint32_t* a, uint32_t b, int acc) {
  asm volatile(MMA_PRE64("%69") DESC("db", "%68", "%71")
               "wgmma.mma_async.sync.aligned.m64n128k16.f32.bf16.bf16 {" REGS64 "}, {%64,%65,%66,%67}, db, p, 1, 1, %70;\n}\n"
               : R8(0), R8(8), R8(16), R8(24), R8(32), R8(40), R8(48), R8(56)
               : "r"(a[0]), "r"(a[1]), "r"(a[2]), "r"(a[3]), "r"(b), "r"(acc), "n"(TB), "n"(OB >> 4));
}
#define W8(b) "=f"(d[b + 0]), "=f"(d[b + 1]), "=f"(d[b + 2]), "=f"(d[b + 3]), "=f"(d[b + 4]), "=f"(d[b + 5]), "=f"(d[b + 6]), "=f"(d[b + 7])
#define MMA_N64 MMA_PRE64("%37") DESC("db", "%36", "%38") \
  "wgmma.mma_async.sync.aligned.m64n64k16.f32.bf16.bf16 {%0,%1,%2,%3,%4,%5,%6,%7,%8,%9,%10,%11,%12,%13,%14,%15,%16,%17,%18,%19,%20,%21," \
  "%22,%23,%24,%25,%26,%27,%28,%29,%30,%31}, {%32,%33,%34,%35}, db, p, 1, 1, 0;\n}\n"
template <int H, int OB, bool ACC>
__device__ __forceinline__ void mma_n64_rs(float (&d)[64], const uint32_t* a, uint32_t b) {
  if (ACC) asm volatile(MMA_N64 : R8(32 * H), R8(32 * H + 8), R8(32 * H + 16), R8(32 * H + 24) : "r"(a[0]), "r"(a[1]), "r"(a[2]), "r"(a[3]), "r"(b), "n"(1), "n"(OB >> 4));
  else asm volatile(MMA_N64 : W8(32 * H), W8(32 * H + 8), W8(32 * H + 16), W8(32 * H + 24) : "r"(a[0]), "r"(a[1]), "r"(a[2]), "r"(a[3]), "r"(b), "n"(0), "n"(OB >> 4));
}
template <int OB>
__device__ __forceinline__ void mma_n128_rs0(float (&d)[64], const uint32_t* a, uint32_t b) {
  asm volatile(MMA_PRE64("%69") DESC("db", "%68", "%70")
               "wgmma.mma_async.sync.aligned.m64n128k16.f32.bf16.bf16 {" REGS64 "}, {%64,%65,%66,%67}, db, p, 1, 1, 0;\n}\n"
               : W8(0), W8(8), W8(16), W8(24), W8(32), W8(40), W8(48), W8(56)
               : "r"(a[0]), "r"(a[1]), "r"(a[2]), "r"(a[3]), "r"(b), "n"(0), "n"(OB >> 4));
}
#define MMA_SSH MMA_PRE("%67") DESC("db", "%65", "%69") "add.u32 t, %64, %68;\nmov.b64 da, {t, %66};\n" \
  "wgmma.mma_async.sync.aligned.m64n128k16.f32.bf16.bf16 {" REGS64 "}, da, db, p, 1, 1, 0, 1;\n}\n"
template <int OA, int OB, bool ACC>
__device__ __forceinline__ void mma_n128_ssh(float (&d)[64], uint32_t a, uint32_t ahi, uint32_t b) {
  if (ACC) asm volatile(MMA_SSH : R8(0), R8(8), R8(16), R8(24), R8(32), R8(40), R8(48), R8(56) : "r"(a), "r"(b), "r"(ahi), "n"(1), "n"(OA >> 4), "n"(OB >> 4));
  else asm volatile(MMA_SSH : W8(0), W8(8), W8(16), W8(24), W8(32), W8(40), W8(48), W8(56) : "r"(a), "r"(b), "r"(ahi), "n"(0), "n"(OA >> 4), "n"(OB >> 4));
}
template <int TB, int OA, int OB>
__device__ __forceinline__ void mma_n128_ss0(float (&d)[64], uint32_t a, uint32_t b) {
  asm volatile(MMA_PRE("%66") DESC("da", "%64", "%68") DESC("db", "%65", "%69")
               "wgmma.mma_async.sync.aligned.m64n128k16.f32.bf16.bf16 {" REGS64 "}, da, db, p, 1, 1, 0, %67;\n}\n"
               : W8(0), W8(8), W8(16), W8(24), W8(32), W8(40), W8(48), W8(56)
               : "r"(a), "r"(b), "n"(0), "n"(TB), "n"(OA >> 4), "n"(OB >> 4));
}
template <int V> struct IC { static constexpr int value = V; __host__ __device__ constexpr operator int() const { return V; } };
template <int N, class F, int... I>
__device__ __forceinline__ void static_for_(F f, std::integer_sequence<int, I...>) { (f(IC<I>{}), ...); }
template <int N, class F>
__device__ __forceinline__ void static_for(F f) { static_for_<N>(f, std::make_integer_sequence<int, N>{}); }
__device__ __forceinline__ uint32_t pack_bf16(float lo, float hi) {
  uint32_t r;
  asm("cvt.rn.bf16x2.f32 %0, %1, %2;" : "=r"(r) : "f"(hi), "f"(lo));
  return r;
}
__device__ __forceinline__ float bf_lo(uint32_t v) { return __uint_as_float(v << 16); }
__device__ __forceinline__ float bf_hi(uint32_t v) { return __uint_as_float(v & 0xFFFF0000u); }
__device__ __forceinline__ float bf_round(float v) { return bf_lo(pack_bf16(v, v)); }
__device__ __forceinline__ void stsm4(uint32_t addr, uint32_t r0, uint32_t r1, uint32_t r2, uint32_t r3) {
  asm volatile("stmatrix.sync.aligned.m8n8.x4.shared.b16 [%0], {%1,%2,%3,%4};" ::"r"(addr), "r"(r0), "r"(r1), "r"(r2), "r"(r3) : "memory");
}
__device__ __forceinline__ uint4 lds128(uint32_t addr) {
  uint4 v;
  asm volatile("ld.shared.v4.u32 {%0,%1,%2,%3}, [%4];" : "=r"(v.x), "=r"(v.y), "=r"(v.z), "=r"(v.w) : "r"(addr));
  return v;
}
__device__ __forceinline__ float ex2(float x) {
  float y;
  asm("ex2.approx.ftz.f32 %0, %1;" : "=f"(y) : "f"(x));
  return y;
}
__device__ __forceinline__ void stage_store_128(uint32_t base, int lane, const uint32_t* pk) {
  const int row = (lane & 7) + ((lane >> 3) & 1) * 8;
  const uint32_t rb = base + row * 128;
  const int hi = lane >> 4;
#pragma unroll
  for (int j = 0; j < 8; j++) {
    const int chunk = 2 * j + hi;
    const uint32_t a = rb + (j >> 2) * 8192 + (((chunk & 7) ^ (lane & 7)) << 4);
    stsm4(a, pk[4 * j + 0], pk[4 * j + 1], pk[4 * j + 2], pk[4 * j + 3]);
  }
}
__device__ __forceinline__ void ln_round(float mean, float var, float& m_bf, float& inv_s) {
  const uint32_t mv = pack_bf16(mean, var);
  m_bf = bf_lo(mv);
  float sq, rc;
  asm("sqrt.approx.ftz.f32 %0, %1;" : "=f"(sq) : "f"(bf_round(bf_hi(mv) + 1e-5f)));
  asm("rcp.approx.ftz.f32 %0, %1;" : "=f"(rc) : "f"(bf_round(sq)));
  inv_s = rc;
}
__device__ __forceinline__ uint32_t hadd2_bf(uint32_t a, uint32_t b) {
  uint32_t r;
  asm("add.rn.bf16x2 %0, %1, %2;" : "=r"(r) : "r"(a), "r"(b));
  return r;
}
__device__ __forceinline__ uint32_t ln_split(float inv_s) {
  const float hi = bf_round(inv_s);
  return pack_bf16(inv_s - hi, hi);
}
__device__ __forceinline__ uint32_t ln_apply(uint32_t h, uint32_t nm2, uint32_t inv2) {
  uint32_t r;
  asm("{\n.reg .b16 l, u;\n.reg .b32 d, t, ll, uu;\nmov.b32 {l, u}, %3;\nmov.b32 ll, {l, l};\nmov.b32 uu, {u, u};\n"
      "add.rn.bf16x2 d, %1, %2;\nmul.rn.bf16x2 t, d, ll;\nfma.rn.bf16x2 %0, d, uu, t;\n}" : "=r"(r) : "r"(h), "r"(nm2), "r"(inv2));
  return r;
}
__device__ __forceinline__ void mma16816(float* d, uint32_t a0, uint32_t a1, uint32_t a2, uint32_t a3, uint32_t b0, uint32_t b1) {
  asm volatile("mma.sync.aligned.m16n8k16.row.col.f32.bf16.bf16.f32 {%0,%1,%2,%3}, {%4,%5,%6,%7}, {%8,%9}, {%0,%1,%2,%3};"
               : "+f"(d[0]), "+f"(d[1]), "+f"(d[2]), "+f"(d[3]) : "r"(a0), "r"(a1), "r"(a2), "r"(a3), "r"(b0), "r"(b1));
}

constexpr float AT_C = 0.08838834764831845f * 1.4426950408889634f;
#define L_MIN 3.5527137e-15f
#define L_MAX 1.8446744e19f
struct AtState {
  float S[64], O[64];
  uint32_t P[32], Q[32];
  float l[4];
};
template <int I0, int I1>
__device__ __forceinline__ void at_exp(AtState& s) {
#pragma unroll
  for (int i = I0; i < I1; i++) asm volatile("ex2.approx.ftz.f32 %0, %0;" : "+f"(s.S[i]));
#pragma unroll
  for (int i = I0; i < I1; i++) asm volatile("add.f32 %0, %0, %1;" : "+f"(s.l[i & 3]) : "f"(s.S[i]));
}
template <int I0, int I1>
__device__ __forceinline__ void at_pack(AtState& s) {
#pragma unroll
  for (int i = I0; i < I1; i++) asm volatile("cvt.rn.bf16x2.f32 %0, %1, %2;" : "=r"(s.P[i]) : "f"(s.S[2 * i + 1]), "f"(s.S[2 * i]));
}
template <int J0>
__device__ __forceinline__ void at_mask(AtState& s, int r, int lane) {
  const int d = r + (lane >> 2) - (lane & 3) * 2;
#pragma unroll
  for (int j = 0; j < 8; j++) {
    float dummy0 = 0.f, dummy1 = 0.f;
    float& lo0 = j < 7 ? s.S[4 * (J0 + (j < 7 ? j + 1 : j)) + 2] : dummy0;
    float& lo1 = j < 7 ? s.S[4 * (J0 + (j < 7 ? j + 1 : j)) + 3] : dummy1;
    asm("{\n.reg .pred p, q;\nsetp.lt.s32 p, %4, %5;\nsetp.le.s32 q, %4, %5;\n"
        "@p add.f32 %0, %0, 0fFF800000;\n@q add.f32 %1, %1, 0fFF800000;\n@p add.f32 %2, %2, 0fFF800000;\n@q add.f32 %3, %3, 0fFF800000;\n}"
        : "+f"(s.S[4 * (J0 + j)]), "+f"(s.S[4 * (J0 + j) + 1]), "+f"(lo0), "+f"(lo1) : "r"(d), "r"(8 * j));
  }
}
template <int D>
__device__ __forceinline__ uint32_t ld_pair(const __nv_bfloat16* p) {
  uint32_t r;
  asm volatile("{\n.reg .b16 a, b;\nld.global.cg.b16 a, [%1];\nld.global.cg.b16 b, [%1 + %2];\nmov.b32 %0, {a, b};\n}" : "=r"(r) : "l"(p), "n"(2 * D) : "memory");
  return r;
}
__device__ __forceinline__ uint32_t ld_word(const uint32_t* p) {
  uint32_t r;
  asm volatile("ld.global.cg.b32 %0, [%1];" : "=r"(r) : "l"(p) : "memory");
  return r;
}
__device__ __noinline__ void slow_rows(const __nv_bfloat16* wq, int head, int row0) {
  const int lane = fresh_lane(), r = lane >> 2, c = lane & 3;
  uint32_t q[32];
  float o[32];
#pragma unroll
  for (int i = 0; i < 32; i++) q[i] = 0;
  const uint32_t* xa = reinterpret_cast<const uint32_t*>(g_xn + (size_t)(row0 + r) * DM) + c;
#pragma unroll 1
  for (int h = 0; h < 2; h++) {
    const __nv_bfloat16* wb = wq + (size_t)2 * c * NQ + head * HD + 64 * h + 8 * (r >> 1) + (r & 1);
#pragma unroll
    for (int i = 0; i < 32; i++) o[i] = 0.f;
#pragma unroll 1
    for (int kk = 0; kk < DM / 16; kk++) {
      const uint32_t a0 = ld_word(xa + 8 * kk), a1 = ld_word(xa + 8 * kk + 4 * DM), a2 = ld_word(xa + 8 * kk + 4), a3 = ld_word(xa + 8 * kk + 4 * DM + 4);
#pragma unroll
      for (int n = 0; n < 8; n++) {
        const __nv_bfloat16* b = wb + (size_t)16 * kk * NQ + 32 * (n >> 2) + 2 * (n & 3);
        mma16816(o + 4 * n, a0, a1, a2, a3, ld_pair<NQ>(b), ld_pair<NQ>(b + 8 * NQ));
        if (n & 1) sched_fence();
      }
    }
#pragma unroll
    for (int i = 0; i < 16; i++) { q[i] = q[16 + i]; q[16 + i] = pack_bf16(o[2 * i] * AT_C, o[2 * i + 1] * AT_C); }
  }
#pragma unroll 1
  for (int h = 0; h < 2; h++) {
    float m0 = -INFINITY, m1 = -INFINITY, l0 = 0.f, l1 = 0.f;
#pragma unroll
    for (int i = 0; i < 32; i++) o[i] = 0.f;
#pragma unroll 1
    for (int k0 = 0; k0 <= row0; k0 += 16) {
      float e[8] = {0.f, 0.f, 0.f, 0.f, 0.f, 0.f, 0.f, 0.f};
      const __nv_bfloat16* kt = g_kv + (size_t)(head * 16 + (k0 >> 7)) * KV_TILE + (k0 & 127) * 32;
      const uint32_t* kp = reinterpret_cast<const uint32_t*>(kt + r * 32) + c;
#pragma unroll
      for (int kk = 0; kk < 8; kk++) {
        const uint32_t* k0p = kp + (kk >> 1) * 2048 + (((kk & 1) * 2) ^ (r >> 1)) * 4;
        const uint32_t* k1p = kp + (kk >> 1) * 2048 + (((kk & 1) * 2 + 1) ^ (r >> 1)) * 4;
        mma16816(e, q[4 * kk], q[4 * kk + 1], q[4 * kk + 2], q[4 * kk + 3], ld_word(k0p), ld_word(k1p));
        mma16816(e + 4, q[4 * kk], q[4 * kk + 1], q[4 * kk + 2], q[4 * kk + 3], ld_word(k0p + 128), ld_word(k1p + 128));
        if (kk & 1) sched_fence();
      }
      if (k0 == row0) {
#pragma unroll
        for (int i = 0; i < 8; i++) if ((i >> 2) * 8 + 2 * c + (i & 1) > r + (i & 2) * 4) e[i] = -INFINITY;
      }
      float a0 = fmaxf(fmaxf(e[0], e[1]), fmaxf(e[4], e[5])), a1 = fmaxf(fmaxf(e[2], e[3]), fmaxf(e[6], e[7]));
      a0 = fmaxf(a0, __shfl_xor_sync(~0u, a0, 1)); a1 = fmaxf(a1, __shfl_xor_sync(~0u, a1, 1));
      a0 = fmaxf(a0, __shfl_xor_sync(~0u, a0, 2)); a1 = fmaxf(a1, __shfl_xor_sync(~0u, a1, 2));
      a0 = fmaxf(a0, m0); a1 = fmaxf(a1, m1);
      const float sc0 = ex2(m0 - a0), sc1 = ex2(m1 - a1);
      m0 = a0; m1 = a1;
#pragma unroll
      for (int i = 0; i < 8; i++) e[i] = ex2(e[i] - ((i & 2) ? m1 : m0));
      l0 = l0 * sc0 + (e[0] + e[1]) + (e[4] + e[5]);
      l1 = l1 * sc1 + (e[2] + e[3]) + (e[6] + e[7]);
      const uint32_t p0 = pack_bf16(e[0], e[1]), p1 = pack_bf16(e[2], e[3]), p2 = pack_bf16(e[4], e[5]), p3 = pack_bf16(e[6], e[7]);
      const __nv_bfloat16* vp = kt + (size_t)512 * KV_TILE + h * 8192 + 2 * c * 32 + r;
#pragma unroll
      for (int n = 0; n < 8; n++) {
        o[4 * n] *= sc0; o[4 * n + 1] *= sc0; o[4 * n + 2] *= sc1; o[4 * n + 3] *= sc1;
        mma16816(o + 4 * n, p0, p1, p2, p3, ld_pair<32>(vp + (n >> 2) * 4096 + ((n ^ c) & 3) * 8), ld_pair<32>(vp + (n >> 2) * 4096 + ((n ^ c) & 3) * 8 + 256));
        if (n & 1) sched_fence();
      }
    }
    l0 += __shfl_xor_sync(~0u, l0, 1); l1 += __shfl_xor_sync(~0u, l1, 1);
    l0 += __shfl_xor_sync(~0u, l0, 2); l1 += __shfl_xor_sync(~0u, l1, 2);
#pragma unroll
    for (int i = 0; i < 4; i++) {
      const float* v = o + 16 * (i >> 1) + 2 * (i & 1);
      const float f = __fdividef(1.f, (i & 1) ? l1 : l0);
      *reinterpret_cast<uint4*>(g_ctx + (size_t)((row0 >> 7) * 32 + head) * KV_TILE + (2 * h + (i >> 1)) * 4096 + ((row0 & 127) + r + (i & 1) * 8) * 32 + (c ^ (r >> 1)) * 8) =
          make_uint4(pack_bf16(v[0] * f, v[1] * f), pack_bf16(v[4] * f, v[5] * f), pack_bf16(v[8] * f, v[9] * f), pack_bf16(v[12] * f, v[13] * f));
    }
  }
}

constexpr int UNIT = 16384, SLOT = 32768;
constexpr int OFF_SIDE = 2 * SLOT;
__host__ __device__ constexpr int kv_a(int kb) { return (kb < 6 ? kb : 3 * kb - 10) * UNIT; }
__host__ __device__ constexpr int kv_b(int s) { return ((0x76DCA9 >> (4 * s)) & 15) * UNIT; }
__host__ __device__ constexpr int q_aw(int s) { return (3 * s + (s & 1)) * UNIT; }
__host__ __device__ constexpr int q_b(int s) { return (3 * s + 2 - 2 * (s & 1)) * UNIT; }
__host__ __device__ constexpr int k_slot(int j, int r) { return (j < 2 ? 2 * j : (r == 2 ? 0 : 3 + r)) * SLOT; }
__host__ __device__ constexpr int v_slot(int j) { return (6 - (j & 1)) * SLOT; }
__host__ __device__ constexpr int r3(int st) { return ((0x654130 >> (4 * st)) & 7) * SLOT; }
constexpr int OFF_BAR = 229376;
constexpr int OFF_MISC = OFF_BAR + 512;
constexpr int SMEM_BYTES = OFF_MISC + 2080 + TL_EXTRA;
constexpr int OFF_RSTAT = OFF_MISC + 1056;
enum : int {
  B_FULL1 = 0, B_FULLQ = 6, B_FULLB = 10, B_KF = 11, B_VF = 14, B_FULL3 = 16, B_WF = 22, B_DEP = 24, B_OUT2 = 29, B_PF = 30, B_SET = 31,
  B_SET2 = 32, B_LNGO = 33, B_WR = 34,
  B_KE = 35, B_VE = 38, B_WE = 40, B_PUB = 42, B_OUT = 48,
  B_EMPTY1 = 49, B_EMPTYQ = 55, B_X = 59, B_EMPTY3 = 64,
  B_NUM = 70
};
#define TUNABLE(name, v) constexpr int name = v
TUNABLE(LN_GO, 3);
TUNABLE(EP1, 2);
TUNABLE(SIDE_NS, 400);
TUNABLE(SET_KB, 44); TUNABLE(SET_NS, 40);
TUNABLE(PF_KB, 54); TUNABLE(PF_N, 7); TUNABLE(PF_NS, 300);
TUNABLE(PS_DLY, 120); TUNABLE(Y_DLY, 700); TUNABLE(Y_DLY0, 1500);
constexpr int DB = 12;
constexpr int PRE = 6;
constexpr int WIN = 6;
constexpr int OFF_STG = r3(0), OFF_SCR = r3(1);
struct Params {
  CUtensorMap xn, ckv, wq, wk, wv, wo, x, wd, wg, wu;
};

__global__ void __cluster_dims__(2, 1, 1) __launch_bounds__(384, 1)
fused_kernel(uint32_t zero, const __nv_bfloat16* __restrict__ x, __nv_bfloat16* g_kv, __nv_bfloat16* g_ctx, uint4* g_xr,
             __nv_bfloat16* __restrict__ out, __nv_bfloat16* g_xn, unsigned* g_cnt, const __nv_bfloat16* __restrict__ w_r,
             const __nv_bfloat16* __restrict__ wdown, const __nv_bfloat16* __restrict__ wq, const __grid_constant__ Params p) {
  extern __shared__ __align__(1024) uint8_t sp[];
  const uint32_t sb = s2u(sp);
  const uint32_t bar = sb + OFF_BAR;
  auto B = [&](int i) { return bar + 8 * i; };
  const int tid = threadIdx.x, warp = __shfl_sync(~0u, tid >> 5, 0), wg = warp >> 2, lane = tid & 31;
  const int cta = blockIdx.x, rank = cta & 1, cl = cta >> 1;
  const int mp = cl < 4 ? 1 : (cl < 36 ? (cl & 7) : (0x3207654 >> (4 * ((cl - 36) % 7))) & 7);
  const int gq = cl < 4 ? 4 + cl : (cl < 36 ? (cl - 4) >> 3 : 4 + (cl - 36) / 7);
  const int mt = 2 * mp + rank;
  const int qa = 15 - gq;
  const int ta = gq ? gq : 15, tb = 15 - ta;
  const int rid = mt * 8 + gq;
  const int fid = mt * 7 + gq - 1;
  const bool ffn = gq > 0;
  TL(0, 0, warp == 4);
  auto load_pre = [&](int i) {
    e_expect(B(B_FULL1 + i), (i & 1) ? UNIT : 2 * UNIT);
    if (!(i & 1)) tma_ld2(sb + kv_a(i >> 1), &p.ckv, B(B_FULL1 + i), i * 32, mt * 128);
    tma_ld3(sb + kv_b(i) + rank * 8192, &p.wk, B(B_FULL1 + i), 0, i * 32, (gq + 8) * 4 + rank * 2);
    tma_ld3(sb + kv_b(i) + 8192 - rank * 8192, &p.wk, B(B_FULL1 + i), 0, i * 32, (gq + 8) * 4 + 2 - rank * 2);
  };
  if (warp == 0) {
    e_init(B(B_FULL1), 1);
    asm volatile("fence.mbarrier_init.release.cluster;" ::: "memory");
    TL(0, 16, true);
    load_pre(0);
    TL(0, 17, true);
#pragma unroll
    for (int kb = 1; kb < PRE; kb++) e_init(B(B_FULL1 + kb), 1);
  } else {
#pragma unroll 1
    for (int i = PRE - 1 + warp; i < B_NUM; i += 11) e_init(B(i), i >= B_EMPTY1 ? 16 : (i >= B_KE ? 8 : (i == B_WR ? 2 : 1)));
  }
  asm volatile("fence.mbarrier_init.release.cluster;" ::: "memory");
  cluster_arrive();
  const int rid0 = rid, warp0 = warp;
  if (wg == 0) {
    reg_dealloc<40>();
    if (warp == 0) {
      TL(0, 12, true);
#pragma unroll 1
      for (int kb = 1; kb < PRE; kb++) load_pre(kb);
      if (mt >= PRE) { tma_pf3(&p.wk, 0, mt * 32, (gq + 8) * 4); tma_pf3(&p.wk, 0, mt * 32, (gq + 8) * 4 + 2); }
      if (gq >= PRE / 2) tma_pf2(&p.ckv, gq * 64, mt * 128);
      TL(0, 15, true);
    }
    TL(0, 18, warp == 0);
    __syncwarp();
    cluster_wait();
    uint4* const xr = g_xr + rid * XR_SIZE;
    auto side_piece = [&](int c, int piece) {
      const uint32_t fb = B(B_WF + (c & 1));
      if (piece == 0) e_expect(fb, ffn ? UNIT : 0);
      if (ffn) tma_ld2_ef(sb + OFF_SIDE + (c & 1) * UNIT + piece * 4096, (piece & 2) ? &p.wg : &p.wu, fb, fid * 32, c * 128 + (piece & 1) * 64);
    };
    if (warp == 0) {
      {
        int st = 0; uint32_t ph = 0;
#pragma unroll 1
        for (int i = PRE; i < 64; i++) {
          const int t = i >> 4, h = i & 15;
          const uint32_t fb = B(B_FULL1 + st);
          const bool with_a = (i & 0x31) == 0;
          mbar_wait_c(B(B_EMPTY1 + st), ph);
          e_expect(fb, with_a ? 2 * UNIT : UNIT);
          if (with_a) tma_ld2(sb + kv_a(h >> 1), &p.ckv, fb, h * 32, mt * 128);
          tma_ld3_mc(sb + kv_b(st) + rank * 8192, (t & 1) ? &p.wv : &p.wk, fb, 0, h * 32, (gq + ((t >> 1) ^ 1) * 8) * 4 + rank * 2, 3);
          if (i == 2 * LN_GO) e_arrive(B(B_LNGO));
          if (i == 24) { prefetch_tm(&p.wq); prefetch_tm(&p.xn); }
          if ((h >> 1) == (t ? 0 : 4) && t < 3) tma_pf3((t & 1) ? &p.wk : &p.wv, 0, mt * 32, (gq + (((t + 1) >> 1) ^ 1) * 8) * 4 + (h & 1) * 2);
          if ((i | 2) == 50) tma_pf3(&p.wq, 0, (gq + 4 * h) * 64, mt * 2);
          if (++st == 6) { st = 0; ph ^= 1; }
        }
        prefetch_tm(&p.wo); prefetch_tm(&p.wd); prefetch_tm(&p.x); prefetch_tm(&p.wg); prefetch_tm(&p.wu);
        mbar_wait_c(B(B_DEP + 0), 0);
        uint32_t kpar = 7, vpar = 3;
        auto load_aw = [&](int kb, int head) {
          const uint32_t d = sb + q_aw(kb & 3), fb = B(B_FULLQ + (kb & 3));
          tma_ld2_mc(d + rank * 8192, &p.xn, fb, kb * 64, ta * 128 + rank * 64, 3);
          tma_ld3(d + UNIT, &p.wq, fb, 0, kb * 64, head * 2);
        };
        auto load_b = [&](int kb, uint32_t fb) { tma_ld2_mc(sb + q_b(kb & 3) + rank * 8192, &p.xn, fb, kb * 64, tb * 128 + rank * 64, 3); };
        auto load3 = [&](int kb, int s) {
          const uint32_t d = sb + r3(s), fb = B(B_FULL3 + s);
          e_expect(fb, SLOT);
          bulk_ld(d, g_ctx + (size_t)(mt * 64 + kb) * 8192, UNIT, fb);
          tma_ld3_mc(d + UNIT + rank * 8192, &p.wo, fb, 0, kb * 64, gq * 2 + rank, 3);
        };
#pragma unroll 1
        for (int half = 0; half < 2; half++) {
          const int head = mt + 16 * half;
#pragma unroll 1
          for (int kb = 2 * half; kb < 16; kb++) {
            if (kb >= 4) mbar_wait_c(B(B_EMPTYQ + (kb & 3)), ((kb >> 2) & 1) ^ 1);
            else if (half) mbar_wait_c(B(B_X + kb), 0);
            else if (kb > 0) mbar_wait_c(B(B_EMPTY1 + (2 * kb + 3) % 6), kb == 1);
            e_expect(B(B_FULLQ + (kb & 3)), 3 * UNIT);
            load_aw(kb, head);
            load_b(kb, B(B_FULLQ + (kb & 3)));
          }
          mbar_wait_c(B(B_DEP + 1 + half), 0);
          if (half) mbar_wait_c(B(B_X + 4), 0);
          const __nv_bfloat16* kt = g_kv + (size_t)head * 16 * KV_TILE;
          l2_prefetch(kt, SLOT);
          auto blk = [&](int j) { return qa >= DB ? (j > qa ? 16 - j : j) : (j == DB ? qa : (j == qa ? 16 - DB : (j > qa ? 16 - j : j))); };
          auto load_v = [&](int j) {
            const int r = j & 1;
            mbar_wait_c(B(B_VE + r), (vpar >> r) & 1);
            vpar ^= 1 << r;
            e_expect(B(B_VF + r), SLOT);
            bulk_ld(sb + v_slot(j), kt + (size_t)(512 + blk(j)) * KV_TILE, SLOT, B(B_VF + r));
          };
          int r = 0;
#pragma unroll 1
          for (int j = 0; j < 17; j++) {
            if (j < 2) mbar_wait_c(B(B_EMPTYQ + j), 1);
            if (j == 2) mbar_wait_c(B(B_KE), kpar & 1);
            mbar_wait_c(B(B_KE + r), (kpar >> r) & 1);
            kpar ^= 1 << r;
            e_expect(B(B_KF + r), SLOT);
            bulk_ld(sb + k_slot(j, r), kt + blk(j) * KV_TILE, SLOT, B(B_KF + r));
            if (++r == 3) r = 0;
            if (j == 2) { mbar_wait_c(B(B_EMPTYQ + 2), 1); mbar_wait_c(B(B_EMPTYQ + 3), 1); }
            if (j != 1) load_v(j ? j - 1 : 0);
            if (half && j < 16) l2_prefetch(kt + (size_t)(512 + j) * KV_TILE + gq * 2048, 4096);
            if (half == 0) {
              if (j == 16) {
                tma_pf3(&p.wq, 0, (4 + gq) * 64, (mt + 16) * 2);
                tma_pf2(&p.xn, (4 + (mp & 3)) * 64, ((mp & 4) ? qa : gq) * 128 + rank * 64);
              }
            } else if (j >= 14) {
              tma_pf3(&p.wo, 0, (5 + mp + 8 * (16 - j)) * 64, gq * 2 + rank);
            } else if (j >= 5 && j < 13) {
              side_piece((j - 5) >> 2, (j - 5) & 3);
            }
          }
          mbar_wait_c(B(B_X + 0), half);
          if (half == 0) {
            for (int kb = 0; kb < 2; kb++) { e_expect(B(B_FULLQ + kb), 2 * UNIT); load_aw(kb, mt + 16); }
          } else {
            mbar_wait_c(B(B_DEP + 3), 0);
            load3(0, 0);
          }
          mbar_wait_c(B(B_X + 1), half);
          if (half) load3(1, 1);
          load_v(16);
          if (gq == 0) mbar_wait_c(B(B_X + 2), half);
          if (half == 0) { e_expect(B(B_FULLB), 2 * UNIT); load_b(0, B(B_FULLB)); load_b(1, B(B_FULLB)); }
        }
        st = 2; ph = 1;
#pragma unroll 1
        for (int kb = 2; kb < 64; kb++) {
          if (kb == 32) mbar_wait_c(B(B_DEP + 4), 0);
          if (kb >= 6) mbar_wait_c(B(B_EMPTY3 + st), ph);
          else if (kb > 2) mbar_wait_c(B(B_X + kb - 1), 1);
          load3(kb, st);
          if (++st == 6) { st = 0; ph ^= 1; }
          if (kb == PF_KB) e_arrive(B(B_PF));
          if (kb == SET_KB) e_arrive(B(B_SET));
          if (kb == 58) l2_prefetch(xr, XR_CAND * 16);
        }
        if (ffn) {
#pragma unroll 1
          for (int j = 0; j < 2; j++) {
            mbar_wait_c(B(B_EMPTY3 + 4 + j), 1);
            e_expect(B(B_FULL3 + 4 + j), SLOT);
            tma_ld3(sb + r3(4 + j), &p.wd, B(B_FULL3 + 4 + j), 0, fid * 32, 8 * j);
          }
        }
        const uint4* kp = g_xr + ((lane >> 1) * 8 + gq) * XR_SIZE + XR_KEY + (lane & 1) * 2;
        mbar_wait_c(B(B_OUT), 0);
        uint32_t k1, k2, m1;
#pragma unroll 1
        for (int n = 0; n < 0x400000; n++) {
          uint4 a, b;
          asm volatile("ld.relaxed.gpu.global.v4.u32 {%0,%1,%2,%3}, [%4];" : "=r"(a.x), "=r"(a.y), "=r"(a.z), "=r"(a.w) : "l"(kp) : "memory");
          asm volatile("ld.relaxed.gpu.global.v4.u32 {%0,%1,%2,%3}, [%4 + 16];" : "=r"(b.x), "=r"(b.y), "=r"(b.z), "=r"(b.w) : "l"(kp) : "memory");
          const uint32_t a1 = max(a.x, a.z), a2 = max(min(a.x, a.z), max(a.y, a.w));
          const uint32_t b1 = max(b.x, b.z), b2 = max(min(b.x, b.z), max(b.y, b.w));
          k1 = max(a1, b1); k2 = max(min(a1, b1), max(a2, b2));
          m1 = __reduce_max_sync(~0u, max(k1, k2));
          if (m1 != 0xFFFFFFFFu) break;
        }
        const uint32_t m2 = __reduce_max_sync(~0u, k1 == m1 ? k2 : k1);
        const uint32_t t0 = ~m1 & 0x7FFF, t1 = ~m2 & 0x7FFF;
        const uint32_t o0 = (t0 >> 7) * (8 * XR_SIZE * 16) + (t0 & 0x70) * 64, o1 = (t1 >> 7) * (8 * XR_SIZE * 16) + (t1 & 0x70) * 64 + ((t0 ^ t1) < 16 ? 256 : 0);
        asm volatile(ELECT "st.shared.v4.u32 [%0], {%1,%2,%3,%4};\n}" ::"r"(sb + OFF_MISC + 256), "r"(o0), "r"(o1), "r"(m1), "r"(m2) : "memory");
        e_arrive(B(B_OUT2));
        if (rid == 127) { g_cnt[lane] = 0; g_cnt[32 + lane] = 0; }
      }
    } else {
      if (warp >= 2) {
#pragma unroll 1
        for (int i = tid - 64; i < XR_CAND; i += 64) xr[i] = make_uint4(~0u, ~0u, ~0u, ~0u);
        if (warp == 2) { __syncwarp(); if (lane == 0) mbar_arrive(B(B_WR)); }
      }
      if (warp == 3) {
        float ws = 0.f;
#pragma unroll 1
        for (int j = 0; j < 4; j++) {
          const uint4 q = __ldg(reinterpret_cast<const uint4*>(w_r) + j * 32 + lane);
          ws += bf_lo(q.x) + bf_hi(q.x) + bf_lo(q.y) + bf_hi(q.y) + bf_lo(q.z) + bf_hi(q.z) + bf_lo(q.w) + bf_hi(q.w);
        }
#pragma unroll
        for (int o = 16; o; o >>= 1) ws += __shfl_xor_sync(~0u, ws, o);
        uint2* tab = reinterpret_cast<uint2*>(sp + OFF_MISC + 512);
        tab[lane] = make_uint2(0x3F803F80u, 0x3F803F80u);
        tab[32 + lane] = __ldg(reinterpret_cast<const uint2*>(w_r + gq * 128) + lane);
        if (lane == 0) *reinterpret_cast<float*>(sp + OFF_MISC + 1024) = ws;
        __syncwarp();
        if (lane == 0) mbar_arrive(B(B_WR));
      }
      __syncwarp();
      mbar_wait_u(B(B_LNGO), 0);
#pragma unroll 1
      for (int r = warp == 2 ? 0 : (warp + 1) >> 1; r < 16; r += 3) {
        const uint4* src = reinterpret_cast<const uint4*>(x + (size_t)(cta * 16 + r) * DM) + lane;
        uint4 v[4];
#pragma unroll
        for (int j = 0; j < 4; j++) v[j] = __ldcs(src + j * 32);
        float a0 = 0.f, a1 = 0.f, b0 = 0.f, b1 = 0.f;
#pragma unroll
        for (int j = 0; j < 4; j++) {
          const uint32_t u[4] = {v[j].x, v[j].y, v[j].z, v[j].w};
#pragma unroll
          for (int i = 0; i < 4; i++) { const float a = bf_lo(u[i]), b = bf_hi(u[i]); a0 += a; a1 += b; b0 = fmaf(a, a, b0); b1 = fmaf(b, b, b1); }
        }
        a0 += a1; b0 += b1;
#pragma unroll
        for (int o = 16; o; o >>= 1) { a0 += __shfl_xor_sync(~0u, a0, o); b0 += __shfl_xor_sync(~0u, b0, o); }
        const float mean = a0 * (1.f / DM);
        float mb, inv;
        ln_round(mean, fmaxf(fmaf(b0, 1.f / DM, -mean * mean), 0.f), mb, inv);
        const uint32_t nm2 = pack_bf16(-mb, -mb), inv2 = ln_split(inv);
        uint4* dst = reinterpret_cast<uint4*>(g_xn + (size_t)(cta * 16 + r) * DM) + lane;
#pragma unroll
        for (int j = 0; j < 4; j++) {
          dst[j * 32] = make_uint4(ln_apply(v[j].x, nm2, inv2), ln_apply(v[j].y, nm2, inv2), ln_apply(v[j].z, nm2, inv2), ln_apply(v[j].w, nm2, inv2));
        }
      }
      __syncwarp();
      if (lane == 0) {
        fence_gpu();
        red_add(&g_cnt[C_LN + (cta >> 3)], 1);
        TL(0, 20 + warp, true);
        if (warp == 3) {
          spin_until_ge<true>(&g_cnt[C_LN + gq], 24);
#pragma unroll 1
          for (int i = 0; i < 5; i++) {
            const int c = i == 0 ? C_LN + qa : (i < 3 ? C_KV + (i - 1) * 8 + mp : C_CTX + (i - 3) * 16 + mt);
            spin_until_ge<true>(&g_cnt[c], i == 0 ? 24 : 16);
            fence_async_all();
            mbar_arrive(B(B_DEP + i));
          }
        } else if (warp == 1) {
          mbar_wait(B(B_WR), 0);
#pragma unroll 1
          for (int i = 0; i < 6; i++) {
            const int c = i < 2 ? C_KV + gq + (i ^ 1) * 8 : C_CTX + ((i - 2) >> 1) * 16 + ((i & 1) ? tb : ta);
            mbar_wait(B(B_PUB + i), 0);
            fence_gpu();
            red_add(&g_cnt[c], 1);
          }
        }
      }
      __syncwarp();
      if (warp == 2) {
#pragma unroll 1
        for (int c = 2; c < WIN + 4; c++) {
          mbar_wait_u(B(B_WE + (c & 1)), ((c >> 1) & 1) ^ 1);
          if (c == WIN || c == WIN + 1) {
            e_expect(B(B_WF + (c & 1)), UNIT);
            tma_ld3_ef(sb + OFF_SIDE + (c & 1) * UNIT, &p.x, B(B_WF + (c & 1)), 0, mt * 128 + (c & 1) * 64, gq * 2);
          } else {
#pragma unroll 1
            for (int i = 0; i < 4; i++) { side_piece(c < WIN ? c : c - 2, i); __nanosleep(SIDE_NS); }
          }
        }
      } else if (warp == 1) {
        mbar_wait_u(B(B_SET), 0);
#pragma unroll 1
        for (int i = XR_CAND + lane; i < XR_SIZE; i += 32) { xr[i] = make_uint4(~0u, ~0u, ~0u, ~0u); __nanosleep(SET_NS); }
        __syncwarp();
        if (lane == 0) { fence_gpu(); mbar_arrive(B(B_SET2)); }
      } else {
        mbar_wait_u(B(B_PF), 0);
#pragma unroll 1
        for (int i = 0; i < PF_N; i++) {
          asm volatile("prefetch.global.L2 [%0];" ::"l"((const char*)wdown + (size_t)cta * 57344 + (i * 32 + lane) * 128));
          __nanosleep(PF_NS);
        }
      }
      __syncwarp();
      mbar_wait_u(B(B_OUT), 0);
      {
        const int sub = lane >> 4;
        const uint32_t src = sb + OFF_STG + ((lane & 15) >> 3) * 8192 + sub * 128;
        __nv_bfloat16* dst = out + (size_t)(mt * 128 + sub) * DM + gq * 128 + (lane & 15) * 8;
        auto ld = [&](int r, uint2& rs, uint4& v) {
          asm volatile("ld.shared.v2.u32 {%0,%1}, [%2];" : "=r"(rs.x), "=r"(rs.y) : "r"(sb + OFF_RSTAT + ((r + sub) & 127) * 8));
          v = lds128(src + ((r >> 6) & 1) * 16384 + (r & 63) * 128 + (((lane ^ (r + sub)) & 7) << 4));
        };
        uint2 rs; uint4 v;
        ld(2 * warp - 2, rs, v);
#pragma unroll 1
        for (int r = 2 * warp - 2; r < 128; r += 6) {
          const uint2 cs = rs; const uint4 c = v;
          ld(r + 6, rs, v);
          asm volatile("{\n.reg .pred p;\nsetp.ge.s32 p, %5, 0;\n@p st.global.v4.u32 [%0], {%1,%2,%3,%4};\n}" ::"l"(dst + (size_t)r * DM),
                       "r"(hadd2_bf(c.x, ln_apply(c.x, cs.x, cs.y))), "r"(hadd2_bf(c.y, ln_apply(c.y, cs.x, cs.y))),
                       "r"(hadd2_bf(c.z, ln_apply(c.z, cs.x, cs.y))), "r"(hadd2_bf(c.w, ln_apply(c.w, cs.x, cs.y))), "r"(cs.y) : "memory");
        }
      }
      TL(2, 25, warp == 1);
    }
    __syncwarp();
    cluster_arrive();
    cluster_wait();
  } else {
    reg_alloc<232>();
    const int rid_c = rid0 + zero, warp_c = warp0 + zero;
    const int lane = fresh_lane(), rid = rid_c, mt = rid >> 3, gq = rid & 7, qa = 15 - gq, ta = gq ? gq : 15, tb = 15 - ta;
    const int warp = warp_c, cw = warp - 4, w = cw >> 2;
    cluster_wait();
    auto publish = [&](int i) { __syncwarp(); e_arrive(B(B_PUB + i)); };
    auto release2 = [&](uint32_t b, bool cond = true) { mbar_arrive_both(b, lane, cond); };
    AtState s;
    const uint32_t dA = mk_desc(sb + w * 8192, 16);
    const uint32_t dW = mk_desc(sb, 8192);
    auto mma_kb = [&](float (&d)[64], uint32_t a, uint32_t b, int accum) {
      static_for<4>([&](auto k) { mma_n128_ss<1, k * 32, k * 2048>(d, dA + (a >> 4), dW + (b >> 4), k == 0 ? accum : 1); });
    };
    auto mma_kc = [&](float (&d)[64], auto a, auto b, int accum) {
      static_for<4>([&](auto k) { mma_n128_ss<1, decltype(a)::value + k * 32, decltype(b)::value + k * 2048>(d, dA, dW, k == 0 ? accum : 1); });
    };
    auto issue_q = [&](int kb, auto accum, bool rel = true) {
      const int st = kb & 3;
      if (accum) mbar_wait_c(B(B_FULLQ + st), (kb >> 2) & 1);
      wg_fence();
      mma_kb(s.S, q_aw(st), q_aw(st) + UNIT, accum);
      wg_commit();
      if (accum) {
        wg_wait<1>();
        release2(B(B_EMPTYQ + ((kb - 1) & 3)), rel);
        wg_fence();
      }
      mma_kb(s.O, q_b(st), q_aw(st) + UNIT, accum);
      wg_commit();
    };
    {
      uint4 pk[16];
      __nv_bfloat16* pdst = g_kv;
      auto put = [&](int i) { __stcs(reinterpret_cast<uint4*>(pdst + (i & 1) * 256 + ((i >> 1) & 3) * 4096 + (i >> 3) * 16 * KV_TILE), pk[i]); };
      float acc1[128];
      TL(0, 1, warp == 4);
      int st = 0; uint32_t ph = 0;
      const uint32_t dH = mk_desc(sb, 4096);
      mbar_wait_c(B(B_FULL1), 0);
      auto issue = [&](int h, auto accum) {
        if (accum) mbar_wait_c(B(B_FULL1 + st), ph);
        wg_fence();
        static_for<2>([&](auto k) { mma_n256_ss<1, k * 32, k * 2048>(acc1, dA + (kv_a(h >> 1) >> 4) + (h & 1) * 4, dH + (kv_b(st) >> 4), k == 0 ? (int)accum : 1); });
        wg_commit();
      };
#pragma unroll 1
      for (int t = 0; t < 4; t++) {
        issue(0, IC<0>{});
        TL(0, 2 + 2 * t, warp == 4);
        if (t > 0) { put(0); put(1); }
        int prev = st;
        if (++st == 6) { st = 0; ph ^= 1; }
#pragma unroll 1
        for (int h = 1; h < 16; h++) {
          if (h == 14 && w == 1) bar_sync(5, 256);
          issue(h, IC<1>{});
          if (h == 15 && w == 0) bar_arrive(5, 256);
          if (t > 0) {
#pragma unroll
            for (int i = 2; i < 16; i++) if (h == (i < 4 ? 1 : i - 2)) put(i);
            if (h == 13 && t == 2) publish(0);
          }
          wg_wait<1>();
          if (!(h & 1)) TK(24 + t * 8 + (h >> 1) - 1);
          release2(B(B_EMPTY1 + prev));
          prev = st;
          if (++st == 6) { st = 0; ph ^= 1; }
        }
        pdst = g_kv + (size_t)(((t & 1) * 32 + (gq + ((t >> 1) ^ 1) * 8) * 2) * 16 + mt) * KV_TILE + (cw * 16 + (lane >> 2)) * 32 + ((lane ^ (lane >> 3)) & 3) * 8;
        mbar_wait_c(B(t < 3 ? B_FULL1 + st : B_FULLQ), t < 3 ? ph : 0);
        wg_wait<0>();
        TK(24 + t * 8 + 7);
        fence_regs(acc1);
        release2(B(B_EMPTY1 + prev));
        TL(0, 3 + 2 * t, warp == 4);
#pragma unroll
        for (int a = 0; a < 8; a++)
#pragma unroll
          for (int h = 0; h < 2; h++)
            pk[2 * a + h] = make_uint4(pack_bf16(acc1[16 * a + 2 * h], acc1[16 * a + 2 * h + 1]), pack_bf16(acc1[16 * a + 4 + 2 * h], acc1[16 * a + 5 + 2 * h]),
                                       pack_bf16(acc1[16 * a + 8 + 2 * h], acc1[16 * a + 9 + 2 * h]), pack_bf16(acc1[16 * a + 12 + 2 * h], acc1[16 * a + 13 + 2 * h]));
      }
      issue_q(0, IC<0>{});
      TL(0, 10, warp == 4);
      put(0); put(1);
#pragma unroll 1
      for (int kb = 1; kb < 8; kb++) {
        issue_q(kb, IC<1>{});
        TK(66 + kb - 1);
#pragma unroll
        for (int i = 1; i < 8; i++) if (kb == i) { put(2 * i); put(2 * i + 1); }
      }
      publish(1);
      TL(0, 11, warp == 4);
    }
    __nv_bfloat16* cdst;
    uint32_t redo = 0;
    auto put_ctx = [&](int i, bool cond) {
      asm volatile("{\n.reg .pred p;\nsetp.ne.u32 p, %5, 0;\n@p st.global.cs.v4.u32 [%0], {%1,%2,%3,%4};\n}" ::"l"(cdst + (i & 1) * 256 + (i >> 1) * 4096),
                   "r"(s.P[4 * i]), "r"(s.P[4 * i + 1]), "r"(s.P[4 * i + 2]), "r"(s.P[4 * i + 3]), "r"((uint32_t)(cond && !(redo & 2))) : "memory");
    };
    {
      const int wrow = cw * 16;
      const int wrow2 = gq ? wrow : wrow ^ 64;
      const uint32_t dK = mk_desc(sb, 16), dV = mk_desc(sb, 8192);
      uint32_t kph = 0, vph = 0;
      auto q_store = [&](const float (&d)[64], auto i0, auto i1) {
        const int r0 = lane >> 2;
        const uint32_t a = sb + SLOT + (wrow + r0) * 128 + (((lane & 3) ^ (((r0 & 1) << 2) | (r0 >> 1))) << 4);
#pragma unroll
        for (int i = i0; i < i1; i++) {
          const float* o = d + 16 * (i >> 1) + 2 * (i & 1);
          asm volatile("st.shared.v4.u32 [%0], {%1,%2,%3,%4};" ::"r"((a ^ ((i & 2) << 5)) + (i >> 2) * UNIT + (i & 1) * 1024),
                       "r"(pack_bf16(o[0] * AT_C, o[1] * AT_C)), "r"(pack_bf16(o[4] * AT_C, o[5] * AT_C)),
                       "r"(pack_bf16(o[8] * AT_C, o[9] * AT_C)), "r"(pack_bf16(o[12] * AT_C, o[13] * AT_C)) : "memory");
        }
        __syncwarp();
      };
      auto q_load = [&](auto k0, auto k1) {
        const uint32_t a = sb + SLOT + (wrow + (lane & 15)) * 128 + (((lane >> 4) ^ (((lane & 1) << 2) | ((lane >> 1) & 3))) << 4);
#pragma unroll
        for (int k = k0; k < k1; k++)
          asm volatile("ldmatrix.sync.aligned.m8n8.x4.shared.b16 {%0,%1,%2,%3}, [%4];"
                       : "=r"(s.Q[4 * k]), "=r"(s.Q[4 * k + 1]), "=r"(s.Q[4 * k + 2]), "=r"(s.Q[4 * k + 3]) : "r"((a ^ ((k & 3) << 5)) + (k >> 2) * UNIT) : "memory");
      };
      auto q_load_if = [&](auto k, bool cond, float after) {
        const uint32_t a = sb + SLOT + (wrow2 + (lane & 15)) * 128 + (((lane >> 4) ^ (((lane & 1) << 2) | ((lane >> 1) & 3))) << 4);
        asm volatile("{\n.reg .pred p;\nsetp.ne.u32 p, %5, 0;\n@p ldmatrix.sync.aligned.m8n8.x4.shared.b16 {%0,%1,%2,%3}, [%4];\n}"
                     : "+r"(s.Q[4 * k]), "+r"(s.Q[4 * k + 1]), "+r"(s.Q[4 * k + 2]), "+r"(s.Q[4 * k + 3])
                     : "r"((a ^ ((k & 3) << 5)) + (k >> 2) * UNIT + (__float_as_uint(after) >> 31)), "r"((uint32_t)cond) : "memory");
      };
      auto issue_s = [&](uint32_t dk, auto mid) {
        mma_n128_rs0<0>(s.S, s.Q, dk);
        static_for<7>([&](auto i) {
          constexpr int k = i + 1;
          if (k == 4) mid();
          mma_n128_rs<0, (k >> 1) * 8192 + (k & 1) * 32>(s.S, s.Q + 4 * k, dk, 1);
        });
        wg_commit();
      };
      auto wait_v = [&](int jv) {
        mbar_wait_c(B(B_VF + (jv & 1)), (vph >> (jv & 1)) & 1);
        vph ^= 1 << (jv & 1);
      };
      auto issue_pva = [&](int jv, int accum) {
        wg_fence();
        static_for<4>([&](auto k) { mma_n128_rs<1, k * 1024>(s.O, s.P + 4 * k, dV + (v_slot(jv) >> 4), k == 0 ? accum : 1); });
        wg_commit();
      };
      auto issue_pvb = [&](int jv, bool upper) {
        if (upper) {
          wg_fence();
          static_for<4>([&](auto k) { mma_n128_rs<1, (k + 4) * 1024>(s.O, s.P + 16 + 4 * k, dV + (v_slot(jv) >> 4), 1); });
          wg_commit();
        } else {
          asm volatile("wgmma.fence.sync.aligned;\nwgmma.commit_group.sync.aligned;" ::: "memory");
        }
      };
      auto issue_pv = [&](int jv, int accum, bool upper) { wait_v(jv); issue_pva(jv, accum); issue_pvb(jv, upper); };
      if (w == 1) bar_arrive(1, 256);
#pragma unroll 1
      for (int half = 0; half < 2; half++) {
        const int head = mt + 16 * half;
        redo = 0;
        float inv[2];
        auto ep_prep = [&]() {
          float l0 = s.l[0] + s.l[1], l1 = s.l[2] + s.l[3];
          l0 += __shfl_xor_sync(~0u, l0, 1); l1 += __shfl_xor_sync(~0u, l1, 1);
          l0 += __shfl_xor_sync(~0u, l0, 2); l1 += __shfl_xor_sync(~0u, l1, 2);
          asm("rcp.approx.ftz.f32 %0, %1;" : "=f"(inv[0]) : "f"(l0));
          asm("rcp.approx.ftz.f32 %0, %1;" : "=f"(inv[1]) : "f"(l1));
          return __any_sync(~0u, !(fminf(l0, l1) >= L_MIN && l0 + l1 <= L_MAX));
        };
        auto ep_out = [&](auto i0, auto i1) {
          __nv_bfloat16* dst = g_ctx + (size_t)(ta * 32 + head) * KV_TILE + (wrow + (lane >> 2)) * 32 + ((lane ^ (lane >> 3)) & 3) * 8;
#pragma unroll
          for (int i = i0; i < i1; i++) {
            const float* o = s.O + 16 * (i >> 1) + 2 * (i & 1);
            const float c = inv[i & 1];
            asm volatile("st.global.cs.v4.u32 [%0], {%1,%2,%3,%4};" ::"l"(dst + (i & 1) * 256 + (i >> 1) * 4096), "r"(pack_bf16(o[0] * c, o[1] * c)),
                         "r"(pack_bf16(o[4] * c, o[5] * c)), "r"(pack_bf16(o[8] * c, o[9] * c)), "r"(pack_bf16(o[12] * c, o[13] * c)) : "memory");
          }
        };
        auto ep_rest = [&]() {
          ep_out(IC<EP1>{}, IC<8>{});
          if (!__any_sync(~0u, redo)) publish(2 + 2 * half);
          fence_regs(s.O);
        };
#pragma unroll 1
        for (int kb = 8; kb < 14; kb++) {
          if (kb == 13) {
            if (w) { wg_wait<0>(); release2(B(B_EMPTYQ)); }
            bar_sync(1 + w, 256);
          }
          issue_q(kb, IC<1>{}, kb != 13 || !w);
          TK(66 + half * 24 + kb - 1);
        }
        TL(1, 20 * half + 0, warp == 4);
        mbar_wait_c(B(B_FULLQ + 2), 1);
        wg_fence();
        mma_kc(s.S, IC<q_aw(2)>{}, IC<q_aw(2) + UNIT>{}, 1);
        wg_commit();
        wg_wait<1>();
        TK(66 + half * 24 + 13);
        release2(B(B_EMPTYQ + 1));
        mbar_wait_c(B(B_FULLQ + 3), 1);
        wg_fence();
        mma_kc(s.S, IC<q_aw(3)>{}, IC<q_aw(3) + UNIT>{}, 1);
        wg_commit();
        bar_arrive(2 - w, 256);
        bar_sync(6 + w, 128);
        wg_wait<0>();
        TK(66 + half * 24 + 14);
        fence_regs(s.S);
        static_for<4>([&](auto i) {
          q_store(s.S, IC<2 * i>{}, IC<2 * i + 2>{});
          q_load(IC<2 * i>{}, IC<2 * i + 2>{});
        });
        TL(1, 20 * half + 1, warp == 4);
        TC(w, 17 * half, 0);
        mbar_wait_c(B(B_KF), kph & 1);
        kph ^= 1;
        bar_sync(1 + w, 256);
        TC(w, 17 * half, 2);
        fence_regs(s.O); fence_regs(s.Q);
        wg_fence();
        issue_s(dK, []() {});
        mma_kc(s.O, IC<q_b(2)>{}, IC<q_aw(2) + UNIT>{}, 1);
        mma_kc(s.O, IC<q_b(3)>{}, IC<q_aw(3) + UNIT>{}, 1);
        wg_commit();
        bar_arrive(2 - w, 256);
        wg_wait<1>();
        TC(w, 17 * half, 4);
        fence_regs(s.S);
        e_arrive(B(B_KE));
        s.l[0] = s.l[1] = s.l[2] = s.l[3] = 0.f;
        at_exp<0, 48>(s);
        at_pack<0, 22>(s);
        sched_fence();
        wg_wait<0>();
        fence_regs(s.O); fence_regs(s.Q);
        release2(B(B_EMPTYQ + 2)); release2(B(B_EMPTYQ + 3));
        at_exp<48, 64>(s);
        at_pack<22, 32>(s);
        q_store(s.O, IC<0>{}, IC<8>{});
        TL(1, 20 * half + 2, warp == 4);
        int kr = 1;
        bool kok = false;
        inv[0] = inv[1] = 0.f;
        const int db = gq ? max(qa, DB) : 16;
#pragma unroll 1
        for (int j = 1; j < 17; j++) {
          const bool diag = j == ta || j == db;
          TC(w, j + 17 * half, 0);
          if (!kok) mbar_wait_c(B(B_KF + kr), (kph >> kr) & 1);
          kph ^= 1 << kr;
          if (j == ta + 2) ep_out(IC<0>{}, IC<EP1>{});
          bar_sync(1 + w, 256);
          TC(w, j + 17 * half, 2);
          fence_regs(s.O); fence_regs(s.P); fence_regs(s.Q);
          const uint32_t ke = B(B_KE + kr), dk = dK + (k_slot(j, kr) >> 4);
          if (++kr == 3) kr = 0;
          auto issue_rest = [&](auto trimmed) {
            TC(w, j + 17 * half, 1);
            if (j == ta + 1) {
              if (ep_prep()) redo = 1;
              s.l[0] = s.l[1] = s.l[2] = s.l[3] = 0.f;
            }
            if (!trimmed && j == ta + 2) ep_rest();
            TC(w, j + 17 * half, 3);
            if (trimmed) wait_v(j - 1);
            issue_pva(j - 1, j != 1 && j != ta + 2);
            issue_pvb(j - 1, w == 1 || (j != ta + 1 && j != db + 1));
            bar_arrive(2 - w, 256);
          };
          auto s_done = [&](auto n) {
            wg_wait<2>();
            TC(w, j + 17 * half, 4);
            fence_part<0, n>(s.S); fence_regs(s.Q);
            e_arrive(ke);
            release2(B(B_X + j - 14), j >= 14);
          };
          auto pv_half = [&]() { sched_fence(); wg_wait<1>(); fence_regs(s.P); };
          auto pv_done = [&]() {
            sched_fence();
            wg_wait<0>();
            fence_regs(s.O); fence_regs(s.P);
            e_arrive(B(B_VE + ((j - 1) & 1)));
            release2(B(B_X + 3), j == 16);
            kok = mbar_test(B(B_KF + kr), (kph >> kr) & 1);
          };
          if (diag && w == (j == 16)) {
            wg_fence();
            static_for<8>([&](auto k) { mma_n64_rs<0, (k >> 1) * 8192 + (k & 1) * 32, k != 0>(s.S, s.Q + 4 * k, dk); });
            wg_commit();
            issue_rest(IC<1>{});
            s_done(IC<32>{});
            at_mask<0>(s, wrow & 63, lane);
            pv_half();
            static_for<8>([&](auto k) {
              at_exp<4 * k, 4 * k + 4>(s);
              q_load_if(k, j == ta, s.S[4 * k]);
            });
            at_pack<0, 16>(s);
            pv_done();
          } else {
            wg_fence();
            issue_s(dk, [&]() { wait_v(j - 1); wg_fence(); });
            issue_rest(IC<0>{});
            if (!diag) {
              s_done(IC<64>{});
              at_exp<0, 24>(s);
              pv_half();
              at_exp<24, 48>(s);
              at_pack<0, 16>(s);
              pv_done();
              at_exp<48, 64>(s);
              at_pack<16, 32>(s);
            } else {
              s_done(IC<64>{});
              at_mask<8>(s, wrow & 63, lane);
              static_for<8>([&](auto k) {
                at_exp<7 * k, 7 * k + 7>(s);
                q_load_if(k, j == ta, s.S[7 * k + 3]);
                if (k == 2) pv_half();
                if (k == 5) { at_pack<0, 16>(s); pv_done(); }
              });
              at_exp<56, 64>(s);
              at_pack<16, 32>(s);
            }
          }
          TL(1, 20 * half + 2 + j, warp == 4);
        }
        TK(84 + half * 24);
        mbar_wait_c(B(half ? B_FULL3 : B_FULLQ), 0);
        if (gq == 0) ep_out(IC<0>{}, IC<EP1>{});
        bar_sync(1 + w, 256);
        fence_regs(s.O); fence_regs(s.P);
        const uint32_t ga = dA - half * w * 256, gb = ga + (half ? 512 : 4), gh = half ? 0x80000020u : 0x40000040u, go = (2 + half) * (SLOT >> 4);
        wg_fence();
        static_for<4>([&](auto k) { mma_n128_ssh<(k & 1) * 32, UNIT + k * 2048, k != 0>(s.S, k < 2 ? ga : gb, gh, dW); });
        mbar_wait_c(B(half ? B_FULL3 + 1 : B_FULLQ + 1), 0);
        wg_fence();
        static_for<4>([&](auto k) { mma_n128_ssh<(k & 1) * 32, UNIT + k * 2048, true>(s.S, (k < 2 ? ga : gb) + go, gh, dW + go); });
        wg_commit();
        TK(85 + half * 24);
        if (gq == 0) ep_rest();
        issue_pv(16, gq != 0, w == 0 || gq != 0);
        if (w == 0 || half == 0) bar_arrive(2 - w, 256);
        TK(86 + half * 24);
        wg_wait<2>();
        release2(B(B_EMPTY3), half); release2(B(B_EMPTY3 + 1), half);
        if (ep_prep()) redo |= 2;
        sched_fence();
        wg_wait<0>();
        TK(87 + half * 24);
        fence_regs(s.S);
        fence_regs(s.O);
        e_arrive(B(B_VE));
        release2(B(B_X + 4));
        fence_regs(s.P);
        {
          const int r = fresh_lane();
          cdst = g_ctx + (size_t)(tb * 32 + head) * KV_TILE + (wrow2 + (r >> 2)) * 32 + ((r ^ (r >> 3)) & 3) * 8;
        }
#pragma unroll
        for (int i = 0; i < 32; i++) {
          const float* o = s.O + 16 * (i >> 3) + 2 * ((i >> 2) & 1) + 4 * (i & 3);
          s.P[i] = pack_bf16(o[0] * inv[(i >> 2) & 1], o[1] * inv[(i >> 2) & 1]);
        }
        fence_regs(s.P);
        if (__builtin_expect(__any_sync(~0u, redo != 0), 0)) {
#pragma unroll
          for (int i = 0; i < 8; i++) put_ctx(i, true);
#pragma unroll 1
          for (int t = 0; t < 2; t++) {
            if (__any_sync(~0u, (redo >> t) & 1)) slow_rows(wq, head, t ? tb * 128 + wrow2 : ta * 128 + wrow);
          }
          if (__any_sync(~0u, redo & 1)) publish(2 + 2 * half);
#pragma unroll
          for (int i = 0; i < 32; i++) s.P[i] = 0;
          redo = 2;
        }
        TL(1, 20 * half + 19, warp == 4);
        TK(88 + half * 24);
        if (half) break;
        mbar_wait_c(B(B_FULLB), 0);
        TK(89);
        wg_fence();
        mma_n128_ss0<1, q_b(0), UNIT>(s.O, dA, dW);
        static_for<3>([&](auto k) { mma_n128_ss<1, q_b(0) + k * 32 + 32, UNIT + k * 2048 + 2048>(s.O, dA, dW, 1); });
        wg_commit();
        mma_kc(s.O, IC<q_b(1)>{}, IC<q_aw(1) + UNIT>{}, 1);
        wg_commit();
        wg_wait<1>();
        release2(B(B_EMPTYQ));
        put_ctx(0, true);
#pragma unroll 1
        for (int kb = 2; kb < 8; kb++) {
          issue_q(kb, IC<1>{});
          TK(90 + kb - 1);
#pragma unroll
          for (int i = 1; i < 8; i++) put_ctx(i, kb == (i < 7 ? i + 1 : 7));
        }
        publish(3);
      }
    }
    const int rid_ = rid + zero, cw_ = cw + zero;
    {
    const int lane = fresh_lane(), rid = rid_, mt = rid >> 3, gq = rid & 7, cw = cw_, w = cw >> 2, ct = cw * 32 + lane;
    const int fid = mt * 7 + gq - 1;
    const bool ffn = gq > 0;
    const uint32_t stg = sb + OFF_STG + w * 16384 + (cw & 3) * 2048;
    const int wr_ = w * 64 + (lane & 7) + (lane >> 4) * 8;
    const uint32_t wl = sb + ((lane >> 3) & 1) * 8192 + wr_ * 64 + (((cw ^ (wr_ >> 1)) & 3) << 4);
    __syncwarp();
    float (&acc)[64] = s.S;
    uint32_t wf[128];
    auto grab = [&](auto c, uint32_t off) {
#pragma unroll
      for (int m = 0; m < 4; m++)
        asm volatile("ldmatrix.sync.aligned.m8n8.x4.trans.shared.b16 {%0,%1,%2,%3}, [%4];"
                     : "=r"(wf[16 * c + 4 * m]), "=r"(wf[16 * c + 4 * m + 1]), "=r"(wf[16 * c + 4 * m + 2]), "=r"(wf[16 * c + 4 * m + 3])
                     : "r"(wl + off + m * 1024) : "memory");
    };
    const int r0 = lane >> 2;
    uint32_t hp[32], rt[16];
    {
      const uint32_t dC = mk_desc(sb + w * 4096, 16);
      uint32_t dep = 0;
      auto hand = [&](uint32_t b, int n) {
        asm volatile("{\n.reg .pred p;\n.reg .b32 t;\nsetp.lt.u32 p, %1, %4;\nmad.lo.u32 t, %2, %3, %0;\n@p mbarrier.arrive.shared::cta.b64 _, [t];\n}"
                     ::"r"(b + 8 * lane), "r"(lane), "r"(dep), "r"(zero), "r"(n) : "memory");
      };
      auto kblock = [&](auto st, uint32_t ph, bool rel) {
        mbar_wait_c(B(B_FULL3 + st), ph);
        wg_fence();
        static_for<4>([&](auto k) { mma_n128_ssh<r3(decltype(st)::value) + (k >> 1) * 8192 + (k & 1) * 32, r3(decltype(st)::value) + UNIT + k * 2048, true>(acc, dC, 0x80000020u, dW); });
        wg_commit();
        wg_wait<1>();
        release2(B(B_EMPTY3 + (st + 5) % 6), rel);
      };
      auto ldsm_if = [&](uint32_t* r, uint32_t a, bool c, auto trans) {
        if (trans) asm volatile("{\n.reg .pred p;\nsetp.ne.u32 p, %5, 0;\n@p ldmatrix.sync.aligned.m8n8.x4.trans.shared.b16 {%0,%1,%2,%3}, [%4];\n}"
                                : "+r"(r[0]), "+r"(r[1]), "+r"(r[2]), "+r"(r[3]) : "r"(a), "r"((uint32_t)c) : "memory");
        else asm volatile("{\n.reg .pred p;\nsetp.ne.u32 p, %5, 0;\n@p ldmatrix.sync.aligned.m8n8.x4.shared.b16 {%0,%1,%2,%3}, [%4];\n}"
                          : "+r"(r[0]), "+r"(r[1]), "+r"(r[2]), "+r"(r[3]) : "r"(a), "r"((uint32_t)c) : "memory");
      };
#pragma unroll
      for (int i = 0; i < 48; i++) asm volatile("" : "=r"(wf[i]));
#pragma unroll 1
      for (int lap = 0; lap < 3; lap++) {
        kblock(IC<2>{}, lap & 1, lap > 0);
#pragma unroll
        for (int i = 0; i < 3; i++) put_ctx(3 * i, lap == i);
        kblock(IC<3>{}, lap & 1, true);
        mbar_wait_c(B(B_WF + (lap & 1)), lap >> 1);
#pragma unroll
        for (int i = 0; i < 12; i++) ldsm_if(wf + 4 * i, wl + OFF_SIDE + ((i >> 2) & 1) * UNIT + (i & 3) * 1024, lap == (i >> 2), IC<1>{});
        kblock(IC<4>{}, lap & 1, true);
        sched_fence();
        dep = 0;
#pragma unroll
        for (int i = 0; i < 12; i++) dep ^= wf[4 * i];
        hand(B(B_WE + (lap & 1)), 1);
#pragma unroll
        for (int i = 0; i < 3; i++) put_ctx(3 * i + 1, lap == i);
        kblock(IC<5>{}, lap & 1, true);
        if (lap == 2) publish(5);
        kblock(IC<0>{}, (lap & 1) ^ 1, true);
#pragma unroll
        for (int i = 0; i < 2; i++) put_ctx(3 * i + 2, lap == i);
        kblock(IC<1>{}, (lap & 1) ^ 1, true);
        TL(2, 40 + lap, warp == 4);
      }
#pragma unroll
      for (int i = 48; i < 96; i++) asm volatile("" : "=r"(wf[i]));
#pragma unroll
      for (int i = 0; i < 32; i++) asm volatile("" : "=r"(hp[i]), "=r"(rt[i >> 1]));
      const uint32_t xa = sb + OFF_SIDE + w * UNIT + (cw & 3) * 2048 + (lane & 15) * 128 + (((lane >> 4) ^ (lane & 7)) << 4);
#pragma unroll 1
      for (int lap = 3; lap < 11; lap++) {
        if (lap == 10 && w == 1) bar_sync(5, 256);
        kblock(IC<2>{}, lap & 1, true);
        if (lap == 10 && w == 0) bar_arrive(5, 256);
        kblock(IC<3>{}, lap & 1, true);
        if (lap == 10) break;
        if (lap < WIN) {
          mbar_wait_c(B(B_WF + (lap & 1)), (lap >> 1) & 1);
#pragma unroll
          for (int i = 12; i < 24; i++) ldsm_if(wf + 4 * i, wl + OFF_SIDE + ((i >> 2) & 1) * UNIT + (i & 3) * 1024, lap == (i >> 2), IC<1>{});
        } else if (lap == WIN) {
          mbar_wait_c(B(B_WF), (WIN >> 1) & 1);
          mbar_wait_c(B(B_WF + 1), (WIN >> 1) & 1);
#pragma unroll
          for (int j = 0; j < 8; j++) ldsm_if(hp + 4 * j, (xa ^ ((j & 3) << 5)) + (j >> 2) * 8192, true, IC<0>{});
        } else if (lap == 9) {
          mbar_wait_c(B(B_WR), 0);
          mbar_wait_c(B(B_SET2), 0);
#pragma unroll
          for (int j = 0; j < 4; j++) ldsm_if(rt + 4 * j, sb + OFF_MISC + 512 + (lane & 1) * 256 + (lane >> 3) * 16 + j * 64, true, IC<0>{});
        }
        kblock(IC<4>{}, lap & 1, true);
        sched_fence();
        dep = 0;
#pragma unroll
        for (int i = 0; i < 20; i++) dep ^= i < 12 ? wf[48 + 4 * i] : hp[4 * (i - 12)];
        hand(B(B_WE + (lap < WIN ? lap & 1 : 0)), lap < WIN ? 1 : (lap == WIN ? 2 : 0));
        kblock(IC<5>{}, lap & 1, true);
        kblock(IC<0>{}, (lap & 1) ^ 1, true);
        kblock(IC<1>{}, (lap & 1) ^ 1, true);
        TL(2, 40 + lap, warp == 4);
      }
    }
    uint4* const xr = g_xr + rid * XR_SIZE;
    uint4* const psd = xr + XR_PS + cw * 16 + r0;
    settle(psd, zero);
    sched_fence();
    wg_wait<0>();
    fence_regs(acc);
    TL(2, 10, warp == 4);
    {
      float d[4] = {0.f, 0.f, 0.f, 0.f}, qa[4] = {0.f, 0.f, 0.f, 0.f}, qb[4] = {0.f, 0.f, 0.f, 0.f};
#pragma unroll
      for (int j = 0; j < 16; j++) {
        hp[2 * j] = hadd2_bf(hp[2 * j], pack_bf16(acc[4 * j], acc[4 * j + 1]));
        hp[2 * j + 1] = hadd2_bf(hp[2 * j + 1], pack_bf16(acc[4 * j + 2], acc[4 * j + 3]));
        if (j & 1) {
          mma16816(d, hp[2 * j - 2], hp[2 * j - 1], hp[2 * j], hp[2 * j + 1], rt[j - 1], rt[j]);
          mma16816(qa, hp[2 * j - 2], hp[2 * j - 1], hp[2 * j], hp[2 * j + 1], hp[2 * j - 2], hp[2 * j]);
          mma16816(qb, hp[2 * j - 2], hp[2 * j - 1], hp[2 * j], hp[2 * j + 1], hp[2 * j - 1], hp[2 * j + 1]);
        }
      }
      asm volatile("{\n.reg .pred p;\nsetp.eq.u32 p, %7, %8;\n@p st.global.cg.v4.f32 [%0], {%1,%2,%3,%3};\n@p st.global.cg.v4.f32 [%0 + 128], {%4,%5,%6,%6};\n}"
                   ::"l"(psd), "f"(d[0]), "f"(d[1]), "f"((r0 & 1) ? qa[1] : qa[0]), "f"(d[2]), "f"(d[3]), "f"((r0 & 1) ? qb[3] : qb[2]),
                   "r"(lane & 3), "r"(r0 >> 1) : "memory");
      sched_fence();
    }
    mbar_wait_c(B(B_EMPTY3), 0);
    __syncwarp();
    stage_store_128(stg, lane, hp);
    TL(2, 11, warp == 4);
    __syncwarp();
    uint4 cout;
    uint32_t ckey;
    {
      const float wsum = *reinterpret_cast<const float*>(sp + OFF_MISC + 1024);
      const uint4* pp = g_xr + (mt * 8 + (ct & 1) * 4) * XR_SIZE + XR_PS + (ct >> 1);
      uint2* kd = reinterpret_cast<uint2*>(xr + XR_KEY) + cw;
      const uint32_t tok = 0x7FFFu - (mt * 128 + (ct >> 1));
      settle(pp, zero); settle(kd, zero); settle(tok, zero);
      spin_clk(PS_DLY);
      float s1, s2, s3;
#pragma unroll 1
      for (int n = 0; n < 0x400000; n++) {
        float4 z[4];
#pragma unroll
        for (int i = 0; i < 4; i++)
          asm volatile("ld.relaxed.gpu.global.v4.f32 {%0,%1,%2,%3}, [%4];" : "=f"(z[i].x), "=f"(z[i].y), "=f"(z[i].z), "=f"(z[i].w) : "l"(pp + i * XR_SIZE) : "memory");
        s1 = (z[0].x + z[1].x) + (z[2].x + z[3].x); s3 = (z[0].y + z[1].y) + (z[2].y + z[3].y); s2 = (z[0].z + z[1].z) + (z[2].z + z[3].z);
        const float t = s1 + s2 + s3;
        s1 += __shfl_xor_sync(~0u, s1, 1); s2 += __shfl_xor_sync(~0u, s2, 1); s3 += __shfl_xor_sync(~0u, s3, 1);
        if (__all_sync(~0u, t == t)) break;
        uint32_t m = 0;
#pragma unroll
        for (int i = 0; i < 4; i++) m = max(max(m, __float_as_uint(z[i].x)), max(__float_as_uint(z[i].y), __float_as_uint(z[i].z)));
        if (__all_sync(~0u, m != 0xFFFFFFFFu)) break;
      }
      TL(2, 12, warp == 4);
      const float mean = s1 * (1.f / DM);
      float mb, inv;
      ln_round(mean, fmaxf(fmaf(s2, 1.f / DM, -mean * mean), 0.f), mb, inv);
      const uint32_t u = pack_bf16(0.f, fmaf(s3 - mb * wsum, inv, 0.f));
      const uint32_t key = ((u ^ (((int)u >> 31) | 0x80000000u)) & 0xFFFF0000u) | tok;
      const uint32_t c1 = __reduce_max_sync(~0u, key);
      const uint32_t c2 = __reduce_max_sync(~0u, key == c1 ? 0u : key);
      asm volatile(ELECT "st.global.cg.v2.u32 [%0], {%1,%2};\n}" ::"l"(kd), "r"(c1), "r"(c2) : "memory");
      sched_fence();
      const uint32_t nm2 = pack_bf16(-mb, -mb), inv2 = ln_split(inv);
      if (!(ct & 1)) *reinterpret_cast<uint2*>(sp + OFF_RSTAT + (ct >> 1) * 8) = make_uint2(nm2, inv2 | (key >= c2 ? 0x80000000u : 0u));
      ckey = (lane >> 4) ? c2 : c1;
      const int row = (0x7FFF - (ckey & 0x7FFF)) & 15;
      const uint32_t rn = __shfl_sync(~0u, nm2, row * 2);
      const uint32_t ri = __shfl_sync(~0u, inv2, row * 2);
      const uint4 v = lds128(stg + ((lane & 15) >> 3) * 8192 + row * 128 + (((lane & 7) ^ (row & 7)) << 4));
      const uint4 n = make_uint4(ln_apply(v.x, rn, ri), ln_apply(v.y, rn, ri), ln_apply(v.z, rn, ri), ln_apply(v.w, rn, ri));
      __stcg(xr + XR_CAND + cw * 64 + 32 + lane, n);
      __stcg(xr + XR_CAND + cw * 64 + lane, v);
      cdst = out + (size_t)(0x7FFF - (ckey & 0x7FFF)) * DM + gq * 128 + (lane & 15) * 8;
      cout = make_uint4(hadd2_bf(v.x, n.x), hadd2_bf(v.y, n.y), hadd2_bf(v.z, n.z), hadd2_bf(v.w, n.w));
    }
    publish(B_OUT - B_PUB);
    cluster_arrive();
    TL(2, 13, warp == 4);
    uint32_t wd[16][4];
    if (ffn) {
      static_for<2>([&](auto i) {
        mbar_wait_b(B(B_WF + i), ((WIN >> 1) & 1) ^ 1);
        grab(IC<WIN + i>{}, OFF_SIDE + i * UNIT);
      });
      mbar_wait_b(B(B_FULL3 + 4 + w), 0);
#pragma unroll
      for (int i = 0; i < 16; i++) {
        const int k = (i & 1) * 16 + (lane & 7) + (lane >> 4) * 8;
        asm volatile("ldmatrix.sync.aligned.m8n8.x4.trans.shared.b16 {%0,%1,%2,%3}, [%4];"
                     : "=r"(wd[i][0]), "=r"(wd[i][1]), "=r"(wd[i][2]), "=r"(wd[i][3])
                     : "r"(sb + r3(4) + w * SLOT + (2 * (cw & 3) + (i >> 3)) * 4096 + k * 128 + (((2 * ((i >> 1) & 3) + ((lane >> 3) & 1)) ^ (lane & 7)) << 4)) : "memory");
      }
    }
    const int fc = 16 * (rid >> 1) + 4 * (rid & 1) + (lane & 3) + 8 * (lane >> 4), ft = (lane >> 3) & 1;
    const char* pc = reinterpret_cast<const char*>(g_xr + ((ct & 127) >> 4) * XR_SIZE + XR_CAND + 32 + (ct & 15));
    const char* pf = reinterpret_cast<const char*>(g_xr + (fc >> 7) * XR_SIZE + XR_CAND) + (fc & 127) * 2;
    const uint32_t xs = sb + OFF_SCR + w * 2112 + ((ct & 127) >> 2) * 64 + (((ct >> 3) & 3) << 4) + (ct & 3) * 4;
    const uint32_t xb = sb + OFF_SCR + (r0 & 1) * 2112 + w * 128 + (((lane ^ w) & 3) << 4);
    settle(pc, zero); settle(pf, zero); settle(cdst, zero); settle(xs, zero); settle(xb, zero);
    mbar_wait_b(B(B_OUT2), 0);
    const uint4 top = lds128(sb + OFF_MISC + 256);
    TL(2, 14, warp == 4);
    uint32_t fh, fn;
    {
      pc += w ? top.y : top.x;
      pf += ft ? top.y : top.x;
      uint4 v;
#pragma unroll 1
      for (int n = 0; n < 0x400000; n++) {
        asm volatile("ld.relaxed.gpu.global.v4.u32 {%0,%1,%2,%3}, [%4];" : "=r"(v.x), "=r"(v.y), "=r"(v.z), "=r"(v.w) : "l"(pc) : "memory");
        asm volatile("ld.relaxed.gpu.global.u16 %0, [%1];" : "=r"(fh) : "l"(pf) : "memory");
        asm volatile("ld.relaxed.gpu.global.u16 %0, [%1 + 512];" : "=r"(fn) : "l"(pf) : "memory");
        asm volatile("st.shared.u32 [%0], %1;" ::"r"(xs), "r"(v.x) : "memory");
        asm volatile("st.shared.u32 [%0], %1;" ::"r"(xs ^ 16), "r"(v.y) : "memory");
        asm volatile("st.shared.u32 [%0], %1;" ::"r"(xs ^ 32), "r"(v.z) : "memory");
        asm volatile("st.shared.u32 [%0], %1;" ::"r"(xs ^ 48), "r"(v.w) : "memory");
        if (__all_sync(~0u, max(max(v.x, v.y), max(v.z, v.w)) != 0xFFFFFFFFu && max(fh, fn) != 0xFFFFu)) break;
      }
    }
    bar_sync(3, 256);
    asm volatile("{\n.reg .pred p;\nsetp.lt.u32 p, %5, %6;\n@p st.global.v4.u32 [%0], {%1,%2,%3,%4};\n}" ::"l"(cdst), "r"(cout.x), "r"(cout.y), "r"(cout.z),
                 "r"(cout.w), "r"(ckey), "r"(top.w) : "memory");
    if (ffn) {
      TL(2, 15, warp == 4);
      float d[4][4] = {};
      auto xl = [&](int i) { return lds128((xb ^ ((i & 2) << 4)) + (i >> 1) * 256 + (i & 1) * 64); };
      uint4 b0 = xl(0), b1 = xl(1);
#pragma unroll
      for (int i = 0; i < 16; i += 2) {
        const uint4 c0 = b0, c1 = b1;
        if (i < 14) { b0 = xl(i + 2); b1 = xl(i + 3); }
        mma16816(d[0], wf[8 * i], wf[8 * i + 1], wf[8 * i + 2], wf[8 * i + 3], c0.x, c0.y);
        mma16816(d[1], wf[8 * i + 4], wf[8 * i + 5], wf[8 * i + 6], wf[8 * i + 7], c0.z, c0.w);
        mma16816(d[2], wf[8 * i + 8], wf[8 * i + 9], wf[8 * i + 10], wf[8 * i + 11], c1.x, c1.y);
        mma16816(d[3], wf[8 * i + 12], wf[8 * i + 13], wf[8 * i + 14], wf[8 * i + 15], c1.z, c1.w);
      }
      const float e0 = (d[0][0] + d[1][0]) + (d[2][0] + d[3][0]), e1 = (d[0][1] + d[1][1]) + (d[2][1] + d[3][1]);
      const float e2 = (d[0][2] + d[1][2]) + (d[2][2] + d[3][2]), e3 = (d[0][3] + d[1][3]) + (d[2][3] + d[3][3]);
      asm volatile("st.shared.v2.f32 [%0], {%1,%2};" ::"r"(sb + OFF_SCR + 8192 + ((w * 2 + (lane & 1)) * 32 + (cw & 3) * 8 + r0) * 8),
                   "f"((lane & 1) ? e1 : e0), "f"((lane & 1) ? e3 : e2) : "memory");
      bar_sync(3, 256);
      TL(2, 16, warp == 4);
      const uint32_t ra = sb + OFF_SCR + 8192 + (r0 & 1) * 256 + (r0 >> 1) * 64 + (lane & 3) * 16;
      const uint4 p0 = lds128(ra), p1 = lds128(ra + 512);
      auto act = [](uint32_t u0, uint32_t u1, uint32_t g0, uint32_t g1) {
        const uint32_t ug = pack_bf16(__uint_as_float(u0) + __uint_as_float(u1), __uint_as_float(g0) + __uint_as_float(g1));
        const float g = bf_hi(ug);
        float r;
        asm("rcp.approx.ftz.f32 %0, %1;" : "=f"(r) : "f"(1.f + ex2(g * -1.4426950408889634f)));
        return bf_round(g * r) * bf_lo(ug);
      };
      const uint32_t av = pack_bf16(act(p0.x, p1.x, p0.y, p1.y), act(p0.z, p1.z, p0.w, p1.w));
      uint32_t b[4];
#pragma unroll
      for (int i = 0; i < 4; i++) b[i] = __shfl_sync(~0u, av, 8 * i + (lane & 7));
      TL(2, 17, warp == 4);
      float y[2][4] = {{0.f, 0.f, 0.f, 0.f}, {0.f, 0.f, 0.f, 0.f}};
#pragma unroll
      for (int c = 0; c < 4; c++) {
        const bool on = (lane >> 3) == c;
        const uint32_t b0 = on ? b[0] : 0, b1 = on ? b[1] : 0, b2 = on ? b[2] : 0, b3 = on ? b[3] : 0;
#pragma unroll
        for (int a = 0; a < 2; a++) {
          const int i = 8 * a + 2 * c;
          mma16816(y[a], wd[i][0], wd[i][1], wd[i][2], wd[i][3], b0, b1);
          mma16816(y[a], wd[i + 1][0], wd[i + 1][1], wd[i + 1][2], wd[i + 1][3], b2, b3);
        }
      }
      float4* yd = reinterpret_cast<float4*>(g_xr + (cw * 16 + (lane & 3) * 2 + (lane >> 4)) * XR_SIZE + XR_Y + fid * 4 + (r0 & 3));
      __stcg(yd, make_float4(y[0][0], y[0][1], y[0][2], y[0][3]));
      __stcg(yd + 8 * XR_SIZE, make_float4(y[1][0], y[1][1], y[1][2], y[1][3]));
    }
    TL(2, 18, warp == 4);
    if (cw == 0) {
      const uint32_t fk = ft ? top.w : top.z;
      uint32_t u = fk >> 16;
      u = (u & 0x8000u) ? (u & 0x7FFFu) : (~u & 0xFFFFu);
      float rs = bf_round(__fdividef(1.f, 1.f + __expf(-__uint_as_float(u << 16))));
      uint16_t* op = reinterpret_cast<uint16_t*>(out) + (size_t)(~fk & 0x7FFF) * DM + fc;
      settle(op, zero); settle(__float_as_uint(rs), zero);
      spin_clk(ffn ? Y_DLY : Y_DLY + Y_DLY0);
      float v[4];
#pragma unroll 1
      for (int n = 0; n < 0x400000; n++) {
        float4 z[14];
#pragma unroll
        for (int i = 0; i < 14; i++)
          asm volatile("ld.relaxed.gpu.global.v4.f32 {%0,%1,%2,%3}, [%4];" : "=f"(z[i].x), "=f"(z[i].y), "=f"(z[i].z), "=f"(z[i].w) : "l"(xr + XR_Y + lane + 32 * i) : "memory");
        float a[4] = {z[0].x, z[0].y, z[0].z, z[0].w}, b[4] = {z[1].x, z[1].y, z[1].z, z[1].w};
#pragma unroll
        for (int i = 2; i < 14; i += 2) {
          a[0] += z[i].x; a[1] += z[i].y; a[2] += z[i].z; a[3] += z[i].w;
          b[0] += z[i + 1].x; b[1] += z[i + 1].y; b[2] += z[i + 1].z; b[3] += z[i + 1].w;
        }
#pragma unroll
        for (int i = 0; i < 4; i++) v[i] = a[i] + b[i];
        const float t = (v[0] + v[1]) + (v[2] + v[3]);
        if (__all_sync(~0u, t == t)) break;
        uint32_t m = 0;
#pragma unroll
        for (int i = 0; i < 14; i++) m = max(max(m, max(__float_as_uint(z[i].x), __float_as_uint(z[i].y))), max(__float_as_uint(z[i].z), __float_as_uint(z[i].w)));
        if (__all_sync(~0u, m != 0xFFFFFFFFu)) break;
      }
      TL(2, 30, true);
      const bool hi = lane & 16, odd = lane & 8;
      const float a0 = (hi ? v[2] : v[0]) + __shfl_xor_sync(~0u, hi ? v[0] : v[2], 16), a1 = (hi ? v[3] : v[1]) + __shfl_xor_sync(~0u, hi ? v[1] : v[3], 16);
      float yv = (odd ? a1 : a0) + __shfl_xor_sync(~0u, odd ? a0 : a1, 8);
      yv += __shfl_xor_sync(~0u, yv, 4);
      const uint32_t o = hadd2_bf(fh, hadd2_bf(fn, pack_bf16(bf_round(yv) * rs, 0.f)));
      if (!(lane & 4)) *op = (uint16_t)o;
      TL(2, 21, true);
    }
    TL(2, 20, warp == 4);
    }
    __syncwarp();
    cluster_wait();
  }
}

typedef CUresult (*EncodeFn)(CUtensorMap*, CUtensorMapDataType, cuuint32_t, void*, const cuuint64_t*, const cuuint64_t*, const cuuint32_t*,
                             const cuuint32_t*, CUtensorMapInterleave, CUtensorMapSwizzle, CUtensorMapL2promotion, CUtensorMapFloatOOBfill);
EncodeFn g_enc = nullptr;

void map2(CUtensorMap* m, const void* ptr, uint64_t rows, uint64_t cols, uint32_t bc, uint32_t br) {
  const CUtensorMapSwizzle sw = bc == 64 ? CU_TENSOR_MAP_SWIZZLE_128B : CU_TENSOR_MAP_SWIZZLE_64B;
  cuuint64_t gd[2] = {cols, rows}, gs[1] = {cols * 2};
  cuuint32_t bd[2] = {bc, br}, es[2] = {1, 1};
  g_enc(m, CU_TENSOR_MAP_DATA_TYPE_BFLOAT16, 2, (void*)ptr, gd, gs, bd, es, CU_TENSOR_MAP_INTERLEAVE_NONE, sw,
        CU_TENSOR_MAP_L2_PROMOTION_L2_128B, CU_TENSOR_MAP_FLOAT_OOB_FILL_NONE);
}
void map3(CUtensorMap* m, const void* ptr, uint64_t rows, uint64_t cols, uint32_t br, uint32_t bch) {
  cuuint64_t gd[3] = {64, rows, cols / 64}, gs[2] = {cols * 2, 128};
  cuuint32_t bd[3] = {64, br, bch}, es[3] = {1, 1, 1};
  g_enc(m, CU_TENSOR_MAP_DATA_TYPE_BFLOAT16, 3, (void*)ptr, gd, gs, bd, es, CU_TENSOR_MAP_INTERLEAVE_NONE, CU_TENSOR_MAP_SWIZZLE_128B,
        CU_TENSOR_MAP_L2_PROMOTION_L2_128B, CU_TENSOR_MAP_FLOAT_OOB_FILL_NONE);
}

}

extern "C" void kernel_launch(void* const* d_in, const int* in_sizes, int n_in, void* d_out, int out_size) {
  const __nv_bfloat16* x = (const __nv_bfloat16*)d_in[0];
  const __nv_bfloat16* ckv = (const __nv_bfloat16*)d_in[1];
  const __nv_bfloat16* wq = (const __nv_bfloat16*)d_in[2];
  const __nv_bfloat16* wk = (const __nv_bfloat16*)d_in[3];
  const __nv_bfloat16* wv = (const __nv_bfloat16*)d_in[4];
  const __nv_bfloat16* wo = (const __nv_bfloat16*)d_in[5];
  const __nv_bfloat16* w_r = (const __nv_bfloat16*)d_in[7];
  const __nv_bfloat16* wgate = (const __nv_bfloat16*)d_in[8];
  const __nv_bfloat16* wup = (const __nv_bfloat16*)d_in[9];
  const __nv_bfloat16* wdown = (const __nv_bfloat16*)d_in[10];
  __nv_bfloat16* out = (__nv_bfloat16*)d_out;

  if (!g_enc) {
    void* fn = nullptr;
    cudaDriverEntryPointQueryResult qr;
    cudaGetDriverEntryPoint("cuTensorMapEncodeTiled", &fn, cudaEnableDefault, &qr);
    g_enc = (EncodeFn)fn;
    cudaFuncSetAttribute(fused_kernel, cudaFuncAttributeMaxDynamicSharedMemorySize, SMEM_BYTES);
  }
  void *xn, *kv, *ctx, *xr, *cnt;
  cudaGetSymbolAddress(&xr, g_xr);
  cudaGetSymbolAddress(&cnt, g_cnt);
  cudaGetSymbolAddress(&xn, g_xn);
  cudaGetSymbolAddress(&kv, g_kv);
  cudaGetSymbolAddress(&ctx, g_ctx);

  Params p;
  map2(&p.xn, xn, SEQ, DM, 64, 64);
  map2(&p.ckv, ckv, SEQ, DC, 64, 128);
  map3(&p.wq, wq, DM, NQ, 64, 2);
  map3(&p.wk, wk, DC, NQ, 32, 2);
  map3(&p.wv, wv, DC, NQ, 32, 2);
  map3(&p.wo, wo, NQ, DM, 64, 1);
  map3(&p.x, x, SEQ, DM, 64, 2);
  map3(&p.wd, wdown, FF, DM, 32, 8);
  map2(&p.wg, wgate, DM, FF, 32, 64);
  map2(&p.wu, wup, DM, FF, 32, 64);
  fused_kernel<<<128, 384, SMEM_BYTES, cudaStreamPerThread>>>(0u, x, (__nv_bfloat16*)kv, (__nv_bfloat16*)ctx, (uint4*)xr, out, (__nv_bfloat16*)xn,
                                                               (unsigned*)cnt, w_r, wdown, wq, p);
}
```
